```python
import torch

def _softmax(x, axis=-1):
    return torch.softmax(x, dim=axis)

def _gelu(x):
    return torch.nn.functional.gelu(x, approximate='tanh')

def _silu(x):
    return torch.nn.functional.silu(x)

def _sigmoid(x):
    return torch.sigmoid(x)

def _layernorm(x, axis=-1, eps=1e-05):
    m = x.mean(dim=axis, keepdim=True)
    v = x.var(dim=axis, keepdim=True, unbiased=False)
    return (x - m) / torch.sqrt(v + eps)

def _scatter_add(tgt, idx, src, axis=0):
    return tgt.clone().index_add_(axis, idx, src)

def _segment_sum(src, seg, n):
    out = torch.zeros((n,) + src.shape[1:], dtype=src.dtype)
    return out.index_add_(0, seg, src)

def _pad(x, pw):
    flat = tuple((v for pair in reversed(pw) for v in pair))
    return torch.nn.functional.pad(x, flat)
kernel_name = 'concat_heads__memory_aug_recurrent_mem_tr__ssm_conv_h3__prompt'

def setup_inputs():

    _w = lambda a: (lambda t: t.to(torch.bfloat16) if t.is_floating_point() else t)(torch.as_tensor(a))

    def _A_setup():
        B, S, Dm = (1, 2048, 1024)
        H, Dh = (32, 128)
        M, seg = (8, 32)
        seg = min(seg, S)
        S = S // seg * seg
        return {'x': _w((lambda *s: torch.randn(*s, dtype=torch.bfloat16) * 0.05)(B, S, Dm)), 'mem0': _w((lambda *s: torch.randn(*s, dtype=torch.bfloat16) * 0.4)(B, M, Dm)), 'Wq': _w((lambda *s: torch.randn(*s, dtype=torch.bfloat16) * 6.4)(Dm, H, Dh) * Dm ** (-0.5)), 'Wk': _w((lambda *s: torch.randn(*s, dtype=torch.bfloat16) * 6.4)(Dm, H, Dh) * Dm ** (-0.5)), 'Wv': _w((lambda *s: torch.randn(*s, dtype=torch.bfloat16) * 0.4)(Dm, H, Dh) * Dm ** (-0.5)), 'Wo': _w((lambda *s: torch.randn(*s, dtype=torch.bfloat16) * 0.4)(H, Dh, Dm) * (H * Dh) ** (-0.5)), 'seg_len': seg}
    _A_in = _A_setup()

    def _B_setup():
        B, S, D = (1, 2048, 1024)
        ks = 4
        return {'q': _w((lambda *s: torch.randn(*s, dtype=torch.bfloat16) * 0.05)(B, S, D)), 'k': _w((lambda *s: torch.randn(*s, dtype=torch.bfloat16) * 0.4)(B, S, D)), 'v': _w((lambda *s: torch.randn(*s, dtype=torch.bfloat16) * 0.4)(B, S, D)), 'shift_k': _w((lambda *s: torch.randn(*s, dtype=torch.bfloat16) * 0.4)(D, ks) * 0.5), 'ssm_k': _w((lambda *s: torch.randn(*s, dtype=torch.bfloat16) * 0.4)(D, S) * (1.0 / S ** 0.5)), 'ssm_D': _w((lambda *s: torch.randn(*s, dtype=torch.bfloat16) * 0.4)(D))}
    _B_in = _B_setup()
    return {'A_x': _A_in['x'], 'A_mem0': _A_in['mem0'], 'A_Wq': _A_in['Wq'], 'A_Wk': _A_in['Wk'], 'A_Wv': _A_in['Wv'], 'A_Wo': _A_in['Wo'], 'A_seg_len': _A_in['seg_len'], 'B_q': _B_in['q'], 'B_k': _B_in['k'], 'B_v': _B_in['v'], 'B_shift_k': _B_in['shift_k'], 'B_ssm_k': _B_in['ssm_k'], 'B_ssm_D': _B_in['ssm_D']}

def reference(A_x, A_mem0, A_Wq, A_Wk, A_Wv, A_Wo, A_seg_len, B_q, B_k, B_v, B_shift_k, B_ssm_k, B_ssm_D):

    def _A_ref(x, mem0, Wq, Wk, Wv, Wo, seg_len):
        B, S, Dm = x.shape
        H, Dh = (Wq.shape[1], Wq.shape[2])
        M = mem0.shape[1]
        scale = Dh ** (-0.5)
        n_seg = S // seg_len
        L = M + seg_len
        idx = torch.arange(L)
        mask = (idx[:, None] < M) | (idx[:, None] >= idx[None, :])
        mem = mem0
        outs = []
        for s in range(n_seg):
            xs = x[:, s * seg_len:(s + 1) * seg_len, :].clone()
            h = torch.concatenate([mem, xs], axis=1)
            q = torch.einsum('btd,dhe->bhte', h, Wq)
            k = torch.einsum('btd,dhe->bhte', h, Wk)
            v = torch.einsum('btd,dhe->bhte', h, Wv)
            scores = torch.einsum('bhqe,bhke->bhqk', q, k) * scale
            scores = torch.where(mask[None, None], scores, -1000000000.0)
            p = _softmax(scores, axis=-1)
            o = torch.einsum('bhqk,bhke->bhqe', p, v)
            o = torch.einsum('bhte,hed->btd', o, Wo)
            mem = o[:, :M, :].clone()
            outs.append(o[:, M:, :])
        return torch.concatenate(outs, axis=1)

    def _B_ref(q, k, v, shift_k, ssm_k, ssm_D):
        B, S, D = q.shape
        ks = shift_k.shape[-1]
        k_pad = _pad(k, ((0, 0), (ks - 1, 0), (0, 0)))
        k_shift = torch.zeros_like(k)
        for t in range(ks):
            k_shift = k_shift + k_pad[:, t:t + S, :] * shift_k[:, ks - 1 - t][None, None, :]
        kv = k_shift * v
        L = 2 * S
        kv_pad = _pad(kv, ((0, 0), (0, S), (0, 0)))
        kf_pad = _pad(ssm_k, ((0, 0), (0, S)))
        kv_f = (lambda x, axes=(-2, -1): torch.fft.rfft2(x.float(), dim=axes))(kv_pad[:, None, :, :], axes=(1, 2))
        kf_f = (lambda x, axes=(-2, -1): torch.fft.rfft2(x.float(), dim=axes))(kf_pad[:, None, :], axes=(1, 2))
        kf_f = (lambda x, *d: x.permute(*d))(kf_f, 1, 2, 0)
        y_f = kv_f * kf_f[None, :, :, :]
        y = (lambda x, s, axes=(-2, -1): torch.fft.irfft2(x, s=s, dim=axes).to(torch.bfloat16))(y_f, (1, L), axes=(1, 2))[:, 0, :S, :]
        y = y + kv * ssm_D[None, None, :]
        return q * y
    a = _A_ref(A_x, A_mem0, A_Wq, A_Wk, A_Wv, A_Wo, A_seg_len)
    b = _B_ref(B_q, B_k, B_v, B_shift_k, B_ssm_k, B_ssm_D)
    return torch.concatenate([a, b], axis=-1)
```

```cpp
#include <cuda_runtime.h>
#include <cuda_bf16.h>
#include <cuda.h>
#include <stdint.h>
#include <type_traits>

typedef __nv_bfloat16 bf16;

constexpr int S_LEN = 2048, DM = 1024, NH = 32, DH = 128, NSEG = 64, SEG = 32;
constexpr int HD = NH * DH;
constexpr int OUT_LD = 2048;
constexpr unsigned SENT = 0xFFFFFFFFu;

__device__ bf16 g_tok[4 * NH * 3 * SEG * DH];
__device__ bf16 g_ox[(size_t)S_LEN * HD];
__device__ uint4 g_mbox[3 * 131072];
__device__ unsigned g_xflag[128];
__device__ unsigned g_reg[4];
__device__ unsigned g_cls[256];
__device__ unsigned g_err;
constexpr uint32_t WIN = 2u << 20;
__host__ __device__ constexpr uint32_t page_off(uint32_t idx, uint32_t c) {
    return ((idx & 1) << 13) | ((idx >> 1) << 16) | (((c ^ idx ^ (idx >> 1) ^ (idx >> 2) ^ (idx >> 4)) & 1) << 12);
}
#define STAT(i, c)
#define KT_START(k)
#define KT_END(k)

__device__ __forceinline__ uint32_t smem_u32(const void* p) { return (uint32_t)__cvta_generic_to_shared(p); }
__device__ __forceinline__ void ldsm4(uint32_t& r0, uint32_t& r1, uint32_t& r2, uint32_t& r3, uint32_t a) {
    asm volatile("ldmatrix.sync.aligned.m8n8.x4.shared.b16 {%0,%1,%2,%3}, [%4];" : "=r"(r0), "=r"(r1), "=r"(r2), "=r"(r3) : "r"(a) : "memory");
}
__device__ __forceinline__ void ldsm4t(uint32_t& r0, uint32_t& r1, uint32_t& r2, uint32_t& r3, uint32_t a) {
    asm volatile("ldmatrix.sync.aligned.m8n8.x4.trans.shared.b16 {%0,%1,%2,%3}, [%4];" : "=r"(r0), "=r"(r1), "=r"(r2), "=r"(r3) : "r"(a) : "memory");
}
__device__ __forceinline__ void ldsm2(uint32_t& r0, uint32_t& r1, uint32_t a) {
    asm volatile("ldmatrix.sync.aligned.m8n8.x2.shared.b16 {%0,%1}, [%2];" : "=r"(r0), "=r"(r1) : "r"(a) : "memory");
}
__device__ __forceinline__ void stg128(void* p, uint4 v) {
    asm volatile("st.global.v4.u32 [%0], {%1,%2,%3,%4};" ::"l"(p), "r"(v.x), "r"(v.y), "r"(v.z), "r"(v.w) : "memory");
}
__device__ __forceinline__ void stsm4(uint32_t a, uint32_t r0, uint32_t r1, uint32_t r2, uint32_t r3) {
    asm volatile("stmatrix.sync.aligned.m8n8.x4.shared.b16 [%0], {%1,%2,%3,%4};" ::"r"(a), "r"(r0), "r"(r1), "r"(r2), "r"(r3) : "memory");
}
__device__ __forceinline__ void mma16816(float (&d)[4], uint32_t a0, uint32_t a1, uint32_t a2, uint32_t a3, uint32_t b0, uint32_t b1) {
    asm("mma.sync.aligned.m16n8k16.row.col.f32.bf16.bf16.f32 {%0,%1,%2,%3},{%4,%5,%6,%7},{%8,%9},{%0,%1,%2,%3};"
                 : "+f"(d[0]), "+f"(d[1]), "+f"(d[2]), "+f"(d[3])
                 : "r"(a0), "r"(a1), "r"(a2), "r"(a3), "r"(b0), "r"(b1));
}
__device__ __forceinline__ uint32_t movmat(uint32_t a) {
    uint32_t d;
    asm volatile("movmatrix.sync.aligned.m8n8.trans.b16 %0, %1;" : "=r"(d) : "r"(a));
    return d;
}
__device__ __forceinline__ uint32_t pack_bf16(float lo, float hi) {
    uint32_t r;
    asm("cvt.rn.bf16x2.f32 %0, %1, %2;" : "=r"(r) : "f"(hi), "f"(lo));
    return r;
}
__device__ __forceinline__ float bf16_round(float x) { return __bfloat162float(__float2bfloat16_rn(x)); }
__device__ __forceinline__ float bf_lo(uint32_t w) { return __uint_as_float(w << 16); }
__device__ __forceinline__ float bf_hi(uint32_t w) { return __uint_as_float(w & 0xFFFF0000u); }
__device__ __forceinline__ void bar_sync(int id, int n) { asm volatile("bar.sync %0, %1;" ::"r"(id), "r"(n) : "memory"); }
__device__ __forceinline__ void bar_sync_keep(int id, int n, uint32_t a, uint32_t b) {
    asm volatile("bar.sync %0, %1; // %2 %3" ::"r"(id), "r"(n), "r"(a), "r"(b) : "memory");
}
__device__ __forceinline__ bool bar_red_or(int id, int n, bool p) {
    uint32_t r;
    asm volatile("{.reg .pred p, q; setp.ne.u32 p, %3, 0; bar.red.or.pred q, %1, %2, p; selp.u32 %0, 1, 0, q;}" : "=r"(r) : "r"(id), "r"(n), "r"((uint32_t)p) : "memory");
    return r != 0;
}
__device__ __forceinline__ void bar_arrive(int id, int n) { asm volatile("bar.arrive %0, %1;" ::"r"(id), "r"(n) : "memory"); }
__device__ __forceinline__ void cp_async16(uint32_t dst, const void* src) {
    asm volatile("cp.async.cg.shared.global [%0], [%1], 16;" ::"r"(dst), "l"(src) : "memory");
}
__device__ __forceinline__ void cp_commit() { asm volatile("cp.async.commit_group;" ::: "memory"); }
template <int N> __device__ __forceinline__ void cp_wait() { asm volatile("cp.async.wait_group %0;" ::"n"(N) : "memory"); }
__device__ __forceinline__ uint4 ld_relaxed_v4(const void* p) {
    uint4 v;
    asm volatile("ld.relaxed.gpu.global.v4.u32 {%0,%1,%2,%3}, [%4];" : "=r"(v.x), "=r"(v.y), "=r"(v.z), "=r"(v.w) : "l"(p) : "memory");
    return v;
}
__device__ __forceinline__ void st_relaxed_u32(void* p, uint32_t v) { asm volatile("st.relaxed.gpu.global.u32 [%0], %1;" ::"l"(p), "r"(v) : "memory"); }
__device__ __forceinline__ void st_relaxed_v2(void* p, uint32_t a, uint32_t b) {
    asm volatile("st.relaxed.gpu.global.v2.u32 [%0], {%1,%2};" ::"l"(p), "r"(a), "r"(b) : "memory");
}
__device__ __forceinline__ void sts128(uint32_t a, uint4 v) {
    asm volatile("st.shared.v4.u32 [%0], {%1,%2,%3,%4};" ::"r"(a), "r"(v.x), "r"(v.y), "r"(v.z), "r"(v.w) : "memory");
}
__device__ __forceinline__ uint4 lds128(uint32_t a) {
    uint4 v;
    asm volatile("ld.shared.v4.u32 {%0,%1,%2,%3}, [%4];" : "=r"(v.x), "=r"(v.y), "=r"(v.z), "=r"(v.w) : "r"(a) : "memory");
    return v;
}
__device__ __forceinline__ void sts32(uint32_t a, uint32_t v) { asm volatile("st.shared.u32 [%0], %1;" ::"r"(a), "r"(v) : "memory"); }
__device__ __forceinline__ uint32_t lds32(uint32_t a) {
    uint32_t v;
    asm volatile("ld.shared.u32 %0, [%1];" : "=r"(v) : "r"(a) : "memory");
    return v;
}
__device__ __forceinline__ void mbar_init(uint32_t a, uint32_t c) { asm volatile("mbarrier.init.shared::cta.b64 [%0], %1;" ::"r"(a), "r"(c) : "memory"); }
__device__ __forceinline__ void mbar_expect_tx(uint32_t a, uint32_t bytes) {
    asm volatile("mbarrier.arrive.expect_tx.shared::cta.b64 _, [%0], %1;" ::"r"(a), "r"(bytes) : "memory");
}
__device__ __forceinline__ void mbar_arrive(uint32_t a) { asm volatile("mbarrier.arrive.shared::cta.b64 _, [%0];" ::"r"(a) : "memory"); }
__device__ __forceinline__ void mbar_wait(uint32_t a, uint32_t parity) {
    asm volatile("{.reg .pred p; .reg .u32 c;\n"
                 "mbarrier.try_wait.parity.shared::cta.b64 p, [%0], %1;\n"
                 "@p bra MBW_DONE;\n"
                 "mov.u32 c, 0;\n"
                 "MBW_LOOP:\n"
                 "mbarrier.try_wait.parity.shared::cta.b64 p, [%0], %1;\n"
                 "@p bra MBW_DONE;\n"
                 "add.u32 c, c, 1;\n"
                 "setp.lt.u32 p, c, 0x200000;\n"
                 "@p bra MBW_LOOP;\n"
                 "trap;\n"
                 "MBW_DONE:}" ::"r"(a), "r"(parity) : "memory");
}
__device__ __forceinline__ void bulk_load(uint32_t dst, const void* src, uint32_t bytes, uint32_t bar) {
    asm volatile("cp.async.bulk.shared::cluster.global.mbarrier::complete_tx::bytes [%0], [%1], %2, [%3];" ::"r"(dst), "l"(src), "r"(bytes), "r"(bar) : "memory");
}
__device__ __forceinline__ void tma_load_2d(uint32_t dst, const CUtensorMap* map, int c0, int c1, uint32_t bar) {
    asm volatile("cp.async.bulk.tensor.2d.shared::cluster.global.mbarrier::complete_tx::bytes [%0], [%1, {%3, %4}], [%2];"
                 ::"r"(dst), "l"(map), "r"(bar), "r"(c0), "r"(c1) : "memory");
}
__device__ __forceinline__ uint64_t make_desc(uint32_t saddr, uint32_t lbo, uint32_t sbo) {
    return (uint64_t)((saddr & 0x3FFFF) >> 4) | ((uint64_t)((lbo >> 4) & 0x3FFF) << 16) | ((uint64_t)((sbo >> 4) & 0x3FFF) << 32) | ((uint64_t)1 << 62);
}
__device__ __forceinline__ void wg_fence() { asm volatile("wgmma.fence.sync.aligned;" ::: "memory"); }
__device__ __forceinline__ void wg_commit() { asm volatile("wgmma.commit_group.sync.aligned;" ::: "memory"); }
template <int N> __device__ __forceinline__ void wg_wait() { asm volatile("wgmma.wait_group.sync.aligned %0;" ::"n"(N) : "memory"); }

#define R4(b) "+f"(d[b + 0]), "+f"(d[b + 1]), "+f"(d[b + 2]), "+f"(d[b + 3])
#define R16(b) R4(b), R4(b + 4), R4(b + 8), R4(b + 12)
__device__ __forceinline__ void wgmma_n128(float (&d)[64], uint64_t da, uint64_t db) {
    asm volatile(
        "wgmma.mma_async.sync.aligned.m64n128k16.f32.bf16.bf16 "
        "{%0,%1,%2,%3,%4,%5,%6,%7,%8,%9,%10,%11,%12,%13,%14,%15,%16,%17,%18,%19,%20,%21,%22,%23,%24,%25,%26,%27,%28,%29,%30,%31,"
        "%32,%33,%34,%35,%36,%37,%38,%39,%40,%41,%42,%43,%44,%45,%46,%47,%48,%49,%50,%51,%52,%53,%54,%55,%56,%57,%58,%59,%60,%61,%62,%63},"
        "%64,%65,1,1,1,0,1;"
        : R16(0), R16(16), R16(32), R16(48)
        : "l"(da), "l"(db));
}
__device__ __forceinline__ void wgmma_n256(float (&d)[128], uint64_t da, uint64_t db) {
    asm volatile(
        "wgmma.mma_async.sync.aligned.m64n256k16.f32.bf16.bf16 "
        "{%0,%1,%2,%3,%4,%5,%6,%7,%8,%9,%10,%11,%12,%13,%14,%15,%16,%17,%18,%19,%20,%21,%22,%23,%24,%25,%26,%27,%28,%29,%30,%31,"
        "%32,%33,%34,%35,%36,%37,%38,%39,%40,%41,%42,%43,%44,%45,%46,%47,%48,%49,%50,%51,%52,%53,%54,%55,%56,%57,%58,%59,%60,%61,%62,%63,"
        "%64,%65,%66,%67,%68,%69,%70,%71,%72,%73,%74,%75,%76,%77,%78,%79,%80,%81,%82,%83,%84,%85,%86,%87,%88,%89,%90,%91,%92,%93,%94,%95,"
        "%96,%97,%98,%99,%100,%101,%102,%103,%104,%105,%106,%107,%108,%109,%110,%111,%112,%113,%114,%115,%116,%117,%118,%119,%120,%121,%122,%123,%124,%125,%126,%127},"
        "%128,%129,1,1,1,0,1;"
        : R16(0), R16(16), R16(32), R16(48), R16(64), R16(80), R16(96), R16(112)
        : "l"(da), "l"(db));
}
template <int BN> struct WgAcc;
template <> struct WgAcc<128> { static __device__ __forceinline__ void mma(float (&d)[64], uint64_t a, uint64_t b) { wgmma_n128(d, a, b); } };
template <> struct WgAcc<256> { static __device__ __forceinline__ void mma(float (&d)[128], uint64_t a, uint64_t b) { wgmma_n256(d, a, b); } };

__device__ __forceinline__ void wgmma_rs32(float (&d)[16], const uint32_t (&a)[4], uint64_t db, bool acc) {
    asm volatile(
        "{.reg .pred p; setp.ne.b32 p, %21, 0;\n"
        "wgmma.mma_async.sync.aligned.m64n32k16.f32.bf16.bf16 {%0,%1,%2,%3,%4,%5,%6,%7,%8,%9,%10,%11,%12,%13,%14,%15}, {%16,%17,%18,%19}, %20, p, 1, 1, 0;}"
        : R16(0) : "r"(a[0]), "r"(a[1]), "r"(a[2]), "r"(a[3]), "l"(db), "n"(1) );
}
__device__ __forceinline__ void wgmma_rs32_first(float (&d)[16], const uint32_t (&a)[4], uint64_t db) {
    asm volatile(
        "{.reg .pred p; setp.ne.b32 p, %21, 0;\n"
        "wgmma.mma_async.sync.aligned.m64n32k16.f32.bf16.bf16 {%0,%1,%2,%3,%4,%5,%6,%7,%8,%9,%10,%11,%12,%13,%14,%15}, {%16,%17,%18,%19}, %20, p, 1, 1, 0;}"
        : R16(0) : "r"(a[0]), "r"(a[1]), "r"(a[2]), "r"(a[3]), "l"(db), "n"(0) );
}
__device__ __forceinline__ void wgmma_ss32(float (&d)[16], uint64_t da, uint64_t db) {
    asm volatile(
        "wgmma.mma_async.sync.aligned.m64n32k16.f32.bf16.bf16 {%0,%1,%2,%3,%4,%5,%6,%7,%8,%9,%10,%11,%12,%13,%14,%15}, %16, %17, 1, 1, 1, 1, 0;"
        : R16(0) : "l"(da), "l"(db));
}
__device__ __forceinline__ void st_async4(uint32_t a, float x, float y, float z, float w, uint32_t bar) {
    asm volatile("st.async.weak.shared::cluster.mbarrier::complete_tx::bytes.v4.f32 [%0], {%1,%2,%3,%4}, [%5];" ::"r"(a), "f"(x), "f"(y), "f"(z), "f"(w), "r"(bar) : "memory");
}
__device__ __forceinline__ void st_async2(uint32_t a, float x, float y, uint32_t bar) {
    asm volatile("st.async.weak.shared::cluster.mbarrier::complete_tx::bytes.v2.f32 [%0], {%1,%2}, [%3];" ::"r"(a), "f"(x), "f"(y), "r"(bar) : "memory");
}
__device__ __forceinline__ void st_async1(uint32_t a, uint32_t x, uint32_t bar) {
    asm volatile("st.async.weak.shared::cluster.mbarrier::complete_tx::bytes.b32 [%0], %1, [%2];" ::"r"(a), "r"(x), "r"(bar) : "memory");
}
__device__ __forceinline__ void stsm4t(uint32_t a, uint32_t r0, uint32_t r1, uint32_t r2, uint32_t r3) {
    asm volatile("stmatrix.sync.aligned.m8n8.x4.trans.shared.b16 [%0], {%1,%2,%3,%4};" ::"r"(a), "r"(r0), "r"(r1), "r"(r2), "r"(r3) : "memory");
}
__device__ __forceinline__ void ldsm4t(uint32_t (&r)[4], uint32_t a) { ldsm4t(r[0], r[1], r[2], r[3], a); }
__device__ __forceinline__ void ldsm4(uint32_t (&r)[4], uint32_t a) { ldsm4(r[0], r[1], r[2], r[3], a); }
__device__ __forceinline__ void mma16816(float (&d)[4], const uint32_t (&a)[4], uint32_t b0, uint32_t b1) { mma16816(d, a[0], a[1], a[2], a[3], b0, b1); }
__device__ __forceinline__ void sched_fence(uint32_t v) {
    asm volatile("{.reg .pred p; setp.ne.u32 p, %0, 0xFFFFFFFF; @p bra.uni SF_OK; trap; SF_OK:}" ::"r"(v) : "memory");
}
__device__ __forceinline__ void mma16816v(float (&d)[4], const uint32_t (&a)[4], uint32_t b0, uint32_t b1) {
    asm volatile("mma.sync.aligned.m16n8k16.row.col.f32.bf16.bf16.f32 {%0,%1,%2,%3},{%4,%5,%6,%7},{%8,%9},{%0,%1,%2,%3};"
                 : "+f"(d[0]), "+f"(d[1]), "+f"(d[2]), "+f"(d[3]) : "r"(a[0]), "r"(a[1]), "r"(a[2]), "r"(a[3]), "r"(b0), "r"(b1));
}
__device__ __forceinline__ uint32_t uniform(uint32_t v) { return __reduce_max_sync(~0u, v); }

template <int BN, int STAGES> struct GemmCfg {
    static constexpr int A_BYTES = 128 * 64 * 2;
    static constexpr int B_BYTES = BN * 64 * 2;
    static constexpr int STAGE_BYTES = A_BYTES + B_BYTES;
    static constexpr int EPI_BYTES = 128 * BN * 2;
    static constexpr int SMEM = STAGES * STAGE_BYTES + EPI_BYTES + 1024 + 256;
};

template <int BN, int STAGES>
__global__ void __cluster_dims__(2, 1, 1) __launch_bounds__(288, 1)
gemm_kernel(const __grid_constant__ CUtensorMap mapA, const __grid_constant__ CUtensorMap mapB0, const __grid_constant__ CUtensorMap mapB1,
            const __grid_constant__ CUtensorMap mapB2, const __grid_constant__ CUtensorMap mapC, int tiles_m, int tiles_n, int kblocks) {
    using Cfg = GemmCfg<BN, STAGES>;
    KT_START(BN == 256 ? 0 : 3);
    extern __shared__ uint8_t smem_raw[];
    const uint32_t sbase = (smem_u32(smem_raw) + 1023) & ~1023u;
    const uint32_t epi = sbase + STAGES * Cfg::STAGE_BYTES;
    const uint32_t bars = epi + Cfg::EPI_BYTES;
    const int warp = threadIdx.x >> 5, lane = threadIdx.x & 31;
    const uint32_t rank = blockIdx.x & 1;
    if (threadIdx.x == 0) {
        for (int i = 0; i < STAGES; i++) { mbar_init(bars + 8 * i, 1); mbar_init(bars + 8 * (STAGES + i), 16); }
        asm volatile("fence.mbarrier_init.release.cluster;" ::: "memory");
    }
    __syncthreads();
    asm volatile("barrier.cluster.arrive.release.aligned; barrier.cluster.wait.acquire.aligned;" ::: "memory");
    const int npairs = (tiles_m >> 1) * tiles_n, ncl = gridDim.x >> 1;
    if (warp == 8) {
        if (lane == 0) {
            int st = 0; uint32_t ph = 1;
            for (int pr = blockIdx.x >> 1; pr < npairs; pr += ncl) {
                const int tm = 2 * (pr % (tiles_m >> 1)) + rank, tn = pr / (tiles_m >> 1);
                const int n0 = tn * BN;
                const CUtensorMap* mb = (n0 < 4096) ? &mapB0 : (n0 < 8192 ? &mapB1 : &mapB2);
                const int nb = n0 & 4095;
                for (int kb = 0; kb < kblocks; kb++) {
                    mbar_wait(bars + 8 * (STAGES + st), ph);
                    const uint32_t full = bars + 8 * st;
                    mbar_expect_tx(full, Cfg::STAGE_BYTES);
                    const uint32_t sa = sbase + st * Cfg::STAGE_BYTES;
                    tma_load_2d(sa, &mapA, kb * 64, tm * 128, full);
#pragma unroll
                    for (int i = 0; i < BN / 128; i++) {
                        const int bx = rank * (BN / 128) + i;
                        asm volatile("cp.async.bulk.tensor.2d.shared::cluster.global.mbarrier::complete_tx::bytes.multicast::cluster [%0], [%1, {%3, %4}], [%2], %5;"
                                     ::"r"(sa + Cfg::A_BYTES + bx * 8192), "l"(mb), "r"(full), "r"(nb + bx * 64), "r"(kb * 64), "h"((uint16_t)3) : "memory");
                    }
                    if (++st == STAGES) { st = 0; ph ^= 1; }
                }
            }
        }
    } else {
        const int wg = warp >> 2;
        uint32_t peer_empty;
        asm volatile("mapa.shared::cluster.u32 %0, %1, %2;" : "=r"(peer_empty) : "r"(bars + 8 * STAGES), "r"(rank ^ 1));
        auto release = [&](int stg) {
            if (lane == 0) {
                mbar_arrive(bars + 8 * (STAGES + stg));
                asm volatile("mbarrier.arrive.shared::cluster.b64 _, [%0];" ::"r"(peer_empty + 8 * stg) : "memory");
            }
        };
        const uint32_t ew = epi + wg * (64 * BN * 2);
        int st = 0; uint32_t ph = 0;
        for (int pr = blockIdx.x >> 1; pr < npairs; pr += ncl) {
            const int tm = 2 * (pr % (tiles_m >> 1)) + rank, tn = pr / (tiles_m >> 1);
            float d[BN / 2];
#pragma unroll
            for (int i = 0; i < BN / 2; i++) d[i] = 0.f;
            int prev = -1;
            for (int kb = 0; kb < kblocks; kb++) {
                mbar_wait(bars + 8 * st, ph);
                const uint32_t sa = sbase + st * Cfg::STAGE_BYTES;
                const uint64_t da = make_desc(sa + wg * 8192, 16, 1024);
                const uint64_t db = make_desc(sa + Cfg::A_BYTES, 8192, 1024);
                wg_fence();
#pragma unroll
                for (int k = 0; k < 4; k++) WgAcc<BN>::mma(d, da + k * 2, db + k * 128);
                wg_commit();
                if (prev >= 0) { wg_wait<1>(); release(prev); }
                prev = st;
                if (++st == STAGES) { st = 0; ph ^= 1; }
            }
            wg_wait<0>();
            release(prev);
            if ((warp & 3) == 0 && lane == 0) asm volatile("cp.async.bulk.wait_group.read 0;" ::: "memory");
            bar_sync(1 + wg, 128);
            const int r = (warp & 3) * 16 + (lane & 7) + ((lane >> 3) & 1) * 8;
#pragma unroll
            for (int c = 0; c < BN / 64; c++)
#pragma unroll
                for (int i = 0; i < 4; i++) {
                    const int b = (c * 8 + i * 2) * 4;
                    stsm4(ew + c * 8192 + r * 128 + (((i * 2 + (lane >> 4)) ^ (r & 7)) * 16), pack_bf16(d[b], d[b + 1]), pack_bf16(d[b + 2], d[b + 3]),
                          pack_bf16(d[b + 4], d[b + 5]), pack_bf16(d[b + 6], d[b + 7]));
                }
            asm volatile("fence.proxy.async.shared::cta;" ::: "memory");
            bar_sync(1 + wg, 128);
            if ((warp & 3) == 0 && lane == 0) {
#pragma unroll
                for (int c = 0; c < BN / 64; c++)
                    asm volatile("cp.async.bulk.tensor.2d.global.shared::cta.bulk_group [%0, {%2, %3}], [%1];"
                                 ::"l"(&mapC), "r"(ew + c * 8192), "r"(tn * BN + c * 64), "r"(tm * 128 + wg * 64) : "memory");
                asm volatile("cp.async.bulk.commit_group;" ::: "memory");
            }
        }
        if ((warp & 3) == 0 && lane == 0) asm volatile("cp.async.bulk.wait_group 0;" ::: "memory");
    }
    __syncwarp();
    KT_END(BN == 256 ? 0 : 3);
    asm volatile("barrier.cluster.arrive.relaxed; barrier.cluster.wait;" ::: "memory");
}

#define WO_RF1 8
constexpr int SM_KV0 = 0, SM_KV1 = 16384;
constexpr int SM_XT = 32768;
constexpr int SM_STG = 65536;
constexpr int SM_QX = SM_STG + 6144;
constexpr int SM_Z = SM_QX + 2048;
constexpr int SM_RT = SM_Z + 8192;
constexpr int SM_QKV = SM_RT + 12288;
constexpr int SM_R1 = SM_QKV + 6144;
constexpr int SM_R2 = SM_R1 + 2048;
constexpr int SM_O = SM_R2 + 1024;
constexpr int SM_S = SM_O + 2048;
constexpr int SM_TO = SM_S + 1024;
constexpr int SM_WORK_END = SM_TO + 2560;
constexpr int STG_QK = 0, STG_V = 98304;
constexpr int STG_WO = STG_V;
constexpr int SM_WO1 = STG_WO + 16384;
constexpr int SM_WQK = 147456;
constexpr int SM_WV = SM_WQK + 32768;
constexpr int SM_WO2 = SM_WV + 16384;
constexpr int SM_BARS = SM_WO2 + 32768;
enum { MB_W0 = SM_BARS, MB_W1 = SM_BARS + 8, MB_W2 = SM_BARS + 16, MB_W3 = SM_BARS + 24, MB_XT = SM_BARS + 32  , MB_KV = SM_BARS + 48  ,
       MB_Q = SM_BARS + 64, MB_R1 = SM_BARS + 72, MB_R2 = SM_BARS + 80, MB_RT0 = SM_BARS + 88, MB_RT1 = SM_BARS + 96, MB_FREE = SM_BARS + 104,
       MB_P = SM_BARS + 112, MB_V = SM_BARS + 120, MB_STG = SM_BARS + 128, SM_ROLE = SM_BARS + 136, SM_TL = SM_BARS + 144 };
constexpr int CHAIN_SMEM = SM_TL + 128;
static_assert(SM_WORK_END <= SM_WO1, "work area");
static_assert(CHAIN_SMEM <= 232448, "smem");

#define DLY_X 200
#define DLY_V 0
#define DLY_Y 250
#define DLY_Z 200
#define XFLIP 0
#define YFLIP 0
#define ZFLIP 1
#define GO_AT 13
#define REG_A 240
#define REG_B 208
#define REG_C (3 * 168 - REG_A - REG_B)
__host__ __device__ constexpr bool k_in_smem(int k) { return (k & 3) == 1; }
__host__ __device__ constexpr int k_reg_idx(int k) { return k_in_smem(k) ? 0 : k - (k + 2) / 4; }

enum { BAR_MEM = 1, BAR_GO, BAR_PUB, BAR_QK, BAR_S, BAR_O, BAR_SENT, BAR_COMM, BAR_T, BAR_PV, BAR_PDONE };

__device__ __forceinline__ uint32_t umax4(const uint4& v) { return max(max(v.x, v.y), max(v.z, v.w)); }
__device__ __forceinline__ unsigned gtime() { unsigned t; asm volatile("mov.u32 %0, %%globaltimer_lo;" : "=r"(t)::"memory"); return t; }
__device__ __forceinline__ unsigned clock32() { unsigned t; asm volatile("mov.u32 %0, %%clock;" : "=r"(t)::"memory"); return t; }
__device__ __forceinline__ void spin_cycles(int d) {
    if (d > 0) { const unsigned c0 = clock32(); while (clock32() - c0 < (unsigned)d) {} }
}
__device__ __forceinline__ float ex2_approx(float x) { float y; asm("ex2.approx.ftz.f32 %0, %1;" : "=f"(y) : "f"(x)); return y; }
__device__ __forceinline__ float rcp_approx(float x) { float y; asm("rcp.approx.ftz.f32 %0, %1;" : "=f"(y) : "f"(x)); return y; }
__device__ __forceinline__ void st_sent(const void* p) { asm volatile("st.relaxed.gpu.global.v4.u32 [%0], {%1,%1,%1,%1};" ::"l"(p), "r"(SENT) : "memory"); }
__device__ __forceinline__ uint4 poll1(const char* p) {
    uint4 v = ld_relaxed_v4(p);
    int guard = 0;
    while (umax4(v) == SENT) {
        if (++guard > (1 << 20)) __trap();
        v = ld_relaxed_v4(p);
    }
    return v;
}
template <class F> __device__ __forceinline__ void softmax40(uint32_t (&pw)[5], uint32_t sa, F mid) {
    const float LOG2E = 1.4426950408889634f;
    float e[10];
#pragma unroll
    for (int i = 0; i < 5; i++) {
        const uint32_t w = lds32(sa + i * 128);
        e[2 * i] = bf_lo(w); e[2 * i + 1] = bf_hi(w);
    }
    mid();
    float m = fmaxf(fmaxf(fmaxf(e[0], e[1]), fmaxf(e[2], e[3])), fmaxf(fmaxf(fmaxf(e[4], e[5]), fmaxf(e[6], e[7])), fmaxf(e[8], e[9])));
    m = fmaxf(m, __shfl_xor_sync(~0u, m, 1));
    m = fmaxf(m, __shfl_xor_sync(~0u, m, 2));
    const float mb2 = m * LOG2E;
#pragma unroll
    for (int i = 0; i < 10; i++) e[i] = ex2_approx(fmaf(e[i], LOG2E, -mb2));
    float sum = (((e[0] + e[1]) + (e[2] + e[3])) + ((e[4] + e[5]) + (e[6] + e[7]))) + (e[8] + e[9]);
    sum += __shfl_xor_sync(~0u, sum, 1);
    sum += __shfl_xor_sync(~0u, sum, 2);
    const float inv = rcp_approx(sum);
#pragma unroll
    for (int i = 0; i < 5; i++) pw[i] = pack_bf16(e[2 * i] * inv, e[2 * i + 1] * inv);
}
__device__ __forceinline__ uint32_t scale_scores(const float (&a)[4], const float (&b)[4]) {
    const float scale = 0.08838834764831845f;
    const uint32_t w = pack_bf16(a[0] + b[0], a[1] + b[1]);
    return pack_bf16(bf_lo(w) * scale, bf_hi(w) * scale);
}

__device__ __forceinline__ uint32_t peer_addr(uint32_t a, uint32_t rank) {
    uint32_t r;
    asm("mapa.shared::cluster.u32 %0, %1, %2;" : "=r"(r) : "r"(a), "r"(rank));
    return r;
}

#define TL(i) do {} while (0)
#define TLDUMP() do {} while (0)

__global__ void __cluster_dims__(2, 1, 1) __launch_bounds__(384, 1)
chain_kernel(const __grid_constant__ CUtensorMap mapX, const __grid_constant__ CUtensorMap mapT32, const __grid_constant__ CUtensorMap mapT8,
             const __grid_constant__ CUtensorMap mapWq, const __grid_constant__ CUtensorMap mapWk, const __grid_constant__ CUtensorMap mapWv,
             const __grid_constant__ CUtensorMap mapWo, const bf16* __restrict__ mem0, char* __restrict__ mbox) {
    KT_START(2);
    extern __shared__ __align__(1024) uint8_t smem_chain[];
    constexpr uint32_t SB0 = 1024;
    if ((smem_u32(smem_chain) & 0xFFFFFF) != SB0) __trap();
    const int kh = blockIdx.x & 1;
    if (threadIdx.x == 0) {
        const uint32_t sb = smem_u32(smem_chain);
        for (int i = 0; i < 14; i++) mbar_init(sb + SM_BARS + 8 * i, 1);
        mbar_init(sb + MB_P, 4); mbar_init(sb + MB_V, 6); mbar_init(sb + MB_STG, 8);
        asm volatile("fence.mbarrier_init.release.cluster;" ::: "memory");
        if (kh == 0) {
            unsigned smid, ncl = gridDim.x >> 1;
            asm volatile("mov.u32 %0, %%smid;" : "=r"(smid));
            const unsigned c = g_cls[smid] & 1, i = atomicAdd(&g_reg[c], 1u);
            unsigned p = c * 32 + i;
            if (i >= 32) {
                unsigned n0, n1; int guard = 0;
                do {
                    asm volatile("ld.relaxed.gpu.global.u32 %0, [%1];" : "=r"(n0) : "l"(g_reg) : "memory");
                    asm volatile("ld.relaxed.gpu.global.u32 %0, [%1];" : "=r"(n1) : "l"(g_reg + 1) : "memory");
                } while (n0 + n1 < ncl && ++guard < (1 << 20));
                const unsigned k = (c ? n0 : n1) + i - 32;
                p = k < 32 ? (c ^ 1) * 32 + k : 64;
            }
            p |= g_reg[2] << 8;
            uint32_t ra;
            asm volatile("mapa.shared::cluster.u32 %0, %1, 1;" : "=r"(ra) : "r"(sb + SM_ROLE));
            asm volatile("st.shared::cluster.u32 [%0], %1;" ::"r"(ra), "r"(p) : "memory");
            sts32(sb + SM_ROLE, p);
        }
    }
    __syncthreads();
    asm volatile("barrier.cluster.arrive.release.aligned; barrier.cluster.wait.acquire.aligned;" ::: "memory");
    const uint32_t rw = uniform(lds32(smem_u32(smem_chain) + SM_ROLE));
    const int pair = rw & 255, yflip = (rw >> 8) ^ YFLIP;
    if (pair >= 64) return;
    const int h = pair >> 1, nh = pair & 1, j = 2 * nh + kh, role = 2 * pair + kh;
    const int warp = uniform(threadIdx.x >> 5);
    const uint32_t id = (threadIdx.x & 127) | (kh << 7) | (pair << 8) | ((yflip & 1) << 14);
#define PHASE() const uint32_t me = __shfl_sync(~0u, id, id); const int ln = me & 31, g = (me >> 5) & 3, kh = (me >> 7) & 1, nh = (me >> 8) & 1, h = (me >> 9) & 31, yflip = me >> 14; \
    const bool lead = __all_sync(~0u, g == 0); const uint32_t rsb = peer_addr(SB0, kh ^ 1), sb = peer_addr(SB0, kh), frag = ((ln & 7) + (ln >> 4) * 8) * 128 + (((2 * g + ((ln >> 3) & 1)) ^ (ln & 7)) * 16); \
    (void)nh; (void)h; (void)yflip; (void)lead; (void)rsb; (void)sb; (void)frag
#define XBOX() (mbox + (WIN + page_off((me >> 8) & 31, ((me >> 13) & 1) ^ XFLIP) + ((s & 3) << 14)))
    if (warp >= 8) {
        asm volatile("setmaxnreg.dec.sync.aligned.u32 %0;" ::"n"(REG_C));
        const int lane = __shfl_sync(~0u, (int)(threadIdx.x & 31), threadIdx.x & 31), g = warp & 3;
        const uint32_t rsb = peer_addr(SB0, kh ^ 1), sb = peer_addr(SB0, kh);
        char* const xbox = mbox + WIN + page_off(pair & 31, (pair >> 5) ^ XFLIP);
        const int ct = g * 32 + lane;
        if (warp == 8) {
            const CUtensorMap* ws = kh ? &mapWq : &mapWk;
            const CUtensorMap* wn = kh ? &mapWk : &mapWq;
            const int col = h * DH + 64 * nh, row = 512 * kh;
            if (lane == 0) { mbar_expect_tx(sb + MB_W0, 49152); mbar_expect_tx(sb + MB_W1, 98304); mbar_expect_tx(sb + MB_W2, 81920); mbar_expect_tx(sb + MB_W3, 32768); }
            __syncwarp();
            if (lane < 24) {
                const int k = lane + (lane + 2) / 3;
                tma_load_2d(sb + STG_V + lane * 2048, &mapWv, col, row + 16 * k, sb + MB_W0);
                tma_load_2d(sb + STG_QK + lane * 2048, ws, col, row + 16 * k, sb + MB_W1);
                tma_load_2d(sb + STG_QK + (24 + lane) * 2048, wn, col, row + 16 * k, sb + MB_W1);
            }
            if (lane < 8) {
                const int k = 4 * lane + 1;
                tma_load_2d(sb + SM_WQK + lane * 4096, ws, col, row + 16 * k, sb + MB_W2);
                tma_load_2d(sb + SM_WQK + lane * 4096 + 2048, wn, col, row + 16 * k, sb + MB_W2);
                tma_load_2d(sb + SM_WV + lane * 2048, &mapWv, col, row + 16 * k, sb + MB_W2);
            }
            if (lane < 2) tma_load_2d(sb + SM_WO2 + lane * 16384, &mapWo, 256 * j + 128 + 64 * lane, h * DH, sb + MB_W2);
            __syncwarp();
            bar_sync(BAR_PV, 160);
            if (lane < 2) tma_load_2d(sb + STG_WO + lane * 16384, &mapWo, 256 * j + 64 * lane, h * DH, sb + MB_W3);
            __syncwarp();
        }
        bar_sync(BAR_PDONE, 384);
        for (int c = ct; c < 512; c += 128) {
            uint32_t w[4];
#pragma unroll
            for (int r = 0; r < 4; r++) {
                const uint32_t lo = reinterpret_cast<const uint16_t*>(mem0)[(2 * r) * DM + 512 * kh + c], hi = reinterpret_cast<const uint16_t*>(mem0)[(2 * r + 1) * DM + 512 * kh + c];
                w[r] = lo | (hi << 16);
            }
            sts128(sb + SM_Z + c * 16, make_uint4(w[0], w[1], w[2], w[3]));
        }
        auto load_xt = [&](int seg, int half) {
            mbar_expect_tx(sb + MB_XT + half * 8, 16384);
            asm volatile("cp.async.bulk.tensor.3d.shared::cluster.global.mbarrier::complete_tx::bytes [%0], [%1, {%3, %4, %5}], [%2];"
                         ::"r"(sb + SM_XT + half * 16384), "l"(&mapX), "r"(sb + MB_XT + half * 8), "r"(0), "r"(seg * SEG), "r"(8 * kh + 4 * half) : "memory");
        };
        auto tok_start = [&](int s) {
            if (lane == 0) {
                if (s > -3 && s + 2 < NSEG) {
                    mbar_wait(sb + MB_STG, (s + 2) & 1);
                    const int row = (((s + 2) & 3) * NH + h) * 96;
                    asm volatile("cp.async.bulk.tensor.2d.global.shared::cta.bulk_group [%0, {%2, %3}], [%1];" ::"l"(&mapT32), "r"(sb + SM_STG), "r"(64 * nh), "r"(row + 32 * kh) : "memory");
#pragma unroll
                    for (int i = 0; i < 2; i++)
                        asm volatile("cp.async.bulk.tensor.2d.global.shared::cta.bulk_group [%0, {%2, %3}], [%1];" ::"l"(&mapT8), "r"(sb + SM_STG + 4096 + i * 1024), "r"(64 * nh), "r"(row + 64 + 16 * kh + 8 * i) : "memory");
                    asm volatile("cp.async.bulk.commit_group;" ::: "memory");
                    asm volatile("cp.async.bulk.wait_group.read 0;" ::: "memory");
                }
                if (s < 0) {
                    asm volatile("mbarrier.arrive.shared::cluster.b64 _, [%0];" ::"r"(rsb + MB_FREE) : "memory");
                    mbar_wait(sb + MB_FREE, (s + 3) & 1);
                }
                if (s + 3 < NSEG) load_xt(s + 3, 0);
            }
            __syncwarp();
        };
        auto tok_mid = [&](int s) {
            if (lane == 0 && s + 3 < NSEG) load_xt(s + 3, 1);
            if (s + 1 >= 0 && s + 1 < NSEG) {
                if (lane < 4) {
                    unsigned f; int guard = 0;
                    do { asm volatile("ld.acquire.gpu.global.u32 %0, [%1];" : "=r"(f) : "l"(g_xflag + h * 4 + lane) : "memory"); } while (f <= (unsigned)(s + 1) && ++guard < (1 << 20));
                    if (f <= (unsigned)(s + 1)) __trap();
                }
                __syncwarp();
                if (lane == 0) {
                    asm volatile("fence.proxy.async;" ::: "memory");
                    const uint32_t bar = sb + MB_KV + ((s + 1) & 1) * 8, dst = sb + (((s + 1) & 1) ? SM_KV1 : SM_KV0) + kh * 8192;
                    mbar_expect_tx(bar, 16384);
#pragma unroll
                    for (int i = 0; i < 2; i++)
                        asm volatile("cp.async.bulk.tensor.2d.shared::cluster.global.mbarrier::complete_tx::bytes.multicast::cluster [%0], [%1, {%3, %4}], [%2], %5;"
                                     ::"r"(dst + i * 4096), "l"(&mapT32), "r"(bar), "r"(i * 64), "r"((((s + 1) & 3) * NH + h) * 96 + 32 + 32 * kh), "h"((uint16_t)3) : "memory");
                }
            }
            if (lane == 0) {
                if (s >= 0) {
                    mbar_expect_tx(sb + MB_Q, 2048);
#pragma unroll
                    for (int i = 0; i < 2; i++) tma_load_2d(sb + SM_QX + i * 1024, &mapT8, i * 64, ((s & 3) * NH + h) * 96 + 8 * j, sb + MB_Q);
                }
                if (s > -3 && s + 2 < NSEG) {
                    asm volatile("cp.async.bulk.wait_group 0;" ::: "memory");
                    asm volatile("fence.proxy.async;" ::: "memory");
                    asm volatile("fence.acq_rel.gpu;" ::: "memory");
                    st_relaxed_u32(g_xflag + role, s + 3);
                }
            }
            __syncwarp();
        };
        if (warp == 9) {
#pragma unroll 1
            for (int s = -3; s < 0; s++) { tok_start(s); tok_mid(s); }
        }
        bar_arrive(BAR_MEM, 384);
        const int c = role >> 6, idx = role & 63;
        const char* const ybox = mbox + page_off(idx, c ^ yflip);
        char* const zline = mbox + WIN + page_off(32 + (idx >> 5), c ^ ZFLIP) + (idx & 31) * 128;
        const char* const xsrc = mbox + WIN + page_off((pair ^ 1) & 31, (pair >> 5) ^ XFLIP) + ct * 16;
        const char* const zsrc = mbox + WIN + page_off(32 + kh, ZFLIP) + ct * 16;
        const int zo = (page_off(32 + kh, ZFLIP) & 4096) ? -4096 : 4096;
        const uint32_t xdst = sb + SM_QKV + (nh ^ 1) * 1024 + (ct >> 6) * 2048 + (ct & 63) * 16;
        auto get_qk = [&](int s) {
            const char* p = xsrc + ((s & 3) << 14);
            asm volatile("" ::"l"(p));
            bar_sync(BAR_PUB, 256);
            spin_cycles(DLY_X);
            sts128(xdst, poll1(p));
            bar_arrive(BAR_QK, s + 1 < NSEG ? 288 : 256);
        };
        auto get_v = [&](int s) {
            const int vc = (g & 1) * 32 + lane - ct;
            spin_cycles(DLY_V);
            sts128(sb + SM_QKV + 4096 + (nh ^ 1) * 1024 + (ct + vc) * 16, poll1(xsrc + ((s & 3) << 14) + 2048 + vc * 16));
            __syncwarp();
            if (lane == 0) mbar_arrive(sb + MB_V);
        };
        auto get_z = [&](int s) {
            const char* z0 = zsrc + (((s + 1) & 3) << 14);
            const char* z1 = z0 + zo;
            asm volatile("" ::"l"(z0), "l"(z1));
            bar_sync(BAR_COMM, 128);
            spin_cycles(DLY_Z);
            uint4 v[4];
            v[0] = ld_relaxed_v4(z0); v[1] = ld_relaxed_v4(z0 + 2048); v[2] = ld_relaxed_v4(z1); v[3] = ld_relaxed_v4(z1 + 2048);
            int guard = 0;
            while (max(max(umax4(v[0]), umax4(v[1])), max(umax4(v[2]), umax4(v[3]))) == SENT) {
                if (++guard > (1 << 20)) __trap();
                if (umax4(v[0]) == SENT) v[0] = ld_relaxed_v4(z0);
                if (umax4(v[1]) == SENT) v[1] = ld_relaxed_v4(z0 + 2048);
                if (umax4(v[2]) == SENT) v[2] = ld_relaxed_v4(z1);
                if (umax4(v[3]) == SENT) v[3] = ld_relaxed_v4(z1 + 2048);
            }
            STAT(0, __any_sync(~0u, guard > 0) && warp == 8);
#pragma unroll
            for (int i = 0; i < 4; i++) sts128(sb + SM_Z + ct * 16 + i * 2048, v[i]);
            bar_arrive(BAR_MEM, 384);
        };
        if (warp == 8) {
#pragma unroll 1
            for (int s = 0; s < NSEG; s++) {
                get_qk(s);
                TL(16);
                get_v(s);
                TL(17);
                if (s + 1 == NSEG) break;
                const uint32_t b0 = (lane >> 2 == 0) ? 0x00003F80u : (lane >> 2 == 1 ? 0x3F800000u : 0u), b1 = (lane >> 2 == 2) ? 0x00003F80u : (lane >> 2 == 3 ? 0x3F800000u : 0u);
                const char* ycur = ybox + ((s & 3) << 14) + (lane & 3) * 128 + (lane >> 2) * 16;
                char* zdst = zline + (((s + 1) & 3) << 14) + (lane >> 2) * 16 + (lane & 1) * 8;
                asm volatile("" ::"l"(ycur), "l"(zdst));
                bar_sync(BAR_SENT, 288);
                spin_cycles(DLY_Y);
                uint4 v[8];
                uint32_t m = 0;
#pragma unroll
                for (int i = 0; i < 8; i++) v[i] = ld_relaxed_v4(ycur + i * 512);
#pragma unroll
                for (int i = 0; i < 8; i++) m = max(m, umax4(v[i]));
                if (__any_sync(~0u, m == SENT)) {
                    int guard = 0;
                    do {
#pragma unroll
                        for (int i = 0; i < 8; i++)
                            if (umax4(v[i]) == SENT) v[i] = ld_relaxed_v4(ycur + i * 512);
                        m = 0;
#pragma unroll
                        for (int i = 0; i < 8; i++) m = max(m, umax4(v[i]));
                        if (++guard > (1 << 20)) __trap();
                    } while (m == SENT);
                    __syncwarp();
                    STAT(2, true);
                }
                TL(18);
                float d0[4] = {0.f, 0.f, 0.f, 0.f}, d1[4] = {0.f, 0.f, 0.f, 0.f}, d2[4] = {0.f, 0.f, 0.f, 0.f}, d3[4] = {0.f, 0.f, 0.f, 0.f};
                mma16816(d0, v[0].x, v[0].y, v[0].z, v[0].w, b0, b1);
                mma16816(d1, v[1].x, v[1].y, v[1].z, v[1].w, b0, b1);
                mma16816(d2, v[2].x, v[2].y, v[2].z, v[2].w, b0, b1);
                mma16816(d3, v[3].x, v[3].y, v[3].z, v[3].w, b0, b1);
                mma16816(d0, v[4].x, v[4].y, v[4].z, v[4].w, b0, b1);
                mma16816(d1, v[5].x, v[5].y, v[5].z, v[5].w, b0, b1);
                mma16816(d2, v[6].x, v[6].y, v[6].z, v[6].w, b0, b1);
                mma16816(d3, v[7].x, v[7].y, v[7].z, v[7].w, b0, b1);
                if ((lane & 3) < 2) {
                    const uint32_t w0 = pack_bf16((d0[0] + d1[0]) + (d2[0] + d3[0]), (d0[1] + d1[1]) + (d2[1] + d3[1]));
                    const uint32_t w1 = pack_bf16((d0[2] + d1[2]) + (d2[2] + d3[2]), (d0[3] + d1[3]) + (d2[3] + d3[3]));
                    st_relaxed_v2(zdst, w0, w1);
                }
                TL(19);
                get_z(s);
                TL(20);
            }
        } else if (warp == 9) {
#pragma unroll 1
            for (int s = 0; s < NSEG; s++) {
                tok_start(s);
                get_qk(s);
                tok_mid(s);
                TL(22);
                if (s + 1 == NSEG) break;
                get_z(s);
            }
        } else if (warp == 10) {
#pragma unroll 1
            for (int s = 0; s < NSEG; s++) {
                TLDUMP();
                get_qk(s);
                if (s >= 1) {
                    const uint32_t sp = ((s - 1) & 3) << 14;
#pragma unroll
                    for (int i = 0; i < 8; i++) st_sent(ybox + sp + (i * 32 + lane) * 16);
                    st_sent(xbox + sp + kh * 1024 + lane * 16);
                    st_sent(xbox + sp + kh * 1024 + 512 + lane * 16);
                    st_sent(xbox + sp + 2048 + ((lane >> 3) * 2 + kh) * 128 + (lane & 7) * 16);
                    if (lane < 8) st_sent(zline + sp + lane * 16);
                    asm volatile("fence.acq_rel.gpu;" ::: "memory");
                    TL(23);
                }
                if (s + 1 == NSEG) break;
                get_z(s);
            }
        } else {
#pragma unroll 1
            for (int s = 0; s < NSEG; s++) {
                get_qk(s);
                get_v(s);
                if (s + 1 == NSEG) break;
                get_z(s);
            }
        }
    } else if (warp < 4) {
        asm volatile("setmaxnreg.inc.sync.aligned.u32 %0;" ::"n"(REG_A));
        uint32_t wa[2][24][4];
        {
            PHASE();
            const uint32_t fa = sb + frag;
            mbar_wait(sb + MB_W1, 0);
#pragma unroll
            for (int t = 0; t < 2; t++)
#pragma unroll
                for (int r = 0; r < 24; r++) ldsm4t(wa[t][r], fa + STG_QK + (t * 24 + r) * 2048);
            mbar_wait(sb + MB_W2, 0);
            bar_arrive(BAR_PDONE, 384);
        }
#pragma unroll 1
        for (int s = -3; s < NSEG; s++) {
            if (s >= 0) {
                {
                    PHASE();
                    const uint32_t aw = sb + SM_WQK + frag;
                    const uint32_t l16 = ln * 16, mb = sb + SM_Z + l16;
                    uint32_t pre[2][4];
                    ldsm4t(pre[0], aw); ldsm4t(pre[1], aw + 2048);
                    if (g == 0 && ln == 0) mbar_expect_tx(sb + MB_R1, 2048);
                    bar_sync_keep(BAR_MEM, 384, mb, aw);
                    if (lead) TL(0);
                    float acc[2][2][4];
#pragma unroll
                    for (int t = 0; t < 4; t++) { acc[t >> 1][t & 1][0] = acc[t >> 1][t & 1][1] = acc[t >> 1][t & 1][2] = acc[t >> 1][t & 1][3] = 0.f; }
                    uint32_t b[2][4];
                    ldsm4t(b[0], mb); ldsm4t(b[1], mb + 512);
#pragma unroll
                    for (int p = 0; p < 16; p++) {
#pragma unroll
                        for (int c = 0; c < 2; c++) {
                            const int u = c ^ ((p >> 1) & 1), k = 2 * p + u;
                            if (k_in_smem(k)) {
                                mma16816v(acc[0][c], pre[0], b[p & 1][2 * u], b[p & 1][2 * u + 1]);
                                mma16816v(acc[1][c], pre[1], b[p & 1][2 * u], b[p & 1][2 * u + 1]);
                                if (k + 4 < 32) { ldsm4t(pre[0], aw + ((k >> 2) + 1) * 4096); ldsm4t(pre[1], aw + ((k >> 2) + 1) * 4096 + 2048); }
                            } else {
                                mma16816v(acc[0][c], wa[0][k_reg_idx(k)], b[p & 1][2 * u], b[p & 1][2 * u + 1]);
                                mma16816v(acc[1][c], wa[1][k_reg_idx(k)], b[p & 1][2 * u], b[p & 1][2 * u + 1]);
                            }
                        }
                        if (p + 2 < 16) ldsm4t(b[p & 1], mb + (p + 2) * 512);
                        if (p == GO_AT) bar_arrive(BAR_GO, 256);
                    }
                    st_async4(rsb + SM_R1 + g * 512 + l16, acc[0][0][0] + acc[0][1][0], acc[0][0][1] + acc[0][1][1], acc[0][0][2] + acc[0][1][2], acc[0][0][3] + acc[0][1][3], rsb + MB_R1);
                    if (lead) TL(1);
                    char* xd = XBOX() + kh * 1024 + g * 256 + ln * 4;
                    const uint32_t qo = SM_QKV + kh * 2048 + nh * 1024 + g * 256 + ln * 4;
                    const float o0 = acc[1][0][0] + acc[1][1][0], o1 = acc[1][0][1] + acc[1][1][1], o2 = acc[1][0][2] + acc[1][1][2], o3 = acc[1][0][3] + acc[1][1][3];
                    asm volatile("" ::"l"(xd), "r"(qo), "f"(o0), "f"(o1), "f"(o2), "f"(o3));
                    mbar_wait(sb + MB_R1, s & 1);
                    const uint4 v = lds128(sb + SM_R1 + g * 512 + l16);
                    const uint32_t w0 = pack_bf16(o0 + __uint_as_float(v.x), o1 + __uint_as_float(v.y)), w1 = pack_bf16(o2 + __uint_as_float(v.z), o3 + __uint_as_float(v.w));
                    st_relaxed_u32(xd, w0);
                    st_relaxed_u32(xd + 128, w1);
                    bar_arrive(BAR_PUB, 256);
                    st_async1(rsb + qo, w0, rsb + MB_P);
                    st_async1(rsb + qo + 128, w1, rsb + MB_P);
                    sts32(sb + qo, w0);
                    sts32(sb + qo + 128, w1);
                    __syncwarp();
                    if (ln == 0) { if (g == 0) mbar_expect_tx(sb + MB_P, 1024); else mbar_arrive(sb + MB_P); }
                    if (lead) TL(2);
                }
                if (s + 1 == NSEG) break;
                PHASE();
                const uint32_t l4 = sb + ln * 4, l16 = sb + ln * 16;
                uint32_t va[3][4];
                {
                    const uint32_t vaddr = sb + ((s & 1) ? SM_KV1 : SM_KV0) + 8192 + frag;
                    mbar_wait(sb + MB_KV + (s & 1) * 8, (s >> 1) & 1);
                    ldsm4t(va[0], vaddr); ldsm4t(va[1], vaddr + 2048);
                    if (lead) {
                        float sc[4] = {0.f, 0.f, 0.f, 0.f}, sd[4] = {0.f, 0.f, 0.f, 0.f};
                        const uint32_t q0 = l16 + SM_QKV + nh * 1024, q1 = l16 + SM_QKV + (nh ^ 1) * 1024;
                        uint32_t a[2][4], kb[2][4];
                        mbar_wait(sb + MB_P, s & 1);
#pragma unroll
                        for (int p = 0; p < 2; p++) { ldsm4t(a[p], q0 + p * 512); ldsm4t(kb[p], q0 + 2048 + p * 512); }
#pragma unroll
                        for (int p = 0; p < 2; p++) { mma16816(sc, a[p][0], 0u, a[p][1], 0u, kb[p][0], kb[p][1]); mma16816(sd, a[p][2], 0u, a[p][3], 0u, kb[p][2], kb[p][3]); }
                        bar_sync_keep(BAR_QK, 288, q1, l4);
#pragma unroll
                        for (int p = 0; p < 2; p++) { ldsm4t(a[p], q1 + p * 512); ldsm4t(kb[p], q1 + 2048 + p * 512); }
#pragma unroll
                        for (int p = 0; p < 2; p++) { mma16816(sc, a[p][0], 0u, a[p][1], 0u, kb[p][0], kb[p][1]); mma16816(sd, a[p][2], 0u, a[p][3], 0u, kb[p][2], kb[p][3]); }
                        sts32(l4 + SM_S + 512, scale_scores(sc, sd));
                    }
                }
                const uint32_t fo = sb + SM_WO2 + 16384 + frag;
                bar_sync_keep(BAR_S, 256, l4, fo);
                if (lead) TL(4);
                uint32_t pw[5], a1[4][4];
                softmax40(pw, l4 + SM_S, [&]() {
#pragma unroll
                    for (int k = 0; k < 2; k++) ldsm4t(a1[k], fo + k * 2048);
                    mbar_wait(sb + MB_V, s & 1);
                    ldsm2(va[2][0], va[2][1], l16 + SM_QKV + 4096 + g * 256);
                });
                char* yd = mbox + (page_off(24 + 2 * g + 32 * nh, kh ^ yflip) + ((s & 3) << 14) + h * 128 + ln * 4);
                char* yd1 = mbox + (page_off(25 + 2 * g + 32 * nh, kh ^ yflip) + ((s & 3) << 14) + h * 128 + ln * 4);
                {
                    float o0[4] = {0.f, 0.f, 0.f, 0.f}, o1[4] = {0.f, 0.f, 0.f, 0.f}, o2[4] = {0.f, 0.f, 0.f, 0.f};
                    mma16816(o0, va[0], pw[0], pw[1]);
                    mma16816(o1, va[1], pw[2], pw[3]);
                    mma16816(o2, va[2][0], va[2][1], 0u, 0u, pw[4], 0u);
                    sts32(l4 + SM_O + g * 256, pack_bf16((o0[0] + o1[0]) + o2[0], (o0[1] + o1[1]) + o2[1]));
                    sts32(l4 + SM_O + g * 256 + 128, pack_bf16((o0[2] + o1[2]) + o2[2], (o0[3] + o1[3]) + o2[3]));
                }
                ldsm4t(a1[2], fo + 2 * 2048); ldsm4t(a1[3], fo + 3 * 2048);
                asm volatile("" ::"l"(yd), "l"(yd1));
                bar_sync_keep(BAR_O, 256, l16, l16);
                if (lead) TL(5);
                {
                    float y0[4] = {0.f, 0.f, 0.f, 0.f}, y1[4] = {0.f, 0.f, 0.f, 0.f};
                    uint32_t b[2][4];
                    ldsm4t(b[0], l16 + SM_O); ldsm4t(b[1], l16 + SM_O + 512);
#pragma unroll
                    for (int p = 0; p < 4; p++) {
                        mma16816(y0, a1[(2 * p) & 3], b[p & 1][0], b[p & 1][1]);
                        if (p < 2) ldsm4t(a1[(2 * p) & 3], fo + (2 * p + 4) * 2048);
                        mma16816(y1, a1[(2 * p + 1) & 3], b[p & 1][2], b[p & 1][3]);
                        if (p < 2) ldsm4t(a1[(2 * p + 1) & 3], fo + (2 * p + 5) * 2048);
                        if (p < 2) ldsm4t(b[p & 1], l16 + SM_O + (p + 2) * 512);
                    }
                    st_relaxed_u32(yd, pack_bf16(y0[0] + y1[0], y0[1] + y1[1]));
                    st_relaxed_u32(yd1, pack_bf16(y0[2] + y1[2], y0[3] + y1[3]));
                }
                bar_arrive(BAR_SENT, 288);
                if (lead) TL(6);
            }
            if (s + 3 < NSEG) {
                PHASE();
                const uint64_t db = make_desc(SB0 + SM_XT, 16, 1024), da = make_desc(SB0 + SM_WQK, 16, 1024);
                const uint32_t rt = SM_RT + g * 2048 + ln * 16;
                float d[16];
                if (g == 0 && ln == 0) mbar_expect_tx(sb + MB_RT0, 8192);
                mbar_wait(sb + MB_XT, (s + 3) & 1);
#pragma unroll
                for (int t = 0; t < 2; t++) {
                    wg_fence();
#pragma unroll
                    for (int k = 0; k < 32; k++) {
                        if (t == 0 && k == 16) { wg_commit(); mbar_wait(sb + MB_XT + 8, (s + 3) & 1); wg_fence(); }
                        const uint64_t dk = db + (k >> 2) * 256 + (k & 3) * 2;
                        if (k == 0) wgmma_rs32_first(d, wa[t][0], dk);
                        else if (k_in_smem(k)) wgmma_ss32(d, da + ((k >> 2) * 2 + t) * 128, dk);
                        else wgmma_rs32(d, wa[t][k_reg_idx(k)], dk, true);
                    }
                    wg_commit();
                    wg_wait<0>();
                    if (lead) TL(7 + t);
                    if (t == 0) {
#pragma unroll
                        for (int i = 0; i < 4; i++) st_async4(rsb + rt + i * 512, d[4 * i], d[4 * i + 1], d[4 * i + 2], d[4 * i + 3], rsb + MB_RT0);
                    }
                }
                mbar_wait(sb + MB_RT0, (s + 3) & 1);
                uint32_t w[8];
#pragma unroll
                for (int i = 0; i < 4; i++) {
                    const uint4 v = lds128(sb + rt + i * 512);
                    w[2 * i] = pack_bf16(d[4 * i] + __uint_as_float(v.x), d[4 * i + 1] + __uint_as_float(v.y));
                    w[2 * i + 1] = pack_bf16(d[4 * i + 2] + __uint_as_float(v.z), d[4 * i + 3] + __uint_as_float(v.w));
                }
                const uint32_t so = sb + SM_STG + frag;
                stsm4t(so, w[0], w[1], w[2], w[3]);
                stsm4t(so + 2048, w[4], w[5], w[6], w[7]);
                asm volatile("fence.proxy.async.shared::cta;" ::: "memory");
                __syncwarp();
                if (ln == 0) mbar_arrive(sb + MB_STG);
                if (lead) TL(9);
            }
        }
    } else {
        asm volatile("setmaxnreg.inc.sync.aligned.u32 %0;" ::"n"(REG_B));
        uint32_t wv[24][4], wo[8 + WO_RF1][4];
        {
            PHASE();
            const uint32_t fa = sb + frag;
            mbar_wait(sb + MB_W0, 0);
#pragma unroll
            for (int r = 0; r < 24; r++) ldsm4t(wv[r], fa + STG_V + r * 2048);
            bar_arrive(BAR_PV, 160);
            mbar_wait(sb + MB_W3, 0);
#pragma unroll
            for (int r = 0; r < 8 + WO_RF1; r++) ldsm4t(wo[r], fa + STG_WO + r * 2048);
            mbar_wait(sb + MB_W2, 0);
            bar_arrive(BAR_PDONE, 384);
        }
        auto tattn = [&](int s) {
            PHASE();
            const int j = 2 * nh + kh;
            const uint32_t kv = sb + ((s & 1) ? SM_KV1 : SM_KV0), l4 = sb + ln * 4;
            mbar_wait(sb + MB_Q, s & 1);
            {
                float sc[4] = {0.f, 0.f, 0.f, 0.f}, sd[4] = {0.f, 0.f, 0.f, 0.f}, mc[4] = {0.f, 0.f, 0.f, 0.f}, md[4] = {0.f, 0.f, 0.f, 0.f};
                const uint32_t sw = (((ln >> 3) ^ (ln & 7)) * 16);
                const uint32_t qa = sb + SM_QX + (ln & 7) * 128 + sw, ka = kv + (g * 8 + (ln & 7)) * 128 + sw, km = sb + SM_QKV + 2048 + ln * 16;
#pragma unroll
                for (int p = 0; p < 4; p++) {
                    uint32_t a[4], b[4];
                    ldsm4(a, (qa ^ ((p & 1) * 64)) + (p >> 1) * 1024);
                    ldsm4(b, (ka ^ ((p & 1) * 64)) + (p >> 1) * 4096);
                    mma16816(sc, a[0], 0u, a[1], 0u, b[0], b[1]);
                    mma16816(sd, a[2], 0u, a[3], 0u, b[2], b[3]);
                    if (lead) {
                        ldsm4t(b, km + p * 512);
                        mma16816(mc, a[0], 0u, a[1], 0u, b[0], b[1]);
                        mma16816(md, a[2], 0u, a[3], 0u, b[2], b[3]);
                    }
                }
                uint32_t w2 = scale_scores(sc, sd);
                const int d = 8 * j + (ln >> 2) - (8 * g + 2 * (ln & 3));
                if (d < 0) w2 = (w2 & 0xFFFF0000u) | 0xFF80u;
                if (d < 1) w2 = (w2 & 0x0000FFFFu) | 0xFF800000u;
                sts32(l4 + SM_S + g * 128, w2);
                if (g == 0) sts32(l4 + SM_S + 512, scale_scores(mc, md));
            }
            bar_sync(BAR_T, 128);
            uint32_t pw[5];
            softmax40(pw, l4 + SM_S, []() {});
            uint32_t w[4];
#pragma unroll
            for (int m = 0; m < 2; m++) {
                const uint32_t vaddr = kv + 8192 + (g >> 1) * 4096 + ((ln & 7) + (ln >> 4) * 8) * 128 + (((4 * (g & 1) + 2 * m + ((ln >> 3) & 1)) ^ (ln & 7)) * 16);
                uint32_t va[3][4];
                ldsm4t(va[0], vaddr); ldsm4t(va[1], vaddr + 2048);
                ldsm2(va[2][0], va[2][1], sb + SM_QKV + 4096 + (2 * g + m) * 256 + ln * 16);
                float o0[4] = {0.f, 0.f, 0.f, 0.f}, o1[4] = {0.f, 0.f, 0.f, 0.f};
                mma16816(o0, va[0], pw[0], pw[1]);
                mma16816(o1, va[1], pw[2], pw[3]);
                mma16816(o0, va[2][0], va[2][1], 0u, 0u, pw[4], 0u);
                w[2 * m] = pack_bf16(o0[0] + o1[0], o0[1] + o1[1]);
                w[2 * m + 1] = pack_bf16(o0[2] + o1[2], o0[3] + o1[3]);
            }
            stsm4t(sb + SM_TO + g * 640 + (ln & 7) * 80 + (ln >> 3) * 16, w[0], w[1], w[2], w[3]);
            __syncwarp();
            stg128(g_ox + (size_t)(s * SEG + 8 * j + (ln >> 2)) * HD + h * DH + 32 * g + (ln & 3) * 8, lds128(sb + SM_TO + g * 640 + (ln >> 2) * 80 + (ln & 3) * 16));
        };
#pragma unroll 1
        for (int s = -3; s < NSEG; s++) {
            if (s >= 0) {
                {
                    PHASE();
                    const uint32_t aw = sb + SM_WV + frag;
                    const uint32_t mb = sb + SM_Z + ln * 16;
                    uint32_t pre[2][4];
                    ldsm4t(pre[0], aw); ldsm4t(pre[1], aw + 2048);
                    if (g == 0 && ln == 0) mbar_expect_tx(sb + MB_R2, 1024);
                    bar_arrive(BAR_MEM, 384);
                    bar_sync_keep(BAR_GO, 256, mb, aw);
                    float acc[4][4];
#pragma unroll
                    for (int t = 0; t < 4; t++) { acc[t][0] = acc[t][1] = acc[t][2] = acc[t][3] = 0.f; }
                    uint32_t b[3][4];
                    ldsm4t(b[0], mb); ldsm4t(b[1], mb + 512); ldsm4t(b[2], mb + 1024);
#pragma unroll
                    for (int p = 0; p < 16; p++) {
#pragma unroll
                        for (int u = 0; u < 2; u++) {
                            const int k = 2 * p + u;
                            if (k_in_smem(k)) {
                                mma16816v(acc[(k + (k >> 2)) & 3], pre[(k >> 2) & 1], b[p % 3][2 * u], b[p % 3][2 * u + 1]);
                                if (k + 8 < 32) ldsm4t(pre[(k >> 2) & 1], aw + ((k >> 2) + 2) * 2048);
                            } else {
                                mma16816v(acc[(k + (k >> 2)) & 3], wv[k_reg_idx(k)], b[p % 3][2 * u], b[p % 3][2 * u + 1]);
                            }
                        }
                        if (p + 3 < 16) ldsm4t(b[p % 3], mb + (p + 3) * 512);
                    }
                    float o[4];
#pragma unroll
                    for (int i = 0; i < 4; i++) o[i] = (acc[0][i] + acc[1][i]) + (acc[2][i] + acc[3][i]);
                    st_async2(rsb + SM_R2 + g * 256 + ln * 8, kh ? o[0] : o[2], kh ? o[1] : o[3], rsb + MB_R2);
                    if (lead) TL(10);
                    char* xd = XBOX() + 2048 + (2 * g + kh) * 128 + ln * 4;
                    const uint32_t qo = SM_QKV + 4096 + nh * 1024 + (2 * g + kh) * 128 + ln * 4;
                    const float o0 = kh ? o[2] : o[0], o1 = kh ? o[3] : o[1];
                    asm volatile("" ::"l"(xd), "r"(qo), "f"(o0), "f"(o1));
                    mbar_wait(sb + MB_R2, s & 1);
                    uint32_t vx, vy;
                    asm volatile("ld.shared.v2.u32 {%0,%1}, [%2];" : "=r"(vx), "=r"(vy) : "r"(sb + SM_R2 + g * 256 + ln * 8) : "memory");
                    const uint32_t w0 = pack_bf16(o0 + __uint_as_float(vx), o1 + __uint_as_float(vy));
                    st_relaxed_u32(xd, w0);
                    st_async1(rsb + qo, w0, rsb + MB_V);
                    sts32(sb + qo, w0);
                    __syncwarp();
                    if (ln == 0) { if (g == 0) mbar_expect_tx(sb + MB_V, 512); else mbar_arrive(sb + MB_V); }
                    if (lead) TL(11);
                }
                if (s + 1 == NSEG) {
                    PHASE();
                    mbar_wait(sb + MB_KV + (s & 1) * 8, (s >> 1) & 1);
                    mbar_wait(sb + MB_P, s & 1);
                    bar_sync(BAR_QK, 256);
                    mbar_wait(sb + MB_V, s & 1);
                    tattn(s);
                    break;
                }
                PHASE();
                const uint32_t l4 = sb + ln * 4, l16 = sb + ln * 16;
                uint32_t va[3][4];
                {
                    const uint32_t kv = sb + ((s & 1) ? SM_KV1 : SM_KV0);
                    const uint32_t ka = kv + (g * 8 + (ln & 7)) * 128 + (((ln >> 3) ^ (ln & 7)) * 16);
                    const uint32_t vaddr = kv + 12288 + frag;
                    const uint32_t q0 = l16 + SM_QKV + nh * 1024, q1 = l16 + SM_QKV + (nh ^ 1) * 1024;
                    float sc[4] = {0.f, 0.f, 0.f, 0.f}, sd[4] = {0.f, 0.f, 0.f, 0.f};
                    uint32_t a[2][4], kb[2][4];
                    mbar_wait(sb + MB_KV + (s & 1) * 8, (s >> 1) & 1);
#pragma unroll
                    for (int p = 0; p < 2; p++) ldsm4(kb[p], (ka ^ (p * 64)) + nh * 4096);
                    mbar_wait(sb + MB_P, s & 1);
#pragma unroll
                    for (int p = 0; p < 2; p++) ldsm4t(a[p], q0 + p * 512);
#pragma unroll
                    for (int p = 0; p < 2; p++) { mma16816(sc, a[p][0], 0u, a[p][1], 0u, kb[p][0], kb[p][1]); mma16816(sd, a[p][2], 0u, a[p][3], 0u, kb[p][2], kb[p][3]); }
#pragma unroll
                    for (int p = 0; p < 2; p++) ldsm4(kb[p], (ka ^ (p * 64)) + (nh ^ 1) * 4096);
                    ldsm4t(va[0], vaddr); ldsm4t(va[1], vaddr + 2048);
                    if (lead) TL(12);
                    bar_sync_keep(BAR_QK, 288, q1, l4);
                    if (lead) TL(3);
#pragma unroll
                    for (int p = 0; p < 2; p++) ldsm4t(a[p], q1 + p * 512);
#pragma unroll
                    for (int p = 0; p < 2; p++) { mma16816(sc, a[p][0], 0u, a[p][1], 0u, kb[p][0], kb[p][1]); mma16816(sd, a[p][2], 0u, a[p][3], 0u, kb[p][2], kb[p][3]); }
                    sts32(l4 + SM_S + g * 128, scale_scores(sc, sd));
                }
                const uint32_t fo = sb + frag;
                bar_sync_keep(BAR_S, 256, l4, fo);
                uint32_t pw[5], a1[4][4];
                softmax40(pw, l4 + SM_S, [&]() {
#pragma unroll
                    for (int k = 0; k < 3; k++) ldsm4t(a1[k], fo + SM_WO2 + k * 2048);
                    mbar_wait(sb + MB_V, s & 1);
                    ldsm2(va[2][0], va[2][1], l16 + SM_QKV + 4096 + 1024 + g * 256);
                });
                const uint32_t yo = page_off(2 * g + 32 * nh, kh ^ yflip) + ((s & 3) << 14) + h * 128 + ln * 4;
                char* yd = mbox + yo;
                char* yd1 = mbox + (yo ^ 4096);
                {
                    float o0[4] = {0.f, 0.f, 0.f, 0.f}, o1[4] = {0.f, 0.f, 0.f, 0.f}, o2[4] = {0.f, 0.f, 0.f, 0.f};
                    mma16816(o0, va[0], pw[0], pw[1]);
                    mma16816(o1, va[1], pw[2], pw[3]);
                    mma16816(o2, va[2][0], va[2][1], 0u, 0u, pw[4], 0u);
                    sts32(l4 + SM_O + 1024 + g * 256, pack_bf16((o0[0] + o1[0]) + o2[0], (o0[1] + o1[1]) + o2[1]));
                    sts32(l4 + SM_O + 1024 + g * 256 + 128, pack_bf16((o0[2] + o1[2]) + o2[2], (o0[3] + o1[3]) + o2[3]));
                }
                ldsm4t(a1[3], fo + SM_WO2 + 3 * 2048);
                asm volatile("" ::"l"(yd), "l"(yd1));
                bar_sync_keep(BAR_O, 256, l16, l16);
                {
                    float y0[4] = {0.f, 0.f, 0.f, 0.f}, y1[4] = {0.f, 0.f, 0.f, 0.f}, y2[4] = {0.f, 0.f, 0.f, 0.f};
                    uint32_t b[2][4];
                    ldsm4t(b[0], l16 + SM_O); ldsm4t(b[1], l16 + SM_O + 512);
#pragma unroll
                    for (int k = 0; k < 8; k++) {
                        const int p = k >> 1, u = k & 1;
                        mma16816(y2, a1[k & 3], b[p & 1][2 * u], b[p & 1][2 * u + 1]);
                        if (k < 4) ldsm4t(a1[k & 3], fo + SM_WO2 + (k + 4) * 2048);
                        mma16816(y0, wo[k], b[p & 1][2 * u], b[p & 1][2 * u + 1]);
                        if (k < WO_RF1) mma16816(y1, wo[8 + (k < WO_RF1 ? k : 0)], b[p & 1][2 * u], b[p & 1][2 * u + 1]);
                        else { uint32_t t[4]; ldsm4t(t, fo + SM_WO1 + k * 2048); mma16816(y1, t, b[p & 1][2 * u], b[p & 1][2 * u + 1]); }
                        if (u == 1 && p < 2) ldsm4t(b[p & 1], l16 + SM_O + (p + 2) * 512);
                    }
                    st_relaxed_u32(yd1 + 0x80000, pack_bf16(y2[0], y2[1]));
                    st_relaxed_u32(yd + 0x82000, pack_bf16(y2[2], y2[3]));
                    st_relaxed_u32(yd, pack_bf16(y0[0], y0[1]));
                    st_relaxed_u32(yd1 + 0x2000, pack_bf16(y0[2], y0[3]));
                    st_relaxed_u32(yd + 0x40000, pack_bf16(y1[0], y1[1]));
                    st_relaxed_u32(yd1 + 0x42000, pack_bf16(y1[2], y1[3]));
                }
                bar_arrive(BAR_SENT, 288);
                if (lead) TL(13);
                tattn(s);
                if (warp == 4) TL(14);
            }
            if (s + 3 < NSEG) {
                PHASE();
                const uint64_t db = make_desc(SB0 + SM_XT, 16, 1024), da = make_desc(SB0 + SM_WV, 16, 1024);
                float d[16];
                if (g == 0 && ln == 0) mbar_expect_tx(sb + MB_RT1, 4096);
                mbar_wait(sb + MB_XT, (s + 3) & 1);
                mbar_wait(sb + MB_XT + 8, (s + 3) & 1);
                wg_fence();
#pragma unroll
                for (int k = 0; k < 32; k++) {
                    const uint64_t dk = db + (k >> 2) * 256 + (k & 3) * 2;
                    if (k == 0) wgmma_rs32_first(d, wv[0], dk);
                    else if (k_in_smem(k)) wgmma_ss32(d, da + (k >> 2) * 128, dk);
                    else wgmma_rs32(d, wv[k_reg_idx(k)], dk, true);
                }
                wg_commit();
                const uint32_t rt = SM_RT + 8192 + g * 1024 + ln * 16;
                wg_wait<0>();
#pragma unroll
                for (int i = 0; i < 2; i++)
                    st_async4(rsb + rt + i * 512, kh ? d[4 * i] : d[8 + 4 * i], kh ? d[4 * i + 1] : d[9 + 4 * i], kh ? d[4 * i + 2] : d[10 + 4 * i], kh ? d[4 * i + 3] : d[11 + 4 * i], rsb + MB_RT1);
                float o[8];
#pragma unroll
                for (int i = 0; i < 8; i++) o[i] = kh ? d[8 + i] : d[i];
                mbar_wait(sb + MB_RT1, (s + 3) & 1);
                uint32_t w[4];
#pragma unroll
                for (int i = 0; i < 2; i++) {
                    const uint4 v = lds128(sb + rt + i * 512);
                    w[2 * i] = pack_bf16(o[4 * i] + __uint_as_float(v.x), o[4 * i + 1] + __uint_as_float(v.y));
                    w[2 * i + 1] = pack_bf16(o[4 * i + 2] + __uint_as_float(v.z), o[4 * i + 3] + __uint_as_float(v.w));
                }
                stsm4t(sb + SM_STG + 4096 + frag, w[0], w[1], w[2], w[3]);
                asm volatile("fence.proxy.async.shared::cta;" ::: "memory");
                __syncwarp();
                if (ln == 0) mbar_arrive(sb + MB_STG);
                if (lead) TL(15);
            }
        }
    }
    KT_END(2);
    asm volatile("barrier.cluster.arrive.relaxed; barrier.cluster.wait;" ::: "memory");
}

constexpr int B_UCH = 39 * 128 + 16;
constexpr int B_KLEN = 2128;
constexpr int B_KCH = 2 * B_KLEN * 2 + 64;
constexpr int B_SM_U = 0;
constexpr int B_SM_K = 16 * B_UCH;
constexpr int B_SM_BAR = B_SM_K + 16 * B_KCH;
constexpr int B_SMEM = B_SM_BAR + 16 + 128;
static_assert(16 * B_KCH >= 2 * 65536, "the k / v tiles alias the kernel copies");
#define PROBE_N 5
constexpr int B_C = 2056;

__device__ __forceinline__ uint32_t bf16_mul(uint32_t a, uint32_t b) {
    uint32_t d;
    asm("mul.rn.bf16x2 %0, %1, %2;" : "=r"(d) : "r"(a), "r"(b));
    return d;
}
__device__ __forceinline__ uint32_t bf16_add(uint32_t a, uint32_t b) {
    uint32_t d;
    asm("add.rn.bf16x2 %0, %1, %2;" : "=r"(d) : "r"(a), "r"(b));
    return d;
}

__device__ __forceinline__ uint32_t atomic_round_trip(char* p) {
    uint32_t t0, t1, v;
    asm volatile("{.reg .pred p;\n"
                 "mov.u32 %0, %%clock;\n"
                 "atom.relaxed.gpu.global.add.u32 %2, [%3], 1;\n"
                 "setp.ne.u32 p, %2, 0x7FFFFFFF;\n"
                 "mov.u32 %1, 0;\n"
                 "@p mov.u32 %1, %%clock;}" : "=&r"(t0), "=&r"(t1), "=&r"(v) : "l"(p) : "memory");
    return t1 - t0;
}
__device__ __forceinline__ uint32_t far_first(char* a, char* b, int lane) {
    if (lane < 16) stg128((lane < 8 ? a : b) + (lane & 7) * 16, make_uint4(0, 0, 0, 0));
    __syncwarp();
    uint32_t ta = ~0u, tb = ~0u;
    if (lane == 0) {
        __threadfence();
#pragma unroll 1
        for (int i = 0; i < PROBE_N; i++) { ta = min(ta, atomic_round_trip(a)); tb = min(tb, atomic_round_trip(b)); }
    }
    return ta > tb;
}
__device__ __forceinline__ void measure_distance(char* mbox, int lane) {
    const uint32_t b = blockIdx.x;
    unsigned smid;
    asm volatile("mov.u32 %0, %%smid;" : "=r"(smid));
    char* w1 = mbox + WIN + (b & 31) * 128;
    const uint32_t c = far_first(w1 + page_off(40 + (b >> 5), 0), w1 + page_off(40 + (b >> 5), 1), lane);
    if (lane == 0) g_cls[smid] = c;
    if (b == 0) {
        const uint32_t c0 = far_first(mbox + page_off(0, 0), mbox + page_off(0, 1), lane);
        if (lane == 0) { g_reg[2] = c0 ^ c; g_reg[0] = 0; g_reg[1] = 0; }
    }
    if (b == 1) for (int i = lane; i < 128; i += 32) g_xflag[i] = 0;
    __syncwarp();
}

#define SP(i)
__global__ void __launch_bounds__(512, 1)
ssm_kernel(const __grid_constant__ CUtensorMap mapK, const __grid_constant__ CUtensorMap mapV, const bf16* __restrict__ Q, const bf16* __restrict__ shiftk,
           const bf16* __restrict__ ssmk, const bf16* __restrict__ Dv, bf16* __restrict__ out, char* __restrict__ mbox) {
    extern __shared__ __align__(128) uint8_t smem_raw[];
    const uint32_t sb = (smem_u32(smem_raw) + 127) & ~127u;
    const int ch0 = (blockIdx.x >> 1) * 16, half = blockIdx.x & 1;
    const int t = threadIdx.x, warp = t >> 5, lane = t & 31;
    const int tmax = half ? 1536 : 2048;
    KT_START(1);
    SP(0);
    if (blockIdx.x >= 128) {
        if (warp == 15) measure_distance(mbox, lane);
        return;
    }
    const uint32_t stg_k = sb + B_SM_K, stg_v = stg_k + 65536, bar = sb + B_SM_BAR;
    if (t == 0) {
        mbar_init(bar, 1);
        asm volatile("fence.mbarrier_init.release.cluster;" ::: "memory");
        mbar_expect_tx(bar, 2 * tmax * 32);
        for (int r = 0; r < tmax; r += 256) {
            tma_load_2d(stg_k + r * 32, &mapK, ch0, r, bar);
            tma_load_2d(stg_v + r * 32, &mapV, ch0, r, bar);
        }
    }
    uint4 kr[8];
    {
        const uint4* src = reinterpret_cast<const uint4*>(ssmk + (size_t)(ch0 + warp) * S_LEN) + lane;
#pragma unroll
        for (int i = 0; i < 8; i++) kr[i] = __ldg(src + i * 32);
        const uint32_t ub = sb + B_SM_U + warp * B_UCH;
        for (int i = lane; i < 7 * 8; i += 32) sts128(ub + i * 16, make_uint4(0, 0, 0, 0));
    }
    const int hr = lane & 1, cc = ch0 + hr * 8;
    uint32_t w[4][4];
#pragma unroll
    for (int p = 0; p < 4; p++) {
        const uint4 sw = __ldg(reinterpret_cast<const uint4*>(shiftk + (size_t)cc * 4 + p * 8));
        w[0][p] = __byte_perm(sw.x, sw.z, 0x5410); w[1][p] = __byte_perm(sw.x, sw.z, 0x7632);
        w[2][p] = __byte_perm(sw.y, sw.w, 0x5410); w[3][p] = __byte_perm(sw.y, sw.w, 0x7632);
    }
    __syncthreads();
    if (warp == 15) measure_distance(mbox, lane);
    mbar_wait(bar, 0);
    SP(1);
    if (warp * 128 < tmax) {
#pragma unroll 2
        for (int i = 0; i < 8; i++) {
            const int tt = warp * 128 + i * 16 + (lane >> 1);
            const uint32_t ka = stg_k + tt * 32 + hr * 16;
            const uint4 z = make_uint4(0, 0, 0, 0);
            const uint4 k0 = lds128(ka), k1 = tt >= 1 ? lds128(ka - 32) : z, k2 = tt >= 2 ? lds128(ka - 64) : z, k3 = tt >= 3 ? lds128(ka - 96) : z;
            const uint4 vv = lds128(stg_v + tt * 32 + hr * 16);
            uint4 o;
#pragma unroll
            for (int p = 0; p < 4; p++) {
                uint32_t a = bf16_mul(((const uint32_t*)&k3)[p], w[3][p]);
                a = bf16_add(a, bf16_mul(((const uint32_t*)&k2)[p], w[2][p]));
                a = bf16_add(a, bf16_mul(((const uint32_t*)&k1)[p], w[1][p]));
                a = bf16_add(a, bf16_mul(((const uint32_t*)&k0)[p], w[0][p]));
                ((uint32_t*)&o)[p] = bf16_mul(a, ((const uint32_t*)&vv)[p]);
            }
            sts128(stg_v + tt * 32 + hr * 16, o);
        }
        __syncwarp();
#pragma unroll
        for (int i = 0; i < 8; i++) {
            const int tt = warp * 128 + i * 16;
            uint32_t r0, r1, r2, r3;
            ldsm4t(r0, r1, r2, r3, stg_v + (tt + (lane & 7) + (lane >> 4) * 8) * 32 + ((lane >> 3) & 1) * 16);
            const int chn = (lane & 7) + ((lane >> 3) & 1) * 8, ts = tt + (lane >> 4) * 8, row = 7 + (ts >> 6), unit = (ts & 63) >> 3;
            stsm4(sb + B_SM_U + chn * B_UCH + row * 128 + ((unit ^ (row & 7)) * 16), r0, r1, r2, r3);
        }
    }
    __syncthreads();
    {
        const uint32_t kb = sb + B_SM_K + warp * B_KCH;
#pragma unroll
        for (int i = 0; i < 8; i++) {
            const uint4 lo = kr[i];
            const uint32_t nx = __shfl_down_sync(~0u, lo.x, 1), n0 = (i < 7) ? __shfl_sync(~0u, kr[i < 7 ? i + 1 : 7].x, 0) : 0u;
            const uint32_t hix = (lane < 31) ? nx : n0;
            const int c = 256 - (lane + 32 * i);
            sts128(kb + c * 16, make_uint4(__byte_perm(hix, lo.w, 0x7610), __byte_perm(lo.w, lo.z, 0x7610), __byte_perm(lo.z, lo.y, 0x7610), __byte_perm(lo.y, lo.x, 0x7610)));
            sts128(kb + B_KLEN * 2 + 64 + c * 16, make_uint4(__byte_perm(lo.w, lo.w, 0x1032), __byte_perm(lo.z, lo.z, 0x1032), __byte_perm(lo.y, lo.y, 0x1032), __byte_perm(lo.x, lo.x, 0x1032)));
        }
        const uint32_t k0w = __shfl_sync(~0u, kr[0].x, 0);
        if (lane < 10) {
            const int c = (lane == 0) ? 0 : 256 + lane;
            sts128(kb + c * 16, make_uint4(c == 257 ? (k0w & 0xFFFFu) : 0u, 0u, 0u, 0u));
            sts128(kb + B_KLEN * 2 + 64 + c * 16, make_uint4(0u, 0u, 0u, 0u));
        }
    }
    __syncwarp();
    SP(2);
    SP(3);
    const int tA = half ? 1 : 0, tB = half ? 2 : 3;
    float accA[4][4], accB[4][4];
#pragma unroll
    for (int i = 0; i < 4; i++)
#pragma unroll
        for (int e = 0; e < 4; e++) { accA[i][e] = 0.f; accB[i][e] = 0.f; }
    const int g = lane >> 2, tq = lane & 3;
    const uint32_t kb = sb + B_SM_K + warp * B_KCH;
    const int e0 = B_C - g + 2 * tq;
    const uint32_t fbase = (e0 & 1) ? (kb + B_KLEN * 2 + 64 + (e0 - 1) * 2) : (kb + e0 * 2);
    const uint32_t ub = sb + B_SM_U + warp * B_UCH;
    uint32_t A[8][4];
    auto load_frag = [&](uint32_t (&a)[4], int q) {
        const uint32_t ad = fbase - 16 * q;
        a[0] = lds32(ad); a[1] = lds32(ad - 16); a[2] = lds32(ad + 16); a[3] = lds32(ad);
    };
#pragma unroll
    for (int i = 5; i < 8; i++) load_frag(A[i], 2 * (i - 8));
    const int mA = 8 * tA + 7, mB = 8 * tB + 7;
    auto tile_step = [&](float (&acc)[4][4], int tile, int m, auto mm_c) {
        constexpr int mm = decltype(mm_c)::value;
        const int row = 7 + 8 * tile - m + (lane & 7);
        const uint32_t ra = ub + row * 128;
#pragma unroll
        for (int p = 0; p < 2; p++) {
            uint32_t b[4];
            ldsm4(b[0], b[1], b[2], b[3], ra + (((p * 4 + (lane >> 3)) ^ (row & 7)) * 16));
#pragma unroll
            for (int u = 0; u < 2; u++) {
                const int k = 2 * p + u;
#pragma unroll
                for (int mt = 0; mt < 4; mt++) {
                    const int sl = (mm * 4 + (mt - k) + 8) & 7;
                    mma16816(acc[mt], A[sl][0], A[sl][1], A[sl][2], A[sl][3], b[2 * u], b[2 * u + 1]);
                }
            }
        }
    };
    int m = 0;
#pragma unroll 1
    for (; m <= mA; m += 2) {
#pragma unroll
        for (int i = 0; i < 4; i++) load_frag(A[i], 8 * m + 2 * i);
        tile_step(accB, tB, m, std::integral_constant<int, 0>());
        tile_step(accA, tA, m, std::integral_constant<int, 0>());
#pragma unroll
        for (int i = 0; i < 4; i++) load_frag(A[4 + i], 8 * m + 8 + 2 * i);
        tile_step(accB, tB, m + 1, std::integral_constant<int, 1>());
        tile_step(accA, tA, m + 1, std::integral_constant<int, 1>());
    }
#pragma unroll 1
    for (; m <= mB; m += 2) {
#pragma unroll
        for (int i = 0; i < 4; i++) load_frag(A[i], 8 * m + 2 * i);
        tile_step(accB, tB, m, std::integral_constant<int, 0>());
#pragma unroll
        for (int i = 0; i < 4; i++) load_frag(A[4 + i], 8 * m + 8 + 2 * i);
        tile_step(accB, tB, m + 1, std::integral_constant<int, 1>());
    }
    SP(4);
    {
        const uint32_t dw = (uint32_t)__ldg(reinterpret_cast<const uint16_t*>(Dv) + ch0 + warp) * 0x00010001u;
        __syncwarp();
#pragma unroll
        for (int tl = 0; tl < 2; tl++) {
            const int row = 7 + 8 * (tl ? tB : tA) + (lane & 7);
#pragma unroll
            for (int mp = 0; mp < 2; mp++) {
                const uint32_t a = ub + row * 128 + (((mp * 4 + (lane >> 3)) ^ (row & 7)) * 16);
                uint32_t u0, u1, u2, u3;
                ldsm4t(u0, u1, u2, u3, a);
                const float(&c0)[4] = tl ? accB[2 * mp] : accA[2 * mp];
                const float(&c1)[4] = tl ? accB[2 * mp + 1] : accA[2 * mp + 1];
                const uint32_t y0 = bf16_add(pack_bf16(c0[0], c0[1]), bf16_mul(u0, dw)), y1 = bf16_add(pack_bf16(c0[2], c0[3]), bf16_mul(u1, dw));
                const uint32_t y2 = bf16_add(pack_bf16(c1[0], c1[1]), bf16_mul(u2, dw)), y3 = bf16_add(pack_bf16(c1[2], c1[3]), bf16_mul(u3, dw));
                asm volatile("stmatrix.sync.aligned.m8n8.x4.trans.shared.b16 [%0], {%1,%2,%3,%4};" ::"r"(a), "r"(y0), "r"(y1), "r"(y2), "r"(y3) : "memory");
            }
        }
    }
    const int hh = lane >> 4, tbk = (warp & 7) * 16 + (lane & 15);
    const int tg = ((tbk < 64) ? tA : tB) * 512 + (tbk & 63) * 8;
    uint4 qv[8];
    if (t < 256) {
#pragma unroll
        for (int i = 0; i < 8; i++) qv[i] = __ldg(reinterpret_cast<const uint4*>(Q + (size_t)(tg + i) * DM + ch0 + hh * 8));
    }
    SP(5);
    __syncthreads();
    SP(6);
    if (t < 256) {
        const int row = 7 + (tg >> 6), unit = (tg & 63) >> 3;
        uint4 y[8];
#pragma unroll
        for (int c = 0; c < 8; c++) y[c] = lds128(sb + B_SM_U + (hh * 8 + c) * B_UCH + row * 128 + ((unit ^ (row & 7)) * 16));
#pragma unroll
        for (int i = 0; i < 8; i++) {
            const uint32_t sel = (i & 1) ? 0x7632 : 0x5410;
            uint4 o;
            o.x = bf16_mul(qv[i].x, __byte_perm(((const uint32_t*)&y[0])[i >> 1], ((const uint32_t*)&y[1])[i >> 1], sel));
            o.y = bf16_mul(qv[i].y, __byte_perm(((const uint32_t*)&y[2])[i >> 1], ((const uint32_t*)&y[3])[i >> 1], sel));
            o.z = bf16_mul(qv[i].z, __byte_perm(((const uint32_t*)&y[4])[i >> 1], ((const uint32_t*)&y[5])[i >> 1], sel));
            o.w = bf16_mul(qv[i].w, __byte_perm(((const uint32_t*)&y[6])[i >> 1], ((const uint32_t*)&y[7])[i >> 1], sel));
            stg128(out + (size_t)(tg + i) * OUT_LD + DM + ch0 + hh * 8, o);
        }
    } else {
        const uint4 sent = make_uint4(SENT, SENT, SENT, SENT);
        char* p0 = mbox + blockIdx.x * 16384 + (t - 256) * 16;
#pragma unroll
        for (int i = 0; i < 4; i++) stg128(p0 + i * 4096, sent);
        char* p1 = mbox + WIN + blockIdx.x * 8704 + (t - 256) * 16;
        stg128(p1, sent); stg128(p1 + 4096, sent);
        if (t < 256 + 32) stg128(p1 + 8192, sent);
    }
    KT_END(1);
}

typedef CUresult (*EncodeFn)(CUtensorMap*, CUtensorMapDataType, cuuint32_t, void*, const cuuint64_t*, const cuuint64_t*, const cuuint32_t*,
                             const cuuint32_t*, CUtensorMapInterleave, CUtensorMapSwizzle, CUtensorMapL2promotion, CUtensorMapFloatOOBfill);

static void make_map(EncodeFn fn, CUtensorMap* m, const void* ptr, uint64_t inner, uint64_t outer, uint32_t box_in, uint32_t box_out,
                     CUtensorMapL2promotion promo = CU_TENSOR_MAP_L2_PROMOTION_L2_256B) {
    cuuint64_t dims[2] = {inner, outer};
    cuuint64_t strides[1] = {inner * 2};
    cuuint32_t box[2] = {box_in, box_out};
    cuuint32_t es[2] = {1, 1};
    fn(m, CU_TENSOR_MAP_DATA_TYPE_BFLOAT16, 2, const_cast<void*>(ptr), dims, strides, box, es, CU_TENSOR_MAP_INTERLEAVE_NONE,
       CU_TENSOR_MAP_SWIZZLE_128B, promo, CU_TENSOR_MAP_FLOAT_OOB_FILL_NONE);
}

extern "C" void kernel_launch(void* const* d_in, const int* in_sizes, int n_in, void* d_out, int out_size) {
    const bf16* x = (const bf16*)d_in[0];
    const bf16* mem0 = (const bf16*)d_in[1];
    const bf16* Wq = (const bf16*)d_in[2];
    const bf16* Wk = (const bf16*)d_in[3];
    const bf16* Wv = (const bf16*)d_in[4];
    const bf16* Wo = (const bf16*)d_in[5];
    const bf16* Bq = (const bf16*)d_in[7];
    const bf16* Bk = (const bf16*)d_in[8];
    const bf16* Bv = (const bf16*)d_in[9];
    const bf16* Bsh = (const bf16*)d_in[10];
    const bf16* Bssm = (const bf16*)d_in[11];
    const bf16* BD = (const bf16*)d_in[12];
    bf16* out = (bf16*)d_out;

    static bool init = false;
    static EncodeFn enc = nullptr;
    static void *p_tok, *p_ox, *p_mbox;
    static int nclusters = 64;
    using G2 = GemmCfg<128, 5>;
    if (!init) {
        cudaDriverEntryPointQueryResult qr;
        cudaGetDriverEntryPoint("cuTensorMapEncodeTiled", (void**)&enc, cudaEnableDefault, &qr);
        cudaGetSymbolAddress(&p_tok, g_tok);
        cudaGetSymbolAddress(&p_ox, g_ox);
        cudaGetSymbolAddress(&p_mbox, g_mbox);
        cudaFuncSetAttribute(gemm_kernel<128, 5>, cudaFuncAttributeMaxDynamicSharedMemorySize, G2::SMEM);
        cudaFuncSetAttribute(chain_kernel, cudaFuncAttributeMaxDynamicSharedMemorySize, CHAIN_SMEM);
        cudaFuncSetAttribute(ssm_kernel, cudaFuncAttributeMaxDynamicSharedMemorySize, B_SMEM);
        cudaLaunchConfig_t cfg = {};
        cfg.gridDim = dim3(132); cfg.blockDim = dim3(384); cfg.dynamicSmemBytes = CHAIN_SMEM;
        cudaLaunchAttribute at[1];
        at[0].id = cudaLaunchAttributeClusterDimension; at[0].val.clusterDim.x = 2; at[0].val.clusterDim.y = 1; at[0].val.clusterDim.z = 1;
        cfg.attrs = at; cfg.numAttrs = 1;
        int n = 0;
        if (cudaOccupancyMaxActiveClusters(&n, chain_kernel, &cfg) == cudaSuccess && n > 64) nclusters = n < 66 ? n : 66;
        (void)cudaGetLastError();
        init = true;
    }
    char* mbox = (char*)(((uintptr_t)p_mbox + WIN - 1) & ~(uintptr_t)(WIN - 1));
    CUtensorMap mX, mT32, mT8, mWq, mWk, mWv, mWoC, mOx, mWo, mOut;
    {
        cuuint64_t dims[3] = {64, S_LEN, DM / 64};
        cuuint64_t strides[2] = {DM * 2, 128};
        cuuint32_t box[3] = {64, 32, 4};
        cuuint32_t es[3] = {1, 1, 1};
        enc(&mX, CU_TENSOR_MAP_DATA_TYPE_BFLOAT16, 3, const_cast<bf16*>(x), dims, strides, box, es, CU_TENSOR_MAP_INTERLEAVE_NONE,
            CU_TENSOR_MAP_SWIZZLE_128B, CU_TENSOR_MAP_L2_PROMOTION_L2_256B, CU_TENSOR_MAP_FLOAT_OOB_FILL_NONE);
    }
    make_map(enc, &mT32, p_tok, DH, 4 * NH * 3 * SEG, 64, 32, CU_TENSOR_MAP_L2_PROMOTION_L2_128B);
    make_map(enc, &mT8, p_tok, DH, 4 * NH * 3 * SEG, 64, 8, CU_TENSOR_MAP_L2_PROMOTION_L2_128B);
    make_map(enc, &mWq, Wq, HD, DM, 64, 16, CU_TENSOR_MAP_L2_PROMOTION_L2_128B);
    make_map(enc, &mWk, Wk, HD, DM, 64, 16, CU_TENSOR_MAP_L2_PROMOTION_L2_128B);
    make_map(enc, &mWv, Wv, HD, DM, 64, 16, CU_TENSOR_MAP_L2_PROMOTION_L2_128B);
    make_map(enc, &mWoC, Wo, DM, HD, 64, 128, CU_TENSOR_MAP_L2_PROMOTION_L2_128B);
    make_map(enc, &mOx, p_ox, HD, S_LEN, 64, 128);
    make_map(enc, &mWo, Wo, DM, HD, 64, 64);
    make_map(enc, &mOut, out, OUT_LD, S_LEN, 64, 64);

    CUtensorMap mBk, mBv;
    for (int i = 0; i < 2; i++) {
        cuuint64_t dims[2] = {DM, S_LEN};
        cuuint64_t strides[1] = {DM * 2};
        cuuint32_t box[2] = {16, 256};
        cuuint32_t es[2] = {1, 1};
        enc(i ? &mBv : &mBk, CU_TENSOR_MAP_DATA_TYPE_BFLOAT16, 2, const_cast<bf16*>(i ? Bv : Bk), dims, strides, box, es, CU_TENSOR_MAP_INTERLEAVE_NONE,
            CU_TENSOR_MAP_SWIZZLE_NONE, CU_TENSOR_MAP_L2_PROMOTION_NONE, CU_TENSOR_MAP_FLOAT_OOB_FILL_NONE);
    }
    cudaStream_t st = cudaStreamPerThread;
    ssm_kernel<<<132, 512, B_SMEM, st>>>(mBk, mBv, Bq, Bsh, Bssm, BD, out, mbox);
    chain_kernel<<<2 * nclusters, 384, CHAIN_SMEM, st>>>(mX, mT32, mT8, mWq, mWk, mWv, mWoC, mem0, mbox);
    gemm_kernel<128, 5><<<128, 288, G2::SMEM, st>>>(mOx, mWo, mWo, mWo, mOut, 16, 8, 64);
}
```

```cpp
#include <cuda_runtime.h>
#include <cuda_bf16.h>
#include <cuda.h>
#include <stdint.h>
#include <type_traits>

typedef __nv_bfloat16 bf16;

constexpr int S_LEN = 2048, DM = 1024, NH = 32, DH = 128, NSEG = 64, SEG = 32;
constexpr int HD = NH * DH;
constexpr int OUT_LD = 2048;
constexpr unsigned SENT = 0xFFFFFFFFu;

__device__ bf16 g_tok[4 * NH * 3 * SEG * DH];
__device__ bf16 g_ox[(size_t)S_LEN * HD];
__device__ uint4 g_mbox[3 * 131072];
__device__ unsigned g_xflag[128];
__device__ unsigned g_reg[4];
__device__ unsigned g_cls[256];
__device__ unsigned g_err;
constexpr uint32_t WIN = 2u << 20;
__host__ __device__ constexpr uint32_t page_off(uint32_t idx, uint32_t c) {
    return ((idx & 1) << 13) | ((idx >> 1) << 16) | (((c ^ idx ^ (idx >> 1) ^ (idx >> 2) ^ (idx >> 4)) & 1) << 12);
}
#define STAT(i, c)
#define KT_START(k)
#define KT_END(k)

__device__ __forceinline__ uint32_t smem_u32(const void* p) { return (uint32_t)__cvta_generic_to_shared(p); }
__device__ __forceinline__ void ldsm4(uint32_t& r0, uint32_t& r1, uint32_t& r2, uint32_t& r3, uint32_t a) {
    asm volatile("ldmatrix.sync.aligned.m8n8.x4.shared.b16 {%0,%1,%2,%3}, [%4];" : "=r"(r0), "=r"(r1), "=r"(r2), "=r"(r3) : "r"(a) : "memory");
}
__device__ __forceinline__ void ldsm4t(uint32_t& r0, uint32_t& r1, uint32_t& r2, uint32_t& r3, uint32_t a) {
    asm volatile("ldmatrix.sync.aligned.m8n8.x4.trans.shared.b16 {%0,%1,%2,%3}, [%4];" : "=r"(r0), "=r"(r1), "=r"(r2), "=r"(r3) : "r"(a) : "memory");
}
__device__ __forceinline__ void ldsm2(uint32_t& r0, uint32_t& r1, uint32_t a) {
    asm volatile("ldmatrix.sync.aligned.m8n8.x2.shared.b16 {%0,%1}, [%2];" : "=r"(r0), "=r"(r1) : "r"(a) : "memory");
}
__device__ __forceinline__ void stg128(void* p, uint4 v) {
    asm volatile("st.global.v4.u32 [%0], {%1,%2,%3,%4};" ::"l"(p), "r"(v.x), "r"(v.y), "r"(v.z), "r"(v.w) : "memory");
}
__device__ __forceinline__ void stsm4(uint32_t a, uint32_t r0, uint32_t r1, uint32_t r2, uint32_t r3) {
    asm volatile("stmatrix.sync.aligned.m8n8.x4.shared.b16 [%0], {%1,%2,%3,%4};" ::"r"(a), "r"(r0), "r"(r1), "r"(r2), "r"(r3) : "memory");
}
__device__ __forceinline__ void mma16816(float (&d)[4], uint32_t a0, uint32_t a1, uint32_t a2, uint32_t a3, uint32_t b0, uint32_t b1) {
    asm("mma.sync.aligned.m16n8k16.row.col.f32.bf16.bf16.f32 {%0,%1,%2,%3},{%4,%5,%6,%7},{%8,%9},{%0,%1,%2,%3};"
                 : "+f"(d[0]), "+f"(d[1]), "+f"(d[2]), "+f"(d[3])
                 : "r"(a0), "r"(a1), "r"(a2), "r"(a3), "r"(b0), "r"(b1));
}
__device__ __forceinline__ uint32_t movmat(uint32_t a) {
    uint32_t d;
    asm volatile("movmatrix.sync.aligned.m8n8.trans.b16 %0, %1;" : "=r"(d) : "r"(a));
    return d;
}
__device__ __forceinline__ uint32_t pack_bf16(float lo, float hi) {
    uint32_t r;
    asm("cvt.rn.bf16x2.f32 %0, %1, %2;" : "=r"(r) : "f"(hi), "f"(lo));
    return r;
}
__device__ __forceinline__ float bf16_round(float x) { return __bfloat162float(__float2bfloat16_rn(x)); }
__device__ __forceinline__ float bf_lo(uint32_t w) { return __uint_as_float(w << 16); }
__device__ __forceinline__ float bf_hi(uint32_t w) { return __uint_as_float(w & 0xFFFF0000u); }
__device__ __forceinline__ void bar_sync(int id, int n) { asm volatile("bar.sync %0, %1;" ::"r"(id), "r"(n) : "memory"); }
__device__ __forceinline__ void bar_sync_keep(int id, int n, uint32_t a, uint32_t b) {
    asm volatile("bar.sync %0, %1; // %2 %3" ::"r"(id), "r"(n), "r"(a), "r"(b) : "memory");
}
__device__ __forceinline__ bool bar_red_or(int id, int n, bool p) {
    uint32_t r;
    asm volatile("{.reg .pred p, q; setp.ne.u32 p, %3, 0; bar.red.or.pred q, %1, %2, p; selp.u32 %0, 1, 0, q;}" : "=r"(r) : "r"(id), "r"(n), "r"((uint32_t)p) : "memory");
    return r != 0;
}
__device__ __forceinline__ void bar_arrive(int id, int n) { asm volatile("bar.arrive %0, %1;" ::"r"(id), "r"(n) : "memory"); }
__device__ __forceinline__ void cp_async16(uint32_t dst, const void* src) {
    asm volatile("cp.async.cg.shared.global [%0], [%1], 16;" ::"r"(dst), "l"(src) : "memory");
}
__device__ __forceinline__ void cp_commit() { asm volatile("cp.async.commit_group;" ::: "memory"); }
template <int N> __device__ __forceinline__ void cp_wait() { asm volatile("cp.async.wait_group %0;" ::"n"(N) : "memory"); }
__device__ __forceinline__ uint4 ld_relaxed_v4(const void* p) {
    uint4 v;
    asm volatile("ld.relaxed.gpu.global.v4.u32 {%0,%1,%2,%3}, [%4];" : "=r"(v.x), "=r"(v.y), "=r"(v.z), "=r"(v.w) : "l"(p) : "memory");
    return v;
}
__device__ __forceinline__ void st_relaxed_u32(void* p, uint32_t v) { asm volatile("st.relaxed.gpu.global.u32 [%0], %1;" ::"l"(p), "r"(v) : "memory"); }
__device__ __forceinline__ void st_relaxed_v2(void* p, uint32_t a, uint32_t b) {
    asm volatile("st.relaxed.gpu.global.v2.u32 [%0], {%1,%2};" ::"l"(p), "r"(a), "r"(b) : "memory");
}
__device__ __forceinline__ void sts128(uint32_t a, uint4 v) {
    asm volatile("st.shared.v4.u32 [%0], {%1,%2,%3,%4};" ::"r"(a), "r"(v.x), "r"(v.y), "r"(v.z), "r"(v.w) : "memory");
}
__device__ __forceinline__ uint4 lds128(uint32_t a) {
    uint4 v;
    asm volatile("ld.shared.v4.u32 {%0,%1,%2,%3}, [%4];" : "=r"(v.x), "=r"(v.y), "=r"(v.z), "=r"(v.w) : "r"(a) : "memory");
    return v;
}
__device__ __forceinline__ void sts32(uint32_t a, uint32_t v) { asm volatile("st.shared.u32 [%0], %1;" ::"r"(a), "r"(v) : "memory"); }
__device__ __forceinline__ uint32_t lds32(uint32_t a) {
    uint32_t v;
    asm volatile("ld.shared.u32 %0, [%1];" : "=r"(v) : "r"(a) : "memory");
    return v;
}
__device__ __forceinline__ void mbar_init(uint32_t a, uint32_t c) { asm volatile("mbarrier.init.shared::cta.b64 [%0], %1;" ::"r"(a), "r"(c) : "memory"); }
__device__ __forceinline__ void mbar_expect_tx(uint32_t a, uint32_t bytes) {
    asm volatile("mbarrier.arrive.expect_tx.shared::cta.b64 _, [%0], %1;" ::"r"(a), "r"(bytes) : "memory");
}
__device__ __forceinline__ void mbar_arrive(uint32_t a) { asm volatile("mbarrier.arrive.shared::cta.b64 _, [%0];" ::"r"(a) : "memory"); }
__device__ __forceinline__ void mbar_wait(uint32_t a, uint32_t parity) {
    asm volatile("{.reg .pred p; .reg .u32 c;\n"
                 "mbarrier.try_wait.parity.shared::cta.b64 p, [%0], %1;\n"
                 "@p bra.uni MBW_DONE;\n"
                 "mov.u32 c, 0;\n"
                 "MBW_LOOP:\n"
                 "mbarrier.try_wait.parity.shared::cta.b64 p, [%0], %1;\n"
                 "@p bra.uni MBW_DONE;\n"
                 "add.u32 c, c, 1;\n"
                 "setp.lt.u32 p, c, 0x200000;\n"
                 "@p bra.uni MBW_LOOP;\n"
                 "trap;\n"
                 "MBW_DONE:}" ::"r"(a), "r"(parity) : "memory");
}
__device__ __forceinline__ void bulk_load(uint32_t dst, const void* src, uint32_t bytes, uint32_t bar) {
    asm volatile("cp.async.bulk.shared::cluster.global.mbarrier::complete_tx::bytes [%0], [%1], %2, [%3];" ::"r"(dst), "l"(src), "r"(bytes), "r"(bar) : "memory");
}
__device__ __forceinline__ void tma_load_2d(uint32_t dst, const CUtensorMap* map, int c0, int c1, uint32_t bar) {
    asm volatile("cp.async.bulk.tensor.2d.shared::cluster.global.mbarrier::complete_tx::bytes [%0], [%1, {%3, %4}], [%2];"
                 ::"r"(dst), "l"(map), "r"(bar), "r"(c0), "r"(c1) : "memory");
}
__device__ __forceinline__ uint64_t make_desc(uint32_t saddr, uint32_t lbo, uint32_t sbo) {
    return (uint64_t)((saddr & 0x3FFFF) >> 4) | ((uint64_t)((lbo >> 4) & 0x3FFF) << 16) | ((uint64_t)((sbo >> 4) & 0x3FFF) << 32) | ((uint64_t)1 << 62);
}
__device__ __forceinline__ void wg_fence() { asm volatile("wgmma.fence.sync.aligned;" ::: "memory"); }
__device__ __forceinline__ void wg_commit() { asm volatile("wgmma.commit_group.sync.aligned;" ::: "memory"); }
template <int N> __device__ __forceinline__ void wg_wait() { asm volatile("wgmma.wait_group.sync.aligned %0;" ::"n"(N) : "memory"); }

#define R4(b) "+f"(d[b + 0]), "+f"(d[b + 1]), "+f"(d[b + 2]), "+f"(d[b + 3])
#define R16(b) R4(b), R4(b + 4), R4(b + 8), R4(b + 12)
__device__ __forceinline__ void wgmma_n128(float (&d)[64], uint64_t da, uint64_t db) {
    asm volatile(
        "wgmma.mma_async.sync.aligned.m64n128k16.f32.bf16.bf16 "
        "{%0,%1,%2,%3,%4,%5,%6,%7,%8,%9,%10,%11,%12,%13,%14,%15,%16,%17,%18,%19,%20,%21,%22,%23,%24,%25,%26,%27,%28,%29,%30,%31,"
        "%32,%33,%34,%35,%36,%37,%38,%39,%40,%41,%42,%43,%44,%45,%46,%47,%48,%49,%50,%51,%52,%53,%54,%55,%56,%57,%58,%59,%60,%61,%62,%63},"
        "%64,%65,1,1,1,0,1;"
        : R16(0), R16(16), R16(32), R16(48)
        : "l"(da), "l"(db));
}
__device__ __forceinline__ void wgmma_n256(float (&d)[128], uint64_t da, uint64_t db) {
    asm volatile(
        "wgmma.mma_async.sync.aligned.m64n256k16.f32.bf16.bf16 "
        "{%0,%1,%2,%3,%4,%5,%6,%7,%8,%9,%10,%11,%12,%13,%14,%15,%16,%17,%18,%19,%20,%21,%22,%23,%24,%25,%26,%27,%28,%29,%30,%31,"
        "%32,%33,%34,%35,%36,%37,%38,%39,%40,%41,%42,%43,%44,%45,%46,%47,%48,%49,%50,%51,%52,%53,%54,%55,%56,%57,%58,%59,%60,%61,%62,%63,"
        "%64,%65,%66,%67,%68,%69,%70,%71,%72,%73,%74,%75,%76,%77,%78,%79,%80,%81,%82,%83,%84,%85,%86,%87,%88,%89,%90,%91,%92,%93,%94,%95,"
        "%96,%97,%98,%99,%100,%101,%102,%103,%104,%105,%106,%107,%108,%109,%110,%111,%112,%113,%114,%115,%116,%117,%118,%119,%120,%121,%122,%123,%124,%125,%126,%127},"
        "%128,%129,1,1,1,0,1;"
        : R16(0), R16(16), R16(32), R16(48), R16(64), R16(80), R16(96), R16(112)
        : "l"(da), "l"(db));
}
template <int BN> struct WgAcc;
template <> struct WgAcc<128> { static __device__ __forceinline__ void mma(float (&d)[64], uint64_t a, uint64_t b) { wgmma_n128(d, a, b); } };
template <> struct WgAcc<256> { static __device__ __forceinline__ void mma(float (&d)[128], uint64_t a, uint64_t b) { wgmma_n256(d, a, b); } };

__device__ __forceinline__ void wgmma_rs32(float (&d)[16], const uint32_t (&a)[4], uint64_t db, bool acc) {
    asm volatile(
        "{.reg .pred p; setp.ne.b32 p, %21, 0;\n"
        "wgmma.mma_async.sync.aligned.m64n32k16.f32.bf16.bf16 {%0,%1,%2,%3,%4,%5,%6,%7,%8,%9,%10,%11,%12,%13,%14,%15}, {%16,%17,%18,%19}, %20, p, 1, 1, 0;}"
        : R16(0) : "r"(a[0]), "r"(a[1]), "r"(a[2]), "r"(a[3]), "l"(db), "n"(1) );
}
__device__ __forceinline__ void wgmma_rs32_first(float (&d)[16], const uint32_t (&a)[4], uint64_t db) {
    asm volatile(
        "{.reg .pred p; setp.ne.b32 p, %21, 0;\n"
        "wgmma.mma_async.sync.aligned.m64n32k16.f32.bf16.bf16 {%0,%1,%2,%3,%4,%5,%6,%7,%8,%9,%10,%11,%12,%13,%14,%15}, {%16,%17,%18,%19}, %20, p, 1, 1, 0;}"
        : R16(0) : "r"(a[0]), "r"(a[1]), "r"(a[2]), "r"(a[3]), "l"(db), "n"(0) );
}
__device__ __forceinline__ void wgmma_ss32(float (&d)[16], uint64_t da, uint64_t db) {
    asm volatile(
        "wgmma.mma_async.sync.aligned.m64n32k16.f32.bf16.bf16 {%0,%1,%2,%3,%4,%5,%6,%7,%8,%9,%10,%11,%12,%13,%14,%15}, %16, %17, 1, 1, 1, 1, 0;"
        : R16(0) : "l"(da), "l"(db));
}
__device__ __forceinline__ void st_async4(uint32_t a, float x, float y, float z, float w, uint32_t bar) {
    asm volatile("st.async.weak.shared::cluster.mbarrier::complete_tx::bytes.v4.f32 [%0], {%1,%2,%3,%4}, [%5];" ::"r"(a), "f"(x), "f"(y), "f"(z), "f"(w), "r"(bar) : "memory");
}
__device__ __forceinline__ void st_async2(uint32_t a, float x, float y, uint32_t bar) {
    asm volatile("st.async.weak.shared::cluster.mbarrier::complete_tx::bytes.v2.f32 [%0], {%1,%2}, [%3];" ::"r"(a), "f"(x), "f"(y), "r"(bar) : "memory");
}
__device__ __forceinline__ void st_async1(uint32_t a, uint32_t x, uint32_t bar) {
    asm volatile("st.async.weak.shared::cluster.mbarrier::complete_tx::bytes.b32 [%0], %1, [%2];" ::"r"(a), "r"(x), "r"(bar) : "memory");
}
__device__ __forceinline__ void stsm4t(uint32_t a, uint32_t r0, uint32_t r1, uint32_t r2, uint32_t r3) {
    asm volatile("stmatrix.sync.aligned.m8n8.x4.trans.shared.b16 [%0], {%1,%2,%3,%4};" ::"r"(a), "r"(r0), "r"(r1), "r"(r2), "r"(r3) : "memory");
}
__device__ __forceinline__ void ldsm4t(uint32_t (&r)[4], uint32_t a) { ldsm4t(r[0], r[1], r[2], r[3], a); }
__device__ __forceinline__ void ldsm4(uint32_t (&r)[4], uint32_t a) { ldsm4(r[0], r[1], r[2], r[3], a); }
__device__ __forceinline__ void mma16816(float (&d)[4], const uint32_t (&a)[4], uint32_t b0, uint32_t b1) { mma16816(d, a[0], a[1], a[2], a[3], b0, b1); }
__device__ __forceinline__ void sched_fence(uint32_t v) {
    asm volatile("{.reg .pred p; setp.ne.u32 p, %0, 0xFFFFFFFF; @p bra.uni SF_OK; trap; SF_OK:}" ::"r"(v) : "memory");
}
__device__ __forceinline__ void mma16816v(float (&d)[4], const uint32_t (&a)[4], uint32_t b0, uint32_t b1) {
    asm volatile("mma.sync.aligned.m16n8k16.row.col.f32.bf16.bf16.f32 {%0,%1,%2,%3},{%4,%5,%6,%7},{%8,%9},{%0,%1,%2,%3};"
                 : "+f"(d[0]), "+f"(d[1]), "+f"(d[2]), "+f"(d[3]) : "r"(a[0]), "r"(a[1]), "r"(a[2]), "r"(a[3]), "r"(b0), "r"(b1));
}
__device__ __forceinline__ uint32_t uniform(uint32_t v) { return __reduce_max_sync(~0u, v); }

template <int BN, int STAGES> struct GemmCfg {
    static constexpr int A_BYTES = 128 * 64 * 2;
    static constexpr int B_BYTES = BN * 64 * 2;
    static constexpr int STAGE_BYTES = A_BYTES + B_BYTES;
    static constexpr int EPI_BYTES = 128 * BN * 2;
    static constexpr int SMEM = STAGES * STAGE_BYTES + EPI_BYTES + 1024 + 256;
};

template <int BN, int STAGES>
__global__ void __cluster_dims__(2, 1, 1) __launch_bounds__(288, 1)
gemm_kernel(const __grid_constant__ CUtensorMap mapA, const __grid_constant__ CUtensorMap mapB0, const __grid_constant__ CUtensorMap mapB1,
            const __grid_constant__ CUtensorMap mapB2, const __grid_constant__ CUtensorMap mapC, int tiles_m, int tiles_n, int kblocks) {
    using Cfg = GemmCfg<BN, STAGES>;
    KT_START(BN == 256 ? 0 : 3);
    extern __shared__ uint8_t smem_raw[];
    const uint32_t sbase = (smem_u32(smem_raw) + 1023) & ~1023u;
    const uint32_t epi = sbase + STAGES * Cfg::STAGE_BYTES;
    const uint32_t bars = epi + Cfg::EPI_BYTES;
    const int warp = threadIdx.x >> 5, lane = threadIdx.x & 31;
    const uint32_t rank = blockIdx.x & 1;
    if (threadIdx.x == 0) {
        for (int i = 0; i < STAGES; i++) { mbar_init(bars + 8 * i, 1); mbar_init(bars + 8 * (STAGES + i), 16); }
        asm volatile("fence.mbarrier_init.release.cluster;" ::: "memory");
    }
    __syncthreads();
    asm volatile("barrier.cluster.arrive.release.aligned; barrier.cluster.wait.acquire.aligned;" ::: "memory");
    const int npairs = (tiles_m >> 1) * tiles_n, ncl = gridDim.x >> 1;
    if (warp == 8) {
        if (lane == 0) {
            int st = 0; uint32_t ph = 1;
            for (int pr = blockIdx.x >> 1; pr < npairs; pr += ncl) {
                const int tm = 2 * (pr % (tiles_m >> 1)) + rank, tn = pr / (tiles_m >> 1);
                const int n0 = tn * BN;
                const CUtensorMap* mb = (n0 < 4096) ? &mapB0 : (n0 < 8192 ? &mapB1 : &mapB2);
                const int nb = n0 & 4095;
                for (int kb = 0; kb < kblocks; kb++) {
                    mbar_wait(bars + 8 * (STAGES + st), ph);
                    const uint32_t full = bars + 8 * st;
                    mbar_expect_tx(full, Cfg::STAGE_BYTES);
                    const uint32_t sa = sbase + st * Cfg::STAGE_BYTES;
                    tma_load_2d(sa, &mapA, kb * 64, tm * 128, full);
#pragma unroll
                    for (int i = 0; i < BN / 128; i++) {
                        const int bx = rank * (BN / 128) + i;
                        asm volatile("cp.async.bulk.tensor.2d.shared::cluster.global.mbarrier::complete_tx::bytes.multicast::cluster [%0], [%1, {%3, %4}], [%2], %5;"
                                     ::"r"(sa + Cfg::A_BYTES + bx * 8192), "l"(mb), "r"(full), "r"(nb + bx * 64), "r"(kb * 64), "h"((uint16_t)3) : "memory");
                    }
                    if (++st == STAGES) { st = 0; ph ^= 1; }
                }
            }
        }
    } else {
        const int wg = warp >> 2;
        uint32_t peer_empty;
        asm volatile("mapa.shared::cluster.u32 %0, %1, %2;" : "=r"(peer_empty) : "r"(bars + 8 * STAGES), "r"(rank ^ 1));
        auto release = [&](int stg) {
            if (lane == 0) {
                mbar_arrive(bars + 8 * (STAGES + stg));
                asm volatile("mbarrier.arrive.shared::cluster.b64 _, [%0];" ::"r"(peer_empty + 8 * stg) : "memory");
            }
        };
        const uint32_t ew = epi + wg * (64 * BN * 2);
        int st = 0; uint32_t ph = 0;
        for (int pr = blockIdx.x >> 1; pr < npairs; pr += ncl) {
            const int tm = 2 * (pr % (tiles_m >> 1)) + rank, tn = pr / (tiles_m >> 1);
            float d[BN / 2];
#pragma unroll
            for (int i = 0; i < BN / 2; i++) d[i] = 0.f;
            int prev = -1;
            for (int kb = 0; kb < kblocks; kb++) {
                mbar_wait(bars + 8 * st, ph);
                const uint32_t sa = sbase + st * Cfg::STAGE_BYTES;
                const uint64_t da = make_desc(sa + wg * 8192, 16, 1024);
                const uint64_t db = make_desc(sa + Cfg::A_BYTES, 8192, 1024);
                wg_fence();
#pragma unroll
                for (int k = 0; k < 4; k++) WgAcc<BN>::mma(d, da + k * 2, db + k * 128);
                wg_commit();
                if (prev >= 0) { wg_wait<1>(); release(prev); }
                prev = st;
                if (++st == STAGES) { st = 0; ph ^= 1; }
            }
            wg_wait<0>();
            release(prev);
            if ((warp & 3) == 0 && lane == 0) asm volatile("cp.async.bulk.wait_group.read 0;" ::: "memory");
            bar_sync(1 + wg, 128);
            const int r = (warp & 3) * 16 + (lane & 7) + ((lane >> 3) & 1) * 8;
#pragma unroll
            for (int c = 0; c < BN / 64; c++)
#pragma unroll
                for (int i = 0; i < 4; i++) {
                    const int b = (c * 8 + i * 2) * 4;
                    stsm4(ew + c * 8192 + r * 128 + (((i * 2 + (lane >> 4)) ^ (r & 7)) * 16), pack_bf16(d[b], d[b + 1]), pack_bf16(d[b + 2], d[b + 3]),
                          pack_bf16(d[b + 4], d[b + 5]), pack_bf16(d[b + 6], d[b + 7]));
                }
            asm volatile("fence.proxy.async.shared::cta;" ::: "memory");
            bar_sync(1 + wg, 128);
            if ((warp & 3) == 0 && lane == 0) {
#pragma unroll
                for (int c = 0; c < BN / 64; c++)
                    asm volatile("cp.async.bulk.tensor.2d.global.shared::cta.bulk_group [%0, {%2, %3}], [%1];"
                                 ::"l"(&mapC), "r"(ew + c * 8192), "r"(tn * BN + c * 64), "r"(tm * 128 + wg * 64) : "memory");
                asm volatile("cp.async.bulk.commit_group;" ::: "memory");
            }
        }
        if ((warp & 3) == 0 && lane == 0) asm volatile("cp.async.bulk.wait_group 0;" ::: "memory");
    }
    __syncwarp();
    KT_END(BN == 256 ? 0 : 3);
    asm volatile("barrier.cluster.arrive.relaxed; barrier.cluster.wait;" ::: "memory");
}

#define WO_RF1 6
constexpr int SM_KV = 0, KV_BYTES = 18432;
constexpr int SM_XT = 2 * KV_BYTES;
constexpr int SM_STG = SM_XT + 65536;
constexpr int SM_Z = SM_STG + 6144;
constexpr int SM_RT = SM_Z + 8192;
constexpr int SM_QKV = SM_RT + 12288;
constexpr int SM_R1 = SM_QKV + 6144;
constexpr int SM_R2 = SM_R1 + 2048;
constexpr int SM_O = SM_R2 + 1024;
constexpr int SM_S = SM_O + 2048;
constexpr int SM_TO = SM_S + 1536;
constexpr int SM_WORK_END = SM_TO + 2560;
constexpr int STG_QK = 0, STG_V = 98304;
constexpr int SM_WO1 = SM_WORK_END - WO_RF1 * 2048;
constexpr int STG_WO = SM_WO1 - 16384;
constexpr int SM_WQK = (SM_WO1 + 16384 > STG_V + 49152) ? SM_WO1 + 16384 : STG_V + 49152;
constexpr int SM_WV = SM_WQK + 32768;
constexpr int SM_WO2 = SM_WV + 16384;
constexpr int SM_BARS = SM_WO2 + 32768;
enum { MB_W0 = SM_BARS, MB_W1 = SM_BARS + 8, MB_W2 = SM_BARS + 16, MB_W3 = SM_BARS + 24, MB_XT = SM_BARS + 32  , MB_KV = SM_BARS + 48  ,
       MB_R1 = SM_BARS + 72, MB_R2 = SM_BARS + 80, MB_RT0 = SM_BARS + 88, MB_RT1 = SM_BARS + 96, MB_FREE = SM_BARS + 104,
       MB_P = SM_BARS + 112, MB_V = SM_BARS + 120, MB_STG = SM_BARS + 128, SM_ROLE = SM_BARS + 136 };
constexpr int CHAIN_SMEM = SM_ROLE + 8;
static_assert(SM_WORK_END % 1024 == 0 && STG_WO >= STG_V, "work area");
static_assert(CHAIN_SMEM <= 232448, "smem");

#define DLY_X 200
#define DLY_V 0
#define DLY_Y 250
#define DLY_Z 200
#define XFLIP 0
#define YFLIP 0
#define ZFLIP 1
#define GO_AT 13
#define REG_A 240
#define REG_B 208
#define REG_C (3 * 168 - REG_A - REG_B)
__host__ __device__ constexpr bool k_in_smem(int k) { return (k & 3) == 1; }
__host__ __device__ constexpr int k_reg_idx(int k) { return k_in_smem(k) ? 0 : k - (k + 2) / 4; }

enum { BAR_MEM = 1, BAR_GO, BAR_PUB, BAR_QK, BAR_S, BAR_O, BAR_SENT, BAR_COMM, BAR_PUBV, BAR_PV, BAR_PDONE, BAR_VP, BAR_ZP, BAR_PRO };

__device__ __forceinline__ uint32_t umax4(const uint4& v) { return max(max(v.x, v.y), max(v.z, v.w)); }
__device__ __forceinline__ unsigned gtime() { unsigned t; asm volatile("mov.u32 %0, %%globaltimer_lo;" : "=r"(t)::"memory"); return t; }
__device__ __forceinline__ unsigned clock32() { unsigned t; asm volatile("mov.u32 %0, %%clock;" : "=r"(t)::"memory"); return t; }
__device__ __forceinline__ void spin_cycles(int d) {
    if (d > 0) { const unsigned c0 = clock32(); while (clock32() - c0 < (unsigned)d) {} }
}
__device__ __forceinline__ float ex2_approx(float x) { float y; asm("ex2.approx.ftz.f32 %0, %1;" : "=f"(y) : "f"(x)); return y; }
__device__ __forceinline__ float rcp_approx(float x) { float y; asm("rcp.approx.ftz.f32 %0, %1;" : "=f"(y) : "f"(x)); return y; }
__device__ __forceinline__ void st_sent(const void* p) { asm volatile("st.relaxed.gpu.global.v4.u32 [%0], {%1,%1,%1,%1};" ::"l"(p), "r"(SENT) : "memory"); }
__device__ __forceinline__ uint4 poll1(const char* p) {
    uint4 v = ld_relaxed_v4(p);
    int guard = 0;
    while (umax4(v) == SENT) {
        if (++guard > (1 << 20)) __trap();
        v = ld_relaxed_v4(p);
    }
    return v;
}
template <class F> __device__ __forceinline__ void softmax40(uint32_t (&pw)[5], uint32_t sa, F mid) {
    const float LOG2E = 1.4426950408889634f;
    float e[10];
#pragma unroll
    for (int i = 0; i < 5; i++) {
        const uint32_t w = lds32(sa + i * 128);
        e[2 * i] = bf_lo(w); e[2 * i + 1] = bf_hi(w);
    }
    mid();
    float m = fmaxf(fmaxf(fmaxf(e[0], e[1]), fmaxf(e[2], e[3])), fmaxf(fmaxf(fmaxf(e[4], e[5]), fmaxf(e[6], e[7])), fmaxf(e[8], e[9])));
    m = fmaxf(m, __shfl_xor_sync(~0u, m, 1));
    m = fmaxf(m, __shfl_xor_sync(~0u, m, 2));
    const float mb2 = m * LOG2E;
#pragma unroll
    for (int i = 0; i < 10; i++) e[i] = ex2_approx(fmaf(e[i], LOG2E, -mb2));
    float sum = (((e[0] + e[1]) + (e[2] + e[3])) + ((e[4] + e[5]) + (e[6] + e[7]))) + (e[8] + e[9]);
    sum += __shfl_xor_sync(~0u, sum, 1);
    sum += __shfl_xor_sync(~0u, sum, 2);
    const float inv = rcp_approx(sum);
#pragma unroll
    for (int i = 0; i < 5; i++) pw[i] = pack_bf16(e[2 * i] * inv, e[2 * i + 1] * inv);
}
__device__ __forceinline__ uint32_t scale_scores(float a, float b) {
    const float scale = 0.08838834764831845f;
    const uint32_t w = pack_bf16(a, b);
    return pack_bf16(bf_lo(w) * scale, bf_hi(w) * scale);
}

__device__ __forceinline__ uint32_t peer_addr(uint32_t a, uint32_t rank) {
    uint32_t r;
    asm("mapa.shared::cluster.u32 %0, %1, %2;" : "=r"(r) : "r"(a), "r"(rank));
    return r;
}

#define TL(i) do {} while (0)
#define TLB(i) do {} while (0)
#define TLC(i) do {} while (0)

__global__ void __cluster_dims__(2, 1, 1) __launch_bounds__(384, 1)
chain_kernel(const __grid_constant__ CUtensorMap mapX, const __grid_constant__ CUtensorMap mapT32, const __grid_constant__ CUtensorMap mapT8,
             const __grid_constant__ CUtensorMap mapWq, const __grid_constant__ CUtensorMap mapWk, const __grid_constant__ CUtensorMap mapWv,
             const __grid_constant__ CUtensorMap mapWo, const bf16* __restrict__ mem0, char* __restrict__ mbox) {
    KT_START(2);
    extern __shared__ __align__(1024) uint8_t smem_chain[];
    constexpr uint32_t SB0 = 1024;
    if ((smem_u32(smem_chain) & 0xFFFFFF) != SB0) __trap();
    const int kh = blockIdx.x & 1;
    if (threadIdx.x == 0) {
        const uint32_t sb = smem_u32(smem_chain);
        for (int i = 0; i < 14; i++) mbar_init(sb + SM_BARS + 8 * i, 1);
        mbar_init(sb + MB_P, 4); mbar_init(sb + MB_V, 6); mbar_init(sb + MB_STG, 8);
        asm volatile("fence.mbarrier_init.release.cluster;" ::: "memory");
        if (kh == 0) {
            unsigned smid, ncl = gridDim.x >> 1;
            asm volatile("mov.u32 %0, %%smid;" : "=r"(smid));
            const unsigned c = g_cls[smid] & 1, i = atomicAdd(&g_reg[c], 1u);
            unsigned p = c * 32 + i;
            if (i >= 32) {
                unsigned n0, n1; int guard = 0;
                do {
                    asm volatile("ld.relaxed.gpu.global.u32 %0, [%1];" : "=r"(n0) : "l"(g_reg) : "memory");
                    asm volatile("ld.relaxed.gpu.global.u32 %0, [%1];" : "=r"(n1) : "l"(g_reg + 1) : "memory");
                } while (n0 + n1 < ncl && ++guard < (1 << 20));
                const unsigned k = (c ? n0 : n1) + i - 32;
                p = k < 32 ? (c ^ 1) * 32 + k : 64;
            }
            p |= g_reg[2] << 8;
            uint32_t ra;
            asm volatile("mapa.shared::cluster.u32 %0, %1, 1;" : "=r"(ra) : "r"(sb + SM_ROLE));
            asm volatile("st.shared::cluster.u32 [%0], %1;" ::"r"(ra), "r"(p) : "memory");
            sts32(sb + SM_ROLE, p);
        }
    }
    __syncthreads();
    asm volatile("barrier.cluster.arrive.release.aligned; barrier.cluster.wait.acquire.aligned;" ::: "memory");
    const uint32_t rw = uniform(lds32(smem_u32(smem_chain) + SM_ROLE));
    const int pair = rw & 255, yflip = (rw >> 8) ^ YFLIP;
    if (pair >= 64) return;
    const int h = pair >> 1, nh = pair & 1, j = 2 * nh + kh, role = 2 * pair + kh;
#define WG_ORDER 0x210
    const int warp = uniform(((WG_ORDER >> (4 * (threadIdx.x >> 7))) & 3) * 4 + ((threadIdx.x >> 5) & 3));
    auto make_id = [&]() {
        uint32_t t;
        asm volatile("mov.u32 %0, %%tid.x;" : "=r"(t));
        const uint32_t r = lds32(smem_u32(smem_chain) + SM_ROLE);
        return (t & 127) | ((blockIdx.x & 1) << 7) | ((r & 63) << 8) | ((((r >> 8) ^ YFLIP) & 1) << 14);
    };
#define PHASE() const uint32_t me = __shfl_sync(~0u, id, id); const int ln = me & 31, g = (me >> 5) & 3, kh = (me >> 7) & 1, nh = (me >> 8) & 1, h = (me >> 9) & 31, yflip = me >> 14; \
    const bool lead = __all_sync(~0u, g == 0); const uint32_t rsb = peer_addr(SB0, kh ^ 1), sb = peer_addr(SB0, kh), frag = ((ln & 7) + (ln >> 4) * 8) * 128 + (((2 * g + ((ln >> 3) & 1)) ^ (ln & 7)) * 16); \
    (void)nh; (void)h; (void)yflip; (void)lead; (void)rsb; (void)sb; (void)frag
#define QFRAG() (sb + ((ln & 8) ? SM_KV + (s & 1) * KV_BYTES + 16384 : SM_QKV) + (ln >> 4) * 128 + (ln & 7) * 16)
#define XTDESC() __all_sync(~0u, (s + 3) & 1)
#define XBOX() (mbox + (WIN + page_off((me >> 8) & 31, ((me >> 13) & 1) ^ XFLIP) + ((s & 3) << 14)))
    if (warp >= 8) {
        asm volatile("setmaxnreg.dec.sync.aligned.u32 %0;" ::"n"(REG_C));
        const int lane = __shfl_sync(~0u, (int)(threadIdx.x & 31), threadIdx.x & 31), g = warp & 3;
        const uint32_t rsb = peer_addr(SB0, kh ^ 1), sb = peer_addr(SB0, kh);
        const int ct = g * 32 + lane;
        if (warp == 8) {
            const CUtensorMap* ws = kh ? &mapWq : &mapWk;
            const CUtensorMap* wn = kh ? &mapWk : &mapWq;
            const int col = h * DH + 64 * nh, row = 512 * kh;
            if (lane == 0) { mbar_expect_tx(sb + MB_W0, 49152); mbar_expect_tx(sb + MB_W1, 98304); mbar_expect_tx(sb + MB_W2, 81920); mbar_expect_tx(sb + MB_W3, 32768); }
            __syncwarp();
            if (lane < 24) {
                const int k = lane + (lane + 2) / 3;
                tma_load_2d(sb + STG_V + lane * 2048, &mapWv, col, row + 16 * k, sb + MB_W0);
                tma_load_2d(sb + STG_QK + lane * 2048, ws, col, row + 16 * k, sb + MB_W1);
                tma_load_2d(sb + STG_QK + (24 + lane) * 2048, wn, col, row + 16 * k, sb + MB_W1);
            }
            if (lane < 8) {
                const int k = 4 * lane + 1;
                tma_load_2d(sb + SM_WQK + lane * 4096, ws, col, row + 16 * k, sb + MB_W2);
                tma_load_2d(sb + SM_WQK + lane * 4096 + 2048, wn, col, row + 16 * k, sb + MB_W2);
                tma_load_2d(sb + SM_WV + lane * 2048, &mapWv, col, row + 16 * k, sb + MB_W2);
            }
            if (lane < 2) tma_load_2d(sb + SM_WO2 + lane * 16384, &mapWo, 256 * j + 128 + 64 * lane, h * DH, sb + MB_W2);
            __syncwarp();
            bar_sync(BAR_PV, 160);
            if (lane < 2) tma_load_2d(sb + STG_WO + lane * 16384, &mapWo, 256 * j + 64 * lane, h * DH, sb + MB_W3);
            __syncwarp();
        }
        bar_sync(BAR_PDONE, 384);
        for (int c = ct; c < 512; c += 128) {
            uint32_t w[4];
#pragma unroll
            for (int r = 0; r < 4; r++) {
                const uint32_t lo = reinterpret_cast<const uint16_t*>(mem0)[(2 * r) * DM + 512 * kh + c], hi = reinterpret_cast<const uint16_t*>(mem0)[(2 * r + 1) * DM + 512 * kh + c];
                w[r] = lo | (hi << 16);
            }
            sts128(sb + SM_Z + c * 16, make_uint4(w[0], w[1], w[2], w[3]));
        }
        auto load_xt = [&](int seg, int half) {
            const uint32_t bar = sb + MB_XT + (seg & 1) * 8;
            if (half == 0) mbar_expect_tx(bar, 32768);
            asm volatile("cp.async.bulk.tensor.3d.shared::cluster.global.mbarrier::complete_tx::bytes [%0], [%1, {%3, %4, %5}], [%2];"
                         ::"r"(sb + SM_XT + (seg & 1) * 32768 + half * 16384), "l"(&mapX), "r"(bar), "r"(0), "r"(seg * SEG), "r"(8 * kh + 4 * half) : "memory");
        };
        auto tok_start = [&](int s) {
            if (lane == 0) {
                if (s > -3 && s + 2 < NSEG) {
                    mbar_wait(sb + MB_STG, (s + 2) & 1);
                    const int row = (((s + 2) & 3) * NH + h) * 96;
                    if (kh) {
                        asm volatile("cp.async.bulk.tensor.2d.global.shared::cta.bulk_group [%0, {%2, %3}], [%1];" ::"l"(&mapT32), "r"(sb + SM_STG), "r"(64 * nh), "r"(row + 32) : "memory");
                    } else {
#pragma unroll
                        for (int i = 0; i < 4; i++)
                            asm volatile("cp.async.bulk.global.shared::cta.bulk_group [%0], [%1], 1024;" ::"l"(g_tok + row * DH + i * 1024 + nh * 512), "r"(sb + SM_STG + i * 1024) : "memory");
                    }
#pragma unroll
                    for (int i = 0; i < 2; i++)
                        asm volatile("cp.async.bulk.tensor.2d.global.shared::cta.bulk_group [%0, {%2, %3}], [%1];" ::"l"(&mapT8), "r"(sb + SM_STG + 4096 + i * 1024), "r"(64 * nh), "r"(row + 64 + 16 * kh + 8 * i) : "memory");
                    asm volatile("cp.async.bulk.commit_group;" ::: "memory");
                }
                if (s + 4 < NSEG) load_xt(s + 4, 0);
                asm volatile("cp.async.bulk.wait_group.read 0;" ::: "memory");
                if (s < 0) {
                    asm volatile("mbarrier.arrive.shared::cluster.b64 _, [%0];" ::"r"(rsb + MB_FREE) : "memory");
                    mbar_wait(sb + MB_FREE, (s + 3) & 1);
                }
            }
            __syncwarp();
        };
        auto tok_mid = [&](int s) {
            if (lane == 0) {
                if (s + 4 < NSEG) load_xt(s + 4, 1);
                if (s > -3 && s + 2 < NSEG) {
                    asm volatile("cp.async.bulk.wait_group 0;" ::: "memory");
                    asm volatile("fence.proxy.async.global;" ::: "memory");
                    asm volatile("st.release.gpu.global.u32 [%0], %1;" ::"l"(g_xflag + role), "r"(s + 3) : "memory");
                }
            }
            __syncwarp();
        };
        auto kv_check = [&](int s) {
            if (s + 1 < NSEG) {
                if (lane < 4) {
                    unsigned f; int guard = 0;
                    do {
                        asm volatile("ld.acquire.gpu.global.u32 %0, [%1];" : "=r"(f) : "l"(g_xflag + h * 4 + lane) : "memory");
                        if (++guard > (1 << 20)) __trap();
                    } while (f <= (unsigned)(s + 1));
                }
                __syncwarp();
                asm volatile("fence.proxy.async.global;" ::: "memory");
            }
        };
        auto kv_load = [&](int s) {
            if (lane == 0 && s + 1 < NSEG) {
                const uint32_t bar = sb + MB_KV + ((s + 1) & 1) * 8, dst = sb + SM_KV + ((s + 1) & 1) * KV_BYTES;
                const int row = (((s + 1) & 3) * NH + h) * 96;
                mbar_expect_tx(bar, KV_BYTES);
#pragma unroll
                for (int i = 0; i < 2; i++)
                    asm volatile("cp.async.bulk.tensor.2d.shared::cluster.global.mbarrier::complete_tx::bytes.multicast::cluster [%0], [%1, {%3, %4}], [%2], %5;"
                                 ::"r"(dst + kh * 8192 + i * 4096), "l"(&mapT32), "r"(bar), "r"(i * 64), "r"(row + 32 + 32 * kh), "h"((uint16_t)3) : "memory");
                bulk_load(dst + 16384, g_tok + row * DH + j * 1024, 2048, bar);
            }
            __syncwarp();
        };
        if (warp == 9) {
            if (lane == 0) { load_xt(0, 0); load_xt(0, 1); }
#pragma unroll 1
            for (int s = -3; s < 0; s++) { tok_start(s); bar_arrive(BAR_PRO, 288); tok_mid(s); }
        }
        if (warp == 11) { kv_check(-1); kv_load(-1); }
        bar_arrive(BAR_MEM, 384);
        const uint32_t id = make_id();
#define YBOX(slot) (page_off((me >> 7) & 63, ((me >> 13) ^ yflip) & 1) + (((slot) & 3) << 14))
#define ZLINE(slot) (WIN + page_off(32 + ((me >> 12) & 1), ((me >> 13) & 1) ^ ZFLIP) + ((me >> 7) & 31) * 128 + (((slot) & 3) << 14))
#define XOTHER(slot) (WIN + page_off(((me >> 8) & 31) ^ 1, ((me >> 13) & 1) ^ XFLIP) + (((slot) & 3) << 14))
        auto get_qk = [&](int s) {
            PHASE();
            const char* p = mbox + (XOTHER(s) + (g & 1) * 1024 + ln * 16);
            const uint32_t dst = sb + SM_QKV + (nh ^ 1) * 1024 + (g & 1) * 2048 + ln * 16;
            asm volatile("" ::"l"(p));
            bar_sync_keep(BAR_PUB, 192, dst, dst);
            spin_cycles(DLY_X);
            uint4 v0 = ld_relaxed_v4(p), v1 = ld_relaxed_v4(p + 512);
            int guard = 0;
            while (max(umax4(v0), umax4(v1)) == SENT) {
                if (++guard > (1 << 20)) __trap();
                v0 = ld_relaxed_v4(p); v1 = ld_relaxed_v4(p + 512);
            }
            STAT(1, __any_sync(~0u, guard > 0) && warp == 10);
            sts128(dst, v0); sts128(dst + 512, v1);
        };
        auto get_v = [&](int s) {
            PHASE();
            const char* p = mbox + (XOTHER(s) + 2048 + (me & 63) * 16);
            const uint32_t dst = sb + SM_QKV + 4096 + (nh ^ 1) * 1024 + (me & 63) * 16;
            asm volatile("" ::"l"(p));
            bar_sync_keep(BAR_PUBV, 192, dst, dst);
            spin_cycles(DLY_V);
            sts128(dst, poll1(p));
            __syncwarp();
            if (ln == 0) mbar_arrive(sb + MB_V);
        };
        auto get_z = [&](int s) {
            PHASE();
            const uint32_t zo = WIN + page_off(32 + kh, ZFLIP) + (((s + 1) & 3) << 14) + (me & 127) * 16, dst = sb + SM_Z + (me & 127) * 16;
            const char* z0 = mbox + zo;
            const char* z1 = mbox + (zo ^ 4096);
            asm volatile("" ::"l"(z0), "l"(z1));
            bar_sync_keep(BAR_COMM, 128, dst, dst);
            spin_cycles(DLY_Z);
            uint4 v[4];
            v[0] = ld_relaxed_v4(z0); v[1] = ld_relaxed_v4(z0 + 2048); v[2] = ld_relaxed_v4(z1); v[3] = ld_relaxed_v4(z1 + 2048);
            int guard = 0;
            while (max(max(umax4(v[0]), umax4(v[1])), max(umax4(v[2]), umax4(v[3]))) == SENT) {
                if (++guard > (1 << 20)) __trap();
                if (umax4(v[0]) == SENT) v[0] = ld_relaxed_v4(z0);
                if (umax4(v[1]) == SENT) v[1] = ld_relaxed_v4(z0 + 2048);
                if (umax4(v[2]) == SENT) v[2] = ld_relaxed_v4(z1);
                if (umax4(v[3]) == SENT) v[3] = ld_relaxed_v4(z1 + 2048);
            }
            STAT(0, __any_sync(~0u, guard > 0) && warp == 8);
#pragma unroll
            for (int i = 0; i < 4; i++) sts128(dst + i * 2048, v[i]);
            bar_arrive(BAR_MEM, 384);
        };
        if (warp == 8) {
#pragma unroll 1
            for (int s = 0; s < NSEG; s++) {
                get_v(s);
                TLC(17);
                if (s + 1 == NSEG) break;
                PHASE();
                const uint32_t b0 = (ln >> 2 == 0) ? 0x00003F80u : (ln >> 2 == 1 ? 0x3F800000u : 0u), b1 = (ln >> 2 == 2) ? 0x00003F80u : (ln >> 2 == 3 ? 0x3F800000u : 0u);
                const char* ycur = mbox + (YBOX(s) + (ln & 3) * 128 + (ln >> 2) * 16);
                char* zdst = mbox + (ZLINE(s + 1) + (ln >> 2) * 16 + (ln & 1) * 8);
                asm volatile("" ::"l"(ycur), "l"(zdst));
                bar_sync(BAR_SENT, 288);
                spin_cycles(DLY_Y);
                uint4 v[8];
                uint32_t m = 0;
#pragma unroll
                for (int i = 0; i < 8; i++) v[i] = ld_relaxed_v4(ycur + i * 512);
#pragma unroll
                for (int i = 0; i < 8; i++) m = max(m, umax4(v[i]));
                if (__any_sync(~0u, m == SENT)) {
                    int guard = 0;
                    do {
#pragma unroll
                        for (int i = 0; i < 8; i++)
                            if (umax4(v[i]) == SENT) v[i] = ld_relaxed_v4(ycur + i * 512);
                        m = 0;
#pragma unroll
                        for (int i = 0; i < 8; i++) m = max(m, umax4(v[i]));
                        if (++guard > (1 << 20)) __trap();
                    } while (m == SENT);
                    __syncwarp();
                    STAT(2, true);
                }
                TL(18);
                float d0[4] = {0.f, 0.f, 0.f, 0.f}, d1[4] = {0.f, 0.f, 0.f, 0.f}, d2[4] = {0.f, 0.f, 0.f, 0.f}, d3[4] = {0.f, 0.f, 0.f, 0.f};
                mma16816(d0, v[0].x, v[0].y, v[0].z, v[0].w, b0, b1);
                mma16816(d1, v[1].x, v[1].y, v[1].z, v[1].w, b0, b1);
                mma16816(d2, v[2].x, v[2].y, v[2].z, v[2].w, b0, b1);
                mma16816(d3, v[3].x, v[3].y, v[3].z, v[3].w, b0, b1);
                mma16816(d0, v[4].x, v[4].y, v[4].z, v[4].w, b0, b1);
                mma16816(d1, v[5].x, v[5].y, v[5].z, v[5].w, b0, b1);
                mma16816(d2, v[6].x, v[6].y, v[6].z, v[6].w, b0, b1);
                mma16816(d3, v[7].x, v[7].y, v[7].z, v[7].w, b0, b1);
                if ((ln & 3) < 2) {
                    const uint32_t w0 = pack_bf16((d0[0] + d1[0]) + (d2[0] + d3[0]), (d0[1] + d1[1]) + (d2[1] + d3[1]));
                    const uint32_t w1 = pack_bf16((d0[2] + d1[2]) + (d2[2] + d3[2]), (d0[3] + d1[3]) + (d2[3] + d3[3]));
                    st_relaxed_v2(zdst, w0, w1);
                }
                if (s + 3 < NSEG) bar_arrive(BAR_ZP, 160);
                TL(19);
                get_z(s);
                TL(20);
            }
        } else if (warp == 9) {
#pragma unroll 1
            for (int s = 0; s < NSEG; s++) {
                tok_start(s);
                TLC(21);
                get_qk(s);
                TLC(31);
                bar_arrive(BAR_QK, 192);
                mbar_wait(sb + MB_V, s & 1);
                tok_mid(s);
                TLC(22);
                if (s + 1 == NSEG) break;
                get_z(s);
            }
        } else if (warp == 10) {
#pragma unroll 1
            for (int s = 0; s < NSEG; s++) {
                get_qk(s);
                TLC(16);
                {
                    PHASE();
                    const uint32_t qa = QFRAG(), ka = sb + SM_QKV + 2048 + ln * 16;
                    float sc[4] = {0.f, 0.f, 0.f, 0.f}, sd[4] = {0.f, 0.f, 0.f, 0.f};
                    mbar_wait(sb + MB_KV + (s & 1) * 8, (s >> 1) & 1);
                    mbar_wait(sb + MB_P, s & 1);
                    bar_sync_keep(BAR_QK, 192, qa, ka);
#pragma unroll
                    for (int p = 0; p < 4; p++) {
                        uint32_t a[2][4], kb[4];
                        ldsm4t(kb, ka + p * 512); ldsm4t(a[0], qa + p * 512); ldsm4t(a[1], qa + p * 512 + 256);
                        mma16816(sc, a[0], kb[0], kb[1]);
                        mma16816(sd, a[1], kb[2], kb[3]);
                    }
                    sts32(sb + SM_S + 512 + ln * 4, scale_scores(sc[0] + sd[0], sc[1] + sd[1]));
                    sts32(sb + SM_S + 768 + 512 + ln * 4, scale_scores(sc[2] + sd[2], sc[3] + sd[3]));
                    bar_arrive(BAR_S, s + 1 < NSEG ? 288 : 160);
                }
                if (s >= 1) {
                    PHASE();
                    const char* y = mbox + (YBOX(s - 1) + ln * 16);
                    const char* x = mbox + (XOTHER(s - 1) ^ 0x3000);
#pragma unroll
                    for (int i = 0; i < 8; i++) st_sent(y + i * 512);
                    st_sent(x + kh * 1024 + ln * 16);
                    st_sent(x + kh * 1024 + 512 + ln * 16);
                    st_sent(x + 2048 + ((ln >> 3) * 2 + kh) * 128 + (ln & 7) * 16);
                    if (ln < 8) st_sent(mbox + (ZLINE(s - 1) + ln * 16));
                    asm volatile("fence.release.gpu;" ::: "memory");
                    TL(23);
                }
                if (s + 1 == NSEG) break;
                get_z(s);
            }
        } else {
#pragma unroll 1
            for (int s = 0; s < NSEG; s++) {
                kv_check(s);
                get_v(s);
                kv_load(s);
                if (s + 1 == NSEG) break;
                get_z(s);
            }
        }
    } else if (warp < 4) {
        asm volatile("setmaxnreg.inc.sync.aligned.u32 %0;" ::"n"(REG_A));
        const uint32_t id = make_id();
        uint32_t wa[2][24][4];
        {
            PHASE();
            const uint32_t fa = sb + frag;
            mbar_wait(sb + MB_W1, 0);
#pragma unroll
            for (int t = 0; t < 2; t++)
#pragma unroll
                for (int r = 0; r < 24; r++) ldsm4t(wa[t][r], fa + STG_QK + (t * 24 + r) * 2048);
            mbar_wait(sb + MB_W2, 0);
            bar_arrive(BAR_PDONE, 384);
        }
        auto batch1 = [&](float (&d)[16], auto tc, auto bc) {
            constexpr int t = decltype(tc)::value;
            const uint64_t db = make_desc(SB0 + SM_XT + decltype(bc)::value * 32768, 16, 1024), da = make_desc(SB0 + SM_WQK, 16, 1024);
            wg_fence();
#pragma unroll
            for (int k = 0; k < 32; k++) {
                const uint64_t dk = db + (k >> 2) * 256 + (k & 3) * 2;
                if (k == 0) wgmma_rs32_first(d, wa[t][0], dk);
                else if (k_in_smem(k)) wgmma_ss32(d, da + ((k >> 2) * 2 + t) * 128, dk);
                else wgmma_rs32(d, wa[t][k_reg_idx(k)], dk, true);
            }
            wg_commit();
            wg_wait<0>();
        };
        auto batch = [&](float (&d)[16], bool odd, auto tc) {
            if (odd) batch1(d, tc, std::integral_constant<int, 1>());
            else batch1(d, tc, std::integral_constant<int, 0>());
        };
#pragma unroll 1
        for (int s = -3; s < NSEG; s++) {
            if (s >= 0) {
                {
                    PHASE();
                    const uint32_t aw = sb + SM_WQK + frag;
                    const uint32_t l16 = ln * 16, mb = sb + SM_Z + l16;
                    uint32_t pre[2][4];
                    ldsm4t(pre[0], aw); ldsm4t(pre[1], aw + 2048);
                    if (g == 0 && ln == 0) mbar_expect_tx(sb + MB_R1, 2048);
                    bar_sync_keep(BAR_MEM, 384, mb, aw);
                    if (lead) TLB(0);
                    float acc[2][2][4];
#pragma unroll
                    for (int t = 0; t < 4; t++) { acc[t >> 1][t & 1][0] = acc[t >> 1][t & 1][1] = acc[t >> 1][t & 1][2] = acc[t >> 1][t & 1][3] = 0.f; }
                    uint32_t b[2][4];
                    ldsm4t(b[0], mb); ldsm4t(b[1], mb + 512);
#pragma unroll
                    for (int p = 0; p < 16; p++) {
#pragma unroll
                        for (int c = 0; c < 2; c++) {
                            const int u = c ^ ((p >> 1) & 1), k = 2 * p + u;
                            if (k_in_smem(k)) {
                                mma16816v(acc[0][c], pre[0], b[p & 1][2 * u], b[p & 1][2 * u + 1]);
                                mma16816v(acc[1][c], pre[1], b[p & 1][2 * u], b[p & 1][2 * u + 1]);
                                if (k + 4 < 32) { ldsm4t(pre[0], aw + ((k >> 2) + 1) * 4096); ldsm4t(pre[1], aw + ((k >> 2) + 1) * 4096 + 2048); }
                            } else {
                                mma16816v(acc[0][c], wa[0][k_reg_idx(k)], b[p & 1][2 * u], b[p & 1][2 * u + 1]);
                                mma16816v(acc[1][c], wa[1][k_reg_idx(k)], b[p & 1][2 * u], b[p & 1][2 * u + 1]);
                            }
                        }
                        if (p + 2 < 16) ldsm4t(b[p & 1], mb + (p + 2) * 512);
                        if (p == GO_AT) bar_arrive(BAR_GO, 256);
                    }
                    st_async4(rsb + SM_R1 + g * 512 + l16, acc[0][0][0] + acc[0][1][0], acc[0][0][1] + acc[0][1][1], acc[0][0][2] + acc[0][1][2], acc[0][0][3] + acc[0][1][3], rsb + MB_R1);
                    if (lead) TL(1);
                    char* xd = XBOX() + kh * 1024 + g * 256 + ln * 4;
                    const uint32_t qo = SM_QKV + kh * 2048 + nh * 1024 + g * 256 + ln * 4;
                    const float o0 = acc[1][0][0] + acc[1][1][0], o1 = acc[1][0][1] + acc[1][1][1], o2 = acc[1][0][2] + acc[1][1][2], o3 = acc[1][0][3] + acc[1][1][3];
                    asm volatile("" ::"l"(xd), "r"(qo), "f"(o0), "f"(o1), "f"(o2), "f"(o3));
                    mbar_wait(sb + MB_R1, s & 1);
                    const uint4 v = lds128(sb + SM_R1 + g * 512 + l16);
                    const uint32_t w0 = pack_bf16(o0 + __uint_as_float(v.x), o1 + __uint_as_float(v.y)), w1 = pack_bf16(o2 + __uint_as_float(v.z), o3 + __uint_as_float(v.w));
                    st_relaxed_u32(xd, w0);
                    st_relaxed_u32(xd + 128, w1);
                    bar_arrive(BAR_PUB, 192);
                    st_async1(rsb + qo, w0, rsb + MB_P);
                    st_async1(rsb + qo + 128, w1, rsb + MB_P);
                    sts32(sb + qo, w0);
                    sts32(sb + qo + 128, w1);
                    __syncwarp();
                    if (ln == 0) { if (g == 0) mbar_expect_tx(sb + MB_P, 1024); else mbar_arrive(sb + MB_P); }
                    if (lead) TL(2);
                }
                if (s + 1 == NSEG) break;
            }
            if (s + 3 < NSEG) {
                PHASE();
                const bool db = XTDESC();
                if (g == 0 && ln == 0) mbar_expect_tx(sb + MB_RT0, 8192);
                mbar_wait(sb + MB_XT + ((s + 3) & 1) * 8, ((s + 3) >> 1) & 1);
                bar_sync(s >= 0 ? BAR_VP : BAR_PRO, s >= 0 ? 256 : 288);
                if (lead) TLB(24);
                float d[16];
                batch(d, db, std::integral_constant<int, 0>());
                if (lead) TL(7);
                const uint32_t rt = rsb + SM_RT + g * 2048 + ln * 16;
#pragma unroll
                for (int i = 0; i < 4; i++) st_async4(rt + i * 512, d[4 * i], d[4 * i + 1], d[4 * i + 2], d[4 * i + 3], rsb + MB_RT0);
            }
            if (s >= 0) {
                PHASE();
                const uint32_t l4 = sb + ln * 4, l16 = sb + ln * 16;
                uint32_t va[3][4];
                {
                    const uint32_t vaddr = sb + SM_KV + (s & 1) * KV_BYTES + 8192 + frag;
                    mbar_wait(sb + MB_KV + (s & 1) * 8, (s >> 1) & 1);
                    ldsm4t(va[0], vaddr); ldsm4t(va[1], vaddr + 2048);
                }
                const uint32_t fo = sb + SM_WO2 + 16384 + frag;
                bar_sync_keep(BAR_S, 288, l4, fo);
                if (lead) TLB(4);
                uint32_t pw[5], a1[4][4];
                softmax40(pw, l4 + SM_S, [&]() {
#pragma unroll
                    for (int k = 0; k < 2; k++) ldsm4t(a1[k], fo + k * 2048);
                    mbar_wait(sb + MB_V, s & 1);
                    ldsm4(va[2], (l16 & ~256u) + SM_QKV + 4096 + g * 256);
                });
                char* yd = mbox + (page_off(24 + 2 * g + 32 * nh, kh ^ yflip) + ((s & 3) << 14) + h * 128 + ln * 4);
                char* yd1 = mbox + (page_off(25 + 2 * g + 32 * nh, kh ^ yflip) + ((s & 3) << 14) + h * 128 + ln * 4);
                {
                    float o0[4] = {0.f, 0.f, 0.f, 0.f}, o1[4] = {0.f, 0.f, 0.f, 0.f}, o2[4] = {0.f, 0.f, 0.f, 0.f};
                    mma16816(o0, va[0], pw[0], pw[1]);
                    mma16816(o1, va[1], pw[2], pw[3]);
                    mma16816(o2, va[2], pw[4], 0u);
                    sts32(l4 + SM_O + g * 256, pack_bf16((o0[0] + o1[0]) + o2[0], (o0[1] + o1[1]) + o2[1]));
                    sts32(l4 + SM_O + g * 256 + 128, pack_bf16((o0[2] + o1[2]) + o2[2], (o0[3] + o1[3]) + o2[3]));
                }
                ldsm4t(a1[2], fo + 2 * 2048); ldsm4t(a1[3], fo + 3 * 2048);
                asm volatile("" ::"l"(yd), "l"(yd1));
                bar_sync_keep(BAR_O, 256, l16, l16);
                if (lead) TLB(5);
                {
                    float y0[4] = {0.f, 0.f, 0.f, 0.f}, y1[4] = {0.f, 0.f, 0.f, 0.f};
                    uint32_t b[2][4];
                    ldsm4t(b[0], l16 + SM_O); ldsm4t(b[1], l16 + SM_O + 512);
#pragma unroll
                    for (int p = 0; p < 4; p++) {
                        mma16816(y0, a1[(2 * p) & 3], b[p & 1][0], b[p & 1][1]);
                        if (p < 2) ldsm4t(a1[(2 * p) & 3], fo + (2 * p + 4) * 2048);
                        mma16816(y1, a1[(2 * p + 1) & 3], b[p & 1][2], b[p & 1][3]);
                        if (p < 2) ldsm4t(a1[(2 * p + 1) & 3], fo + (2 * p + 5) * 2048);
                        if (p < 2) ldsm4t(b[p & 1], l16 + SM_O + (p + 2) * 512);
                    }
                    st_relaxed_u32(yd, pack_bf16(y0[0] + y1[0], y0[1] + y1[1]));
                    st_relaxed_u32(yd1, pack_bf16(y0[2] + y1[2], y0[3] + y1[3]));
                }
                if (lead) TL(6);
                if (s + 3 >= NSEG) bar_arrive(BAR_SENT, 288);
            }
            if (s + 3 < NSEG) {
                PHASE();
                const bool db = XTDESC();
                float d[16];
                if (s >= 0) bar_sync(BAR_SENT, 288);
                if (lead) TLB(30);
                batch(d, db, std::integral_constant<int, 1>());
                if (lead) TL(8);
                const uint32_t rt = SM_RT + g * 2048 + ln * 16;
                mbar_wait(sb + MB_RT0, (s + 3) & 1);
                uint32_t w[8];
#pragma unroll
                for (int i = 0; i < 4; i++) {
                    const uint4 v = lds128(sb + rt + i * 512);
                    w[2 * i] = pack_bf16(d[4 * i] + __uint_as_float(v.x), d[4 * i + 1] + __uint_as_float(v.y));
                    w[2 * i + 1] = pack_bf16(d[4 * i + 2] + __uint_as_float(v.z), d[4 * i + 3] + __uint_as_float(v.w));
                }
                if (__all_sync(~0u, kh)) {
                    stsm4t(sb + SM_STG + frag, w[0], w[1], w[2], w[3]);
                    stsm4t(sb + SM_STG + frag + 2048, w[4], w[5], w[6], w[7]);
                } else {
                    const uint32_t so = sb + SM_STG + (ln >> 4) * 1024 + g * 256 + (ln & 15) * 16;
                    stsm4(so, w[0], w[1], w[2], w[3]);
                    stsm4(so + 2048, w[4], w[5], w[6], w[7]);
                }
                asm volatile("fence.proxy.async.shared::cta;" ::: "memory");
                __syncwarp();
                if (ln == 0) mbar_arrive(sb + MB_STG);
                if (lead) TL(9);
            }
        }
    } else {
        asm volatile("setmaxnreg.inc.sync.aligned.u32 %0;" ::"n"(REG_B));
        const uint32_t id = make_id();
        uint32_t wv[24][4], wo[8 + WO_RF1][4];
        {
            PHASE();
            const uint32_t fa = sb + frag;
            mbar_wait(sb + MB_W0, 0);
#pragma unroll
            for (int r = 0; r < 24; r++) ldsm4t(wv[r], fa + STG_V + r * 2048);
            bar_arrive(BAR_PV, 160);
            mbar_wait(sb + MB_W3, 0);
#pragma unroll
            for (int r = 0; r < 8 + WO_RF1; r++) ldsm4t(wo[r], fa + STG_WO + r * 2048);
            mbar_wait(sb + MB_W2, 0);
            bar_arrive(BAR_PDONE, 384);
        }
        auto tattn = [&](int s) {
            PHASE();
            const int j = 2 * nh + kh;
            const uint32_t kv = sb + SM_KV + (s & 1) * KV_BYTES;
            uint32_t pw[5];
            softmax40(pw, sb + ln * 4 + SM_S + 768, []() {});
            if (lead) TL(25);
            uint32_t w[4];
#pragma unroll
            for (int m = 0; m < 2; m++) {
                const uint32_t vaddr = kv + 8192 + (g >> 1) * 4096 + ((ln & 7) + (ln >> 4) * 8) * 128 + (((4 * (g & 1) + 2 * m + ((ln >> 3) & 1)) ^ (ln & 7)) * 16);
                uint32_t va[3][4];
                ldsm4t(va[0], vaddr); ldsm4t(va[1], vaddr + 2048);
                ldsm4(va[2], sb + SM_QKV + 4096 + (2 * g + m) * 256 + (ln & 15) * 16);
                float o0[4] = {0.f, 0.f, 0.f, 0.f}, o1[4] = {0.f, 0.f, 0.f, 0.f};
                mma16816(o0, va[0], pw[0], pw[1]);
                mma16816(o1, va[1], pw[2], pw[3]);
                mma16816(o0, va[2], pw[4], 0u);
                w[2 * m] = pack_bf16(o0[0] + o1[0], o0[1] + o1[1]);
                w[2 * m + 1] = pack_bf16(o0[2] + o1[2], o0[3] + o1[3]);
            }
            if (lead) TL(26);
            stsm4t(sb + SM_TO + g * 640 + (ln & 7) * 80 + (ln >> 3) * 16, w[0], w[1], w[2], w[3]);
            __syncwarp();
            stg128(g_ox + (size_t)(s * SEG + 8 * j + (ln >> 2)) * HD + h * DH + 32 * g + (ln & 3) * 8, lds128(sb + SM_TO + g * 640 + (ln >> 2) * 80 + (ln & 3) * 16));
        };
#pragma unroll 1
        for (int s = -3; s < NSEG; s++) {
            if (s >= 0) {
                {
                    PHASE();
                    const uint32_t aw = sb + SM_WV + frag;
                    const uint32_t mb = sb + SM_Z + ln * 16;
                    uint32_t pre[2][4];
                    ldsm4t(pre[0], aw); ldsm4t(pre[1], aw + 2048);
                    if (g == 0 && ln == 0) mbar_expect_tx(sb + MB_R2, 1024);
                    if (s == 0) bar_arrive(BAR_MEM, 384);
                    bar_sync_keep(BAR_GO, 256, mb, aw);
                    float acc[4][4];
#pragma unroll
                    for (int t = 0; t < 4; t++) { acc[t][0] = acc[t][1] = acc[t][2] = acc[t][3] = 0.f; }
                    uint32_t b[3][4];
                    ldsm4t(b[0], mb); ldsm4t(b[1], mb + 512); ldsm4t(b[2], mb + 1024);
#pragma unroll
                    for (int p = 0; p < 16; p++) {
#pragma unroll
                        for (int u = 0; u < 2; u++) {
                            const int k = 2 * p + u;
                            if (k_in_smem(k)) {
                                mma16816v(acc[(k + (k >> 2)) & 3], pre[(k >> 2) & 1], b[p % 3][2 * u], b[p % 3][2 * u + 1]);
                                if (k + 8 < 32) ldsm4t(pre[(k >> 2) & 1], aw + ((k >> 2) + 2) * 2048);
                            } else {
                                mma16816v(acc[(k + (k >> 2)) & 3], wv[k_reg_idx(k)], b[p % 3][2 * u], b[p % 3][2 * u + 1]);
                            }
                        }
                        if (p + 3 < 16) ldsm4t(b[p % 3], mb + (p + 3) * 512);
                    }
                    float o[4];
#pragma unroll
                    for (int i = 0; i < 4; i++) o[i] = (acc[0][i] + acc[1][i]) + (acc[2][i] + acc[3][i]);
                    if (s + 3 < NSEG) bar_arrive(BAR_VP, 256);
                    st_async2(rsb + SM_R2 + g * 256 + ln * 8, kh ? o[0] : o[2], kh ? o[1] : o[3], rsb + MB_R2);
                    if (lead) TL(10);
                    char* xd = XBOX() + 2048 + (2 * g + kh) * 128 + ln * 4;
                    const uint32_t qo = SM_QKV + 4096 + nh * 1024 + (2 * g + kh) * 128 + ln * 4;
                    const float o0 = kh ? o[2] : o[0], o1 = kh ? o[3] : o[1];
                    asm volatile("" ::"l"(xd), "r"(qo), "f"(o0), "f"(o1));
                    mbar_wait(sb + MB_R2, s & 1);
                    uint32_t vx, vy;
                    asm volatile("ld.shared.v2.u32 {%0,%1}, [%2];" : "=r"(vx), "=r"(vy) : "r"(sb + SM_R2 + g * 256 + ln * 8) : "memory");
                    const uint32_t w0 = pack_bf16(o0 + __uint_as_float(vx), o1 + __uint_as_float(vy));
                    st_relaxed_u32(xd, w0);
                    bar_arrive(BAR_PUBV, 192);
                    st_async1(rsb + qo, w0, rsb + MB_V);
                    sts32(sb + qo, w0);
                    __syncwarp();
                    if (ln == 0) { if (g == 0) mbar_expect_tx(sb + MB_V, 512); else mbar_arrive(sb + MB_V); }
                    if (lead) TL(11);
                }
                PHASE();
                const uint32_t l4 = sb + ln * 4, l16 = sb + ln * 16;
                uint32_t va[3][4];
                {
                    const uint32_t kv = sb + SM_KV + (s & 1) * KV_BYTES, qa = QFRAG();
                    const uint32_t ka = kv + (g * 8 + (ln & 7)) * 128 + (((ln >> 3) ^ (ln & 7)) * 16);
                    float sc[4] = {0.f, 0.f, 0.f, 0.f}, sd[4] = {0.f, 0.f, 0.f, 0.f};
                    uint32_t a[4][4], kb[4][4];
                    mbar_wait(sb + MB_KV + (s & 1) * 8, (s >> 1) & 1);
#pragma unroll
                    for (int p = 0; p < 4; p++) ldsm4(kb[p], (ka ^ ((p & 1) * 64)) + (p >> 1) * 4096);
                    mbar_wait(sb + MB_P, s & 1);
                    if (lead) TL(12);
                    bar_sync_keep(BAR_QK, 192, qa, l4);
                    if (lead) TLB(3);
#pragma unroll
                    for (int k = 0; k < 4; k++) ldsm4t(a[k], qa + k * 256);
#pragma unroll
                    for (int k = 0; k < 8; k++) {
                        mma16816((k & 1) ? sd : sc, a[k & 3], kb[k >> 1][2 * (k & 1)], kb[k >> 1][2 * (k & 1) + 1]);
                        if (k < 4) ldsm4t(a[k], qa + (k + 4) * 256);
                    }
                    sts32(l4 + SM_S + g * 128, scale_scores(sc[0] + sd[0], sc[1] + sd[1]));
                    uint32_t w2 = scale_scores(sc[2] + sd[2], sc[3] + sd[3]);
                    const int d = 8 * (2 * nh + kh) + (ln >> 2) - (8 * g + 2 * (ln & 3));
                    if (d < 0) w2 = (w2 & 0xFFFF0000u) | 0xFF80u;
                    if (d < 1) w2 = (w2 & 0x0000FFFFu) | 0xFF800000u;
                    sts32(l4 + SM_S + 768 + g * 128, w2);
                    if (s + 1 == NSEG) {
                        bar_sync(BAR_S, 160);
                        mbar_wait(sb + MB_V, s & 1);
                        tattn(s);
                        break;
                    }
                    ldsm4t(va[0], kv + 12288 + frag); ldsm4t(va[1], kv + 12288 + 2048 + frag);
                }
                const uint32_t fo = sb + frag;
                bar_sync_keep(BAR_S, 288, l4, fo);
                uint32_t pw[5], a1[4][4];
                softmax40(pw, l4 + SM_S, [&]() {
#pragma unroll
                    for (int k = 0; k < 2; k++) ldsm4t(a1[k], fo + SM_WO2 + k * 2048);
                    mbar_wait(sb + MB_V, s & 1);
                    ldsm4(va[2], (l16 & ~256u) + SM_QKV + 4096 + 1024 + g * 256);
                });
                const uint32_t yo = page_off(2 * g + 32 * nh, kh ^ yflip) + ((s & 3) << 14) + h * 128 + ln * 4;
                char* yd = mbox + yo;
                char* yd1 = mbox + (yo ^ 4096);
                {
                    float o0[4] = {0.f, 0.f, 0.f, 0.f}, o1[4] = {0.f, 0.f, 0.f, 0.f}, o2[4] = {0.f, 0.f, 0.f, 0.f};
                    mma16816(o0, va[0], pw[0], pw[1]);
                    mma16816(o1, va[1], pw[2], pw[3]);
                    mma16816(o2, va[2], pw[4], 0u);
                    sts32(l4 + SM_O + 1024 + g * 256, pack_bf16((o0[0] + o1[0]) + o2[0], (o0[1] + o1[1]) + o2[1]));
                    sts32(l4 + SM_O + 1024 + g * 256 + 128, pack_bf16((o0[2] + o1[2]) + o2[2], (o0[3] + o1[3]) + o2[3]));
                }
                ldsm4t(a1[2], fo + SM_WO2 + 2 * 2048); ldsm4t(a1[3], fo + SM_WO2 + 3 * 2048);
                asm volatile("" ::"l"(yd), "l"(yd1));
                bar_sync_keep(BAR_O, 256, l16, l16);
                {
                    float y0[4] = {0.f, 0.f, 0.f, 0.f}, y1[4] = {0.f, 0.f, 0.f, 0.f}, y2[4] = {0.f, 0.f, 0.f, 0.f};
                    uint32_t b[2][4];
                    ldsm4t(b[0], l16 + SM_O); ldsm4t(b[1], l16 + SM_O + 512);
#pragma unroll
                    for (int k = 0; k < 8; k++) {
                        const int p = k >> 1, u = k & 1;
                        mma16816(y2, a1[k & 3], b[p & 1][2 * u], b[p & 1][2 * u + 1]);
                        if (k < 4) ldsm4t(a1[k & 3], fo + SM_WO2 + (k + 4) * 2048);
                        mma16816(y0, wo[k], b[p & 1][2 * u], b[p & 1][2 * u + 1]);
                        if (k < WO_RF1) mma16816(y1, wo[8 + (k < WO_RF1 ? k : 0)], b[p & 1][2 * u], b[p & 1][2 * u + 1]);
                        else { uint32_t t[4]; ldsm4t(t, fo + SM_WO1 + k * 2048); mma16816(y1, t, b[p & 1][2 * u], b[p & 1][2 * u + 1]); }
                        if (u == 1 && p < 2) ldsm4t(b[p & 1], l16 + SM_O + (p + 2) * 512);
                    }
                    st_relaxed_u32(yd1 + 0x80000, pack_bf16(y2[0], y2[1]));
                    st_relaxed_u32(yd + 0x82000, pack_bf16(y2[2], y2[3]));
                    st_relaxed_u32(yd, pack_bf16(y0[0], y0[1]));
                    st_relaxed_u32(yd1 + 0x2000, pack_bf16(y0[2], y0[3]));
                    st_relaxed_u32(yd + 0x40000, pack_bf16(y1[0], y1[1]));
                    st_relaxed_u32(yd1 + 0x42000, pack_bf16(y1[2], y1[3]));
                }
                bar_arrive(BAR_SENT, 288);
                if (lead) TL(13);
                tattn(s);
                bar_arrive(BAR_MEM, 384);
                if (lead) TL(14);
            }
            if (s + 3 < NSEG) {
                PHASE();
                const bool db = XTDESC();
                float d[16];
                if (g == 0 && ln == 0) mbar_expect_tx(sb + MB_RT1, 4096);
                mbar_wait(sb + MB_XT + ((s + 3) & 1) * 8, ((s + 3) >> 1) & 1);
                bar_sync(s >= 0 ? BAR_ZP : BAR_PRO, s >= 0 ? 160 : 288);
                if (lead) TLB(29);
                auto batch = [&](auto bc) {
                    const uint64_t db = make_desc(SB0 + SM_XT + decltype(bc)::value * 32768, 16, 1024), da = make_desc(SB0 + SM_WV, 16, 1024);
                    wg_fence();
#pragma unroll
                    for (int k = 0; k < 32; k++) {
                        const uint64_t dk = db + (k >> 2) * 256 + (k & 3) * 2;
                        if (k == 0) wgmma_rs32_first(d, wv[0], dk);
                        else if (k_in_smem(k)) wgmma_ss32(d, da + (k >> 2) * 128, dk);
                        else wgmma_rs32(d, wv[k_reg_idx(k)], dk, true);
                    }
                    wg_commit();
                    wg_wait<0>();
                };
                if (db) batch(std::integral_constant<int, 1>());
                else batch(std::integral_constant<int, 0>());
                const uint32_t rt = SM_RT + 8192 + g * 1024 + ln * 16;
                if (lead) TL(27);
#pragma unroll
                for (int i = 0; i < 2; i++)
                    st_async4(rsb + rt + i * 512, kh ? d[4 * i] : d[8 + 4 * i], kh ? d[4 * i + 1] : d[9 + 4 * i], kh ? d[4 * i + 2] : d[10 + 4 * i], kh ? d[4 * i + 3] : d[11 + 4 * i], rsb + MB_RT1);
                float o[8];
#pragma unroll
                for (int i = 0; i < 8; i++) o[i] = kh ? d[8 + i] : d[i];
                mbar_wait(sb + MB_RT1, (s + 3) & 1);
                if (lead) TL(28);
                uint32_t w[4];
#pragma unroll
                for (int i = 0; i < 2; i++) {
                    const uint4 v = lds128(sb + rt + i * 512);
                    w[2 * i] = pack_bf16(o[4 * i] + __uint_as_float(v.x), o[4 * i + 1] + __uint_as_float(v.y));
                    w[2 * i + 1] = pack_bf16(o[4 * i + 2] + __uint_as_float(v.z), o[4 * i + 3] + __uint_as_float(v.w));
                }
                stsm4t(sb + SM_STG + 4096 + frag, w[0], w[1], w[2], w[3]);
                asm volatile("fence.proxy.async.shared::cta;" ::: "memory");
                __syncwarp();
                if (ln == 0) mbar_arrive(sb + MB_STG);
                if (lead) TL(15);
            }
        }
    }
    KT_END(2);
    asm volatile("barrier.cluster.arrive.relaxed; barrier.cluster.wait;" ::: "memory");
}

constexpr int B_UCH = 39 * 128 + 16;
constexpr int B_KLEN = 2128;
constexpr int B_KCH = 2 * B_KLEN * 2 + 64;
constexpr int B_SM_U = 0;
constexpr int B_SM_K = 16 * B_UCH;
constexpr int B_SM_BAR = B_SM_K + 16 * B_KCH;
constexpr int B_SMEM = B_SM_BAR + 16 + 128;
static_assert(16 * B_KCH >= 2 * 65536, "the k / v tiles alias the kernel copies");
#define PROBE_N 5
constexpr int B_C = 2056;

__device__ __forceinline__ uint32_t bf16_mul(uint32_t a, uint32_t b) {
    uint32_t d;
    asm("mul.rn.bf16x2 %0, %1, %2;" : "=r"(d) : "r"(a), "r"(b));
    return d;
}
__device__ __forceinline__ uint32_t bf16_add(uint32_t a, uint32_t b) {
    uint32_t d;
    asm("add.rn.bf16x2 %0, %1, %2;" : "=r"(d) : "r"(a), "r"(b));
    return d;
}

__device__ __forceinline__ uint32_t atomic_round_trip(char* p) {
    uint32_t t0, t1, v;
    asm volatile("{.reg .pred p;\n"
                 "mov.u32 %0, %%clock;\n"
                 "atom.relaxed.gpu.global.add.u32 %2, [%3], 1;\n"
                 "setp.ne.u32 p, %2, 0x7FFFFFFF;\n"
                 "mov.u32 %1, 0;\n"
                 "@p mov.u32 %1, %%clock;}" : "=&r"(t0), "=&r"(t1), "=&r"(v) : "l"(p) : "memory");
    return t1 - t0;
}
__device__ __forceinline__ uint32_t far_first(char* a, char* b, int lane) {
    if (lane < 16) stg128((lane < 8 ? a : b) + (lane & 7) * 16, make_uint4(0, 0, 0, 0));
    __syncwarp();
    uint32_t ta = ~0u, tb = ~0u;
    if (lane == 0) {
        __threadfence();
#pragma unroll 1
        for (int i = 0; i < PROBE_N; i++) { ta = min(ta, atomic_round_trip(a)); tb = min(tb, atomic_round_trip(b)); }
    }
    return ta > tb;
}
__device__ __forceinline__ void measure_distance(char* mbox, int lane) {
    const uint32_t b = blockIdx.x;
    unsigned smid;
    asm volatile("mov.u32 %0, %%smid;" : "=r"(smid));
    char* w1 = mbox + WIN + (b & 31) * 128;
    const uint32_t c = far_first(w1 + page_off(40 + (b >> 5), 0), w1 + page_off(40 + (b >> 5), 1), lane);
    if (lane == 0) g_cls[smid] = c;
    if (b == 0) {
        const uint32_t c0 = far_first(mbox + page_off(0, 0), mbox + page_off(0, 1), lane);
        if (lane == 0) { g_reg[2] = c0 ^ c; g_reg[0] = 0; g_reg[1] = 0; }
    }
    if (b == 1) for (int i = lane; i < 128; i += 32) g_xflag[i] = 0;
    __syncwarp();
}

#define SP(i)
__global__ void __launch_bounds__(512, 1)
ssm_kernel(const __grid_constant__ CUtensorMap mapK, const __grid_constant__ CUtensorMap mapV, const bf16* __restrict__ Q, const bf16* __restrict__ shiftk,
           const bf16* __restrict__ ssmk, const bf16* __restrict__ Dv, bf16* __restrict__ out, char* __restrict__ mbox) {
    extern __shared__ __align__(128) uint8_t smem_raw[];
    const uint32_t sb = (smem_u32(smem_raw) + 127) & ~127u;
    const int ch0 = (blockIdx.x >> 1) * 16, half = blockIdx.x & 1;
    const int t = threadIdx.x, warp = t >> 5, lane = t & 31;
    const int tmax = half ? 1536 : 2048;
    KT_START(1);
    SP(0);
    if (blockIdx.x >= 128) {
        if (warp == 15) measure_distance(mbox, lane);
        return;
    }
    const uint32_t stg_k = sb + B_SM_K, stg_v = stg_k + 65536, bar = sb + B_SM_BAR;
    if (t == 0) {
        mbar_init(bar, 1);
        asm volatile("fence.mbarrier_init.release.cluster;" ::: "memory");
        mbar_expect_tx(bar, 2 * tmax * 32);
        for (int r = 0; r < tmax; r += 256) {
            tma_load_2d(stg_k + r * 32, &mapK, ch0, r, bar);
            tma_load_2d(stg_v + r * 32, &mapV, ch0, r, bar);
        }
    }
    uint4 kr[8];
    {
        const uint4* src = reinterpret_cast<const uint4*>(ssmk + (size_t)(ch0 + warp) * S_LEN) + lane;
#pragma unroll
        for (int i = 0; i < 8; i++) kr[i] = __ldg(src + i * 32);
        const uint32_t ub = sb + B_SM_U + warp * B_UCH;
        for (int i = lane; i < 7 * 8; i += 32) sts128(ub + i * 16, make_uint4(0, 0, 0, 0));
    }
    const int hr = lane & 1, cc = ch0 + hr * 8;
    uint32_t w[4][4];
#pragma unroll
    for (int p = 0; p < 4; p++) {
        const uint4 sw = __ldg(reinterpret_cast<const uint4*>(shiftk + (size_t)cc * 4 + p * 8));
        w[0][p] = __byte_perm(sw.x, sw.z, 0x5410); w[1][p] = __byte_perm(sw.x, sw.z, 0x7632);
        w[2][p] = __byte_perm(sw.y, sw.w, 0x5410); w[3][p] = __byte_perm(sw.y, sw.w, 0x7632);
    }
    __syncthreads();
    if (warp == 15) measure_distance(mbox, lane);
    mbar_wait(bar, 0);
    SP(1);
    if (warp * 128 < tmax) {
#pragma unroll 2
        for (int i = 0; i < 8; i++) {
            const int tt = warp * 128 + i * 16 + (lane >> 1);
            const uint32_t ka = stg_k + tt * 32 + hr * 16;
            const uint4 z = make_uint4(0, 0, 0, 0);
            const uint4 k0 = lds128(ka), k1 = tt >= 1 ? lds128(ka - 32) : z, k2 = tt >= 2 ? lds128(ka - 64) : z, k3 = tt >= 3 ? lds128(ka - 96) : z;
            const uint4 vv = lds128(stg_v + tt * 32 + hr * 16);
            uint4 o;
#pragma unroll
            for (int p = 0; p < 4; p++) {
                uint32_t a = bf16_mul(((const uint32_t*)&k3)[p], w[3][p]);
                a = bf16_add(a, bf16_mul(((const uint32_t*)&k2)[p], w[2][p]));
                a = bf16_add(a, bf16_mul(((const uint32_t*)&k1)[p], w[1][p]));
                a = bf16_add(a, bf16_mul(((const uint32_t*)&k0)[p], w[0][p]));
                ((uint32_t*)&o)[p] = bf16_mul(a, ((const uint32_t*)&vv)[p]);
            }
            sts128(stg_v + tt * 32 + hr * 16, o);
        }
        __syncwarp();
#pragma unroll
        for (int i = 0; i < 8; i++) {
            const int tt = warp * 128 + i * 16;
            uint32_t r0, r1, r2, r3;
            ldsm4t(r0, r1, r2, r3, stg_v + (tt + (lane & 7) + (lane >> 4) * 8) * 32 + ((lane >> 3) & 1) * 16);
            const int chn = (lane & 7) + ((lane >> 3) & 1) * 8, ts = tt + (lane >> 4) * 8, row = 7 + (ts >> 6), unit = (ts & 63) >> 3;
            stsm4(sb + B_SM_U + chn * B_UCH + row * 128 + ((unit ^ (row & 7)) * 16), r0, r1, r2, r3);
        }
    }
    __syncthreads();
    {
        const uint32_t kb = sb + B_SM_K + warp * B_KCH;
#pragma unroll
        for (int i = 0; i < 8; i++) {
            const uint4 lo = kr[i];
            const uint32_t nx = __shfl_down_sync(~0u, lo.x, 1), n0 = (i < 7) ? __shfl_sync(~0u, kr[i < 7 ? i + 1 : 7].x, 0) : 0u;
            const uint32_t hix = (lane < 31) ? nx : n0;
            const int c = 256 - (lane + 32 * i);
            sts128(kb + c * 16, make_uint4(__byte_perm(hix, lo.w, 0x7610), __byte_perm(lo.w, lo.z, 0x7610), __byte_perm(lo.z, lo.y, 0x7610), __byte_perm(lo.y, lo.x, 0x7610)));
            sts128(kb + B_KLEN * 2 + 64 + c * 16, make_uint4(__byte_perm(lo.w, lo.w, 0x1032), __byte_perm(lo.z, lo.z, 0x1032), __byte_perm(lo.y, lo.y, 0x1032), __byte_perm(lo.x, lo.x, 0x1032)));
        }
        const uint32_t k0w = __shfl_sync(~0u, kr[0].x, 0);
        if (lane < 10) {
            const int c = (lane == 0) ? 0 : 256 + lane;
            sts128(kb + c * 16, make_uint4(c == 257 ? (k0w & 0xFFFFu) : 0u, 0u, 0u, 0u));
            sts128(kb + B_KLEN * 2 + 64 + c * 16, make_uint4(0u, 0u, 0u, 0u));
        }
    }
    __syncwarp();
    SP(2);
    SP(3);
    const int tA = half ? 1 : 0, tB = half ? 2 : 3;
    float accA[4][4], accB[4][4];
#pragma unroll
    for (int i = 0; i < 4; i++)
#pragma unroll
        for (int e = 0; e < 4; e++) { accA[i][e] = 0.f; accB[i][e] = 0.f; }
    const int g = lane >> 2, tq = lane & 3;
    const uint32_t kb = sb + B_SM_K + warp * B_KCH;
    const int e0 = B_C - g + 2 * tq;
    const uint32_t fbase = (e0 & 1) ? (kb + B_KLEN * 2 + 64 + (e0 - 1) * 2) : (kb + e0 * 2);
    const uint32_t ub = sb + B_SM_U + warp * B_UCH;
    uint32_t A[8][4];
    auto load_frag = [&](uint32_t (&a)[4], int q) {
        const uint32_t ad = fbase - 16 * q;
        a[0] = lds32(ad); a[1] = lds32(ad - 16); a[2] = lds32(ad + 16); a[3] = lds32(ad);
    };
#pragma unroll
    for (int i = 5; i < 8; i++) load_frag(A[i], 2 * (i - 8));
    const int mA = 8 * tA + 7, mB = 8 * tB + 7;
    auto tile_step = [&](float (&acc)[4][4], int tile, int m, auto mm_c) {
        constexpr int mm = decltype(mm_c)::value;
        const int row = 7 + 8 * tile - m + (lane & 7);
        const uint32_t ra = ub + row * 128;
#pragma unroll
        for (int p = 0; p < 2; p++) {
            uint32_t b[4];
            ldsm4(b[0], b[1], b[2], b[3], ra + (((p * 4 + (lane >> 3)) ^ (row & 7)) * 16));
#pragma unroll
            for (int u = 0; u < 2; u++) {
                const int k = 2 * p + u;
#pragma unroll
                for (int mt = 0; mt < 4; mt++) {
                    const int sl = (mm * 4 + (mt - k) + 8) & 7;
                    mma16816(acc[mt], A[sl][0], A[sl][1], A[sl][2], A[sl][3], b[2 * u], b[2 * u + 1]);
                }
            }
        }
    };
    int m = 0;
#pragma unroll 1
    for (; m <= mA; m += 2) {
#pragma unroll
        for (int i = 0; i < 4; i++) load_frag(A[i], 8 * m + 2 * i);
        tile_step(accB, tB, m, std::integral_constant<int, 0>());
        tile_step(accA, tA, m, std::integral_constant<int, 0>());
#pragma unroll
        for (int i = 0; i < 4; i++) load_frag(A[4 + i], 8 * m + 8 + 2 * i);
        tile_step(accB, tB, m + 1, std::integral_constant<int, 1>());
        tile_step(accA, tA, m + 1, std::integral_constant<int, 1>());
    }
#pragma unroll 1
    for (; m <= mB; m += 2) {
#pragma unroll
        for (int i = 0; i < 4; i++) load_frag(A[i], 8 * m + 2 * i);
        tile_step(accB, tB, m, std::integral_constant<int, 0>());
#pragma unroll
        for (int i = 0; i < 4; i++) load_frag(A[4 + i], 8 * m + 8 + 2 * i);
        tile_step(accB, tB, m + 1, std::integral_constant<int, 1>());
    }
    SP(4);
    {
        const uint32_t dw = (uint32_t)__ldg(reinterpret_cast<const uint16_t*>(Dv) + ch0 + warp) * 0x00010001u;
        __syncwarp();
#pragma unroll
        for (int tl = 0; tl < 2; tl++) {
            const int row = 7 + 8 * (tl ? tB : tA) + (lane & 7);
#pragma unroll
            for (int mp = 0; mp < 2; mp++) {
                const uint32_t a = ub + row * 128 + (((mp * 4 + (lane >> 3)) ^ (row & 7)) * 16);
                uint32_t u0, u1, u2, u3;
                ldsm4t(u0, u1, u2, u3, a);
                const float(&c0)[4] = tl ? accB[2 * mp] : accA[2 * mp];
                const float(&c1)[4] = tl ? accB[2 * mp + 1] : accA[2 * mp + 1];
                const uint32_t y0 = bf16_add(pack_bf16(c0[0], c0[1]), bf16_mul(u0, dw)), y1 = bf16_add(pack_bf16(c0[2], c0[3]), bf16_mul(u1, dw));
                const uint32_t y2 = bf16_add(pack_bf16(c1[0], c1[1]), bf16_mul(u2, dw)), y3 = bf16_add(pack_bf16(c1[2], c1[3]), bf16_mul(u3, dw));
                asm volatile("stmatrix.sync.aligned.m8n8.x4.trans.shared.b16 [%0], {%1,%2,%3,%4};" ::"r"(a), "r"(y0), "r"(y1), "r"(y2), "r"(y3) : "memory");
            }
        }
    }
    const int hh = lane >> 4, tbk = (warp & 7) * 16 + (lane & 15);
    const int tg = ((tbk < 64) ? tA : tB) * 512 + (tbk & 63) * 8;
    uint4 qv[8];
    if (t < 256) {
#pragma unroll
        for (int i = 0; i < 8; i++) qv[i] = __ldg(reinterpret_cast<const uint4*>(Q + (size_t)(tg + i) * DM + ch0 + hh * 8));
    }
    SP(5);
    __syncthreads();
    SP(6);
    if (t < 256) {
        const int row = 7 + (tg >> 6), unit = (tg & 63) >> 3;
        uint4 y[8];
#pragma unroll
        for (int c = 0; c < 8; c++) y[c] = lds128(sb + B_SM_U + (hh * 8 + c) * B_UCH + row * 128 + ((unit ^ (row & 7)) * 16));
#pragma unroll
        for (int i = 0; i < 8; i++) {
            const uint32_t sel = (i & 1) ? 0x7632 : 0x5410;
            uint4 o;
            o.x = bf16_mul(qv[i].x, __byte_perm(((const uint32_t*)&y[0])[i >> 1], ((const uint32_t*)&y[1])[i >> 1], sel));
            o.y = bf16_mul(qv[i].y, __byte_perm(((const uint32_t*)&y[2])[i >> 1], ((const uint32_t*)&y[3])[i >> 1], sel));
            o.z = bf16_mul(qv[i].z, __byte_perm(((const uint32_t*)&y[4])[i >> 1], ((const uint32_t*)&y[5])[i >> 1], sel));
            o.w = bf16_mul(qv[i].w, __byte_perm(((const uint32_t*)&y[6])[i >> 1], ((const uint32_t*)&y[7])[i >> 1], sel));
            stg128(out + (size_t)(tg + i) * OUT_LD + DM + ch0 + hh * 8, o);
        }
    } else {
        const uint4 sent = make_uint4(SENT, SENT, SENT, SENT);
        char* p0 = mbox + blockIdx.x * 16384 + (t - 256) * 16;
#pragma unroll
        for (int i = 0; i < 4; i++) stg128(p0 + i * 4096, sent);
        char* p1 = mbox + WIN + blockIdx.x * 8704 + (t - 256) * 16;
        stg128(p1, sent); stg128(p1 + 4096, sent);
        if (t < 256 + 32) stg128(p1 + 8192, sent);
    }
    KT_END(1);
}

typedef CUresult (*EncodeFn)(CUtensorMap*, CUtensorMapDataType, cuuint32_t, void*, const cuuint64_t*, const cuuint64_t*, const cuuint32_t*,
                             const cuuint32_t*, CUtensorMapInterleave, CUtensorMapSwizzle, CUtensorMapL2promotion, CUtensorMapFloatOOBfill);

static void make_map(EncodeFn fn, CUtensorMap* m, const void* ptr, uint64_t inner, uint64_t outer, uint32_t box_in, uint32_t box_out,
                     CUtensorMapL2promotion promo = CU_TENSOR_MAP_L2_PROMOTION_L2_256B) {
    cuuint64_t dims[2] = {inner, outer};
    cuuint64_t strides[1] = {inner * 2};
    cuuint32_t box[2] = {box_in, box_out};
    cuuint32_t es[2] = {1, 1};
    fn(m, CU_TENSOR_MAP_DATA_TYPE_BFLOAT16, 2, const_cast<void*>(ptr), dims, strides, box, es, CU_TENSOR_MAP_INTERLEAVE_NONE,
       CU_TENSOR_MAP_SWIZZLE_128B, promo, CU_TENSOR_MAP_FLOAT_OOB_FILL_NONE);
}

extern "C" void kernel_launch(void* const* d_in, const int* in_sizes, int n_in, void* d_out, int out_size) {
    const bf16* x = (const bf16*)d_in[0];
    const bf16* mem0 = (const bf16*)d_in[1];
    const bf16* Wq = (const bf16*)d_in[2];
    const bf16* Wk = (const bf16*)d_in[3];
    const bf16* Wv = (const bf16*)d_in[4];
    const bf16* Wo = (const bf16*)d_in[5];
    const bf16* Bq = (const bf16*)d_in[7];
    const bf16* Bk = (const bf16*)d_in[8];
    const bf16* Bv = (const bf16*)d_in[9];
    const bf16* Bsh = (const bf16*)d_in[10];
    const bf16* Bssm = (const bf16*)d_in[11];
    const bf16* BD = (const bf16*)d_in[12];
    bf16* out = (bf16*)d_out;

    static bool init = false;
    static EncodeFn enc = nullptr;
    static void *p_tok, *p_ox, *p_mbox;
    static int nclusters = 64;
    using G2 = GemmCfg<128, 5>;
    if (!init) {
        cudaDriverEntryPointQueryResult qr;
        cudaGetDriverEntryPoint("cuTensorMapEncodeTiled", (void**)&enc, cudaEnableDefault, &qr);
        cudaGetSymbolAddress(&p_tok, g_tok);
        cudaGetSymbolAddress(&p_ox, g_ox);
        cudaGetSymbolAddress(&p_mbox, g_mbox);
        cudaFuncSetAttribute(gemm_kernel<128, 5>, cudaFuncAttributeMaxDynamicSharedMemorySize, G2::SMEM);
        cudaFuncSetAttribute(chain_kernel, cudaFuncAttributeMaxDynamicSharedMemorySize, CHAIN_SMEM);
        cudaFuncSetAttribute(ssm_kernel, cudaFuncAttributeMaxDynamicSharedMemorySize, B_SMEM);
        cudaLaunchConfig_t cfg = {};
        cfg.gridDim = dim3(132); cfg.blockDim = dim3(384); cfg.dynamicSmemBytes = CHAIN_SMEM;
        cudaLaunchAttribute at[1];
        at[0].id = cudaLaunchAttributeClusterDimension; at[0].val.clusterDim.x = 2; at[0].val.clusterDim.y = 1; at[0].val.clusterDim.z = 1;
        cfg.attrs = at; cfg.numAttrs = 1;
        int n = 0;
        if (cudaOccupancyMaxActiveClusters(&n, chain_kernel, &cfg) == cudaSuccess && n > 64) nclusters = n < 66 ? n : 66;
        (void)cudaGetLastError();
        init = true;
    }
    char* mbox = (char*)(((uintptr_t)p_mbox + WIN - 1) & ~(uintptr_t)(WIN - 1));
    CUtensorMap mX, mT32, mT8, mWq, mWk, mWv, mWoC, mOx, mWo, mOut;
    {
        cuuint64_t dims[3] = {64, S_LEN, DM / 64};
        cuuint64_t strides[2] = {DM * 2, 128};
        cuuint32_t box[3] = {64, 32, 4};
        cuuint32_t es[3] = {1, 1, 1};
        enc(&mX, CU_TENSOR_MAP_DATA_TYPE_BFLOAT16, 3, const_cast<bf16*>(x), dims, strides, box, es, CU_TENSOR_MAP_INTERLEAVE_NONE,
            CU_TENSOR_MAP_SWIZZLE_128B, CU_TENSOR_MAP_L2_PROMOTION_L2_256B, CU_TENSOR_MAP_FLOAT_OOB_FILL_NONE);
    }
    make_map(enc, &mT32, p_tok, DH, 4 * NH * 3 * SEG, 64, 32, CU_TENSOR_MAP_L2_PROMOTION_L2_128B);
    make_map(enc, &mT8, p_tok, DH, 4 * NH * 3 * SEG, 64, 8, CU_TENSOR_MAP_L2_PROMOTION_L2_128B);
    make_map(enc, &mWq, Wq, HD, DM, 64, 16, CU_TENSOR_MAP_L2_PROMOTION_L2_128B);
    make_map(enc, &mWk, Wk, HD, DM, 64, 16, CU_TENSOR_MAP_L2_PROMOTION_L2_128B);
    make_map(enc, &mWv, Wv, HD, DM, 64, 16, CU_TENSOR_MAP_L2_PROMOTION_L2_128B);
    make_map(enc, &mWoC, Wo, DM, HD, 64, 128, CU_TENSOR_MAP_L2_PROMOTION_L2_128B);
    make_map(enc, &mOx, p_ox, HD, S_LEN, 64, 128);
    make_map(enc, &mWo, Wo, DM, HD, 64, 64);
    make_map(enc, &mOut, out, OUT_LD, S_LEN, 64, 64);

    CUtensorMap mBk, mBv;
    for (int i = 0; i < 2; i++) {
        cuuint64_t dims[2] = {DM, S_LEN};
        cuuint64_t strides[1] = {DM * 2};
        cuuint32_t box[2] = {16, 256};
        cuuint32_t es[2] = {1, 1};
        enc(i ? &mBv : &mBk, CU_TENSOR_MAP_DATA_TYPE_BFLOAT16, 2, const_cast<bf16*>(i ? Bv : Bk), dims, strides, box, es, CU_TENSOR_MAP_INTERLEAVE_NONE,
            CU_TENSOR_MAP_SWIZZLE_NONE, CU_TENSOR_MAP_L2_PROMOTION_NONE, CU_TENSOR_MAP_FLOAT_OOB_FILL_NONE);
    }
    cudaStream_t st = cudaStreamPerThread;
    ssm_kernel<<<132, 512, B_SMEM, st>>>(mBk, mBv, Bq, Bsh, Bssm, BD, out, mbox);
    chain_kernel<<<2 * nclusters, 384, CHAIN_SMEM, st>>>(mX, mT32, mT8, mWq, mWk, mWv, mWoC, mem0, mbox);
    gemm_kernel<128, 5><<<128, 288, G2::SMEM, st>>>(mOx, mWo, mWo, mWo, mOut, 16, 8, 64);
}
```

```cpp
#include <cuda_runtime.h>
#include <cuda_bf16.h>
#include <cuda.h>
#include <stdint.h>
#include <type_traits>

typedef __nv_bfloat16 bf16;

constexpr int S_LEN = 2048, DM = 1024, NH = 32, DH = 128, NSEG = 64, SEG = 32;
constexpr int HD = NH * DH;
constexpr int OUT_LD = 2048;
constexpr unsigned SENT = 0xFFFFFFFFu;

__device__ bf16 g_tok[4 * NH * 3 * SEG * DH];
__device__ bf16 g_ox[(size_t)S_LEN * HD];
__device__ uint4 g_mbox[4 * 131072];
__device__ unsigned g_xflag[128];
__device__ unsigned g_reg[4];
__device__ unsigned g_cls[256];
__device__ unsigned g_err;
constexpr uint32_t WIN = 2u << 20;
__host__ __device__ constexpr uint32_t page_off(uint32_t idx, uint32_t c) {
    return ((idx & 1) << 13) | ((idx >> 1) << 16) | (((c ^ idx ^ (idx >> 1) ^ (idx >> 2) ^ (idx >> 4)) & 1) << 12);
}
#define STAT(i, c) (void)(c)
#define KT_START(k)
#define KT_END(k)

__device__ __forceinline__ uint32_t smem_u32(const void* p) { return (uint32_t)__cvta_generic_to_shared(p); }
__device__ __forceinline__ void ldsm4(uint32_t& r0, uint32_t& r1, uint32_t& r2, uint32_t& r3, uint32_t a) {
    asm volatile("ldmatrix.sync.aligned.m8n8.x4.shared.b16 {%0,%1,%2,%3}, [%4];" : "=r"(r0), "=r"(r1), "=r"(r2), "=r"(r3) : "r"(a) : "memory");
}
__device__ __forceinline__ void ldsm4t(uint32_t& r0, uint32_t& r1, uint32_t& r2, uint32_t& r3, uint32_t a) {
    asm volatile("ldmatrix.sync.aligned.m8n8.x4.trans.shared.b16 {%0,%1,%2,%3}, [%4];" : "=r"(r0), "=r"(r1), "=r"(r2), "=r"(r3) : "r"(a) : "memory");
}
__device__ __forceinline__ void ldsm2(uint32_t& r0, uint32_t& r1, uint32_t a) {
    asm volatile("ldmatrix.sync.aligned.m8n8.x2.shared.b16 {%0,%1}, [%2];" : "=r"(r0), "=r"(r1) : "r"(a) : "memory");
}
__device__ __forceinline__ void stg128(void* p, uint4 v) {
    asm volatile("st.global.v4.u32 [%0], {%1,%2,%3,%4};" ::"l"(p), "r"(v.x), "r"(v.y), "r"(v.z), "r"(v.w) : "memory");
}
__device__ __forceinline__ void stsm4(uint32_t a, uint32_t r0, uint32_t r1, uint32_t r2, uint32_t r3) {
    asm volatile("stmatrix.sync.aligned.m8n8.x4.shared.b16 [%0], {%1,%2,%3,%4};" ::"r"(a), "r"(r0), "r"(r1), "r"(r2), "r"(r3) : "memory");
}
__device__ __forceinline__ void mma16816(float (&d)[4], uint32_t a0, uint32_t a1, uint32_t a2, uint32_t a3, uint32_t b0, uint32_t b1) {
    asm("mma.sync.aligned.m16n8k16.row.col.f32.bf16.bf16.f32 {%0,%1,%2,%3},{%4,%5,%6,%7},{%8,%9},{%0,%1,%2,%3};"
                 : "+f"(d[0]), "+f"(d[1]), "+f"(d[2]), "+f"(d[3])
                 : "r"(a0), "r"(a1), "r"(a2), "r"(a3), "r"(b0), "r"(b1));
}
__device__ __forceinline__ void mma1688(float (&d)[4], uint32_t a0, uint32_t a1, uint32_t b0) {
    asm("mma.sync.aligned.m16n8k8.row.col.f32.bf16.bf16.f32 {%0,%1,%2,%3},{%4,%5},{%6},{%0,%1,%2,%3};"
        : "+f"(d[0]), "+f"(d[1]), "+f"(d[2]), "+f"(d[3]) : "r"(a0), "r"(a1), "r"(b0));
}
__device__ __forceinline__ uint32_t movmat(uint32_t a) {
    uint32_t d;
    asm volatile("movmatrix.sync.aligned.m8n8.trans.b16 %0, %1;" : "=r"(d) : "r"(a));
    return d;
}
__device__ __forceinline__ uint32_t pack_bf16(float lo, float hi) {
    uint32_t r;
    asm("cvt.rn.bf16x2.f32 %0, %1, %2;" : "=r"(r) : "f"(hi), "f"(lo));
    return r;
}
__device__ __forceinline__ float bf16_round(float x) { return __bfloat162float(__float2bfloat16_rn(x)); }
__device__ __forceinline__ float bf_lo(uint32_t w) { return __uint_as_float(w << 16); }
__device__ __forceinline__ float bf_hi(uint32_t w) { return __uint_as_float(w & 0xFFFF0000u); }
__device__ __forceinline__ void bar_sync(int id, int n) { asm volatile("bar.sync %0, %1;" ::"r"(id), "r"(n) : "memory"); }
__device__ __forceinline__ void bar_sync_keep(int id, int n, uint32_t a, uint32_t b) {
    asm volatile("bar.sync %0, %1; // %2 %3" ::"r"(id), "r"(n), "r"(a), "r"(b) : "memory");
}
__device__ __forceinline__ bool bar_red_or(int id, int n, bool p) {
    uint32_t r;
    asm volatile("{.reg .pred p, q; setp.ne.u32 p, %3, 0; bar.red.or.pred q, %1, %2, p; selp.u32 %0, 1, 0, q;}" : "=r"(r) : "r"(id), "r"(n), "r"((uint32_t)p) : "memory");
    return r != 0;
}
__device__ __forceinline__ void bar_arrive(int id, int n) { asm volatile("bar.arrive %0, %1;" ::"r"(id), "r"(n) : "memory"); }
__device__ __forceinline__ void cp_async16(uint32_t dst, const void* src) {
    asm volatile("cp.async.cg.shared.global [%0], [%1], 16;" ::"r"(dst), "l"(src) : "memory");
}
__device__ __forceinline__ void cp_commit() { asm volatile("cp.async.commit_group;" ::: "memory"); }
template <int N> __device__ __forceinline__ void cp_wait() { asm volatile("cp.async.wait_group %0;" ::"n"(N) : "memory"); }
__device__ __forceinline__ uint4 ld_relaxed_v4(const void* p) {
    uint4 v;
    asm volatile("ld.relaxed.gpu.global.v4.u32 {%0,%1,%2,%3}, [%4];" : "=r"(v.x), "=r"(v.y), "=r"(v.z), "=r"(v.w) : "l"(p) : "memory");
    return v;
}
__device__ __forceinline__ void st_relaxed_u32(void* p, uint32_t v) { asm volatile("st.relaxed.gpu.global.u32 [%0], %1;" ::"l"(p), "r"(v) : "memory"); }
__device__ __forceinline__ void st_relaxed_v2(void* p, uint32_t a, uint32_t b) {
    asm volatile("st.relaxed.gpu.global.v2.u32 [%0], {%1,%2};" ::"l"(p), "r"(a), "r"(b) : "memory");
}
__device__ __forceinline__ void sts128(uint32_t a, uint4 v) {
    asm volatile("st.shared.v4.u32 [%0], {%1,%2,%3,%4};" ::"r"(a), "r"(v.x), "r"(v.y), "r"(v.z), "r"(v.w) : "memory");
}
__device__ __forceinline__ uint4 lds128(uint32_t a) {
    uint4 v;
    asm volatile("ld.shared.v4.u32 {%0,%1,%2,%3}, [%4];" : "=r"(v.x), "=r"(v.y), "=r"(v.z), "=r"(v.w) : "r"(a) : "memory");
    return v;
}
__device__ __forceinline__ void sts32(uint32_t a, uint32_t v) { asm volatile("st.shared.u32 [%0], %1;" ::"r"(a), "r"(v) : "memory"); }
__device__ __forceinline__ uint32_t lds32(uint32_t a) {
    uint32_t v;
    asm volatile("ld.shared.u32 %0, [%1];" : "=r"(v) : "r"(a) : "memory");
    return v;
}
__device__ __forceinline__ void mbar_init(uint32_t a, uint32_t c) { asm volatile("mbarrier.init.shared::cta.b64 [%0], %1;" ::"r"(a), "r"(c) : "memory"); }
__device__ __forceinline__ void mbar_expect_tx(uint32_t a, uint32_t bytes) {
    asm volatile("mbarrier.arrive.expect_tx.shared::cta.b64 _, [%0], %1;" ::"r"(a), "r"(bytes) : "memory");
}
__device__ __forceinline__ void mbar_arrive(uint32_t a) { asm volatile("mbarrier.arrive.shared::cta.b64 _, [%0];" ::"r"(a) : "memory"); }
__device__ __forceinline__ void mbar_wait(uint32_t a, uint32_t parity) {
    asm volatile("{.reg .pred p; .reg .u32 c;\n"
                 "mov.u32 c, 0;\n"
                 "MBW_LOOP:\n"
                 "add.u32 c, c, 1;\n"
                 "setp.gt.u32 p, c, 0x10000;\n"
                 "@!p mbarrier.try_wait.parity.shared::cta.b64 p, [%0], %1;\n"
                 "@!p bra.uni MBW_LOOP;}" ::"r"(a), "r"(parity) : "memory");
}
__device__ __forceinline__ void mbar_wait_w(uint32_t a, uint32_t parity) {
    asm volatile("{.reg .pred p; .reg .u32 c;\n"
                 "mov.u32 c, 0;\n"
                 "MBW_LOOP:\n"
                 "add.u32 c, c, 1;\n"
                 "setp.gt.u32 p, c, 0x10000;\n"
                 "@!p mbarrier.try_wait.parity.shared::cta.b64 p, [%0], %1;\n"
                 "vote.sync.all.pred p, p, 0xFFFFFFFF;\n"
                 "@!p bra.uni MBW_LOOP;}" ::"r"(a), "r"(parity) : "memory");
}
__device__ __forceinline__ void mbar_expect_tx_if0(uint32_t sel, uint32_t a, uint32_t bytes) {
    asm volatile("{.reg .pred p; setp.eq.u32 p, %2, 0; @p mbarrier.arrive.expect_tx.shared::cta.b64 _, [%0], %1;}" ::"r"(a), "r"(bytes), "r"(sel) : "memory");
}
__device__ __forceinline__ void mbar_arrive_if0(uint32_t sel, uint32_t a) {
    asm volatile("{.reg .pred p; setp.eq.u32 p, %1, 0; @p mbarrier.arrive.shared::cta.b64 _, [%0];}" ::"r"(a), "r"(sel) : "memory");
}
__device__ __forceinline__ void bulk_load(uint32_t dst, const void* src, uint32_t bytes, uint32_t bar) {
    asm volatile("cp.async.bulk.shared::cluster.global.mbarrier::complete_tx::bytes [%0], [%1], %2, [%3];" ::"r"(dst), "l"(src), "r"(bytes), "r"(bar) : "memory");
}
__device__ __forceinline__ void tma_load_2d(uint32_t dst, const CUtensorMap* map, int c0, int c1, uint32_t bar) {
    asm volatile("cp.async.bulk.tensor.2d.shared::cluster.global.mbarrier::complete_tx::bytes [%0], [%1, {%3, %4}], [%2];"
                 ::"r"(dst), "l"(map), "r"(bar), "r"(c0), "r"(c1) : "memory");
}
__device__ __forceinline__ void tma_store_2d(const CUtensorMap* map, uint32_t src, int c0, int c1) {
    asm volatile("cp.async.bulk.tensor.2d.global.shared::cta.bulk_group [%0, {%2, %3}], [%1];" ::"l"(map), "r"(src), "r"(c0), "r"(c1) : "memory");
}
__device__ __forceinline__ char* make_ptr(uint32_t lo, uint32_t hi) {
    uint64_t p;
    asm("mov.b64 %0, {%1, %2};" : "=l"(p) : "r"(lo), "r"(hi));
    return reinterpret_cast<char*>(p);
}
__device__ __forceinline__ uint64_t make_desc(uint32_t saddr, uint32_t lbo, uint32_t sbo) {
    return (uint64_t)((saddr & 0x3FFFF) >> 4) | ((uint64_t)((lbo >> 4) & 0x3FFF) << 16) | ((uint64_t)((sbo >> 4) & 0x3FFF) << 32) | ((uint64_t)1 << 62);
}
__device__ __forceinline__ void wg_fence() { asm volatile("wgmma.fence.sync.aligned;" ::: "memory"); }
__device__ __forceinline__ void wg_commit() { asm volatile("wgmma.commit_group.sync.aligned;" ::: "memory"); }
template <int N> __device__ __forceinline__ void wg_wait() { asm volatile("wgmma.wait_group.sync.aligned %0;" ::"n"(N) : "memory"); }

#define R4(b) "+f"(d[b + 0]), "+f"(d[b + 1]), "+f"(d[b + 2]), "+f"(d[b + 3])
#define R16(b) R4(b), R4(b + 4), R4(b + 8), R4(b + 12)
__device__ __forceinline__ void wgmma_n128(float (&d)[64], uint64_t da, uint64_t db) {
    asm volatile(
        "wgmma.mma_async.sync.aligned.m64n128k16.f32.bf16.bf16 "
        "{%0,%1,%2,%3,%4,%5,%6,%7,%8,%9,%10,%11,%12,%13,%14,%15,%16,%17,%18,%19,%20,%21,%22,%23,%24,%25,%26,%27,%28,%29,%30,%31,"
        "%32,%33,%34,%35,%36,%37,%38,%39,%40,%41,%42,%43,%44,%45,%46,%47,%48,%49,%50,%51,%52,%53,%54,%55,%56,%57,%58,%59,%60,%61,%62,%63},"
        "%64,%65,1,1,1,0,1;"
        : R16(0), R16(16), R16(32), R16(48)
        : "l"(da), "l"(db));
}
__device__ __forceinline__ void wgmma_n256(float (&d)[128], uint64_t da, uint64_t db) {
    asm volatile(
        "wgmma.mma_async.sync.aligned.m64n256k16.f32.bf16.bf16 "
        "{%0,%1,%2,%3,%4,%5,%6,%7,%8,%9,%10,%11,%12,%13,%14,%15,%16,%17,%18,%19,%20,%21,%22,%23,%24,%25,%26,%27,%28,%29,%30,%31,"
        "%32,%33,%34,%35,%36,%37,%38,%39,%40,%41,%42,%43,%44,%45,%46,%47,%48,%49,%50,%51,%52,%53,%54,%55,%56,%57,%58,%59,%60,%61,%62,%63,"
        "%64,%65,%66,%67,%68,%69,%70,%71,%72,%73,%74,%75,%76,%77,%78,%79,%80,%81,%82,%83,%84,%85,%86,%87,%88,%89,%90,%91,%92,%93,%94,%95,"
        "%96,%97,%98,%99,%100,%101,%102,%103,%104,%105,%106,%107,%108,%109,%110,%111,%112,%113,%114,%115,%116,%117,%118,%119,%120,%121,%122,%123,%124,%125,%126,%127},"
        "%128,%129,1,1,1,0,1;"
        : R16(0), R16(16), R16(32), R16(48), R16(64), R16(80), R16(96), R16(112)
        : "l"(da), "l"(db));
}
template <int BN> struct WgAcc;
template <> struct WgAcc<128> { static __device__ __forceinline__ void mma(float (&d)[64], uint64_t a, uint64_t b) { wgmma_n128(d, a, b); } };
template <> struct WgAcc<256> { static __device__ __forceinline__ void mma(float (&d)[128], uint64_t a, uint64_t b) { wgmma_n256(d, a, b); } };

__device__ __forceinline__ void wgmma_rs32(float (&d)[16], const uint32_t (&a)[4], uint64_t db, bool acc) {
    asm volatile(
        "{.reg .pred p; setp.ne.b32 p, %21, 0;\n"
        "wgmma.mma_async.sync.aligned.m64n32k16.f32.bf16.bf16 {%0,%1,%2,%3,%4,%5,%6,%7,%8,%9,%10,%11,%12,%13,%14,%15}, {%16,%17,%18,%19}, %20, p, 1, 1, 0;}"
        : R16(0) : "r"(a[0]), "r"(a[1]), "r"(a[2]), "r"(a[3]), "l"(db), "n"(1) );
}
__device__ __forceinline__ void wgmma_rs32_first(float (&d)[16], const uint32_t (&a)[4], uint64_t db) {
    asm volatile(
        "{.reg .pred p; setp.ne.b32 p, %21, 0;\n"
        "wgmma.mma_async.sync.aligned.m64n32k16.f32.bf16.bf16 {%0,%1,%2,%3,%4,%5,%6,%7,%8,%9,%10,%11,%12,%13,%14,%15}, {%16,%17,%18,%19}, %20, p, 1, 1, 0;}"
        : R16(0) : "r"(a[0]), "r"(a[1]), "r"(a[2]), "r"(a[3]), "l"(db), "n"(0) );
}
__device__ __forceinline__ void wgmma_ss32(float (&d)[16], uint64_t da, uint64_t db) {
    asm volatile(
        "wgmma.mma_async.sync.aligned.m64n32k16.f32.bf16.bf16 {%0,%1,%2,%3,%4,%5,%6,%7,%8,%9,%10,%11,%12,%13,%14,%15}, %16, %17, 1, 1, 1, 1, 0;"
        : R16(0) : "l"(da), "l"(db));
}
template <int OFF, int ACC> __device__ __forceinline__ void wgmma_rs32u(float (&d)[16], const uint32_t (&a)[4], uint32_t lo) {
    asm volatile(
        "{.reg .pred p; .reg .b32 l; .reg .b64 e; setp.ne.b32 p, %22, 0; add.u32 l, %20, %21; mov.b64 e, {l, 0x40000040};\n"
        "wgmma.mma_async.sync.aligned.m64n32k16.f32.bf16.bf16 {%0,%1,%2,%3,%4,%5,%6,%7,%8,%9,%10,%11,%12,%13,%14,%15}, {%16,%17,%18,%19}, e, p, 1, 1, 0;}"
        : R16(0) : "r"(a[0]), "r"(a[1]), "r"(a[2]), "r"(a[3]), "r"(lo), "n"(OFF), "n"(ACC));
}
template <int OFF> __device__ __forceinline__ void wgmma_ss32u(float (&d)[16], uint64_t da, uint32_t lo) {
    asm volatile(
        "{.reg .b32 l; .reg .b64 e; add.u32 l, %17, %18; mov.b64 e, {l, 0x40000040};\n"
        "wgmma.mma_async.sync.aligned.m64n32k16.f32.bf16.bf16 {%0,%1,%2,%3,%4,%5,%6,%7,%8,%9,%10,%11,%12,%13,%14,%15}, %16, e, 1, 1, 1, 1, 0;}"
        : R16(0) : "l"(da), "r"(lo), "n"(OFF));
}
template <int K0, int K1, class F> __device__ __forceinline__ void static_for(F f) {
    if constexpr (K0 < K1) { f(std::integral_constant<int, K0>()); static_for<K0 + 1, K1>(f); }
}
__device__ __forceinline__ void st_async4(uint32_t a, float x, float y, float z, float w, uint32_t bar) {
    asm volatile("st.async.weak.shared::cluster.mbarrier::complete_tx::bytes.v4.f32 [%0], {%1,%2,%3,%4}, [%5];" ::"r"(a), "f"(x), "f"(y), "f"(z), "f"(w), "r"(bar) : "memory");
}
__device__ __forceinline__ void st_async2(uint32_t a, float x, float y, uint32_t bar) {
    asm volatile("st.async.weak.shared::cluster.mbarrier::complete_tx::bytes.v2.f32 [%0], {%1,%2}, [%3];" ::"r"(a), "f"(x), "f"(y), "r"(bar) : "memory");
}
__device__ __forceinline__ void st_async1(uint32_t a, uint32_t x, uint32_t bar) {
    asm volatile("st.async.weak.shared::cluster.mbarrier::complete_tx::bytes.b32 [%0], %1, [%2];" ::"r"(a), "r"(x), "r"(bar) : "memory");
}
__device__ __forceinline__ void stsm4t(uint32_t a, uint32_t r0, uint32_t r1, uint32_t r2, uint32_t r3) {
    asm volatile("stmatrix.sync.aligned.m8n8.x4.trans.shared.b16 [%0], {%1,%2,%3,%4};" ::"r"(a), "r"(r0), "r"(r1), "r"(r2), "r"(r3) : "memory");
}
__device__ __forceinline__ void ldsm4t(uint32_t (&r)[4], uint32_t a) { ldsm4t(r[0], r[1], r[2], r[3], a); }
__device__ __forceinline__ void ldsm4(uint32_t (&r)[4], uint32_t a) { ldsm4(r[0], r[1], r[2], r[3], a); }
__device__ __forceinline__ void mma16816(float (&d)[4], const uint32_t (&a)[4], uint32_t b0, uint32_t b1) { mma16816(d, a[0], a[1], a[2], a[3], b0, b1); }
__device__ __forceinline__ void sched_fence(uint32_t v) {
    asm volatile("{.reg .pred p; setp.ne.u32 p, %0, 0xFFFFFFFF; vote.sync.all.pred p, p, 0xFFFFFFFF; @p bra.uni SF_OK; exit; SF_OK:}" ::"r"(v) : "memory");
}
__device__ __forceinline__ void mma16816v(float (&d)[4], const uint32_t (&a)[4], uint32_t b0, uint32_t b1) {
    asm volatile("mma.sync.aligned.m16n8k16.row.col.f32.bf16.bf16.f32 {%0,%1,%2,%3},{%4,%5,%6,%7},{%8,%9},{%0,%1,%2,%3};"
                 : "+f"(d[0]), "+f"(d[1]), "+f"(d[2]), "+f"(d[3]) : "r"(a[0]), "r"(a[1]), "r"(a[2]), "r"(a[3]), "r"(b0), "r"(b1));
}
__device__ __forceinline__ uint32_t uniform(uint32_t v) { return __reduce_max_sync(~0u, v); }

template <int BN, int STAGES> struct GemmCfg {
    static constexpr int A_BYTES = 128 * 64 * 2;
    static constexpr int B_BYTES = BN * 64 * 2;
    static constexpr int STAGE_BYTES = A_BYTES + B_BYTES;
    static constexpr int EPI_BYTES = 128 * BN * 2;
    static constexpr int SMEM = STAGES * STAGE_BYTES + EPI_BYTES + 1024 + 256;
};

template <int BN, int STAGES>
__global__ void __cluster_dims__(2, 1, 1) __launch_bounds__(288, 1)
gemm_kernel(const __grid_constant__ CUtensorMap mapA, const __grid_constant__ CUtensorMap mapB0, const __grid_constant__ CUtensorMap mapB1,
            const __grid_constant__ CUtensorMap mapB2, const __grid_constant__ CUtensorMap mapC, int tiles_m, int tiles_n, int kblocks) {
    using Cfg = GemmCfg<BN, STAGES>;
    KT_START(BN == 256 ? 0 : 3);
    extern __shared__ uint8_t smem_raw[];
    const uint32_t sbase = (smem_u32(smem_raw) + 1023) & ~1023u;
    const uint32_t epi = sbase + STAGES * Cfg::STAGE_BYTES;
    const uint32_t bars = epi + Cfg::EPI_BYTES;
    const int warp = threadIdx.x >> 5, lane = threadIdx.x & 31;
    const uint32_t rank = blockIdx.x & 1;
    if (threadIdx.x == 0) {
        for (int i = 0; i < STAGES; i++) { mbar_init(bars + 8 * i, 1); mbar_init(bars + 8 * (STAGES + i), 16); }
        asm volatile("fence.mbarrier_init.release.cluster;" ::: "memory");
    }
    __syncthreads();
    asm volatile("barrier.cluster.arrive.release.aligned; barrier.cluster.wait.acquire.aligned;" ::: "memory");
    const int npairs = (tiles_m >> 1) * tiles_n, ncl = gridDim.x >> 1;
    if (warp == 8) {
        if (lane == 0) {
            int st = 0; uint32_t ph = 1;
            for (int pr = blockIdx.x >> 1; pr < npairs; pr += ncl) {
                const int tm = 2 * (pr % (tiles_m >> 1)) + rank, tn = pr / (tiles_m >> 1);
                const int n0 = tn * BN;
                const CUtensorMap* mb = (n0 < 4096) ? &mapB0 : (n0 < 8192 ? &mapB1 : &mapB2);
                const int nb = n0 & 4095;
                for (int kb = 0; kb < kblocks; kb++) {
                    mbar_wait(bars + 8 * (STAGES + st), ph);
                    const uint32_t full = bars + 8 * st;
                    mbar_expect_tx(full, Cfg::STAGE_BYTES);
                    const uint32_t sa = sbase + st * Cfg::STAGE_BYTES;
                    tma_load_2d(sa, &mapA, kb * 64, tm * 128, full);
#pragma unroll
                    for (int i = 0; i < BN / 128; i++) {
                        const int bx = rank * (BN / 128) + i;
                        asm volatile("cp.async.bulk.tensor.2d.shared::cluster.global.mbarrier::complete_tx::bytes.multicast::cluster [%0], [%1, {%3, %4}], [%2], %5;"
                                     ::"r"(sa + Cfg::A_BYTES + bx * 8192), "l"(mb), "r"(full), "r"(nb + bx * 64), "r"(kb * 64), "h"((uint16_t)3) : "memory");
                    }
                    if (++st == STAGES) { st = 0; ph ^= 1; }
                }
            }
        }
    } else {
        const int wg = warp >> 2;
        uint32_t peer_empty;
        asm volatile("mapa.shared::cluster.u32 %0, %1, %2;" : "=r"(peer_empty) : "r"(bars + 8 * STAGES), "r"(rank ^ 1));
        auto release = [&](int stg) {
            if (lane == 0) {
                mbar_arrive(bars + 8 * (STAGES + stg));
                asm volatile("mbarrier.arrive.shared::cluster.b64 _, [%0];" ::"r"(peer_empty + 8 * stg) : "memory");
            }
        };
        const uint32_t ew = epi + wg * (64 * BN * 2);
        int st = 0; uint32_t ph = 0;
        for (int pr = blockIdx.x >> 1; pr < npairs; pr += ncl) {
            const int tm = 2 * (pr % (tiles_m >> 1)) + rank, tn = pr / (tiles_m >> 1);
            float d[BN / 2];
#pragma unroll
            for (int i = 0; i < BN / 2; i++) d[i] = 0.f;
            int prev = -1;
            for (int kb = 0; kb < kblocks; kb++) {
                mbar_wait(bars + 8 * st, ph);
                const uint32_t sa = sbase + st * Cfg::STAGE_BYTES;
                const uint64_t da = make_desc(sa + wg * 8192, 16, 1024);
                const uint64_t db = make_desc(sa + Cfg::A_BYTES, 8192, 1024);
                wg_fence();
#pragma unroll
                for (int k = 0; k < 4; k++) WgAcc<BN>::mma(d, da + k * 2, db + k * 128);
                wg_commit();
                if (prev >= 0) { wg_wait<1>(); release(prev); }
                prev = st;
                if (++st == STAGES) { st = 0; ph ^= 1; }
            }
            wg_wait<0>();
            release(prev);
            if ((warp & 3) == 0 && lane == 0) asm volatile("cp.async.bulk.wait_group.read 0;" ::: "memory");
            bar_sync(1 + wg, 128);
            const int r = (warp & 3) * 16 + (lane & 7) + ((lane >> 3) & 1) * 8;
#pragma unroll
            for (int c = 0; c < BN / 64; c++)
#pragma unroll
                for (int i = 0; i < 4; i++) {
                    const int b = (c * 8 + i * 2) * 4;
                    stsm4(ew + c * 8192 + r * 128 + (((i * 2 + (lane >> 4)) ^ (r & 7)) * 16), pack_bf16(d[b], d[b + 1]), pack_bf16(d[b + 2], d[b + 3]),
                          pack_bf16(d[b + 4], d[b + 5]), pack_bf16(d[b + 6], d[b + 7]));
                }
            asm volatile("fence.proxy.async.shared::cta;" ::: "memory");
            bar_sync(1 + wg, 128);
            if ((warp & 3) == 0 && lane == 0) {
#pragma unroll
                for (int c = 0; c < BN / 64; c++)
                    asm volatile("cp.async.bulk.tensor.2d.global.shared::cta.bulk_group [%0, {%2, %3}], [%1];"
                                 ::"l"(&mapC), "r"(ew + c * 8192), "r"(tn * BN + c * 64), "r"(tm * 128 + wg * 64) : "memory");
                asm volatile("cp.async.bulk.commit_group;" ::: "memory");
            }
        }
        if ((warp & 3) == 0 && lane == 0) asm volatile("cp.async.bulk.wait_group 0;" ::: "memory");
    }
    __syncwarp();
    KT_END(BN == 256 ? 0 : 3);
    asm volatile("barrier.cluster.arrive.relaxed; barrier.cluster.wait;" ::: "memory");
}

#define WO_RF1 6
constexpr int SM_KV = 0, KV_BYTES = 18432;
constexpr int SM_XT = 2 * KV_BYTES;
constexpr int SM_STG = SM_XT + 65536;
constexpr int SM_Z = SM_STG + 6144;
constexpr int SM_RT = SM_Z + 8192;
constexpr int SM_QKV = SM_RT + 12288;
constexpr int SM_R1 = SM_QKV + 6144;
constexpr int SM_R2 = SM_R1 + 2048;
constexpr int SM_R3 = SM_R2 + 1024;
constexpr int SM_O = SM_R3 + 2048;
constexpr int SM_S = SM_O + 2048;
constexpr int SM_TO = SM_R1;
constexpr int SM_WORK_END = SM_S + 2048;
constexpr int STG_QK = 0, STG_V = 98304;
constexpr int SM_WO1 = SM_WORK_END - WO_RF1 * 2048;
constexpr int STG_WO = SM_WO1 - 16384;
constexpr int SM_WQK = (SM_WO1 + 16384 > STG_V + 49152) ? SM_WO1 + 16384 : STG_V + 49152;
constexpr int SM_WV = SM_WQK + 32768;
constexpr int SM_WO2 = SM_WV + 16384;
constexpr int SM_BARS = SM_WO2 + 32768;
enum { MB_W0 = SM_BARS, MB_W1 = SM_BARS + 8, MB_W2 = SM_BARS + 16, MB_W3 = SM_BARS + 24, MB_XT = SM_BARS + 32  , MB_KV = SM_BARS + 48  ,
       MB_R3 = SM_BARS + 64, MB_R1 = SM_BARS + 72, MB_R2 = SM_BARS + 80, MB_RT0 = SM_BARS + 88, MB_RT1 = SM_BARS + 96, MB_FREE = SM_BARS + 104,
       MB_P = SM_BARS + 112, MB_V = SM_BARS + 120, MB_STG = SM_BARS + 128, SM_ROLE = SM_BARS + 136 };
constexpr int CHAIN_SMEM = SM_ROLE + 8;
static_assert(SM_WORK_END % 1024 == 0 && STG_WO >= STG_V, "work area");
static_assert(CHAIN_SMEM <= 232448 && WO_RF1 >= 6, "smem");

#define DLY_X 200
#define DLY_V 0
#define DLY_Y 250
#define DLY_Z 200
#define Q3_AT 9
#define NA 6
#define SPLIT 8
#define XFLIP 0
#define YFLIP 0
#define ZFLIP 1
#define REG_A 240
#define REG_B 216
#define REG_C (3 * 168 - REG_A - REG_B)

enum { BAR_Y, BAR_MEM, BAR_PUB, BAR_QK, BAR_S, BAR_O, BAR_SENT, BAR_COMM, BAR_PUBV, BAR_PV, BAR_PDONE, BAR_VP, BAR_ZP, BAR_PRO, BAR_O2, BAR_SV,
       BAR_V = BAR_PV, BAR_SENTC = BAR_PDONE, BAR_Q3 = BAR_PRO };

__device__ __forceinline__ uint32_t umax4(const uint4& v) { return max(max(v.x, v.y), max(v.z, v.w)); }
__device__ __forceinline__ unsigned gtime() { unsigned t; asm volatile("mov.u32 %0, %%globaltimer_lo;" : "=r"(t)::"memory"); return t; }
__device__ __forceinline__ unsigned clock32() { unsigned t; asm volatile("mov.u32 %0, %%clock;" : "=r"(t)::"memory"); return t; }
__device__ __forceinline__ void spin_cycles(int d) {
    if (d > 0) { const unsigned c0 = clock32(); while (clock32() - c0 < (unsigned)d) {} }
}
__device__ __forceinline__ float ex2_approx(float x) { float y; asm("ex2.approx.ftz.f32 %0, %1;" : "=f"(y) : "f"(x)); return y; }
__device__ __forceinline__ float rcp_approx(float x) { float y; asm("rcp.approx.ftz.f32 %0, %1;" : "=f"(y) : "f"(x)); return y; }
__device__ __forceinline__ void st_sent(const void* p) { asm volatile("st.relaxed.gpu.global.v4.u32 [%0], {%1,%1,%1,%1};" ::"l"(p), "r"(SENT) : "memory"); }
#define POLL_LD(p, a, b, c, d, addr) "@" p " ld.relaxed.gpu.global.v4.u32 {" a "," b "," c "," d "}, [" addr "];\n"
#define POLL_CK(p, a, b, c, d) "max.u32 m, " a "," b "; max.u32 n, " c "," d "; max.u32 m, m, n; setp.eq.u32 " p ", m, 0xFFFFFFFF;\n"
#define POLL_IO(v) "+r"(v.x), "+r"(v.y), "+r"(v.z), "+r"(v.w)
__device__ __forceinline__ void poll_init(uint4& v) { v = make_uint4(SENT, SENT, SENT, SENT); asm volatile("" : POLL_IO(v)); }
__device__ __forceinline__ int poll2(uint4 (&v)[2], const char* a) {
    int c = 0;
    asm volatile("{.reg .pred p0, p1, p; .reg .u32 m, n;\n"
                 "setp.eq.u32 p0, %8, 0; setp.eq.u32 p1, %8, 0;\n"
                 "POLL_LOOP:\n"
                 POLL_LD("p0", "%0", "%1", "%2", "%3", "%9") POLL_LD("p1", "%4", "%5", "%6", "%7", "%9+512")
                 "add.u32 %8, %8, 1;\n"
                 POLL_CK("p0", "%0", "%1", "%2", "%3") POLL_CK("p1", "%4", "%5", "%6", "%7")
                 "or.pred p, p0, p1; setp.lt.and.u32 p, %8, 0x10000, p; vote.sync.any.pred p, p, 0xFFFFFFFF;\n"
                 "@p bra.uni POLL_LOOP;}" : POLL_IO(v[0]), POLL_IO(v[1]), "+r"(c) : "l"(a) : "memory");
    return c;
}
__device__ __forceinline__ int poll4(uint4 (&v)[4], const char* a) {
    int c = 0;
    asm volatile("{.reg .pred p0, p1, p2, p3, p; .reg .u32 m, n;\n"
                 "setp.eq.u32 p0, %16, 0; setp.eq.u32 p1, %16, 0; setp.eq.u32 p2, %16, 0; setp.eq.u32 p3, %16, 0;\n"
                 "POLL_LOOP:\n"
                 POLL_LD("p0", "%0", "%1", "%2", "%3", "%17") POLL_LD("p1", "%4", "%5", "%6", "%7", "%17+2048")
                 POLL_LD("p2", "%8", "%9", "%10", "%11", "%17+4096") POLL_LD("p3", "%12", "%13", "%14", "%15", "%17+6144")
                 "add.u32 %16, %16, 1;\n"
                 POLL_CK("p0", "%0", "%1", "%2", "%3") POLL_CK("p1", "%4", "%5", "%6", "%7") POLL_CK("p2", "%8", "%9", "%10", "%11") POLL_CK("p3", "%12", "%13", "%14", "%15")
                 "or.pred p, p0, p1; or.pred p, p, p2; or.pred p, p, p3; setp.lt.and.u32 p, %16, 0x10000, p; vote.sync.any.pred p, p, 0xFFFFFFFF;\n"
                 "@p bra.uni POLL_LOOP;}" : POLL_IO(v[0]), POLL_IO(v[1]), POLL_IO(v[2]), POLL_IO(v[3]), "+r"(c) : "l"(a) : "memory");
    return c;
}
__device__ __forceinline__ uint32_t max_bf16x2(uint32_t a, uint32_t b) { uint32_t r; asm("max.bf16x2 %0, %1, %2;" : "=r"(r) : "r"(a), "r"(b)); return r; }
template <class F> __device__ __forceinline__ void softmax40(uint32_t (&pw)[6], uint32_t sa, F mid) {
    const float LOG2E = 1.4426950408889634f;
    uint32_t w[5];
    float e[10];
#pragma unroll
    for (int i = 0; i < 5; i++) w[i] = lds32(sa + i * 128);
    uint32_t m = max_bf16x2(max_bf16x2(max_bf16x2(w[0], w[1]), max_bf16x2(w[2], w[3])), w[4]);
    m = max_bf16x2(m, __shfl_xor_sync(~0u, m, 1));
    m = max_bf16x2(m, __shfl_xor_sync(~0u, m, 2));
    const float mb2 = fmaxf(bf_lo(m), bf_hi(m)) * LOG2E;
#pragma unroll
    for (int i = 0; i < 5; i++) {
        e[2 * i] = ex2_approx(fmaf(bf_lo(w[i]), LOG2E, -mb2));
        e[2 * i + 1] = ex2_approx(fmaf(bf_hi(w[i]), LOG2E, -mb2));
    }
    mid();
#pragma unroll
    for (int i = 0; i < 5; i++) pw[i] = pack_bf16(e[2 * i], e[2 * i + 1]);
    const float sum = (((e[0] + e[1]) + (e[2] + e[3])) + ((e[4] + e[5]) + (e[6] + e[7]))) + (e[8] + e[9]);
    const float hi = bf_hi(__float_as_uint(sum));
    pw[5] = pack_bf16(sum - hi, hi);
}
template <class F> __device__ __forceinline__ void pv32(uint32_t (&w)[4], const uint32_t (&va)[2][2][4], const uint32_t (&vm)[4], const uint32_t (&pw)[6], F mid) {
    float o[2][3][4], t[4] = {0.f, 0.f, 0.f, 0.f};
    mma1688(t, 0x3F803F80u, 0x3F803F80u, pw[5]);
#pragma unroll
    for (int i = 0; i < 3; i++)
#pragma unroll
        for (int m = 0; m < 2; m++) {
            o[m][i][0] = o[m][i][1] = o[m][i][2] = o[m][i][3] = 0.f;
            if (i < 2) mma16816(o[m][i], va[m][i & 1], pw[2 * i], pw[2 * i + 1]);
            else mma1688(o[m][i], vm[2 * m], vm[2 * m + 1], pw[4]);
        }
    mid();
    const float i0 = rcp_approx(t[0]), i1 = rcp_approx(t[1]);
#pragma unroll
    for (int m = 0; m < 2; m++) {
        w[2 * m] = pack_bf16(((o[m][0][0] + o[m][1][0]) + o[m][2][0]) * i0, ((o[m][0][1] + o[m][1][1]) + o[m][2][1]) * i1);
        w[2 * m + 1] = pack_bf16(((o[m][0][2] + o[m][1][2]) + o[m][2][2]) * i0, ((o[m][0][3] + o[m][1][3]) + o[m][2][3]) * i1);
    }
}
__device__ __forceinline__ uint32_t scale_scores(float a, float b) {
    const float scale = 0.08838834764831845f;
    const uint32_t w = pack_bf16(a, b);
    return pack_bf16(bf_lo(w) * scale, bf_hi(w) * scale);
}

__device__ __forceinline__ uint32_t peer_addr(uint32_t a, uint32_t rank) {
    uint32_t r;
    asm("mapa.shared::cluster.u32 %0, %1, %2;" : "=r"(r) : "r"(a), "r"(rank));
    return r;
}

#define TL(i) do {} while (0)
#define TLB(i) do {} while (0)
#define TLC(i) do {} while (0)

__global__ void __cluster_dims__(2, 1, 1) __launch_bounds__(384, 1)
chain_kernel(const __grid_constant__ CUtensorMap mapX, const __grid_constant__ CUtensorMap mapT32, const __grid_constant__ CUtensorMap mapT16,
             const __grid_constant__ CUtensorMap mapTQ, const __grid_constant__ CUtensorMap mapKV,
             const __grid_constant__ CUtensorMap mapWq, const __grid_constant__ CUtensorMap mapWk, const __grid_constant__ CUtensorMap mapWv,
             const __grid_constant__ CUtensorMap mapWo, const bf16* __restrict__ mem0, char* __restrict__ mbox) {
    KT_START(2);
    extern __shared__ __align__(1024) uint8_t smem_chain[];
    constexpr uint32_t SB0 = 1024;
    if (smem_u32(smem_chain) != (SB0 | ((blockIdx.x & 1) << 24))) __trap();
    const int kh = blockIdx.x & 1;
    if (threadIdx.x == 0) {
        const uint32_t sb = smem_u32(smem_chain);
        for (int i = 0; i < 14; i++) mbar_init(sb + SM_BARS + 8 * i, 1);
        mbar_init(sb + MB_P, 4); mbar_init(sb + MB_V, 4); mbar_init(sb + MB_STG, 8);
        asm volatile("fence.mbarrier_init.release.cluster;" ::: "memory");
        if (kh == 0) {
            unsigned smid, ncl = gridDim.x >> 1;
            asm volatile("mov.u32 %0, %%smid;" : "=r"(smid));
            const unsigned c = g_cls[smid] & 1, i = atomicAdd(&g_reg[c], 1u);
            unsigned p = c * 32 + i;
            if (i >= 32) {
                unsigned n0, n1; int guard = 0;
                do {
                    asm volatile("ld.relaxed.gpu.global.u32 %0, [%1];" : "=r"(n0) : "l"(g_reg) : "memory");
                    asm volatile("ld.relaxed.gpu.global.u32 %0, [%1];" : "=r"(n1) : "l"(g_reg + 1) : "memory");
                } while (n0 + n1 < ncl && ++guard < (1 << 20));
                const unsigned k = (c ? n0 : n1) + i - 32;
                p = k < 32 ? (c ^ 1) * 32 + k : 64;
            }
            p |= g_reg[2] << 8;
            uint32_t ra;
            asm volatile("mapa.shared::cluster.u32 %0, %1, 1;" : "=r"(ra) : "r"(sb + SM_ROLE));
            asm volatile("st.shared::cluster.u32 [%0], %1;" ::"r"(ra), "r"(p) : "memory");
            sts32(sb + SM_ROLE, p);
        }
    }
    __syncthreads();
    asm volatile("barrier.cluster.arrive.release.aligned; barrier.cluster.wait.acquire.aligned;" ::: "memory");
    const uint32_t rw = uniform(lds32(smem_u32(smem_chain) + SM_ROLE));
    const int pair = rw & 255, yflip = (rw >> 8) ^ YFLIP;
    if (pair >= 64) return;
    const int h = pair >> 1, nh = pair & 1, j = 2 * nh + kh, role = 2 * pair + kh;
#define WG_ORDER 0x210
    const int warp = uniform(((WG_ORDER >> (4 * (threadIdx.x >> 7))) & 3) * 4 + ((threadIdx.x >> 5) & 3));
    const uint32_t g = warp & 3, sb = SB0 | (kh << 24), rsb = sb ^ (1u << 24), cls = pair >> 5, kflip = ZFLIP ^ kh;
    const uint32_t mlo = (uint32_t)(uintptr_t)mbox, mhi = (uint32_t)((uintptr_t)mbox >> 32);
    auto lane16 = [&]() {
        uint32_t t;
        asm volatile("mov.u32 %0, %%laneid; shl.b32 %0, %0, 4;" : "=r"(t));
        return t;
    };
#define PHASE(k) uint32_t L; asm volatile("{.reg .u32 t; shr.u32 t, %1, %3; add.u32 %0, %2, t;}" : "=r"(L) : "r"(it), "r"(l16), "n"(8 + (k)))
#define ROWPAT() ((((L << 3) & 0x380) | ((L << 2) & 0x400)) | ((L ^ (L >> 3)) & 0x10) | (L & 0x60))
#define FRAG() (ROWPAT() ^ (g << 5))
#define QFRAG() ((((L >> 1) & 0x80) | (L & 0x70)) + ((L & 0x80) ? SM_KV + 16384 + kvo : SM_QKV))
#define VFRAG() (ROWPAT() ^ ((g & 1) << 6))
#define VBASE() (sb + SM_KV + 8192 + (g >> 1) * 4096 + kvo)
#define XTLO() ((uint32_t)make_desc(SB0 + SM_XT, 16, 1024) + (ui & 1) * 2048)
    if (warp >= 8) {
        asm volatile("setmaxnreg.dec.sync.aligned.u32 %0;" ::"n"(REG_C));
        const uint32_t l16 = lane16(), lane = l16 >> 4;
        const int ct = g * 32 + lane;
        if (warp == 8) {
            const CUtensorMap* ws = kh ? &mapWq : &mapWk;
            const CUtensorMap* wn = kh ? &mapWk : &mapWq;
            const int col = h * DH + 64 * nh, row = 512 * kh;
            if (lane == 0) { mbar_expect_tx(sb + MB_W0, 49152); mbar_expect_tx(sb + MB_W1, 98304); mbar_expect_tx(sb + MB_W2, 81920); mbar_expect_tx(sb + MB_W3, 32768); }
            __syncwarp();
            if (lane < 24) {
                const int k = lane ^ (16 * kflip);
                tma_load_2d(sb + STG_V + lane * 2048, &mapWv, col, row + 16 * k, sb + MB_W0);
                tma_load_2d(sb + STG_QK + lane * 2048, ws, col, row + 16 * k, sb + MB_W1);
                tma_load_2d(sb + STG_QK + (24 + lane) * 2048, wn, col, row + 16 * k, sb + MB_W1);
            }
            if (lane < 8) {
                const int k = (24 + lane) ^ (16 * kflip);
                tma_load_2d(sb + SM_WQK + lane * 4096, ws, col, row + 16 * k, sb + MB_W2);
                tma_load_2d(sb + SM_WQK + lane * 4096 + 2048, wn, col, row + 16 * k, sb + MB_W2);
                tma_load_2d(sb + SM_WV + lane * 2048, &mapWv, col, row + 16 * k, sb + MB_W2);
            }
            if (lane < 2) tma_load_2d(sb + SM_WO2 + lane * 16384, &mapWo, 256 * j + 128 + 64 * lane, h * DH, sb + MB_W2);
            __syncwarp();
            bar_sync(BAR_PV, 160);
            if (lane < 2) tma_load_2d(sb + STG_WO + lane * 16384, &mapWo, 256 * j + 64 * lane, h * DH, sb + MB_W3);
            __syncwarp();
        }
        bar_sync(BAR_PDONE, 384);
        for (int c = ct; c < 512; c += 128) {
            uint32_t w[4];
#pragma unroll
            for (int r = 0; r < 4; r++) {
                const uint32_t lo = reinterpret_cast<const uint16_t*>(mem0)[(2 * r) * DM + 512 * kh + c], hi = reinterpret_cast<const uint16_t*>(mem0)[(2 * r + 1) * DM + 512 * kh + c];
                w[r] = lo | (hi << 16);
            }
            sts128(sb + SM_Z + (c ^ (256 * kflip)) * 16, make_uint4(w[0], w[1], w[2], w[3]));
        }
        auto load_xt = [&](int seg, int half) {
            const uint32_t bar = sb + MB_XT + (seg & 1) * 8;
            if (half == 0) mbar_expect_tx(bar, 32768);
            asm volatile("cp.async.bulk.tensor.3d.shared::cluster.global.mbarrier::complete_tx::bytes [%0], [%1, {%3, %4, %5}], [%2];"
                         ::"r"(sb + SM_XT + (seg & 1) * 32768 + half * 16384), "l"(&mapX), "r"(bar), "r"(0), "r"(seg * SEG), "r"(8 * kh + 4 * (half ^ kflip)) : "memory");
        };
        auto tok_start = [&](int s) {
            if (lane == 0) {
                if (s > -3 && s + 2 < NSEG) {
                    mbar_wait(sb + MB_STG, (s + 2) & 1);
                    asm volatile("fence.proxy.async.shared::cta;" ::: "memory");
                    const int r = ((s + 2) & 3) * NH + h;
                    tma_store_2d(kh ? &mapT32 : &mapTQ, sb + SM_STG, kh ? 64 * nh : 256 * nh, kh ? r * 96 + 32 : r * 12);
                    tma_store_2d(&mapT16, sb + SM_STG + 4096, 64 * nh, r * 96 + 64 + 16 * kh);
                    asm volatile("cp.async.bulk.commit_group;" ::: "memory");
                }
                if (s + 4 < NSEG) load_xt(s + 4, 0);
                asm volatile("cp.async.bulk.wait_group.read 0;" ::: "memory");
                if (s < 0) {
                    asm volatile("mbarrier.arrive.shared::cluster.b64 _, [%0];" ::"r"(rsb + MB_FREE) : "memory");
                    mbar_wait(sb + MB_FREE, (s + 3) & 1);
                }
            }
            __syncwarp();
        };
        auto tok_mid = [&](int s) {
            if (lane == 0) {
                if (s + 4 < NSEG) load_xt(s + 4, 1);
                if (s > -3 && s + 2 < NSEG) {
                    asm volatile("cp.async.bulk.wait_group 0;" ::: "memory");
                    st_relaxed_u32(g_xflag + role, s + 3);
                }
            }
            __syncwarp();
        };
        auto kv_check = [&](int s) {
            if (s + 1 < NSEG) {
                if (lane < 4) {
                    unsigned f; int guard = 0;
                    do {
                        asm volatile("ld.acquire.gpu.global.u32 %0, [%1];" : "=r"(f) : "l"(g_xflag + h * 4 + lane) : "memory");
                        if (++guard > (1 << 20)) __trap();
                    } while (f <= (unsigned)(s + 1));
                }
                __syncwarp();
                asm volatile("fence.proxy.async.global;" ::: "memory");
            }
        };
        auto kv_load = [&](int s) {
            if (lane == 0 && s + 1 < NSEG) {
                const uint32_t bar = sb + MB_KV + ((s + 1) & 1) * 8, dst = sb + SM_KV + ((s + 1) & 1) * KV_BYTES;
                const int row = (((s + 1) & 3) * NH + h) * 96;
                mbar_expect_tx(bar, KV_BYTES);
                asm volatile("cp.async.bulk.tensor.3d.shared::cluster.global.mbarrier::complete_tx::bytes.multicast::cluster [%0], [%1, {%3, %4, %3}], [%2], %5;"
                             ::"r"(dst + kh * 8192), "l"(&mapKV), "r"(bar), "r"(0), "r"(row + 32 + 32 * kh), "h"((uint16_t)3) : "memory");
                bulk_load(dst + 16384, g_tok + row * DH + j * 1024, 2048, bar);
            }
            __syncwarp();
        };
        if (warp == 9) {
            if (lane == 0) { load_xt(0, 0); load_xt(0, 1); }
#pragma unroll 1
            for (int s = -3; s < 0; s++) { tok_start(s); bar_arrive(BAR_PRO, 288); tok_mid(s); }
        }
        if (warp == 11) { kv_check(-1); kv_load(-1); }
        bar_arrive(BAR_MEM, 384);
        const uint32_t ybox = mlo + page_off(role & 63, cls ^ yflip), xoth = mlo + WIN + page_off((pair & 31) ^ 1, cls ^ XFLIP);
        const uint32_t zline = mlo + WIN + page_off(32 + ((role >> 5) & 1), cls ^ ZFLIP) + (role & 31) * 128, zbox = mlo + WIN + (page_off(32 + kh, 0) & ~4096u);
        const uint32_t xtype = g == 0 ? 2 : (g & 1);
        const uint32_t ydst = (lane >> 3) * 128 + ((lane & 7) ^ (lane >> 3)) * 16, ysrc = lane * 128 + ((2 * g) ^ (lane & 7)) * 16;
#pragma unroll 1
        for (int s = 0; s < NSEG; s++) {
            const uint32_t slot = (s & 3) << 14;
            if (g == 3) {
                kv_check(s);
                const uint32_t L = l16, kvo = (s & 1) * KV_BYTES, qa = QFRAG(), sa = sb + SM_S + 512 + (L >> 2);
                float sc[4] = {0.f, 0.f, 0.f, 0.f}, sd[4] = {0.f, 0.f, 0.f, 0.f};
                uint32_t a[4][4], kb[2][4];
                mbar_wait_w(sb + MB_KV + (s & 1) * 8, (s >> 1) & 1);
                mbar_wait_w(sb + MB_P, s & 1);
#pragma unroll
                for (int c = 0; c < 2; c++) {
                    const uint32_t qc = qa + (sb + (nh ^ c) * 1024), kc = L + (sb + SM_QKV + 2048 + (nh ^ c) * 1024);
                    if (c) bar_sync(BAR_QK, 224);
                    ldsm4t(kb[0], kc); ldsm4t(a[0], qc); ldsm4t(a[1], qc + 256);
                    ldsm4t(kb[1], kc + 512); ldsm4t(a[2], qc + 512); ldsm4t(a[3], qc + 768);
                    mma16816v(sc, a[0], kb[0][0], kb[0][1]);
                    mma16816v(sd, a[1], kb[0][2], kb[0][3]);
                    mma16816v(sc, a[2], kb[1][0], kb[1][1]);
                    mma16816v(sd, a[3], kb[1][2], kb[1][3]);
                }
                sts32(sa, scale_scores(sc[0] + sd[0], sc[1] + sd[1]));
                sts32(sa + 768, scale_scores(sc[2] + sd[2], sc[3] + sd[3]));
                bar_arrive(BAR_S, 160);
                TL(25);
                bar_sync(BAR_SV, 352);
                kv_load(s);
            } else {
                if (g == 1) { tok_start(s); TL(21); }
                const char* p = make_ptr(l16 + (xoth + xtype * 1024 + slot), mhi);
                const uint32_t dst = l16 + (sb + SM_QKV + xtype * 2048 + (nh ^ 1) * 1024);
                asm volatile("" ::"l"(p));
                uint4 v[2];
                poll_init(v[0]); poll_init(v[1]);
                if (g == 0) {
                    bar_sync(BAR_PUBV, 160);
                    mbar_wait_w(sb + MB_V, s & 1);
                    spin_cycles(DLY_V);
                } else {
                    bar_sync(BAR_PUB, 192);
                    spin_cycles(DLY_X);
                }
                const int r = poll2(v, p);
                STAT(1, r > 1 && warp == 10);
                sts128(dst, v[0]); sts128(dst + 512, v[1]);
                if (g != 0) bar_arrive(BAR_QK, 224);
                if (g == 0 && s + 1 < NSEG) bar_arrive(BAR_V, 160);
                if (g == 0) { bar_arrive(BAR_SV, 352); TL(17); }
                if (g == 1) {
                    TL(31);
                    bar_sync(BAR_SV, 352);
                    tok_mid(s);
                    TL(22);
                }
                if (g == 2 && s >= 1) {
                    TL(16);
                    const uint32_t prev = (slot - 0x4000) & 0xC000;
                    const char* y = make_ptr(l16 + (ybox + prev), mhi);
                    const char* x = make_ptr(l16 + (xoth + prev + kh * 1536), mhi);
#pragma unroll
                    for (int i = 0; i < 8; i++) st_sent(y + i * 512);
#pragma unroll
                    for (int i = 0; i < 3; i++) st_sent(x + i * 512);
                    st_relaxed_u32(make_ptr(lane * 4 + (zline + (slot ^ 0x8000)), mhi), SENT);
                    TL(23);
                }
            }
            if (s + 1 == NSEG) break;
            {
                const char* p = make_ptr(l16 + (ybox + g * 1024 + slot), mhi);
                char* zdst = make_ptr(lane * 4 + (zline + g * 32 + slot), mhi);
                const uint32_t dst = ydst + (sb + SM_Z + g * 1024), dst1 = (ydst ^ 64) + (sb + SM_Z + g * 1024 + 512), src = ysrc + (sb + SM_Z), src1 = (ysrc ^ 16) + (sb + SM_Z);
                asm volatile("" ::"l"(p), "l"(zdst));
                uint4 v[2];
                poll_init(v[0]); poll_init(v[1]);
                bar_sync(BAR_SENTC, 384);
                spin_cycles(DLY_Y);
                const int r = poll2(v, p);
                STAT(2, r > 1 && warp == 8);
                sts128(dst, v[0]); sts128(dst1, v[1]);
                bar_sync(BAR_Y, 128);
                TL(18);
                uint32_t b[2][4];
                ldsm4t(b[0], src); ldsm4t(b[1], src1);
                const uint32_t one = 0x3F803F80u;
                float d0[4] = {0.f, 0.f, 0.f, 0.f}, d1[4] = {0.f, 0.f, 0.f, 0.f};
                mma16816(d0, one, one, one, one, b[0][0], b[0][1]);
                mma16816(d1, one, one, one, one, b[1][0], b[1][1]);
                mma16816(d0, one, one, one, one, b[0][2], b[0][3]);
                mma16816(d1, one, one, one, one, b[1][2], b[1][3]);
                const uint32_t w = (lane & 4) ? pack_bf16(d1[0], d1[1]) : pack_bf16(d0[0], d0[1]);
                asm volatile("{.reg .pred p; setp.lt.u32 p, %2, 128; @p st.relaxed.gpu.global.u32 [%0], %1;}" ::"l"(zdst), "r"(w), "r"(l16) : "memory");
                if (s + 3 < NSEG) bar_arrive(BAR_ZP, 256);
                TL(19);
            }
            {
                const char* p = make_ptr(l16 + (zbox + g * 512 + slot), mhi);
                const uint32_t dst = l16 + (sb + SM_Z + g * 512);
                asm volatile("" ::"l"(p));
                uint4 v[4];
                poll_init(v[0]); poll_init(v[1]); poll_init(v[2]); poll_init(v[3]);
                bar_sync(BAR_COMM, 128);
                spin_cycles(DLY_Z);
                const int r = poll4(v, p);
                STAT(0, r > 1 && warp == 8);
#pragma unroll
                for (int i = 0; i < 4; i++) sts128(dst + i * 2048, v[i]);
                bar_arrive(BAR_MEM, 384);
                TL(20);
            }
        }
    } else if (warp < 4) {
        asm volatile("setmaxnreg.inc.sync.aligned.u32 %0;" ::"n"(REG_A));
        const uint32_t l16 = lane16();
        uint32_t wa[2][24][4];
        {
            const uint32_t L = l16, fa = sb + FRAG();
            mbar_wait_w(sb + MB_W1, 0);
#pragma unroll
            for (int t = 0; t < 2; t++)
#pragma unroll
                for (int r = 0; r < 24; r++) ldsm4t(wa[t][r], fa + STG_QK + (t * 24 + r) * 2048);
            mbar_wait_w(sb + MB_W2, 0);
            bar_arrive(BAR_PDONE, 384);
        }
        auto batch1 = [&](float (&d)[16], uint32_t lo, auto tc, auto k0c, auto k1c) {
            constexpr int t = decltype(tc)::value;
            const uint64_t da = make_desc(SB0 + SM_WQK, 16, 1024);
            wg_fence();
            static_for<decltype(k0c)::value, decltype(k1c)::value>([&](auto kc) {
                constexpr int k = decltype(kc)::value, off = (k >> 2) * 256 + (k & 3) * 2;
                if constexpr (k >= 24) wgmma_ss32u<off>(d, da + ((k - 24) * 2 + t) * 128, lo);
                else wgmma_rs32u<off, k != 0 || t != 0>(d, wa[t][k], lo);
            });
            wg_commit();
        };
        const uint32_t xbox = mlo + WIN + page_off(pair & 31, cls ^ XFLIP);
        const uint32_t ybox = mlo + page_off(24 + 2 * g + 32 * nh, kh ^ yflip) + h * 128;
#pragma unroll 1
        for (uint32_t it = 0; it < NSEG + 3; it++) {
            const int s = (int)it - 3;
            const uint32_t ui = uniform(it), slot = ((ui + 1) & 3) << 14, kvo = (~ui & 1) * KV_BYTES, xtlo = XTLO();
            {
                const uint32_t first = l16 | (g << 9);
                if (s >= 0) mbar_expect_tx_if0(first, sb + MB_R1, 2048);
                if (s + 3 < NSEG) {
                    mbar_expect_tx_if0(first, sb + MB_RT0, 8192);
                    mbar_wait_w(sb + MB_XT + (ui & 1) * 8, (it >> 1) & 1);
                }
            }
            if (s >= 0) {
                PHASE(0);
                const uint32_t mb = L + (sb + SM_Z), ra = L + (sb + g * 512), r1 = L + (rsb + SM_R1 + g * 512), r1b = rsb + MB_R1;
                sched_fence(r1 | r1b);
                bar_sync(BAR_MEM, 384);
                TLB(0);
                float acc[2][2][4];
#pragma unroll
                for (int t = 0; t < 4; t++) { acc[t >> 1][t & 1][0] = acc[t >> 1][t & 1][1] = acc[t >> 1][t & 1][2] = acc[t >> 1][t & 1][3] = 0.f; }
                uint32_t b[4][4];
                uint4 u0, u1;
#pragma unroll
                for (int p = 0; p < 4; p++) ldsm4t(b[p], mb + p * 512);
#pragma unroll
                for (int p = 0; p < 12; p++) {
#pragma unroll
                    for (int u = 0; u < 2; u++) {
                        mma16816v(acc[0][u], wa[0][2 * p + u], b[p & 3][2 * u], b[p & 3][2 * u + 1]);
                        mma16816v(acc[1][u], wa[1][2 * p + u], b[p & 3][2 * u], b[p & 3][2 * u + 1]);
                    }
                    if (p + 4 < 12) ldsm4t(b[p & 3], mb + (p + 4) * 512);
                    if (p == Q3_AT) {
                        bar_sync(BAR_Q3, 256);
                        u0 = lds128(ra + SM_R3); u1 = lds128(ra + SM_O);
                    }
                }
                st_async4(r1, (acc[0][0][0] + __uint_as_float(u0.x)) + acc[0][1][0], (acc[0][0][1] + __uint_as_float(u0.y)) + acc[0][1][1],
                          (acc[0][0][2] + __uint_as_float(u0.z)) + acc[0][1][2], (acc[0][0][3] + __uint_as_float(u0.w)) + acc[0][1][3], r1b);
                TL(1);
                const float o0 = (acc[1][0][0] + __uint_as_float(u1.x)) + acc[1][1][0], o1 = (acc[1][0][1] + __uint_as_float(u1.y)) + acc[1][1][1];
                const float o2 = (acc[1][0][2] + __uint_as_float(u1.z)) + acc[1][1][2], o3 = (acc[1][0][3] + __uint_as_float(u1.w)) + acc[1][1][3];
                const uint32_t l4 = L >> 2, qo = SM_QKV + kh * 2048 + nh * 1024 + g * 256, qr = l4 + (rsb + qo), ql = l4 + (sb + qo), pb = rsb + MB_P;
                char* xd = make_ptr(l4 + (xbox + kh * 1024 + g * 256 + slot), mhi);
                asm volatile("" ::"l"(xd), "r"(qr), "r"(pb), "r"(qr + 128), "f"(o0), "f"(o1), "f"(o2), "f"(o3));
                mbar_wait_w(sb + MB_R1, s & 1);
                const uint4 v = lds128(ra + SM_R1);
                const uint32_t w0 = pack_bf16(o0 + __uint_as_float(v.x), o1 + __uint_as_float(v.y)), w1 = pack_bf16(o2 + __uint_as_float(v.z), o3 + __uint_as_float(v.w));
                st_relaxed_u32(xd, w0);
                st_relaxed_u32(xd + 128, w1);
                bar_arrive(BAR_PUB, 192);
                st_async1(qr, w0, pb);
                st_async1(qr + 128, w1, pb);
                sts32(ql, w0);
                sts32(ql + 128, w1);
                __syncwarp();
                mbar_expect_tx_if0(L, sb + MB_P, 256);
                TL(2);
                if (s + 3 < NSEG) bar_sync(BAR_VP, 256);
            } else {
                bar_sync(BAR_PRO, 288);
            }
            if (s + 3 < NSEG) {
                float d[16];
                batch1(d, xtlo, std::integral_constant<int, 0>(), std::integral_constant<int, 0>(), std::integral_constant<int, 32>());
                PHASE(1);
                const uint32_t rt = L + (rsb + SM_RT + g * 2048);
                wg_wait<0>();
                TL(7);
#pragma unroll
                for (int i = 0; i < 4; i++) st_async4(rt + i * 512, d[4 * i], d[4 * i + 1], d[4 * i + 2], d[4 * i + 3], rsb + MB_RT0);
            }
            if (s >= 0) {
                PHASE(2);
                {
                    const uint32_t vf = VFRAG(), va0 = vf + VBASE(), va1 = (vf ^ 32) + VBASE(), vma = L + (sb + SM_QKV + 4096 + g * 512), sa = (L >> 2) + (sb + SM_S + 768);
                    const uint32_t to = (L & 0x70) * 5 + ((L >> 3) & 0x30) + (sb + SM_TO + g * 640);
                    uint32_t va[2][4], vm[4], pw[6], w[4];
                    sched_fence((vf | sa) | to);
                    bar_sync(BAR_SV, 352);
                    softmax40(pw, sa, [&]() {
                        ldsm4t(va[0], va0); ldsm4t(va[1], va0 + 2048);
                        ldsm4(vm, vma);
                    });
                    float t[4] = {0.f, 0.f, 0.f, 0.f}, o[2][4] = {{0.f, 0.f, 0.f, 0.f}, {0.f, 0.f, 0.f, 0.f}};
                    mma1688(t, 0x3F803F80u, 0x3F803F80u, pw[5]);
                    mma16816v(o[0], va[0], pw[0], pw[1]);
                    ldsm4t(va[0], va1);
                    mma1688(o[1], vm[2], vm[3], pw[4]);
                    mma16816v(o[0], va[1], pw[2], pw[3]);
                    ldsm4t(va[1], va1 + 2048);
                    mma16816v(o[1], va[0], pw[0], pw[1]);
                    mma1688(o[0], vm[0], vm[1], pw[4]);
                    mma16816v(o[1], va[1], pw[2], pw[3]);
                    const float i0 = rcp_approx(t[0]), i1 = rcp_approx(t[1]);
#pragma unroll
                    for (int m = 0; m < 2; m++) { w[2 * m] = pack_bf16(o[m][0] * i0, o[m][1] * i1); w[2 * m + 1] = pack_bf16(o[m][2] * i0, o[m][3] * i1); }
                    stsm4t(to, w[0], w[1], w[2], w[3]);
                    TL(26);
                }
                auto tout = [&](const uint4& v) {
                    PHASE(3);
                    stg128(reinterpret_cast<char*>(g_ox) + (((L & 0x1C0) << 7) + (L & 0x30) + (((ui - 3) * SEG + 8 * j) * HD + h * DH + 32 * g) * 2), v);
                };
                const uint32_t ti = ((L >> 2) & 0x70) * 5 + (L & 0x30) + (sb + SM_TO + g * 640);
                if (s + 1 == NSEG) { __syncwarp(); tout(lds128(ti)); break; }
                const uint32_t fo = FRAG() + (sb + SM_WO2 + 16384), lo = L + (sb + SM_O), yo = (L >> 2) + (ybox + slot);
                uint32_t a1[6][4];
#pragma unroll
                for (int k = 0; k < 6; k++) ldsm4t(a1[k], fo + k * 2048);
                char* y0p = make_ptr(yo, mhi);
                char* y1p = make_ptr(yo ^ 4096, mhi);
                asm volatile("" ::"l"(y0p), "l"(y1p));
                sched_fence(ti);
                bar_sync(BAR_O2, 256);
                TLB(14);
                float y0[4] = {0.f, 0.f, 0.f, 0.f}, y1[4] = {0.f, 0.f, 0.f, 0.f};
                uint32_t b[2][4];
                ldsm4t(b[0], lo); ldsm4t(b[1], lo + 512);
#pragma unroll
                for (int p = 0; p < 4; p++) {
                    mma16816v(y0, a1[(2 * p) % 6], b[p & 1][0], b[p & 1][1]);
                    mma16816v(y1, a1[(2 * p + 1) % 6], b[p & 1][2], b[p & 1][3]);
                    if (p < 2) ldsm4t(b[p & 1], lo + (p + 2) * 512);
                    if (p == 0) { ldsm4t(a1[0], fo + 6 * 2048); ldsm4t(a1[1], fo + 7 * 2048); }
                }
                const uint4 tv = lds128(ti);
                st_relaxed_u32(y0p, pack_bf16(y0[0] + y1[0], y0[1] + y1[1]));
                st_relaxed_u32(y1p + 0x2000, pack_bf16(y0[2] + y1[2], y0[3] + y1[3]));
                bar_arrive(BAR_SENTC, 384);
                TL(6);
                tout(tv);
            }
            if (s + 3 < NSEG) {
                PHASE(4);
                float d[16];
                const uint32_t rt = L + (sb + SM_RT + g * 2048);
                mbar_wait_w(sb + MB_RT0, it & 1);
#pragma unroll
                for (int i = 0; i < 4; i++) {
                    const uint4 v = lds128(rt + i * 512);
                    d[4 * i] = __uint_as_float(v.x); d[4 * i + 1] = __uint_as_float(v.y); d[4 * i + 2] = __uint_as_float(v.z); d[4 * i + 3] = __uint_as_float(v.w);
                }
                if (s >= 0) bar_sync(BAR_SENT, 256);
                if (SPLIT > 0) batch1(d, xtlo, std::integral_constant<int, 1>(), std::integral_constant<int, 0>(), std::integral_constant<int, SPLIT>());
                if (s >= 0) bar_sync(BAR_ZP, 256);
                TLB(30);
                batch1(d, xtlo, std::integral_constant<int, 1>(), std::integral_constant<int, SPLIT>(), std::integral_constant<int, 32>());
                const uint32_t so = (kh ? FRAG() : ((L & 0x100) << 2) + (L & 0xF0) + g * 256) + (sb + SM_STG);
                wg_wait<0>();
                TL(8);
                uint32_t w[8];
#pragma unroll
                for (int i = 0; i < 8; i++) w[i] = pack_bf16(d[2 * i], d[2 * i + 1]);
                if (kh) {
                    stsm4t(so, w[0], w[1], w[2], w[3]);
                    stsm4t(so + 2048, w[4], w[5], w[6], w[7]);
                } else {
                    stsm4(so, w[0], w[1], w[2], w[3]);
                    stsm4(so + 2048, w[4], w[5], w[6], w[7]);
                }
                __syncwarp();
                mbar_arrive_if0(L, sb + MB_STG);
                TL(9);
            }
        }
    } else {
        asm volatile("setmaxnreg.inc.sync.aligned.u32 %0;" ::"n"(REG_B));
        const uint32_t l16 = lane16();
        uint32_t wv[24][4], wo[8 + WO_RF1][4];
        {
            const uint32_t L = l16, fa = sb + FRAG();
            mbar_wait_w(sb + MB_W0, 0);
#pragma unroll
            for (int r = 0; r < 24; r++) ldsm4t(wv[r], fa + STG_V + r * 2048);
            bar_arrive(BAR_PV, 160);
            mbar_wait_w(sb + MB_W3, 0);
#pragma unroll
            for (int r = 0; r < 8 + WO_RF1; r++) ldsm4t(wo[r], fa + STG_WO + r * 2048);
            mbar_wait_w(sb + MB_W2, 0);
            bar_arrive(BAR_PDONE, 384);
        }
        const uint32_t xbox = mlo + WIN + page_off(pair & 31, cls ^ XFLIP);
        const uint32_t ybox = mlo + page_off(2 * g + 32 * nh, kh ^ yflip) + h * 128;
#pragma unroll 1
        for (uint32_t it = 0; it < NSEG + 3; it++) {
            const int s = (int)it - 3;
            const uint32_t ui = uniform(it), slot = ((ui + 1) & 3) << 14, kvo = (~ui & 1) * KV_BYTES, xtlo = XTLO();
            {
                const uint32_t first = l16 | (g << 9);
                if (s >= 0) mbar_expect_tx_if0(first, sb + MB_R2, 1024);
                if (s + 3 < NSEG) {
                    mbar_expect_tx_if0(first, sb + MB_RT1, 4096);
                    mbar_wait_w(sb + MB_XT + (ui & 1) * 8, (it >> 1) & 1);
                }
            }
            if (s >= 0) {
                PHASE(0);
                const uint32_t fo = FRAG() + sb, l4 = L >> 2;
                {
                    const uint32_t mb = L + (sb + SM_Z), aw = fo + SM_WQK, ra = L + (sb + g * 512), r2 = (L >> 1) + (rsb + SM_R2 + g * 256), r2b = rsb + MB_R2;
                    uint32_t a[NA][4], b[4][4];
#pragma unroll
                    for (int i = 0; i < NA; i++) ldsm4t(a[i], aw + i * 2048);
                    sched_fence(r2 | r2b);
                    bar_sync(BAR_MEM, 384);
#pragma unroll
                    for (int p = 0; p < 4; p++) ldsm4t(b[p], mb + (12 + p) * 512);
                    sched_fence(L);
                    float c[2][4] = {{0.f, 0.f, 0.f, 0.f}, {0.f, 0.f, 0.f, 0.f}};
#pragma unroll
                    for (int i = 0; i < 16; i++) {
                        mma16816v(c[i & 1], a[i % NA], b[i >> 2][i & 2], b[i >> 2][(i & 2) + 1]);
                        ldsm4t(a[i % NA], aw + (i + NA) * 2048);
                    }
                    sts128(ra + SM_R3, make_uint4(__float_as_uint(c[0][0]), __float_as_uint(c[0][1]), __float_as_uint(c[0][2]), __float_as_uint(c[0][3])));
                    sts128(ra + SM_O, make_uint4(__float_as_uint(c[1][0]), __float_as_uint(c[1][1]), __float_as_uint(c[1][2]), __float_as_uint(c[1][3])));
                    bar_arrive(BAR_Q3, 256);
                    TL(29);
                    float acc[4][4];
#pragma unroll
                    for (int t = 0; t < 4; t++) { acc[t][0] = acc[t][1] = acc[t][2] = acc[t][3] = 0.f; }
#pragma unroll
                    for (int i = 16; i < 24; i++) {
                        mma16816v(acc[i & 1], a[i % NA], b[(i - 16) >> 1][2 * (i & 1)], b[(i - 16) >> 1][2 * (i & 1) + 1]);
                        if (i + NA < 24) ldsm4t(a[i % NA], aw + (i + NA) * 2048);
                        else ldsm4t(a[i % NA], mb + (i + NA - 24) * 512);
                    }
#pragma unroll
                    for (int p = 0; p < 12; p++) {
                        mma16816v(acc[(2 * p) & 3], wv[2 * p], a[(24 + p) % NA][0], a[(24 + p) % NA][1]);
                        mma16816v(acc[(2 * p + 1) & 3], wv[2 * p + 1], a[(24 + p) % NA][2], a[(24 + p) % NA][3]);
                        if (p + NA < 12) ldsm4t(a[(24 + p) % NA], mb + (p + NA) * 512);
                    }
                    if (s + 3 < NSEG) bar_arrive(BAR_VP, 256);
                    float o[4];
#pragma unroll
                    for (int i = 0; i < 4; i++) o[i] = (acc[0][i] + acc[1][i]) + (acc[2][i] + acc[3][i]);
                    st_async2(r2, kh ? o[0] : o[2], kh ? o[1] : o[3], r2b);
                    TL(10);
                    const float o0 = kh ? o[2] : o[0], o1 = kh ? o[3] : o[1];
                    const uint32_t qo = SM_QKV + 4096 + nh * 1024 + (2 * g + kh) * 128, qr = l4 + (rsb + qo), ql = l4 + (sb + qo), vb = rsb + MB_V, rl = (L >> 1) + (sb + SM_R2 + g * 256);
                    char* xd = make_ptr(l4 + (xbox + 2048 + (2 * g + kh) * 128 + slot), mhi);
                    asm volatile("" ::"l"(xd), "r"(qr), "r"(vb), "f"(o0), "f"(o1));
                    mbar_wait_w(sb + MB_R2, s & 1);
                    uint32_t vx, vy;
                    asm volatile("ld.shared.v2.u32 {%0,%1}, [%2];" : "=r"(vx), "=r"(vy) : "r"(rl) : "memory");
                    const uint32_t w0 = pack_bf16(o0 + __uint_as_float(vx), o1 + __uint_as_float(vy));
                    st_relaxed_u32(xd, w0);
                    bar_arrive(BAR_PUBV, 160);
                    st_async1(qr, w0, vb);
                    sts32(ql, w0);
                    __syncwarp();
                    mbar_expect_tx_if0(L, sb + MB_V, 128);
                    TL(11);
                }
                const uint32_t vma = L + (sb + SM_QKV + 4096 + g * 512), yo = l4 + (ybox + slot);
                uint32_t va[2][2][4];
                {
                    const uint32_t qa = QFRAG(), vf = VFRAG(), va0 = vf + VBASE(), va1 = (vf ^ 32) + VBASE();
                    const uint32_t kf = ((L << 3) & 0x380) | ((L ^ (L >> 3)) & 0x30) | (L & 0x40), kb0 = sb + SM_KV + kvo + g * 1024;
                    const int d = (int)(L >> 6) - (int)((L >> 3) & 6) + 8 * (j - (int)g);
                    const uint32_t keep = (d < 0 ? 0u : 0xFFFFu) | (d < 1 ? 0u : 0xFFFF0000u), sa = l4 + (sb + SM_S + g * 128);
                    const uint32_t q0 = qa + (sb + nh * 1024), q1 = qa + (sb + (nh ^ 1) * 1024);
                    float sc[4] = {0.f, 0.f, 0.f, 0.f}, sd[4] = {0.f, 0.f, 0.f, 0.f};
                    uint32_t a[4][4], kb[2][4];
                    mbar_wait_w(sb + MB_KV + (~ui & 1) * 8, (s >> 1) & 1);
                    ldsm4(kb[0], kf + (kb0 + nh * 4096)); ldsm4(kb[1], (kf ^ 64) + (kb0 + nh * 4096));
                    mbar_wait_w(sb + MB_P, s & 1);
                    TL(12);
#pragma unroll
                    for (int k = 0; k < 4; k++) ldsm4t(a[k], q0 + k * 256);
#pragma unroll
                    for (int k = 0; k < 4; k++) mma16816v((k & 1) ? sd : sc, a[k], kb[k >> 1][2 * (k & 1)], kb[k >> 1][2 * (k & 1) + 1]);
                    ldsm4(kb[0], kf + (kb0 + (nh ^ 1) * 4096)); ldsm4(kb[1], (kf ^ 64) + (kb0 + (nh ^ 1) * 4096));
                    sched_fence(vf | yo);
                    bar_sync(BAR_QK, 224);
                    TLB(3);
#pragma unroll
                    for (int k = 0; k < 4; k++) ldsm4t(a[k], q1 + k * 256);
                    sched_fence(L);
#pragma unroll
                    for (int k = 0; k < 4; k++) mma16816v((k & 1) ? sd : sc, a[k], kb[k >> 1][2 * (k & 1)], kb[k >> 1][2 * (k & 1) + 1]);
                    ldsm4t(va[0][0], va0); ldsm4t(va[0][1], va0 + 2048);
                    sts32(sa, scale_scores(sc[0] + sd[0], sc[1] + sd[1]));
                    sts32(sa + 768, (scale_scores(sc[2] + sd[2], sc[3] + sd[3]) & keep) | (0xFF80FF80u & ~keep));
                    bar_arrive(BAR_SV, 352);
                    ldsm4t(va[1][0], va1); ldsm4t(va[1][1], va1 + 2048);
                }
                bar_sync(BAR_S, 160);
                TLB(4);
                uint32_t pw[6], vm[4];
                if (s + 1 == NSEG) break;
                softmax40(pw, l4 + (sb + SM_S), [&]() {
                    bar_sync(BAR_V, 160);
                    ldsm4(vm, vma);
                });
                uint32_t a1[4][4];
                {
                    uint32_t w[4];
                    pv32(w, va, vm, pw, [&]() {
                        sched_fence(L);
#pragma unroll
                        for (int k = 0; k < 4; k++) ldsm4t(a1[k], fo + SM_WO2 + k * 2048);
                    });
#pragma unroll
                    for (int i = 0; i < 4; i++) sts32(l4 + (sb + SM_O + g * 512) + i * 128, w[i]);
                }
                const uint32_t lo = L + (sb + SM_O);
                bar_arrive(BAR_O2, 256);
                bar_sync(BAR_O, 128);
                TLB(5);
                {
                    float y0[4] = {0.f, 0.f, 0.f, 0.f}, y1[4] = {0.f, 0.f, 0.f, 0.f}, y2[4] = {0.f, 0.f, 0.f, 0.f};
                    uint32_t b[2][4];
                    ldsm4t(b[0], lo); ldsm4t(b[1], lo + 512);
                    char* yd = make_ptr(yo, mhi);
                    char* yd1 = make_ptr(yo ^ 4096, mhi);
#pragma unroll
                    for (int k = 0; k < 8; k++) {
                        const int p = k >> 1, u = k & 1;
                        mma16816v(y2, a1[k & 3], b[p & 1][2 * u], b[p & 1][2 * u + 1]);
                        if (k < 4) ldsm4t(a1[k & 3], fo + SM_WO2 + (k + 4) * 2048);
                        if (k >= 4 && k + 2 >= WO_RF1 && k + 2 < 8) ldsm4t(a1[k & 3], fo + SM_WO1 + (k + 2) * 2048);
                        mma16816v(y0, wo[k], b[p & 1][2 * u], b[p & 1][2 * u + 1]);
                        if (k < WO_RF1) mma16816v(y1, wo[8 + (k < WO_RF1 ? k : 0)], b[p & 1][2 * u], b[p & 1][2 * u + 1]);
                        else mma16816v(y1, a1[(k - 2) & 3], b[p & 1][2 * u], b[p & 1][2 * u + 1]);
                        if (u == 1 && p < 2) ldsm4t(b[p & 1], lo + (p + 2) * 512);
                    }
                    st_relaxed_u32(yd1 + 0x80000, pack_bf16(y2[0], y2[1]));
                    st_relaxed_u32(yd + 0x82000, pack_bf16(y2[2], y2[3]));
                    st_relaxed_u32(yd, pack_bf16(y0[0], y0[1]));
                    st_relaxed_u32(yd1 + 0x2000, pack_bf16(y0[2], y0[3]));
                    st_relaxed_u32(yd + 0x40000, pack_bf16(y1[0], y1[1]));
                    st_relaxed_u32(yd1 + 0x42000, pack_bf16(y1[2], y1[3]));
                }
                bar_arrive(BAR_SENTC, 384);
                TL(13);
                if (s + 3 < NSEG) bar_sync(BAR_SENT, 256);
            } else {
                bar_sync(BAR_PRO, 288);
            }
            if (s + 3 < NSEG) {
                float d[16];
                const uint64_t da = make_desc(SB0 + SM_WV, 16, 1024);
                wg_fence();
                static_for<0, 32>([&](auto kc) {
                    constexpr int k = decltype(kc)::value, off = (k >> 2) * 256 + (k & 3) * 2;
                    if constexpr (k >= 24) wgmma_ss32u<off>(d, da + (k - 24) * 128, xtlo);
                    else wgmma_rs32u<off, k != 0>(d, wv[k], xtlo);
                });
                wg_commit();
                PHASE(1);
                const uint32_t rt = SM_RT + 8192 + g * 1024, so = FRAG() + (sb + SM_STG + 4096);
                wg_wait<0>();
                TL(27);
#pragma unroll
                for (int i = 0; i < 2; i++)
                    st_async4(L + (rsb + rt + i * 512), kh ? d[4 * i] : d[8 + 4 * i], kh ? d[4 * i + 1] : d[9 + 4 * i], kh ? d[4 * i + 2] : d[10 + 4 * i], kh ? d[4 * i + 3] : d[11 + 4 * i], rsb + MB_RT1);
                float o[8];
#pragma unroll
                for (int i = 0; i < 8; i++) o[i] = kh ? d[8 + i] : d[i];
                mbar_wait_w(sb + MB_RT1, it & 1);
                TL(28);
                uint32_t w[4];
#pragma unroll
                for (int i = 0; i < 2; i++) {
                    const uint4 v = lds128(L + (sb + rt) + i * 512);
                    w[2 * i] = pack_bf16(o[4 * i] + __uint_as_float(v.x), o[4 * i + 1] + __uint_as_float(v.y));
                    w[2 * i + 1] = pack_bf16(o[4 * i + 2] + __uint_as_float(v.z), o[4 * i + 3] + __uint_as_float(v.w));
                }
                stsm4t(so, w[0], w[1], w[2], w[3]);
                __syncwarp();
                mbar_arrive_if0(L, sb + MB_STG);
                TL(15);
            }
        }
    }
    KT_END(2);
    asm volatile("barrier.cluster.arrive.relaxed; barrier.cluster.wait;" ::: "memory");
}
constexpr int B_UCH = 39 * 128 + 16;
constexpr int B_KLEN = 2128;
constexpr int B_KCH = 2 * B_KLEN * 2 + 64;
constexpr int B_SM_U = 0;
constexpr int B_SM_K = 16 * B_UCH;
constexpr int B_SM_BAR = B_SM_K + 16 * B_KCH;
constexpr int B_SMEM = B_SM_BAR + 16 + 128;
static_assert(16 * B_KCH >= 2 * 65536, "the k / v tiles alias the kernel copies");
#define PROBE_N 5
constexpr int B_C = 2056;

__device__ __forceinline__ uint32_t bf16_mul(uint32_t a, uint32_t b) {
    uint32_t d;
    asm("mul.rn.bf16x2 %0, %1, %2;" : "=r"(d) : "r"(a), "r"(b));
    return d;
}
__device__ __forceinline__ uint32_t bf16_add(uint32_t a, uint32_t b) {
    uint32_t d;
    asm("add.rn.bf16x2 %0, %1, %2;" : "=r"(d) : "r"(a), "r"(b));
    return d;
}

__device__ __forceinline__ uint32_t atomic_round_trip(char* p) {
    uint32_t t0, t1, v;
    asm volatile("{.reg .pred p;\n"
                 "mov.u32 %0, %%clock;\n"
                 "atom.relaxed.gpu.global.add.u32 %2, [%3], 1;\n"
                 "setp.ne.u32 p, %2, 0x7FFFFFFF;\n"
                 "mov.u32 %1, 0;\n"
                 "@p mov.u32 %1, %%clock;}" : "=&r"(t0), "=&r"(t1), "=&r"(v) : "l"(p) : "memory");
    return t1 - t0;
}
__device__ __forceinline__ uint32_t far_first(char* a, char* b, int lane) {
    if (lane < 16) stg128((lane < 8 ? a : b) + (lane & 7) * 16, make_uint4(0, 0, 0, 0));
    __syncwarp();
    uint32_t ta = ~0u, tb = ~0u;
    if (lane == 0) {
        __threadfence();
#pragma unroll 1
        for (int i = 0; i < PROBE_N; i++) { ta = min(ta, atomic_round_trip(a)); tb = min(tb, atomic_round_trip(b)); }
    }
    return ta > tb;
}
__device__ __forceinline__ void measure_distance(char* mbox, int lane) {
    const uint32_t b = blockIdx.x;
    unsigned smid;
    asm volatile("mov.u32 %0, %%smid;" : "=r"(smid));
    char* w1 = mbox + WIN + (b & 31) * 128;
    const uint32_t c = far_first(w1 + page_off(40 + (b >> 5), 0), w1 + page_off(40 + (b >> 5), 1), lane);
    if (lane == 0) g_cls[smid] = c;
    if (b == 0) {
        const uint32_t c0 = far_first(mbox + page_off(0, 0), mbox + page_off(0, 1), lane);
        if (lane == 0) { g_reg[2] = c0 ^ c; g_reg[0] = 0; g_reg[1] = 0; }
    }
    if (b == 1) for (int i = lane; i < 128; i += 32) g_xflag[i] = 0;
    __syncwarp();
}

#define SP(i)
__global__ void __launch_bounds__(512, 1)
ssm_kernel(const __grid_constant__ CUtensorMap mapK, const __grid_constant__ CUtensorMap mapV, const bf16* __restrict__ Q, const bf16* __restrict__ shiftk,
           const bf16* __restrict__ ssmk, const bf16* __restrict__ Dv, bf16* __restrict__ out, char* __restrict__ mbox) {
    extern __shared__ __align__(128) uint8_t smem_raw[];
    const uint32_t sb = (smem_u32(smem_raw) + 127) & ~127u;
    const int ch0 = (blockIdx.x >> 1) * 16, half = blockIdx.x & 1;
    const int t = threadIdx.x, warp = t >> 5, lane = t & 31;
    const int tmax = half ? 1536 : 2048;
    KT_START(1);
    SP(0);
    if (blockIdx.x >= 128) {
        if (warp == 15) measure_distance(mbox, lane);
        return;
    }
    const uint32_t stg_k = sb + B_SM_K, stg_v = stg_k + 65536, bar = sb + B_SM_BAR;
    if (t == 0) {
        mbar_init(bar, 1);
        asm volatile("fence.mbarrier_init.release.cluster;" ::: "memory");
        mbar_expect_tx(bar, 2 * tmax * 32);
        for (int r = 0; r < tmax; r += 256) {
            tma_load_2d(stg_k + r * 32, &mapK, ch0, r, bar);
            tma_load_2d(stg_v + r * 32, &mapV, ch0, r, bar);
        }
    }
    uint4 kr[8];
    {
        const uint4* src = reinterpret_cast<const uint4*>(ssmk + (size_t)(ch0 + warp) * S_LEN) + lane;
#pragma unroll
        for (int i = 0; i < 8; i++) kr[i] = __ldg(src + i * 32);
        const uint32_t ub = sb + B_SM_U + warp * B_UCH;
        for (int i = lane; i < 7 * 8; i += 32) sts128(ub + i * 16, make_uint4(0, 0, 0, 0));
    }
    const int hr = lane & 1, cc = ch0 + hr * 8;
    uint32_t w[4][4];
#pragma unroll
    for (int p = 0; p < 4; p++) {
        const uint4 sw = __ldg(reinterpret_cast<const uint4*>(shiftk + (size_t)cc * 4 + p * 8));
        w[0][p] = __byte_perm(sw.x, sw.z, 0x5410); w[1][p] = __byte_perm(sw.x, sw.z, 0x7632);
        w[2][p] = __byte_perm(sw.y, sw.w, 0x5410); w[3][p] = __byte_perm(sw.y, sw.w, 0x7632);
    }
    __syncthreads();
    if (warp == 15) measure_distance(mbox, lane);
    mbar_wait(bar, 0);
    SP(1);
    if (warp * 128 < tmax) {
#pragma unroll 2
        for (int i = 0; i < 8; i++) {
            const int tt = warp * 128 + i * 16 + (lane >> 1);
            const uint32_t ka = stg_k + tt * 32 + hr * 16;
            const uint4 z = make_uint4(0, 0, 0, 0);
            const uint4 k0 = lds128(ka), k1 = tt >= 1 ? lds128(ka - 32) : z, k2 = tt >= 2 ? lds128(ka - 64) : z, k3 = tt >= 3 ? lds128(ka - 96) : z;
            const uint4 vv = lds128(stg_v + tt * 32 + hr * 16);
            uint4 o;
#pragma unroll
            for (int p = 0; p < 4; p++) {
                uint32_t a = bf16_mul(((const uint32_t*)&k3)[p], w[3][p]);
                a = bf16_add(a, bf16_mul(((const uint32_t*)&k2)[p], w[2][p]));
                a = bf16_add(a, bf16_mul(((const uint32_t*)&k1)[p], w[1][p]));
                a = bf16_add(a, bf16_mul(((const uint32_t*)&k0)[p], w[0][p]));
                ((uint32_t*)&o)[p] = bf16_mul(a, ((const uint32_t*)&vv)[p]);
            }
            sts128(stg_v + tt * 32 + hr * 16, o);
        }
        __syncwarp();
#pragma unroll
        for (int i = 0; i < 8; i++) {
            const int tt = warp * 128 + i * 16;
            uint32_t r0, r1, r2, r3;
            ldsm4t(r0, r1, r2, r3, stg_v + (tt + (lane & 7) + (lane >> 4) * 8) * 32 + ((lane >> 3) & 1) * 16);
            const int chn = (lane & 7) + ((lane >> 3) & 1) * 8, ts = tt + (lane >> 4) * 8, row = 7 + (ts >> 6), unit = (ts & 63) >> 3;
            stsm4(sb + B_SM_U + chn * B_UCH + row * 128 + ((unit ^ (row & 7)) * 16), r0, r1, r2, r3);
        }
    }
    __syncthreads();
    {
        const uint32_t kb = sb + B_SM_K + warp * B_KCH;
#pragma unroll
        for (int i = 0; i < 8; i++) {
            const uint4 lo = kr[i];
            const uint32_t nx = __shfl_down_sync(~0u, lo.x, 1), n0 = (i < 7) ? __shfl_sync(~0u, kr[i < 7 ? i + 1 : 7].x, 0) : 0u;
            const uint32_t hix = (lane < 31) ? nx : n0;
            const int c = 256 - (lane + 32 * i);
            sts128(kb + c * 16, make_uint4(__byte_perm(hix, lo.w, 0x7610), __byte_perm(lo.w, lo.z, 0x7610), __byte_perm(lo.z, lo.y, 0x7610), __byte_perm(lo.y, lo.x, 0x7610)));
            sts128(kb + B_KLEN * 2 + 64 + c * 16, make_uint4(__byte_perm(lo.w, lo.w, 0x1032), __byte_perm(lo.z, lo.z, 0x1032), __byte_perm(lo.y, lo.y, 0x1032), __byte_perm(lo.x, lo.x, 0x1032)));
        }
        const uint32_t k0w = __shfl_sync(~0u, kr[0].x, 0);
        if (lane < 10) {
            const int c = (lane == 0) ? 0 : 256 + lane;
            sts128(kb + c * 16, make_uint4(c == 257 ? (k0w & 0xFFFFu) : 0u, 0u, 0u, 0u));
            sts128(kb + B_KLEN * 2 + 64 + c * 16, make_uint4(0u, 0u, 0u, 0u));
        }
    }
    __syncwarp();
    SP(2);
    SP(3);
    const int tA = half ? 1 : 0, tB = half ? 2 : 3;
    float accA[4][4], accB[4][4];
#pragma unroll
    for (int i = 0; i < 4; i++)
#pragma unroll
        for (int e = 0; e < 4; e++) { accA[i][e] = 0.f; accB[i][e] = 0.f; }
    const int g = lane >> 2, tq = lane & 3;
    const uint32_t kb = sb + B_SM_K + warp * B_KCH;
    const int e0 = B_C - g + 2 * tq;
    const uint32_t fbase = (e0 & 1) ? (kb + B_KLEN * 2 + 64 + (e0 - 1) * 2) : (kb + e0 * 2);
    const uint32_t ub = sb + B_SM_U + warp * B_UCH;
    uint32_t A[8][4];
    auto load_frag = [&](uint32_t (&a)[4], int q) {
        const uint32_t ad = fbase - 16 * q;
        a[0] = lds32(ad); a[1] = lds32(ad - 16); a[2] = lds32(ad + 16); a[3] = lds32(ad);
    };
#pragma unroll
    for (int i = 5; i < 8; i++) load_frag(A[i], 2 * (i - 8));
    const int mA = 8 * tA + 7, mB = 8 * tB + 7;
    auto tile_step = [&](float (&acc)[4][4], int tile, int m, auto mm_c) {
        constexpr int mm = decltype(mm_c)::value;
        const int row = 7 + 8 * tile - m + (lane & 7);
        const uint32_t ra = ub + row * 128;
#pragma unroll
        for (int p = 0; p < 2; p++) {
            uint32_t b[4];
            ldsm4(b[0], b[1], b[2], b[3], ra + (((p * 4 + (lane >> 3)) ^ (row & 7)) * 16));
#pragma unroll
            for (int u = 0; u < 2; u++) {
                const int k = 2 * p + u;
#pragma unroll
                for (int mt = 0; mt < 4; mt++) {
                    const int sl = (mm * 4 + (mt - k) + 8) & 7;
                    mma16816(acc[mt], A[sl][0], A[sl][1], A[sl][2], A[sl][3], b[2 * u], b[2 * u + 1]);
                }
            }
        }
    };
    int m = 0;
#pragma unroll 1
    for (; m <= mA; m += 2) {
#pragma unroll
        for (int i = 0; i < 4; i++) load_frag(A[i], 8 * m + 2 * i);
        tile_step(accB, tB, m, std::integral_constant<int, 0>());
        tile_step(accA, tA, m, std::integral_constant<int, 0>());
#pragma unroll
        for (int i = 0; i < 4; i++) load_frag(A[4 + i], 8 * m + 8 + 2 * i);
        tile_step(accB, tB, m + 1, std::integral_constant<int, 1>());
        tile_step(accA, tA, m + 1, std::integral_constant<int, 1>());
    }
#pragma unroll 1
    for (; m <= mB; m += 2) {
#pragma unroll
        for (int i = 0; i < 4; i++) load_frag(A[i], 8 * m + 2 * i);
        tile_step(accB, tB, m, std::integral_constant<int, 0>());
#pragma unroll
        for (int i = 0; i < 4; i++) load_frag(A[4 + i], 8 * m + 8 + 2 * i);
        tile_step(accB, tB, m + 1, std::integral_constant<int, 1>());
    }
    SP(4);
    {
        const uint32_t dw = (uint32_t)__ldg(reinterpret_cast<const uint16_t*>(Dv) + ch0 + warp) * 0x00010001u;
        __syncwarp();
#pragma unroll
        for (int tl = 0; tl < 2; tl++) {
            const int row = 7 + 8 * (tl ? tB : tA) + (lane & 7);
#pragma unroll
            for (int mp = 0; mp < 2; mp++) {
                const uint32_t a = ub + row * 128 + (((mp * 4 + (lane >> 3)) ^ (row & 7)) * 16);
                uint32_t u0, u1, u2, u3;
                ldsm4t(u0, u1, u2, u3, a);
                const float(&c0)[4] = tl ? accB[2 * mp] : accA[2 * mp];
                const float(&c1)[4] = tl ? accB[2 * mp + 1] : accA[2 * mp + 1];
                const uint32_t y0 = bf16_add(pack_bf16(c0[0], c0[1]), bf16_mul(u0, dw)), y1 = bf16_add(pack_bf16(c0[2], c0[3]), bf16_mul(u1, dw));
                const uint32_t y2 = bf16_add(pack_bf16(c1[0], c1[1]), bf16_mul(u2, dw)), y3 = bf16_add(pack_bf16(c1[2], c1[3]), bf16_mul(u3, dw));
                asm volatile("stmatrix.sync.aligned.m8n8.x4.trans.shared.b16 [%0], {%1,%2,%3,%4};" ::"r"(a), "r"(y0), "r"(y1), "r"(y2), "r"(y3) : "memory");
            }
        }
    }
    const int hh = lane >> 4, tbk = (warp & 7) * 16 + (lane & 15);
    const int tg = ((tbk < 64) ? tA : tB) * 512 + (tbk & 63) * 8;
    uint4 qv[8];
    if (t < 256) {
#pragma unroll
        for (int i = 0; i < 8; i++) qv[i] = __ldg(reinterpret_cast<const uint4*>(Q + (size_t)(tg + i) * DM + ch0 + hh * 8));
    }
    SP(5);
    __syncthreads();
    SP(6);
    if (t < 256) {
        const int row = 7 + (tg >> 6), unit = (tg & 63) >> 3;
        uint4 y[8];
#pragma unroll
        for (int c = 0; c < 8; c++) y[c] = lds128(sb + B_SM_U + (hh * 8 + c) * B_UCH + row * 128 + ((unit ^ (row & 7)) * 16));
#pragma unroll
        for (int i = 0; i < 8; i++) {
            const uint32_t sel = (i & 1) ? 0x7632 : 0x5410;
            uint4 o;
            o.x = bf16_mul(qv[i].x, __byte_perm(((const uint32_t*)&y[0])[i >> 1], ((const uint32_t*)&y[1])[i >> 1], sel));
            o.y = bf16_mul(qv[i].y, __byte_perm(((const uint32_t*)&y[2])[i >> 1], ((const uint32_t*)&y[3])[i >> 1], sel));
            o.z = bf16_mul(qv[i].z, __byte_perm(((const uint32_t*)&y[4])[i >> 1], ((const uint32_t*)&y[5])[i >> 1], sel));
            o.w = bf16_mul(qv[i].w, __byte_perm(((const uint32_t*)&y[6])[i >> 1], ((const uint32_t*)&y[7])[i >> 1], sel));
            stg128(out + (size_t)(tg + i) * OUT_LD + DM + ch0 + hh * 8, o);
        }
    } else {
        const uint4 sent = make_uint4(SENT, SENT, SENT, SENT);
        char* p0 = mbox + blockIdx.x * 16384 + (t - 256) * 16;
#pragma unroll
        for (int i = 0; i < 4; i++) stg128(p0 + i * 4096, sent);
        char* p1 = mbox + WIN + blockIdx.x * 8704 + (t - 256) * 16;
        stg128(p1, sent); stg128(p1 + 4096, sent);
        if (t < 256 + 32) stg128(p1 + 8192, sent);
    }
    KT_END(1);
}

typedef CUresult (*EncodeFn)(CUtensorMap*, CUtensorMapDataType, cuuint32_t, void*, const cuuint64_t*, const cuuint64_t*, const cuuint32_t*,
                             const cuuint32_t*, CUtensorMapInterleave, CUtensorMapSwizzle, CUtensorMapL2promotion, CUtensorMapFloatOOBfill);

static void make_map(EncodeFn fn, CUtensorMap* m, const void* ptr, uint64_t inner, uint64_t outer, uint32_t box_in, uint32_t box_out,
                     CUtensorMapL2promotion promo = CU_TENSOR_MAP_L2_PROMOTION_L2_256B) {
    cuuint64_t dims[2] = {inner, outer};
    cuuint64_t strides[1] = {inner * 2};
    cuuint32_t box[2] = {box_in, box_out};
    cuuint32_t es[2] = {1, 1};
    fn(m, CU_TENSOR_MAP_DATA_TYPE_BFLOAT16, 2, const_cast<void*>(ptr), dims, strides, box, es, CU_TENSOR_MAP_INTERLEAVE_NONE,
       CU_TENSOR_MAP_SWIZZLE_128B, promo, CU_TENSOR_MAP_FLOAT_OOB_FILL_NONE);
}

extern "C" void kernel_launch(void* const* d_in, const int* in_sizes, int n_in, void* d_out, int out_size) {
    const bf16* x = (const bf16*)d_in[0];
    const bf16* mem0 = (const bf16*)d_in[1];
    const bf16* Wq = (const bf16*)d_in[2];
    const bf16* Wk = (const bf16*)d_in[3];
    const bf16* Wv = (const bf16*)d_in[4];
    const bf16* Wo = (const bf16*)d_in[5];
    const bf16* Bq = (const bf16*)d_in[7];
    const bf16* Bk = (const bf16*)d_in[8];
    const bf16* Bv = (const bf16*)d_in[9];
    const bf16* Bsh = (const bf16*)d_in[10];
    const bf16* Bssm = (const bf16*)d_in[11];
    const bf16* BD = (const bf16*)d_in[12];
    bf16* out = (bf16*)d_out;

    static bool init = false;
    static EncodeFn enc = nullptr;
    static void *p_tok, *p_ox, *p_mbox;
    static int nclusters = 64;
    using G2 = GemmCfg<128, 5>;
    if (!init) {
        cudaDriverEntryPointQueryResult qr;
        cudaGetDriverEntryPoint("cuTensorMapEncodeTiled", (void**)&enc, cudaEnableDefault, &qr);
        cudaGetSymbolAddress(&p_tok, g_tok);
        cudaGetSymbolAddress(&p_ox, g_ox);
        cudaGetSymbolAddress(&p_mbox, g_mbox);
        cudaFuncSetAttribute(gemm_kernel<128, 5>, cudaFuncAttributeMaxDynamicSharedMemorySize, G2::SMEM);
        cudaFuncSetAttribute(chain_kernel, cudaFuncAttributeMaxDynamicSharedMemorySize, CHAIN_SMEM);
        cudaFuncSetAttribute(ssm_kernel, cudaFuncAttributeMaxDynamicSharedMemorySize, B_SMEM);
        cudaLaunchConfig_t cfg = {};
        cfg.gridDim = dim3(132); cfg.blockDim = dim3(384); cfg.dynamicSmemBytes = CHAIN_SMEM;
        cudaLaunchAttribute at[1];
        at[0].id = cudaLaunchAttributeClusterDimension; at[0].val.clusterDim.x = 2; at[0].val.clusterDim.y = 1; at[0].val.clusterDim.z = 1;
        cfg.attrs = at; cfg.numAttrs = 1;
        int n = 0;
        if (cudaOccupancyMaxActiveClusters(&n, chain_kernel, &cfg) == cudaSuccess && n > 64) nclusters = n < 66 ? n : 66;
        (void)cudaGetLastError();
        init = true;
    }
    char* mbox = (char*)(((uintptr_t)p_mbox + 2 * WIN - 1) & ~(uintptr_t)(2 * WIN - 1));
    CUtensorMap mX, mT32, mT16, mTQ, mKV, mWq, mWk, mWv, mWoC, mOx, mWo, mOut;
    {
        cuuint64_t dims[3] = {64, S_LEN, DM / 64};
        cuuint64_t strides[2] = {DM * 2, 128};
        cuuint32_t box[3] = {64, 32, 4};
        cuuint32_t es[3] = {1, 1, 1};
        enc(&mX, CU_TENSOR_MAP_DATA_TYPE_BFLOAT16, 3, const_cast<bf16*>(x), dims, strides, box, es, CU_TENSOR_MAP_INTERLEAVE_NONE,
            CU_TENSOR_MAP_SWIZZLE_128B, CU_TENSOR_MAP_L2_PROMOTION_L2_256B, CU_TENSOR_MAP_FLOAT_OOB_FILL_NONE);
    }
    make_map(enc, &mT32, p_tok, DH, 4 * NH * 3 * SEG, 64, 32, CU_TENSOR_MAP_L2_PROMOTION_L2_128B);
    make_map(enc, &mT16, p_tok, DH, 4 * NH * 3 * SEG, 64, 16, CU_TENSOR_MAP_L2_PROMOTION_L2_128B);
    {
        cuuint64_t dims[2] = {512, 4 * NH * 12};
        cuuint64_t strides[1] = {2048};
        cuuint32_t box[2] = {256, 4};
        cuuint32_t es[2] = {1, 1};
        enc(&mTQ, CU_TENSOR_MAP_DATA_TYPE_UINT32, 2, p_tok, dims, strides, box, es, CU_TENSOR_MAP_INTERLEAVE_NONE,
            CU_TENSOR_MAP_SWIZZLE_NONE, CU_TENSOR_MAP_L2_PROMOTION_L2_128B, CU_TENSOR_MAP_FLOAT_OOB_FILL_NONE);
    }
    {
        cuuint64_t dims[3] = {64, 4 * NH * 3 * SEG, 2};
        cuuint64_t strides[2] = {DH * 2, 128};
        cuuint32_t box[3] = {64, 32, 2};
        cuuint32_t es[3] = {1, 1, 1};
        enc(&mKV, CU_TENSOR_MAP_DATA_TYPE_BFLOAT16, 3, p_tok, dims, strides, box, es, CU_TENSOR_MAP_INTERLEAVE_NONE,
            CU_TENSOR_MAP_SWIZZLE_128B, CU_TENSOR_MAP_L2_PROMOTION_L2_128B, CU_TENSOR_MAP_FLOAT_OOB_FILL_NONE);
    }
    make_map(enc, &mWq, Wq, HD, DM, 64, 16, CU_TENSOR_MAP_L2_PROMOTION_L2_128B);
    make_map(enc, &mWk, Wk, HD, DM, 64, 16, CU_TENSOR_MAP_L2_PROMOTION_L2_128B);
    make_map(enc, &mWv, Wv, HD, DM, 64, 16, CU_TENSOR_MAP_L2_PROMOTION_L2_128B);
    make_map(enc, &mWoC, Wo, DM, HD, 64, 128, CU_TENSOR_MAP_L2_PROMOTION_L2_128B);
    make_map(enc, &mOx, p_ox, HD, S_LEN, 64, 128);
    make_map(enc, &mWo, Wo, DM, HD, 64, 64);
    make_map(enc, &mOut, out, OUT_LD, S_LEN, 64, 64);

    CUtensorMap mBk, mBv;
    for (int i = 0; i < 2; i++) {
        cuuint64_t dims[2] = {DM, S_LEN};
        cuuint64_t strides[1] = {DM * 2};
        cuuint32_t box[2] = {16, 256};
        cuuint32_t es[2] = {1, 1};
        enc(i ? &mBv : &mBk, CU_TENSOR_MAP_DATA_TYPE_BFLOAT16, 2, const_cast<bf16*>(i ? Bv : Bk), dims, strides, box, es, CU_TENSOR_MAP_INTERLEAVE_NONE,
            CU_TENSOR_MAP_SWIZZLE_NONE, CU_TENSOR_MAP_L2_PROMOTION_NONE, CU_TENSOR_MAP_FLOAT_OOB_FILL_NONE);
    }
    cudaStream_t st = cudaStreamPerThread;
    ssm_kernel<<<132, 512, B_SMEM, st>>>(mBk, mBv, Bq, Bsh, Bssm, BD, out, mbox);
    chain_kernel<<<2 * nclusters, 384, CHAIN_SMEM, st>>>(mX, mT32, mT16, mTQ, mKV, mWq, mWk, mWv, mWoC, mem0, mbox);
    gemm_kernel<128, 5><<<128, 288, G2::SMEM, st>>>(mOx, mWo, mWo, mWo, mOut, 16, 8, 64);
}
```

```cpp
#include <cuda_runtime.h>
#include <cuda_bf16.h>
#include <cuda.h>
#include <stdint.h>
#include <type_traits>

typedef __nv_bfloat16 bf16;

constexpr int S_LEN = 2048, DM = 1024, NH = 32, DH = 128, NSEG = 64, SEG = 32;
constexpr int HD = NH * DH;
constexpr int OUT_LD = 2048;
constexpr unsigned SENT = 0xFFFFFFFFu;

__device__ bf16 g_tok[4 * NH * 3 * SEG * DH];
__device__ bf16 g_ox[(size_t)S_LEN * HD];
__device__ uint4 g_mbox[4 * 131072];
__device__ unsigned g_xflag[128];
__device__ unsigned g_reg[4];
__device__ unsigned g_cls[256];
__device__ unsigned g_err;
constexpr uint32_t WIN = 2u << 20;
__host__ __device__ constexpr uint32_t page_off(uint32_t idx, uint32_t c) {
    return ((idx & 1) << 13) | ((idx >> 1) << 16) | (((c ^ idx ^ (idx >> 1) ^ (idx >> 2) ^ (idx >> 4)) & 1) << 12);
}
#define STAT(i, c) (void)(c)
#define KT_START(k)
#define KT_END(k)

__device__ __forceinline__ uint32_t smem_u32(const void* p) { return (uint32_t)__cvta_generic_to_shared(p); }
__device__ __forceinline__ void ldsm4(uint32_t& r0, uint32_t& r1, uint32_t& r2, uint32_t& r3, uint32_t a) {
    asm volatile("ldmatrix.sync.aligned.m8n8.x4.shared.b16 {%0,%1,%2,%3}, [%4];" : "=r"(r0), "=r"(r1), "=r"(r2), "=r"(r3) : "r"(a) : "memory");
}
__device__ __forceinline__ void ldsm4t(uint32_t& r0, uint32_t& r1, uint32_t& r2, uint32_t& r3, uint32_t a) {
    asm volatile("ldmatrix.sync.aligned.m8n8.x4.trans.shared.b16 {%0,%1,%2,%3}, [%4];" : "=r"(r0), "=r"(r1), "=r"(r2), "=r"(r3) : "r"(a) : "memory");
}
__device__ __forceinline__ void ldsm2(uint32_t& r0, uint32_t& r1, uint32_t a) {
    asm volatile("ldmatrix.sync.aligned.m8n8.x2.shared.b16 {%0,%1}, [%2];" : "=r"(r0), "=r"(r1) : "r"(a) : "memory");
}
__device__ __forceinline__ void stg128(void* p, uint4 v) {
    asm volatile("st.global.v4.u32 [%0], {%1,%2,%3,%4};" ::"l"(p), "r"(v.x), "r"(v.y), "r"(v.z), "r"(v.w) : "memory");
}
__device__ __forceinline__ void stsm4(uint32_t a, uint32_t r0, uint32_t r1, uint32_t r2, uint32_t r3) {
    asm volatile("stmatrix.sync.aligned.m8n8.x4.shared.b16 [%0], {%1,%2,%3,%4};" ::"r"(a), "r"(r0), "r"(r1), "r"(r2), "r"(r3) : "memory");
}
__device__ __forceinline__ void mma16816(float (&d)[4], uint32_t a0, uint32_t a1, uint32_t a2, uint32_t a3, uint32_t b0, uint32_t b1) {
    asm("mma.sync.aligned.m16n8k16.row.col.f32.bf16.bf16.f32 {%0,%1,%2,%3},{%4,%5,%6,%7},{%8,%9},{%0,%1,%2,%3};"
                 : "+f"(d[0]), "+f"(d[1]), "+f"(d[2]), "+f"(d[3])
                 : "r"(a0), "r"(a1), "r"(a2), "r"(a3), "r"(b0), "r"(b1));
}
__device__ __forceinline__ void mma1688(float (&d)[4], uint32_t a0, uint32_t a1, uint32_t b0) {
    asm("mma.sync.aligned.m16n8k8.row.col.f32.bf16.bf16.f32 {%0,%1,%2,%3},{%4,%5},{%6},{%0,%1,%2,%3};"
        : "+f"(d[0]), "+f"(d[1]), "+f"(d[2]), "+f"(d[3]) : "r"(a0), "r"(a1), "r"(b0));
}
__device__ __forceinline__ uint32_t movmat(uint32_t a) {
    uint32_t d;
    asm volatile("movmatrix.sync.aligned.m8n8.trans.b16 %0, %1;" : "=r"(d) : "r"(a));
    return d;
}
__device__ __forceinline__ uint32_t pack_bf16(float lo, float hi) {
    uint32_t r;
    asm("cvt.rn.bf16x2.f32 %0, %1, %2;" : "=r"(r) : "f"(hi), "f"(lo));
    return r;
}
__device__ __forceinline__ float bf16_round(float x) { return __bfloat162float(__float2bfloat16_rn(x)); }
__device__ __forceinline__ float bf_lo(uint32_t w) { return __uint_as_float(w << 16); }
__device__ __forceinline__ float bf_hi(uint32_t w) { return __uint_as_float(w & 0xFFFF0000u); }
__device__ __forceinline__ void bar_sync(int id, int n) { asm volatile("bar.sync %0, %1;" ::"r"(id), "r"(n) : "memory"); }
__device__ __forceinline__ void bar_sync_keep(int id, int n, uint32_t a, uint32_t b) {
    asm volatile("bar.sync %0, %1; // %2 %3" ::"r"(id), "r"(n), "r"(a), "r"(b) : "memory");
}
__device__ __forceinline__ bool bar_red_or(int id, int n, bool p) {
    uint32_t r;
    asm volatile("{.reg .pred p, q; setp.ne.u32 p, %3, 0; bar.red.or.pred q, %1, %2, p; selp.u32 %0, 1, 0, q;}" : "=r"(r) : "r"(id), "r"(n), "r"((uint32_t)p) : "memory");
    return r != 0;
}
__device__ __forceinline__ void bar_arrive(int id, int n) { asm volatile("bar.arrive %0, %1;" ::"r"(id), "r"(n) : "memory"); }
__device__ __forceinline__ void cp_async16(uint32_t dst, const void* src) {
    asm volatile("cp.async.cg.shared.global [%0], [%1], 16;" ::"r"(dst), "l"(src) : "memory");
}
__device__ __forceinline__ void cp_commit() { asm volatile("cp.async.commit_group;" ::: "memory"); }
template <int N> __device__ __forceinline__ void cp_wait() { asm volatile("cp.async.wait_group %0;" ::"n"(N) : "memory"); }
__device__ __forceinline__ uint4 ld_relaxed_v4(const void* p) {
    uint4 v;
    asm volatile("ld.relaxed.gpu.global.v4.u32 {%0,%1,%2,%3}, [%4];" : "=r"(v.x), "=r"(v.y), "=r"(v.z), "=r"(v.w) : "l"(p) : "memory");
    return v;
}
__device__ __forceinline__ void st_relaxed_u32(void* p, uint32_t v) { asm volatile("st.relaxed.gpu.global.u32 [%0], %1;" ::"l"(p), "r"(v) : "memory"); }
__device__ __forceinline__ void st_relaxed_v2(void* p, uint32_t a, uint32_t b) {
    asm volatile("st.relaxed.gpu.global.v2.u32 [%0], {%1,%2};" ::"l"(p), "r"(a), "r"(b) : "memory");
}
__device__ __forceinline__ void sts128(uint32_t a, uint4 v) {
    asm volatile("st.shared.v4.u32 [%0], {%1,%2,%3,%4};" ::"r"(a), "r"(v.x), "r"(v.y), "r"(v.z), "r"(v.w) : "memory");
}
__device__ __forceinline__ uint4 lds128(uint32_t a) {
    uint4 v;
    asm volatile("ld.shared.v4.u32 {%0,%1,%2,%3}, [%4];" : "=r"(v.x), "=r"(v.y), "=r"(v.z), "=r"(v.w) : "r"(a) : "memory");
    return v;
}
__device__ __forceinline__ void sts32(uint32_t a, uint32_t v) { asm volatile("st.shared.u32 [%0], %1;" ::"r"(a), "r"(v) : "memory"); }
__device__ __forceinline__ uint32_t lds32(uint32_t a) {
    uint32_t v;
    asm volatile("ld.shared.u32 %0, [%1];" : "=r"(v) : "r"(a) : "memory");
    return v;
}
__device__ __forceinline__ void mbar_init(uint32_t a, uint32_t c) { asm volatile("mbarrier.init.shared::cta.b64 [%0], %1;" ::"r"(a), "r"(c) : "memory"); }
__device__ __forceinline__ void mbar_expect_tx(uint32_t a, uint32_t bytes) {
    asm volatile("mbarrier.arrive.expect_tx.shared::cta.b64 _, [%0], %1;" ::"r"(a), "r"(bytes) : "memory");
}
__device__ __forceinline__ void mbar_arrive(uint32_t a) { asm volatile("mbarrier.arrive.shared::cta.b64 _, [%0];" ::"r"(a) : "memory"); }
__device__ __forceinline__ void mbar_wait(uint32_t a, uint32_t parity) {
    asm volatile("{.reg .pred p; .reg .u32 c;\n"
                 "mov.u32 c, 0;\n"
                 "MBW_LOOP:\n"
                 "add.u32 c, c, 1;\n"
                 "setp.gt.u32 p, c, 0x10000;\n"
                 "@!p mbarrier.try_wait.parity.shared::cta.b64 p, [%0], %1;\n"
                 "@!p bra.uni MBW_LOOP;}" ::"r"(a), "r"(parity) : "memory");
}
__device__ __forceinline__ void mbar_wait_w(uint32_t a, uint32_t parity) {
    asm volatile("{.reg .pred p; .reg .u32 c;\n"
                 "mov.u32 c, 0;\n"
                 "MBW_LOOP:\n"
                 "add.u32 c, c, 1;\n"
                 "setp.gt.u32 p, c, 0x10000;\n"
                 "@!p mbarrier.try_wait.parity.shared::cta.b64 p, [%0], %1;\n"
                 "vote.sync.all.pred p, p, 0xFFFFFFFF;\n"
                 "@!p bra.uni MBW_LOOP;}" ::"r"(a), "r"(parity) : "memory");
}
__device__ __forceinline__ void mbar_expect_tx_if0(uint32_t sel, uint32_t a, uint32_t bytes) {
    asm volatile("{.reg .pred p; setp.eq.u32 p, %2, 0; @p mbarrier.arrive.expect_tx.shared::cta.b64 _, [%0], %1;}" ::"r"(a), "r"(bytes), "r"(sel) : "memory");
}
__device__ __forceinline__ void mbar_arrive_if0(uint32_t sel, uint32_t a) {
    asm volatile("{.reg .pred p; setp.eq.u32 p, %1, 0; @p mbarrier.arrive.shared::cta.b64 _, [%0];}" ::"r"(a), "r"(sel) : "memory");
}
__device__ __forceinline__ void bulk_load(uint32_t dst, const void* src, uint32_t bytes, uint32_t bar) {
    asm volatile("cp.async.bulk.shared::cluster.global.mbarrier::complete_tx::bytes [%0], [%1], %2, [%3];" ::"r"(dst), "l"(src), "r"(bytes), "r"(bar) : "memory");
}
__device__ __forceinline__ void tma_load_2d(uint32_t dst, const CUtensorMap* map, int c0, int c1, uint32_t bar) {
    asm volatile("cp.async.bulk.tensor.2d.shared::cluster.global.mbarrier::complete_tx::bytes [%0], [%1, {%3, %4}], [%2];"
                 ::"r"(dst), "l"(map), "r"(bar), "r"(c0), "r"(c1) : "memory");
}
__device__ __forceinline__ void tma_store_2d(const CUtensorMap* map, uint32_t src, int c0, int c1) {
    asm volatile("cp.async.bulk.tensor.2d.global.shared::cta.bulk_group [%0, {%2, %3}], [%1];" ::"l"(map), "r"(src), "r"(c0), "r"(c1) : "memory");
}
__device__ __forceinline__ char* make_ptr(uint32_t lo, uint32_t hi) {
    uint64_t p;
    asm("mov.b64 %0, {%1, %2};" : "=l"(p) : "r"(lo), "r"(hi));
    return reinterpret_cast<char*>(p);
}
__device__ __forceinline__ uint64_t make_desc(uint32_t saddr, uint32_t lbo, uint32_t sbo) {
    return (uint64_t)((saddr & 0x3FFFF) >> 4) | ((uint64_t)((lbo >> 4) & 0x3FFF) << 16) | ((uint64_t)((sbo >> 4) & 0x3FFF) << 32) | ((uint64_t)1 << 62);
}
__device__ __forceinline__ void wg_fence() { asm volatile("wgmma.fence.sync.aligned;" ::: "memory"); }
__device__ __forceinline__ void wg_commit() { asm volatile("wgmma.commit_group.sync.aligned;" ::: "memory"); }
template <int N> __device__ __forceinline__ void wg_wait() { asm volatile("wgmma.wait_group.sync.aligned %0;" ::"n"(N) : "memory"); }

#define R4(b) "+f"(d[b + 0]), "+f"(d[b + 1]), "+f"(d[b + 2]), "+f"(d[b + 3])
#define R16(b) R4(b), R4(b + 4), R4(b + 8), R4(b + 12)
__device__ __forceinline__ void wgmma_n128(float (&d)[64], uint64_t da, uint64_t db) {
    asm volatile(
        "wgmma.mma_async.sync.aligned.m64n128k16.f32.bf16.bf16 "
        "{%0,%1,%2,%3,%4,%5,%6,%7,%8,%9,%10,%11,%12,%13,%14,%15,%16,%17,%18,%19,%20,%21,%22,%23,%24,%25,%26,%27,%28,%29,%30,%31,"
        "%32,%33,%34,%35,%36,%37,%38,%39,%40,%41,%42,%43,%44,%45,%46,%47,%48,%49,%50,%51,%52,%53,%54,%55,%56,%57,%58,%59,%60,%61,%62,%63},"
        "%64,%65,1,1,1,0,1;"
        : R16(0), R16(16), R16(32), R16(48)
        : "l"(da), "l"(db));
}
__device__ __forceinline__ void wgmma_n256(float (&d)[128], uint64_t da, uint64_t db) {
    asm volatile(
        "wgmma.mma_async.sync.aligned.m64n256k16.f32.bf16.bf16 "
        "{%0,%1,%2,%3,%4,%5,%6,%7,%8,%9,%10,%11,%12,%13,%14,%15,%16,%17,%18,%19,%20,%21,%22,%23,%24,%25,%26,%27,%28,%29,%30,%31,"
        "%32,%33,%34,%35,%36,%37,%38,%39,%40,%41,%42,%43,%44,%45,%46,%47,%48,%49,%50,%51,%52,%53,%54,%55,%56,%57,%58,%59,%60,%61,%62,%63,"
        "%64,%65,%66,%67,%68,%69,%70,%71,%72,%73,%74,%75,%76,%77,%78,%79,%80,%81,%82,%83,%84,%85,%86,%87,%88,%89,%90,%91,%92,%93,%94,%95,"
        "%96,%97,%98,%99,%100,%101,%102,%103,%104,%105,%106,%107,%108,%109,%110,%111,%112,%113,%114,%115,%116,%117,%118,%119,%120,%121,%122,%123,%124,%125,%126,%127},"
        "%128,%129,1,1,1,0,1;"
        : R16(0), R16(16), R16(32), R16(48), R16(64), R16(80), R16(96), R16(112)
        : "l"(da), "l"(db));
}
template <int BN> struct WgAcc;
template <> struct WgAcc<128> { static __device__ __forceinline__ void mma(float (&d)[64], uint64_t a, uint64_t b) { wgmma_n128(d, a, b); } };
template <> struct WgAcc<256> { static __device__ __forceinline__ void mma(float (&d)[128], uint64_t a, uint64_t b) { wgmma_n256(d, a, b); } };

__device__ __forceinline__ void wgmma_rs32(float (&d)[16], const uint32_t (&a)[4], uint64_t db, bool acc) {
    asm volatile(
        "{.reg .pred p; setp.ne.b32 p, %21, 0;\n"
        "wgmma.mma_async.sync.aligned.m64n32k16.f32.bf16.bf16 {%0,%1,%2,%3,%4,%5,%6,%7,%8,%9,%10,%11,%12,%13,%14,%15}, {%16,%17,%18,%19}, %20, p, 1, 1, 0;}"
        : R16(0) : "r"(a[0]), "r"(a[1]), "r"(a[2]), "r"(a[3]), "l"(db), "n"(1) );
}
__device__ __forceinline__ void wgmma_rs32_first(float (&d)[16], const uint32_t (&a)[4], uint64_t db) {
    asm volatile(
        "{.reg .pred p; setp.ne.b32 p, %21, 0;\n"
        "wgmma.mma_async.sync.aligned.m64n32k16.f32.bf16.bf16 {%0,%1,%2,%3,%4,%5,%6,%7,%8,%9,%10,%11,%12,%13,%14,%15}, {%16,%17,%18,%19}, %20, p, 1, 1, 0;}"
        : R16(0) : "r"(a[0]), "r"(a[1]), "r"(a[2]), "r"(a[3]), "l"(db), "n"(0) );
}
__device__ __forceinline__ void wgmma_ss32(float (&d)[16], uint64_t da, uint64_t db) {
    asm volatile(
        "wgmma.mma_async.sync.aligned.m64n32k16.f32.bf16.bf16 {%0,%1,%2,%3,%4,%5,%6,%7,%8,%9,%10,%11,%12,%13,%14,%15}, %16, %17, 1, 1, 1, 1, 0;"
        : R16(0) : "l"(da), "l"(db));
}
template <int OFF, int ACC> __device__ __forceinline__ void wgmma_rs32u(float (&d)[16], const uint32_t (&a)[4], uint32_t lo) {
    asm volatile(
        "{.reg .pred p; .reg .b32 l; .reg .b64 e; setp.ne.b32 p, %22, 0; add.u32 l, %20, %21; mov.b64 e, {l, 0x40000040};\n"
        "wgmma.mma_async.sync.aligned.m64n32k16.f32.bf16.bf16 {%0,%1,%2,%3,%4,%5,%6,%7,%8,%9,%10,%11,%12,%13,%14,%15}, {%16,%17,%18,%19}, e, p, 1, 1, 0;}"
        : R16(0) : "r"(a[0]), "r"(a[1]), "r"(a[2]), "r"(a[3]), "r"(lo), "n"(OFF), "n"(ACC));
}
template <int OFF> __device__ __forceinline__ void wgmma_ss32u(float (&d)[16], uint64_t da, uint32_t lo) {
    asm volatile(
        "{.reg .b32 l; .reg .b64 e; add.u32 l, %17, %18; mov.b64 e, {l, 0x40000040};\n"
        "wgmma.mma_async.sync.aligned.m64n32k16.f32.bf16.bf16 {%0,%1,%2,%3,%4,%5,%6,%7,%8,%9,%10,%11,%12,%13,%14,%15}, %16, e, 1, 1, 1, 1, 0;}"
        : R16(0) : "l"(da), "r"(lo), "n"(OFF));
}
template <int K0, int K1, class F> __device__ __forceinline__ void static_for(F f) {
    if constexpr (K0 < K1) { f(std::integral_constant<int, K0>()); static_for<K0 + 1, K1>(f); }
}
__device__ __forceinline__ void st_async4(uint32_t a, float x, float y, float z, float w, uint32_t bar) {
    asm volatile("st.async.weak.shared::cluster.mbarrier::complete_tx::bytes.v4.f32 [%0], {%1,%2,%3,%4}, [%5];" ::"r"(a), "f"(x), "f"(y), "f"(z), "f"(w), "r"(bar) : "memory");
}
__device__ __forceinline__ void st_async2(uint32_t a, float x, float y, uint32_t bar) {
    asm volatile("st.async.weak.shared::cluster.mbarrier::complete_tx::bytes.v2.f32 [%0], {%1,%2}, [%3];" ::"r"(a), "f"(x), "f"(y), "r"(bar) : "memory");
}
__device__ __forceinline__ void st_async1(uint32_t a, uint32_t x, uint32_t bar) {
    asm volatile("st.async.weak.shared::cluster.mbarrier::complete_tx::bytes.b32 [%0], %1, [%2];" ::"r"(a), "r"(x), "r"(bar) : "memory");
}
__device__ __forceinline__ void stsm4t(uint32_t a, uint32_t r0, uint32_t r1, uint32_t r2, uint32_t r3) {
    asm volatile("stmatrix.sync.aligned.m8n8.x4.trans.shared.b16 [%0], {%1,%2,%3,%4};" ::"r"(a), "r"(r0), "r"(r1), "r"(r2), "r"(r3) : "memory");
}
__device__ __forceinline__ void ldsm4t(uint32_t (&r)[4], uint32_t a) { ldsm4t(r[0], r[1], r[2], r[3], a); }
__device__ __forceinline__ void ldsm4(uint32_t (&r)[4], uint32_t a) { ldsm4(r[0], r[1], r[2], r[3], a); }
__device__ __forceinline__ void mma16816(float (&d)[4], const uint32_t (&a)[4], uint32_t b0, uint32_t b1) { mma16816(d, a[0], a[1], a[2], a[3], b0, b1); }
__device__ __forceinline__ void sched_fence(uint32_t v) {
    asm volatile("{.reg .pred p; setp.ne.u32 p, %0, 0xFFFFFFFF; vote.sync.all.pred p, p, 0xFFFFFFFF; @p bra.uni SF_OK; exit; SF_OK:}" ::"r"(v) : "memory");
}
__device__ __forceinline__ void mma16816v(float (&d)[4], const uint32_t (&a)[4], uint32_t b0, uint32_t b1) {
    asm volatile("mma.sync.aligned.m16n8k16.row.col.f32.bf16.bf16.f32 {%0,%1,%2,%3},{%4,%5,%6,%7},{%8,%9},{%0,%1,%2,%3};"
                 : "+f"(d[0]), "+f"(d[1]), "+f"(d[2]), "+f"(d[3]) : "r"(a[0]), "r"(a[1]), "r"(a[2]), "r"(a[3]), "r"(b0), "r"(b1));
}
__device__ __forceinline__ uint32_t uniform(uint32_t v) { return __reduce_max_sync(~0u, v); }

template <int BN, int STAGES> struct GemmCfg {
    static constexpr int A_BYTES = 128 * 64 * 2;
    static constexpr int B_BYTES = BN * 64 * 2;
    static constexpr int STAGE_BYTES = A_BYTES + B_BYTES;
    static constexpr int EPI_BYTES = 128 * BN * 2;
    static constexpr int SMEM = STAGES * STAGE_BYTES + EPI_BYTES + 1024 + 256;
};

template <int BN, int STAGES>
__global__ void __cluster_dims__(2, 1, 1) __launch_bounds__(288, 1)
gemm_kernel(const __grid_constant__ CUtensorMap mapA, const __grid_constant__ CUtensorMap mapB0, const __grid_constant__ CUtensorMap mapB1,
            const __grid_constant__ CUtensorMap mapB2, const __grid_constant__ CUtensorMap mapC, int tiles_m, int tiles_n, int kblocks) {
    using Cfg = GemmCfg<BN, STAGES>;
    KT_START(BN == 256 ? 0 : 3);
    extern __shared__ uint8_t smem_raw[];
    const uint32_t sbase = (smem_u32(smem_raw) + 1023) & ~1023u;
    const uint32_t epi = sbase + STAGES * Cfg::STAGE_BYTES;
    const uint32_t bars = epi + Cfg::EPI_BYTES;
    const int warp = threadIdx.x >> 5, lane = threadIdx.x & 31;
    const uint32_t rank = blockIdx.x & 1;
    if (threadIdx.x == 0) {
        for (int i = 0; i < STAGES; i++) { mbar_init(bars + 8 * i, 1); mbar_init(bars + 8 * (STAGES + i), 16); }
        asm volatile("fence.mbarrier_init.release.cluster;" ::: "memory");
    }
    __syncthreads();
    asm volatile("barrier.cluster.arrive.release.aligned; barrier.cluster.wait.acquire.aligned;" ::: "memory");
    const int npairs = (tiles_m >> 1) * tiles_n, ncl = gridDim.x >> 1;
    if (warp == 8) {
        if (lane == 0) {
            int st = 0; uint32_t ph = 1;
            for (int pr = blockIdx.x >> 1; pr < npairs; pr += ncl) {
                const int tm = 2 * (pr % (tiles_m >> 1)) + rank, tn = pr / (tiles_m >> 1);
                const int n0 = tn * BN;
                const CUtensorMap* mb = (n0 < 4096) ? &mapB0 : (n0 < 8192 ? &mapB1 : &mapB2);
                const int nb = n0 & 4095;
                for (int kb = 0; kb < kblocks; kb++) {
                    mbar_wait(bars + 8 * (STAGES + st), ph);
                    const uint32_t full = bars + 8 * st;
                    mbar_expect_tx(full, Cfg::STAGE_BYTES);
                    const uint32_t sa = sbase + st * Cfg::STAGE_BYTES;
                    tma_load_2d(sa, &mapA, kb * 64, tm * 128, full);
#pragma unroll
                    for (int i = 0; i < BN / 128; i++) {
                        const int bx = rank * (BN / 128) + i;
                        asm volatile("cp.async.bulk.tensor.2d.shared::cluster.global.mbarrier::complete_tx::bytes.multicast::cluster [%0], [%1, {%3, %4}], [%2], %5;"
                                     ::"r"(sa + Cfg::A_BYTES + bx * 8192), "l"(mb), "r"(full), "r"(nb + bx * 64), "r"(kb * 64), "h"((uint16_t)3) : "memory");
                    }
                    if (++st == STAGES) { st = 0; ph ^= 1; }
                }
            }
        }
    } else {
        const int wg = warp >> 2;
        uint32_t peer_empty;
        asm volatile("mapa.shared::cluster.u32 %0, %1, %2;" : "=r"(peer_empty) : "r"(bars + 8 * STAGES), "r"(rank ^ 1));
        auto release = [&](int stg) {
            if (lane == 0) {
                mbar_arrive(bars + 8 * (STAGES + stg));
                asm volatile("mbarrier.arrive.shared::cluster.b64 _, [%0];" ::"r"(peer_empty + 8 * stg) : "memory");
            }
        };
        const uint32_t ew = epi + wg * (64 * BN * 2);
        int st = 0; uint32_t ph = 0;
        for (int pr = blockIdx.x >> 1; pr < npairs; pr += ncl) {
            const int tm = 2 * (pr % (tiles_m >> 1)) + rank, tn = pr / (tiles_m >> 1);
            float d[BN / 2];
#pragma unroll
            for (int i = 0; i < BN / 2; i++) d[i] = 0.f;
            int prev = -1;
            for (int kb = 0; kb < kblocks; kb++) {
                mbar_wait(bars + 8 * st, ph);
                const uint32_t sa = sbase + st * Cfg::STAGE_BYTES;
                const uint64_t da = make_desc(sa + wg * 8192, 16, 1024);
                const uint64_t db = make_desc(sa + Cfg::A_BYTES, 8192, 1024);
                wg_fence();
#pragma unroll
                for (int k = 0; k < 4; k++) WgAcc<BN>::mma(d, da + k * 2, db + k * 128);
                wg_commit();
                if (prev >= 0) { wg_wait<1>(); release(prev); }
                prev = st;
                if (++st == STAGES) { st = 0; ph ^= 1; }
            }
            wg_wait<0>();
            release(prev);
            if ((warp & 3) == 0 && lane == 0) asm volatile("cp.async.bulk.wait_group.read 0;" ::: "memory");
            bar_sync(1 + wg, 128);
            const int r = (warp & 3) * 16 + (lane & 7) + ((lane >> 3) & 1) * 8;
#pragma unroll
            for (int c = 0; c < BN / 64; c++)
#pragma unroll
                for (int i = 0; i < 4; i++) {
                    const int b = (c * 8 + i * 2) * 4;
                    stsm4(ew + c * 8192 + r * 128 + (((i * 2 + (lane >> 4)) ^ (r & 7)) * 16), pack_bf16(d[b], d[b + 1]), pack_bf16(d[b + 2], d[b + 3]),
                          pack_bf16(d[b + 4], d[b + 5]), pack_bf16(d[b + 6], d[b + 7]));
                }
            asm volatile("fence.proxy.async.shared::cta;" ::: "memory");
            bar_sync(1 + wg, 128);
            if ((warp & 3) == 0 && lane == 0) {
#pragma unroll
                for (int c = 0; c < BN / 64; c++)
                    asm volatile("cp.async.bulk.tensor.2d.global.shared::cta.bulk_group [%0, {%2, %3}], [%1];"
                                 ::"l"(&mapC), "r"(ew + c * 8192), "r"(tn * BN + c * 64), "r"(tm * 128 + wg * 64) : "memory");
                asm volatile("cp.async.bulk.commit_group;" ::: "memory");
            }
        }
        if ((warp & 3) == 0 && lane == 0) asm volatile("cp.async.bulk.wait_group 0;" ::: "memory");
    }
    __syncwarp();
    KT_END(BN == 256 ? 0 : 3);
    asm volatile("barrier.cluster.arrive.relaxed; barrier.cluster.wait;" ::: "memory");
}

#define WO_RF1 6
constexpr int SM_KV = 0, KV_BYTES = 18432;
constexpr int SM_XT = 2 * KV_BYTES;
constexpr int SM_STG = SM_XT + 65536;
constexpr int SM_Z = SM_STG + 6144;
constexpr int SM_RT = SM_Z + 8192;
constexpr int SM_QKV = SM_RT + 12288;
constexpr int SM_R1 = SM_QKV + 6144;
constexpr int SM_R2 = SM_R1 + 2048;
constexpr int SM_R3 = SM_R2 + 1024;
constexpr int SM_O = SM_R3 + 2048;
constexpr int SM_S = SM_O + 2048;
constexpr int SM_INV = SM_S + 1536;
constexpr int SM_TO = SM_R3;
constexpr int SM_WORK_END = SM_S + 2048;
constexpr int STG_QK = 0, STG_V = 98304;
constexpr int SM_WO1 = SM_WORK_END - WO_RF1 * 2048;
constexpr int STG_WO = SM_WO1 - 16384;
constexpr int SM_WQK = (SM_WO1 + 16384 > STG_V + 49152) ? SM_WO1 + 16384 : STG_V + 49152;
constexpr int SM_WV = SM_WQK + 32768;
constexpr int SM_WO2 = SM_WV + 16384;
constexpr int SM_BARS = SM_WO2 + 32768;
enum { MB_W0 = SM_BARS, MB_W1 = SM_BARS + 8, MB_W2 = SM_BARS + 16, MB_W3 = SM_BARS + 24, MB_XT = SM_BARS + 32  , MB_KV = SM_BARS + 48  ,
       MB_R3 = SM_BARS + 64, MB_R1 = SM_BARS + 72, MB_R2 = SM_BARS + 80, MB_RT0 = SM_BARS + 88, MB_RT1 = SM_BARS + 96, MB_FREE = SM_BARS + 104,
       MB_P = SM_BARS + 112, MB_V = SM_BARS + 120, MB_STG = SM_BARS + 128, SM_ROLE = SM_BARS + 136 };
constexpr int CHAIN_SMEM = SM_ROLE + 8;
static_assert(SM_WORK_END % 1024 == 0 && STG_WO >= STG_V, "work area");
static_assert(CHAIN_SMEM <= 232448 && WO_RF1 >= 6, "smem");

#define DLY_X 300
#define DLY_V 0
#define DLY_Y 150
#define DLY_Z 150
#define Q3_AT 9
#define NA 7
#define NP2 6
#define P2_FENCE 0
#define SPLIT 12
#define XFLIP 0
#define YFLIP 0
#define ZFLIP 1
#define REG_A 240
#define REG_B 216
#define REG_C (3 * 168 - REG_A - REG_B)

enum { BAR_Y, BAR_MEM, BAR_PUB, BAR_QK, BAR_S, BAR_O, BAR_SENT, BAR_COMM, BAR_PUBV, BAR_PV, BAR_PDONE, BAR_VP, BAR_ZP, BAR_PRO, BAR_O2, BAR_SV,
       BAR_V = BAR_PV, BAR_SENTC = BAR_PDONE, BAR_Q3 = BAR_PRO, BAR_INV = BAR_PRO };

__device__ __forceinline__ uint32_t umax4(const uint4& v) { return max(max(v.x, v.y), max(v.z, v.w)); }
__device__ __forceinline__ unsigned gtime() { unsigned t; asm volatile("mov.u32 %0, %%globaltimer_lo;" : "=r"(t)::"memory"); return t; }
__device__ __forceinline__ unsigned clock32() { unsigned t; asm volatile("mov.u32 %0, %%clock;" : "=r"(t)::"memory"); return t; }
__device__ __forceinline__ void spin_cycles(int d) {
    if (d > 0) { const unsigned c0 = clock32(); while (clock32() - c0 < (unsigned)d) {} }
}
__device__ __forceinline__ float ex2_approx(float x) { float y; asm("ex2.approx.ftz.f32 %0, %1;" : "=f"(y) : "f"(x)); return y; }
__device__ __forceinline__ float rcp_approx(float x) { float y; asm("rcp.approx.ftz.f32 %0, %1;" : "=f"(y) : "f"(x)); return y; }
__device__ __forceinline__ void st_sent(const void* p) { asm volatile("st.relaxed.gpu.global.v4.u32 [%0], {%1,%1,%1,%1};" ::"l"(p), "r"(SENT) : "memory"); }
#define POLL_LD(p, a, b, c, d, addr) "@" p " ld.relaxed.gpu.global.v4.u32 {" a "," b "," c "," d "}, [" addr "];\n"
#define POLL_CK(p, a, b, c, d) "max.u32 m, " a "," b "; max.u32 n, " c "," d "; max.u32 m, m, n; setp.eq.u32 " p ", m, 0xFFFFFFFF;\n"
#define POLL_IO(v) "+r"(v.x), "+r"(v.y), "+r"(v.z), "+r"(v.w)
__device__ __forceinline__ void poll_init(uint4& v) { v = make_uint4(SENT, SENT, SENT, SENT); asm volatile("" : POLL_IO(v)); }
__device__ __forceinline__ int poll2(uint4 (&v)[2], const char* a) {
    int c = 0;
    asm volatile("{.reg .pred p0, p1, p; .reg .u32 m, n;\n"
                 "setp.eq.u32 p0, %8, 0; setp.eq.u32 p1, %8, 0;\n"
                 "POLL_LOOP:\n"
                 POLL_LD("p0", "%0", "%1", "%2", "%3", "%9") POLL_LD("p1", "%4", "%5", "%6", "%7", "%9+512")
                 "add.u32 %8, %8, 1;\n"
                 POLL_CK("p0", "%0", "%1", "%2", "%3") POLL_CK("p1", "%4", "%5", "%6", "%7")
                 "or.pred p, p0, p1; setp.lt.and.u32 p, %8, 0x10000, p; vote.sync.any.pred p, p, 0xFFFFFFFF;\n"
                 "@p bra.uni POLL_LOOP;}" : POLL_IO(v[0]), POLL_IO(v[1]), "+r"(c) : "l"(a) : "memory");
    return c;
}
__device__ __forceinline__ int poll4(uint4 (&v)[4], const char* a) {
    int c = 0;
    asm volatile("{.reg .pred p0, p1, p2, p3, p; .reg .u32 m, n;\n"
                 "setp.eq.u32 p0, %16, 0; setp.eq.u32 p1, %16, 0; setp.eq.u32 p2, %16, 0; setp.eq.u32 p3, %16, 0;\n"
                 "POLL_LOOP:\n"
                 POLL_LD("p0", "%0", "%1", "%2", "%3", "%17") POLL_LD("p1", "%4", "%5", "%6", "%7", "%17+2048")
                 POLL_LD("p2", "%8", "%9", "%10", "%11", "%17+4096") POLL_LD("p3", "%12", "%13", "%14", "%15", "%17+6144")
                 "add.u32 %16, %16, 1;\n"
                 POLL_CK("p0", "%0", "%1", "%2", "%3") POLL_CK("p1", "%4", "%5", "%6", "%7") POLL_CK("p2", "%8", "%9", "%10", "%11") POLL_CK("p3", "%12", "%13", "%14", "%15")
                 "or.pred p, p0, p1; or.pred p, p, p2; or.pred p, p, p3; setp.lt.and.u32 p, %16, 0x10000, p; vote.sync.any.pred p, p, 0xFFFFFFFF;\n"
                 "@p bra.uni POLL_LOOP;}" : POLL_IO(v[0]), POLL_IO(v[1]), POLL_IO(v[2]), POLL_IO(v[3]), "+r"(c) : "l"(a) : "memory");
    return c;
}
__device__ __forceinline__ uint32_t max_bf16x2(uint32_t a, uint32_t b) { uint32_t r; asm("max.bf16x2 %0, %1, %2;" : "=r"(r) : "r"(a), "r"(b)); return r; }
template <class F> __device__ __forceinline__ void softmax40(uint32_t (&pw)[6], uint32_t sa, F mid) {
    const float LOG2E = 1.4426950408889634f;
    uint32_t w[5];
    float e[10];
#pragma unroll
    for (int i = 0; i < 5; i++) w[i] = lds32(sa + i * 128);
    uint32_t m = max_bf16x2(max_bf16x2(max_bf16x2(w[0], w[1]), max_bf16x2(w[2], w[3])), w[4]);
    m = max_bf16x2(m, __shfl_xor_sync(~0u, m, 1));
    m = max_bf16x2(m, __shfl_xor_sync(~0u, m, 2));
    const float mb2 = fmaxf(bf_lo(m), bf_hi(m)) * LOG2E;
#pragma unroll
    for (int i = 0; i < 5; i++) {
        e[2 * i] = ex2_approx(fmaf(bf_lo(w[i]), LOG2E, -mb2));
        e[2 * i + 1] = ex2_approx(fmaf(bf_hi(w[i]), LOG2E, -mb2));
    }
    mid();
#pragma unroll
    for (int i = 0; i < 5; i++) pw[i] = pack_bf16(e[2 * i], e[2 * i + 1]);
    const float sum = (((e[0] + e[1]) + (e[2] + e[3])) + ((e[4] + e[5]) + (e[6] + e[7]))) + (e[8] + e[9]);
    const float hi = bf_hi(__float_as_uint(sum));
    pw[5] = pack_bf16(sum - hi, hi);
}
template <bool NORM, class F> __device__ __forceinline__ void pv32(uint32_t (&w)[4], float (&inv)[2], const uint32_t (&va)[2][2][4], const uint32_t (&vm)[4], const uint32_t (&pw)[6], F mid) {
    float o[2][3][4], t[4] = {0.f, 0.f, 0.f, 0.f};
#pragma unroll
    for (int i = 0; i < 3; i++)
#pragma unroll
        for (int m = 0; m < 2; m++) {
            o[m][i][0] = o[m][i][1] = o[m][i][2] = o[m][i][3] = 0.f;
            if (i < 2) mma16816(o[m][i], va[m][i & 1], pw[2 * i], pw[2 * i + 1]);
            else mma1688(o[m][i], vm[2 * m], vm[2 * m + 1], pw[4]);
        }
    mma1688(t, 0x3F803F80u, 0x3F803F80u, pw[5]);
    mid();
    if (NORM) { inv[0] = rcp_approx(t[0]); inv[1] = rcp_approx(t[1]); }
#pragma unroll
    for (int i = 0; i < 4; i++) {
        const float a = (o[i >> 1][0][2 * (i & 1)] + o[i >> 1][1][2 * (i & 1)]) + o[i >> 1][2][2 * (i & 1)];
        const float b = (o[i >> 1][0][2 * (i & 1) + 1] + o[i >> 1][1][2 * (i & 1) + 1]) + o[i >> 1][2][2 * (i & 1) + 1];
        w[i] = NORM ? pack_bf16(a * inv[0], b * inv[1]) : pack_bf16(a, b);
    }
    if (!NORM) { inv[0] = t[0]; inv[1] = t[1]; }
}
__device__ __forceinline__ uint32_t scale_scores(float a, float b) {
    const float scale = 0.08838834764831845f;
    const uint32_t w = pack_bf16(a, b);
    return pack_bf16(bf_lo(w) * scale, bf_hi(w) * scale);
}

__device__ __forceinline__ uint32_t peer_addr(uint32_t a, uint32_t rank) {
    uint32_t r;
    asm("mapa.shared::cluster.u32 %0, %1, %2;" : "=r"(r) : "r"(a), "r"(rank));
    return r;
}

#define TL(i) do {} while (0)
#define TLB(i) do {} while (0)
#define TLC(i) do {} while (0)

__global__ void __cluster_dims__(2, 1, 1) __launch_bounds__(384, 1)
chain_kernel(const __grid_constant__ CUtensorMap mapX, const __grid_constant__ CUtensorMap mapT32, const __grid_constant__ CUtensorMap mapT16,
             const __grid_constant__ CUtensorMap mapTQ, const __grid_constant__ CUtensorMap mapKV,
             const __grid_constant__ CUtensorMap mapWq, const __grid_constant__ CUtensorMap mapWk, const __grid_constant__ CUtensorMap mapWv,
             const __grid_constant__ CUtensorMap mapWo, const bf16* __restrict__ mem0, char* __restrict__ mbox) {
    KT_START(2);
    extern __shared__ __align__(1024) uint8_t smem_chain[];
    constexpr uint32_t SB0 = 1024;
    if (smem_u32(smem_chain) != (SB0 | ((blockIdx.x & 1) << 24))) __trap();
    const int kh = blockIdx.x & 1;
    if (threadIdx.x == 0) {
        const uint32_t sb = smem_u32(smem_chain);
        for (int i = 0; i < 14; i++) mbar_init(sb + SM_BARS + 8 * i, 1);
        mbar_init(sb + MB_P, 4); mbar_init(sb + MB_V, 4); mbar_init(sb + MB_STG, 8);
        asm volatile("fence.mbarrier_init.release.cluster;" ::: "memory");
        if (kh == 0) {
            unsigned smid, ncl = gridDim.x >> 1;
            asm volatile("mov.u32 %0, %%smid;" : "=r"(smid));
            const unsigned c = g_cls[smid] & 1, i = atomicAdd(&g_reg[c], 1u);
            unsigned p = c * 32 + i;
            if (i >= 32) {
                unsigned n0, n1; int guard = 0;
                do {
                    asm volatile("ld.relaxed.gpu.global.u32 %0, [%1];" : "=r"(n0) : "l"(g_reg) : "memory");
                    asm volatile("ld.relaxed.gpu.global.u32 %0, [%1];" : "=r"(n1) : "l"(g_reg + 1) : "memory");
                } while (n0 + n1 < ncl && ++guard < (1 << 20));
                const unsigned k = (c ? n0 : n1) + i - 32;
                p = k < 32 ? (c ^ 1) * 32 + k : 64;
            }
            p |= g_reg[2] << 8;
            uint32_t ra;
            asm volatile("mapa.shared::cluster.u32 %0, %1, 1;" : "=r"(ra) : "r"(sb + SM_ROLE));
            asm volatile("st.shared::cluster.u32 [%0], %1;" ::"r"(ra), "r"(p) : "memory");
            sts32(sb + SM_ROLE, p);
        }
    }
    __syncthreads();
    asm volatile("barrier.cluster.arrive.release.aligned; barrier.cluster.wait.acquire.aligned;" ::: "memory");
    const uint32_t rw = uniform(lds32(smem_u32(smem_chain) + SM_ROLE));
    const int pair = rw & 255, yflip = (rw >> 8) ^ YFLIP;
    if (pair >= 64) return;
    const int h = pair >> 1, nh = pair & 1, j = 2 * nh + kh, role = 2 * pair + kh;
#define WG_ORDER 0x210
    const int warp = uniform(((WG_ORDER >> (4 * (threadIdx.x >> 7))) & 3) * 4 + ((threadIdx.x >> 5) & 3));
    const uint32_t g = warp & 3, sb = SB0 | (kh << 24), rsb = sb ^ (1u << 24), cls = pair >> 5, kflip = ZFLIP ^ kh;
    const uint32_t mlo = (uint32_t)(uintptr_t)mbox, mhi = (uint32_t)((uintptr_t)mbox >> 32);
    auto lane16 = [&]() {
        uint32_t t;
        asm volatile("mov.u32 %0, %%laneid; shl.b32 %0, %0, 4;" : "=r"(t));
        return t;
    };
#define PHASE(k) uint32_t L; asm volatile("{.reg .u32 t; shr.u32 t, %1, %3; add.u32 %0, %2, t;}" : "=r"(L) : "r"(it), "r"(l16), "n"(8 + (k)))
#define ROWPAT() ((((L << 3) & 0x380) | ((L << 2) & 0x400)) | ((L ^ (L >> 3)) & 0x10) | (L & 0x60))
#define FRAG() (ROWPAT() ^ (g << 5))
#define QFRAG() ((((L >> 1) & 0x80) | (L & 0x70)) + ((L & 0x80) ? SM_KV + 16384 + kvo : SM_QKV))
#define VFRAG() (ROWPAT() ^ ((g & 1) << 6))
#define VBASE() (sb + SM_KV + 8192 + (g >> 1) * 4096 + kvo)
#define XTLO() ((uint32_t)make_desc(SB0 + SM_XT, 16, 1024) + (ui & 1) * 2048)
    if (warp >= 8) {
        asm volatile("setmaxnreg.dec.sync.aligned.u32 %0;" ::"n"(REG_C));
        const uint32_t l16 = lane16(), lane = l16 >> 4;
        const int ct = g * 32 + lane;
        if (warp == 8) {
            const CUtensorMap* ws = kh ? &mapWq : &mapWk;
            const CUtensorMap* wn = kh ? &mapWk : &mapWq;
            const int col = h * DH + 64 * nh, row = 512 * kh;
            if (lane == 0) { mbar_expect_tx(sb + MB_W0, 49152); mbar_expect_tx(sb + MB_W1, 98304); mbar_expect_tx(sb + MB_W2, 81920); mbar_expect_tx(sb + MB_W3, 32768); }
            __syncwarp();
            if (lane < 24) {
                const int k = lane ^ (16 * kflip);
                tma_load_2d(sb + STG_V + lane * 2048, &mapWv, col, row + 16 * k, sb + MB_W0);
                tma_load_2d(sb + STG_QK + lane * 2048, ws, col, row + 16 * k, sb + MB_W1);
                tma_load_2d(sb + STG_QK + (24 + lane) * 2048, wn, col, row + 16 * k, sb + MB_W1);
            }
            if (lane < 8) {
                const int k = (24 + lane) ^ (16 * kflip);
                tma_load_2d(sb + SM_WQK + lane * 4096, ws, col, row + 16 * k, sb + MB_W2);
                tma_load_2d(sb + SM_WQK + lane * 4096 + 2048, wn, col, row + 16 * k, sb + MB_W2);
                tma_load_2d(sb + SM_WV + lane * 2048, &mapWv, col, row + 16 * k, sb + MB_W2);
            }
            if (lane < 2) tma_load_2d(sb + SM_WO2 + lane * 16384, &mapWo, 256 * j + 128 + 64 * lane, h * DH, sb + MB_W2);
            __syncwarp();
            bar_sync(BAR_PV, 160);
            if (lane < 2) tma_load_2d(sb + STG_WO + lane * 16384, &mapWo, 256 * j + 64 * lane, h * DH, sb + MB_W3);
            __syncwarp();
        }
        bar_sync(BAR_PDONE, 384);
        for (int c = ct; c < 512; c += 128) {
            uint32_t w[4];
#pragma unroll
            for (int r = 0; r < 4; r++) {
                const uint32_t lo = reinterpret_cast<const uint16_t*>(mem0)[(2 * r) * DM + 512 * kh + c], hi = reinterpret_cast<const uint16_t*>(mem0)[(2 * r + 1) * DM + 512 * kh + c];
                w[r] = lo | (hi << 16);
            }
            sts128(sb + SM_Z + (c ^ (256 * kflip)) * 16, make_uint4(w[0], w[1], w[2], w[3]));
        }
        auto load_xt = [&](int seg, int half) {
            const uint32_t bar = sb + MB_XT + (seg & 1) * 8;
            if (half == 0) mbar_expect_tx(bar, 32768);
            asm volatile("cp.async.bulk.tensor.3d.shared::cluster.global.mbarrier::complete_tx::bytes [%0], [%1, {%3, %4, %5}], [%2];"
                         ::"r"(sb + SM_XT + (seg & 1) * 32768 + half * 16384), "l"(&mapX), "r"(bar), "r"(0), "r"(seg * SEG), "r"(8 * kh + 4 * (half ^ kflip)) : "memory");
        };
        auto tok_start = [&](int s) {
            if (lane == 0) {
                if (s > -3 && s + 2 < NSEG) {
                    mbar_wait(sb + MB_STG, (s + 2) & 1);
                    asm volatile("fence.proxy.async.shared::cta;" ::: "memory");
                    const int r = ((s + 2) & 3) * NH + h;
                    tma_store_2d(kh ? &mapT32 : &mapTQ, sb + SM_STG, kh ? 64 * nh : 256 * nh, kh ? r * 96 + 32 : r * 12);
                    tma_store_2d(&mapT16, sb + SM_STG + 4096, 64 * nh, r * 96 + 64 + 16 * kh);
                    asm volatile("cp.async.bulk.commit_group;" ::: "memory");
                }
                if (s + 4 < NSEG) load_xt(s + 4, 0);
                asm volatile("cp.async.bulk.wait_group.read 0;" ::: "memory");
                if (s < 0) {
                    asm volatile("mbarrier.arrive.shared::cluster.b64 _, [%0];" ::"r"(rsb + MB_FREE) : "memory");
                    mbar_wait(sb + MB_FREE, (s + 3) & 1);
                }
            }
            __syncwarp();
        };
        auto tok_mid = [&](int s) {
            if (lane == 0) {
                if (s + 4 < NSEG) load_xt(s + 4, 1);
                if (s > -3 && s + 2 < NSEG) {
                    asm volatile("cp.async.bulk.wait_group 0;" ::: "memory");
                    st_relaxed_u32(g_xflag + role, s + 3);
                }
            }
            __syncwarp();
        };
        auto kv_check = [&](int s) {
            if (s + 1 < NSEG) {
                if (lane < 4) {
                    unsigned f; int guard = 0;
                    do {
                        asm volatile("ld.acquire.gpu.global.u32 %0, [%1];" : "=r"(f) : "l"(g_xflag + h * 4 + lane) : "memory");
                        if (++guard > (1 << 20)) __trap();
                    } while (f <= (unsigned)(s + 1));
                }
                __syncwarp();
                asm volatile("fence.proxy.async.global;" ::: "memory");
            }
        };
        auto kv_load = [&](int s) {
            if (lane == 0 && s + 1 < NSEG) {
                const uint32_t bar = sb + MB_KV + ((s + 1) & 1) * 8, dst = sb + SM_KV + ((s + 1) & 1) * KV_BYTES;
                const int row = (((s + 1) & 3) * NH + h) * 96;
                mbar_expect_tx(bar, KV_BYTES);
                asm volatile("cp.async.bulk.tensor.3d.shared::cluster.global.mbarrier::complete_tx::bytes.multicast::cluster [%0], [%1, {%3, %4, %3}], [%2], %5;"
                             ::"r"(dst + kh * 8192), "l"(&mapKV), "r"(bar), "r"(0), "r"(row + 32 + 32 * kh), "h"((uint16_t)3) : "memory");
                bulk_load(dst + 16384, g_tok + row * DH + j * 1024, 2048, bar);
            }
            __syncwarp();
        };
        if (warp == 9) {
            if (lane == 0) { load_xt(0, 0); load_xt(0, 1); }
#pragma unroll 1
            for (int s = -3; s < 0; s++) { tok_start(s); bar_arrive(BAR_PRO, 288); tok_mid(s); }
        }
        if (warp == 11) { kv_check(-1); kv_load(-1); }
        bar_arrive(BAR_MEM, 384);
        const uint32_t ybox = mlo + page_off(role & 63, cls ^ yflip), xoth = mlo + WIN + page_off((pair & 31) ^ 1, cls ^ XFLIP);
        const uint32_t zline = mlo + WIN + page_off(32 + ((role >> 5) & 1), cls ^ ZFLIP) + (role & 31) * 128, zbox = mlo + WIN + (page_off(32 + kh, 0) & ~4096u);
        const uint32_t xtype = g == 0 ? 2 : (g & 1);
        const uint32_t ydst = (lane >> 3) * 128 + ((lane & 7) ^ (lane >> 3)) * 16, ysrc = lane * 128 + ((2 * g) ^ (lane & 7)) * 16;
#pragma unroll 1
        for (int s = 0; s < NSEG; s++) {
            const uint32_t slot = (s & 3) << 14;
            if (g == 3) {
                kv_check(s);
                const uint32_t L = l16, kvo = (s & 1) * KV_BYTES, qa = QFRAG(), sa = sb + SM_S + 512 + (L >> 2);
                float sc[4] = {0.f, 0.f, 0.f, 0.f}, sd[4] = {0.f, 0.f, 0.f, 0.f};
                uint32_t a[4][4], kb[2][4];
                mbar_wait_w(sb + MB_KV + (s & 1) * 8, (s >> 1) & 1);
                mbar_wait_w(sb + MB_P, s & 1);
#pragma unroll
                for (int c = 0; c < 2; c++) {
                    const uint32_t qc = qa + (sb + (nh ^ c) * 1024), kc = L + (sb + SM_QKV + 2048 + (nh ^ c) * 1024);
                    if (c) bar_sync(BAR_QK, 224);
                    ldsm4t(kb[0], kc); ldsm4t(a[0], qc); ldsm4t(a[1], qc + 256);
                    ldsm4t(kb[1], kc + 512); ldsm4t(a[2], qc + 512); ldsm4t(a[3], qc + 768);
                    mma16816v(sc, a[0], kb[0][0], kb[0][1]);
                    mma16816v(sd, a[1], kb[0][2], kb[0][3]);
                    mma16816v(sc, a[2], kb[1][0], kb[1][1]);
                    mma16816v(sd, a[3], kb[1][2], kb[1][3]);
                }
                sts32(sa, scale_scores(sc[0] + sd[0], sc[1] + sd[1]));
                sts32(sa + 768, scale_scores(sc[2] + sd[2], sc[3] + sd[3]));
                bar_arrive(BAR_S, 160);
                TL(25);
                bar_sync(BAR_SV, 352);
                kv_load(s);
            } else {
                if (g == 1) { tok_start(s); TL(21); }
                const char* p = make_ptr(l16 + (xoth + xtype * 1024 + slot), mhi);
                const uint32_t dst = l16 + (sb + SM_QKV + xtype * 2048 + (nh ^ 1) * 1024);
                asm volatile("" ::"l"(p));
                uint4 v[2];
                poll_init(v[0]); poll_init(v[1]);
                if (g == 0) {
                    bar_sync(BAR_PUBV, 160);
                    mbar_wait_w(sb + MB_V, s & 1);
                    spin_cycles(DLY_V);
                } else {
                    bar_sync(BAR_PUB, 192);
                    spin_cycles(DLY_X);
                }
                const int r = poll2(v, p);
                STAT(1, r > 1 && warp == 10);
                sts128(dst, v[0]); sts128(dst + 512, v[1]);
                if (g != 0) bar_arrive(BAR_QK, 224);
                if (g == 0) { bar_arrive(BAR_V, 160); bar_arrive(BAR_SV, 352); TL(17); }
                if (g == 1) {
                    TL(31);
                    bar_sync(BAR_SV, 352);
                    tok_mid(s);
                    TL(22);
                }
                if (g == 2 && s >= 1) {
                    TL(16);
                    const uint32_t prev = (slot - 0x4000) & 0xC000;
                    const char* y = make_ptr(l16 + (ybox + prev), mhi);
                    const char* x = make_ptr(l16 + (xoth + prev + kh * 1536), mhi);
#pragma unroll
                    for (int i = 0; i < 8; i++) st_sent(y + i * 512);
#pragma unroll
                    for (int i = 0; i < 3; i++) st_sent(x + i * 512);
                    st_relaxed_u32(make_ptr(lane * 4 + (zline + (slot ^ 0x8000)), mhi), SENT);
                    TL(23);
                }
            }
            if (s + 1 == NSEG) break;
            {
                const char* p = make_ptr(l16 + (ybox + g * 1024 + slot), mhi);
                char* zdst = make_ptr(lane * 4 + (zline + g * 32 + slot), mhi);
                const uint32_t dst = ydst + (sb + SM_Z + g * 1024), dst1 = (ydst ^ 64) + (sb + SM_Z + g * 1024 + 512), src = ysrc + (sb + SM_Z), src1 = (ysrc ^ 16) + (sb + SM_Z);
                asm volatile("" ::"l"(p), "l"(zdst));
                uint4 v[2];
                poll_init(v[0]); poll_init(v[1]);
                bar_sync(BAR_SENTC, 384);
                spin_cycles(DLY_Y);
                const int r = poll2(v, p);
                STAT(2, r > 1 && warp == 8);
                sts128(dst, v[0]); sts128(dst1, v[1]);
                bar_sync(BAR_Y, 128);
                TL(18);
                uint32_t b[2][4];
                ldsm4t(b[0], src); ldsm4t(b[1], src1);
                const uint32_t one = 0x3F803F80u;
                float d0[4] = {0.f, 0.f, 0.f, 0.f}, d1[4] = {0.f, 0.f, 0.f, 0.f};
                mma16816(d0, one, one, one, one, b[0][0], b[0][1]);
                mma16816(d1, one, one, one, one, b[1][0], b[1][1]);
                mma16816(d0, one, one, one, one, b[0][2], b[0][3]);
                mma16816(d1, one, one, one, one, b[1][2], b[1][3]);
                const uint32_t w = (lane & 4) ? pack_bf16(d1[0], d1[1]) : pack_bf16(d0[0], d0[1]);
                asm volatile("{.reg .pred p; setp.lt.u32 p, %2, 128; @p st.relaxed.gpu.global.u32 [%0], %1;}" ::"l"(zdst), "r"(w), "r"(l16) : "memory");
                if (s + 3 < NSEG) bar_arrive(BAR_ZP, 256);
                TL(19);
            }
            {
                const char* p = make_ptr(l16 + (zbox + g * 512 + slot), mhi);
                const uint32_t dst = l16 + (sb + SM_Z + g * 512);
                asm volatile("" ::"l"(p));
                uint4 v[4];
                poll_init(v[0]); poll_init(v[1]); poll_init(v[2]); poll_init(v[3]);
                bar_sync(BAR_COMM, 128);
                spin_cycles(DLY_Z);
                const int r = poll4(v, p);
                STAT(0, r > 1 && warp == 8);
#pragma unroll
                for (int i = 0; i < 4; i++) sts128(dst + i * 2048, v[i]);
                bar_arrive(BAR_MEM, 384);
                TL(20);
            }
        }
    } else if (warp < 4) {
        asm volatile("setmaxnreg.inc.sync.aligned.u32 %0;" ::"n"(REG_A));
        const uint32_t l16 = lane16();
        uint32_t wa[2][24][4];
        {
            const uint32_t L = l16, fa = sb + FRAG();
            mbar_wait_w(sb + MB_W1, 0);
#pragma unroll
            for (int t = 0; t < 2; t++)
#pragma unroll
                for (int r = 0; r < 24; r++) ldsm4t(wa[t][r], fa + STG_QK + (t * 24 + r) * 2048);
            mbar_wait_w(sb + MB_W2, 0);
            bar_arrive(BAR_PDONE, 384);
        }
        auto batch1 = [&](float (&d)[16], uint32_t lo, auto tc, auto k0c, auto k1c) {
            constexpr int t = decltype(tc)::value;
            const uint64_t da = make_desc(SB0 + SM_WQK, 16, 1024);
            wg_fence();
            static_for<decltype(k0c)::value, decltype(k1c)::value>([&](auto kc) {
                constexpr int k = decltype(kc)::value, off = (k >> 2) * 256 + (k & 3) * 2;
                if constexpr (k >= 24) wgmma_ss32u<off>(d, da + ((k - 24) * 2 + t) * 128, lo);
                else wgmma_rs32u<off, k != 0 || t != 0>(d, wa[t][k], lo);
            });
            wg_commit();
        };
        const uint32_t xbox = mlo + WIN + page_off(pair & 31, cls ^ XFLIP);
        const uint32_t ybox = mlo + page_off(24 + 2 * g + 32 * nh, kh ^ yflip) + h * 128;
#pragma unroll 1
        for (uint32_t it = 0; it < NSEG + 3; it++) {
            const int s = (int)it - 3;
            const uint32_t ui = uniform(it), slot = ((ui + 1) & 3) << 14, kvo = (~ui & 1) * KV_BYTES, xtlo = XTLO();
            {
                PHASE(5);
                const uint32_t first = L | (g << 9);
                if (s >= 0) mbar_expect_tx_if0(first, sb + MB_R1, 2048);
                if (s + 3 < NSEG) {
                    mbar_expect_tx_if0(first, sb + MB_RT0, 8192);
                    mbar_wait_w(sb + MB_XT + (ui & 1) * 8, (it >> 1) & 1);
                }
            }
            if (s >= 0) {
                PHASE(0);
                const uint32_t mb = L + (sb + SM_Z), ra = L + (sb + g * 512), r1 = L + (rsb + SM_R1 + g * 512), r1b = rsb + MB_R1;
                sched_fence(r1 | r1b);
                bar_sync(BAR_MEM, 384);
                TLB(0);
                float acc[2][2][4];
#pragma unroll
                for (int t = 0; t < 4; t++) { acc[t >> 1][t & 1][0] = acc[t >> 1][t & 1][1] = acc[t >> 1][t & 1][2] = acc[t >> 1][t & 1][3] = 0.f; }
                uint32_t b[4][4];
                uint4 u0, u1;
#pragma unroll
                for (int p = 0; p < 4; p++) ldsm4t(b[p], mb + p * 512);
#pragma unroll
                for (int p = 0; p < 12; p++) {
#pragma unroll
                    for (int u = 0; u < 2; u++) {
                        mma16816v(acc[0][u], wa[0][2 * p + u], b[p & 3][2 * u], b[p & 3][2 * u + 1]);
                        mma16816v(acc[1][u], wa[1][2 * p + u], b[p & 3][2 * u], b[p & 3][2 * u + 1]);
                    }
                    if (p + 4 < 12) ldsm4t(b[p & 3], mb + (p + 4) * 512);
                    if (p == Q3_AT) {
                        bar_sync(BAR_Q3, 256);
                        u0 = lds128(ra + SM_R3); u1 = lds128(ra + SM_O);
                    }
                }
                st_async4(r1, (acc[0][0][0] + __uint_as_float(u0.x)) + acc[0][1][0], (acc[0][0][1] + __uint_as_float(u0.y)) + acc[0][1][1],
                          (acc[0][0][2] + __uint_as_float(u0.z)) + acc[0][1][2], (acc[0][0][3] + __uint_as_float(u0.w)) + acc[0][1][3], r1b);
                TL(1);
                const float o0 = (acc[1][0][0] + __uint_as_float(u1.x)) + acc[1][1][0], o1 = (acc[1][0][1] + __uint_as_float(u1.y)) + acc[1][1][1];
                const float o2 = (acc[1][0][2] + __uint_as_float(u1.z)) + acc[1][1][2], o3 = (acc[1][0][3] + __uint_as_float(u1.w)) + acc[1][1][3];
                const uint32_t l4 = L >> 2, qo = SM_QKV + kh * 2048 + nh * 1024 + g * 256, qr = l4 + (rsb + qo), ql = l4 + (sb + qo), pb = rsb + MB_P;
                char* xd = make_ptr(l4 + (xbox + kh * 1024 + g * 256 + slot), mhi);
                asm volatile("" ::"l"(xd), "r"(qr), "r"(pb), "r"(qr + 128), "f"(o0), "f"(o1), "f"(o2), "f"(o3));
                mbar_wait_w(sb + MB_R1, s & 1);
                const uint4 v = lds128(ra + SM_R1);
                const uint32_t w0 = pack_bf16(o0 + __uint_as_float(v.x), o1 + __uint_as_float(v.y)), w1 = pack_bf16(o2 + __uint_as_float(v.z), o3 + __uint_as_float(v.w));
                st_relaxed_u32(xd, w0);
                st_relaxed_u32(xd + 128, w1);
                bar_arrive(BAR_PUB, 192);
                st_async1(qr, w0, pb);
                st_async1(qr + 128, w1, pb);
                sts32(ql, w0);
                sts32(ql + 128, w1);
                __syncwarp();
                mbar_expect_tx_if0(L, sb + MB_P, 256);
                TL(2);
                if (s + 3 < NSEG) bar_sync(BAR_VP, 256);
            } else {
                bar_sync(BAR_PRO, 288);
            }
            if (s + 3 < NSEG) {
                float d[16];
                batch1(d, xtlo, std::integral_constant<int, 0>(), std::integral_constant<int, 0>(), std::integral_constant<int, 32>());
                PHASE(1);
                const uint32_t rt = L + (rsb + SM_RT + g * 2048);
                wg_wait<0>();
                TL(7);
#pragma unroll
                for (int i = 0; i < 4; i++) st_async4(rt + i * 512, d[4 * i], d[4 * i + 1], d[4 * i + 2], d[4 * i + 3], rsb + MB_RT0);
            }
            if (s + 1 == NSEG) { bar_arrive(BAR_SV, 352); break; }
            if (s >= 0) {
                PHASE(2);
                const uint32_t fo = FRAG() + (sb + SM_WO2 + 16384), lo = L + (sb + SM_O), yo = (L >> 2) + (ybox + slot);
                uint32_t a1[8][4];
                bar_sync(BAR_SV, 352);
#pragma unroll
                for (int k = 0; k < 8; k++) ldsm4t(a1[k], fo + k * 2048);
                sched_fence(yo);
                bar_sync(BAR_O2, 256);
                TLB(14);
                float y0[4] = {0.f, 0.f, 0.f, 0.f}, y1[4] = {0.f, 0.f, 0.f, 0.f};
                uint32_t b[2][4];
                ldsm4t(b[0], lo); ldsm4t(b[1], lo + 512);
                sched_fence(L);
#pragma unroll
                for (int p = 0; p < 4; p++) {
                    mma16816v(y0, a1[2 * p], b[p & 1][0], b[p & 1][1]);
                    mma16816v(y1, a1[2 * p + 1], b[p & 1][2], b[p & 1][3]);
                    if (p < 2) ldsm4t(b[p & 1], lo + (p + 2) * 512);
                }
                bar_sync(BAR_INV, 256);
                float i0, i1;
                asm volatile("ld.shared.v2.f32 {%0, %1}, [%2];" : "=f"(i0), "=f"(i1) : "r"(((L >> 1) & 0x18) + (sb + SM_INV + g * 32)) : "memory");
                st_relaxed_u32(make_ptr(yo, mhi), pack_bf16((y0[0] + y1[0]) * i0, (y0[1] + y1[1]) * i1));
                st_relaxed_u32(make_ptr(yo ^ 4096, mhi) + 0x2000, pack_bf16((y0[2] + y1[2]) * i0, (y0[3] + y1[3]) * i1));
                bar_arrive(BAR_SENTC, 384);
                TL(6);
            }
            if (s + 3 < NSEG) {
                PHASE(4);
                float d[16];
                const uint32_t rt = L + (sb + SM_RT + g * 2048);
                mbar_wait_w(sb + MB_RT0, it & 1);
#pragma unroll
                for (int i = 0; i < 4; i++) {
                    const uint4 v = lds128(rt + i * 512);
                    d[4 * i] = __uint_as_float(v.x); d[4 * i + 1] = __uint_as_float(v.y); d[4 * i + 2] = __uint_as_float(v.z); d[4 * i + 3] = __uint_as_float(v.w);
                }
                if (s >= 0) bar_sync(BAR_SENT, 256);
                if (SPLIT > 0) batch1(d, xtlo, std::integral_constant<int, 1>(), std::integral_constant<int, 0>(), std::integral_constant<int, SPLIT>());
                if (s >= 0) bar_sync(BAR_ZP, 256);
                TLB(30);
                batch1(d, xtlo, std::integral_constant<int, 1>(), std::integral_constant<int, SPLIT>(), std::integral_constant<int, 32>());
                const uint32_t so = (kh ? FRAG() : ((L & 0x100) << 2) + (L & 0xF0) + g * 256) + (sb + SM_STG);
                wg_wait<0>();
                TL(8);
                uint32_t w[8];
#pragma unroll
                for (int i = 0; i < 8; i++) w[i] = pack_bf16(d[2 * i], d[2 * i + 1]);
                if (kh) {
                    stsm4t(so, w[0], w[1], w[2], w[3]);
                    stsm4t(so + 2048, w[4], w[5], w[6], w[7]);
                } else {
                    stsm4(so, w[0], w[1], w[2], w[3]);
                    stsm4(so + 2048, w[4], w[5], w[6], w[7]);
                }
                __syncwarp();
                mbar_arrive_if0(L, sb + MB_STG);
                TL(9);
            } else {
                bar_arrive(BAR_SENT, 256);
            }
        }
    } else {
        asm volatile("setmaxnreg.inc.sync.aligned.u32 %0;" ::"n"(REG_B));
        const uint32_t l16 = lane16();
        uint32_t wv[24][4], wo[8 + WO_RF1][4];
        {
            const uint32_t L = l16, fa = sb + FRAG();
            mbar_wait_w(sb + MB_W0, 0);
#pragma unroll
            for (int r = 0; r < 24; r++) ldsm4t(wv[r], fa + STG_V + r * 2048);
            bar_arrive(BAR_PV, 160);
            mbar_wait_w(sb + MB_W3, 0);
#pragma unroll
            for (int r = 0; r < 8 + WO_RF1; r++) ldsm4t(wo[r], fa + STG_WO + r * 2048);
            mbar_wait_w(sb + MB_W2, 0);
            bar_arrive(BAR_PDONE, 384);
        }
        const uint32_t xbox = mlo + WIN + page_off(pair & 31, cls ^ XFLIP);
        const uint32_t ybox = mlo + page_off(2 * g + 32 * nh, kh ^ yflip) + h * 128;
#pragma unroll 1
        for (uint32_t it = 0; it < NSEG + 3; it++) {
            const int s = (int)it - 3;
            const uint32_t ui = uniform(it), slot = ((ui + 1) & 3) << 14, kvo = (~ui & 1) * KV_BYTES, xtlo = XTLO();
            {
                PHASE(5);
                const uint32_t first = L | (g << 9);
                if (s >= 0) mbar_expect_tx_if0(first, sb + MB_R2, 1024);
                if (s + 3 < NSEG) {
                    mbar_expect_tx_if0(first, sb + MB_RT1, 4096);
                    mbar_wait_w(sb + MB_XT + (ui & 1) * 8, (it >> 1) & 1);
                }
            }
            if (s >= 0) {
                PHASE(0);
                const uint32_t fo = FRAG() + sb, l4 = L >> 2;
                {
                    const uint32_t mb = L + (sb + SM_Z), aw = fo + SM_WQK, ra = L + (sb + g * 512), r2 = (L >> 1) + (rsb + SM_R2 + g * 256), r2b = rsb + MB_R2;
                    uint32_t a[NA][4], b[4][4];
#pragma unroll
                    for (int i = 0; i < NA; i++) ldsm4t(a[i], aw + i * 2048);
                    sched_fence(L);
                    bar_sync(BAR_MEM, 384);
#pragma unroll
                    for (int p = 0; p < 4; p++) ldsm4t(b[p], mb + (12 + p) * 512);
                    sched_fence(L);
                    float c[2][4] = {{0.f, 0.f, 0.f, 0.f}, {0.f, 0.f, 0.f, 0.f}};
#pragma unroll
                    for (int i = 0; i < 16; i++) {
                        mma16816v(c[i & 1], a[i % NA], b[i >> 2][i & 2], b[i >> 2][(i & 2) + 1]);
                        ldsm4t(a[i % NA], aw + (i + NA) * 2048);
                    }
                    sts128(ra + SM_R3, make_uint4(__float_as_uint(c[0][0]), __float_as_uint(c[0][1]), __float_as_uint(c[0][2]), __float_as_uint(c[0][3])));
                    sts128(ra + SM_O, make_uint4(__float_as_uint(c[1][0]), __float_as_uint(c[1][1]), __float_as_uint(c[1][2]), __float_as_uint(c[1][3])));
                    bar_arrive(BAR_Q3, 256);
                    TL(29);
                    float acc[4][4];
#pragma unroll
                    for (int t = 0; t < 4; t++) { acc[t][0] = acc[t][1] = acc[t][2] = acc[t][3] = 0.f; }
#pragma unroll
                    for (int i = 16; i < 24; i++) {
                        mma16816v(acc[i & 1], a[i % NA], b[(i - 16) >> 1][2 * (i & 1)], b[(i - 16) >> 1][2 * (i & 1) + 1]);
                        if (i + NA < 24) ldsm4t(a[i % NA], aw + (i + NA) * 2048);
                        else ldsm4t(a[i % NA], mb + (i + NA - 24) * 512);
                    }
#pragma unroll
                    for (int p = 0; p < 12; p++) {
                        mma16816v(acc[(2 * p) & 3], wv[2 * p], a[(24 + p) % NA][0], a[(24 + p) % NA][1]);
                        mma16816v(acc[(2 * p + 1) & 3], wv[2 * p + 1], a[(24 + p) % NA][2], a[(24 + p) % NA][3]);
                        if (p + NA < 12) ldsm4t(a[(24 + p) % NA], mb + (p + NA) * 512);
                    }
                    if (s + 3 < NSEG) bar_arrive(BAR_VP, 256);
                    float o[4];
#pragma unroll
                    for (int i = 0; i < 4; i++) o[i] = (acc[0][i] + acc[1][i]) + (acc[2][i] + acc[3][i]);
                    st_async2(r2, kh ? o[0] : o[2], kh ? o[1] : o[3], r2b);
                    TL(10);
                    const float o0 = kh ? o[2] : o[0], o1 = kh ? o[3] : o[1];
                    const uint32_t qo = SM_QKV + 4096 + nh * 1024 + (2 * g + kh) * 128, qr = l4 + (rsb + qo), ql = l4 + (sb + qo), vb = rsb + MB_V, rl = (L >> 1) + (sb + SM_R2 + g * 256);
                    char* xd = make_ptr(l4 + (xbox + 2048 + (2 * g + kh) * 128 + slot), mhi);
                    asm volatile("" ::"l"(xd), "r"(qr), "r"(vb), "f"(o0), "f"(o1));
                    mbar_wait_w(sb + MB_R2, s & 1);
                    uint32_t vx, vy;
                    asm volatile("ld.shared.v2.u32 {%0,%1}, [%2];" : "=r"(vx), "=r"(vy) : "r"(rl) : "memory");
                    const uint32_t w0 = pack_bf16(o0 + __uint_as_float(vx), o1 + __uint_as_float(vy));
                    st_relaxed_u32(xd, w0);
                    bar_arrive(BAR_PUBV, 160);
                    st_async1(qr, w0, vb);
                    sts32(ql, w0);
                    __syncwarp();
                    mbar_expect_tx_if0(L, sb + MB_V, 128);
                    TL(11);
                }
                const uint32_t vma = L + (sb + SM_QKV + 4096 + g * 512), yo = l4 + (ybox + slot);
                uint32_t va[2][2][4];
                {
                    const uint32_t qa = QFRAG(), vf = VFRAG(), va0 = vf + VBASE(), va1 = (vf ^ 32) + VBASE();
                    const uint32_t kf = ((L << 3) & 0x380) | ((L ^ (L >> 3)) & 0x30) | (L & 0x40), kb0 = sb + SM_KV + kvo + g * 1024;
                    const int d = (int)(L >> 6) - (int)((L >> 3) & 6) + 8 * (j - (int)g);
                    const uint32_t keep = (d < 0 ? 0u : 0xFFFFu) | (d < 1 ? 0u : 0xFFFF0000u), sa = l4 + (sb + SM_S + g * 128);
                    const uint32_t q0 = qa + (sb + nh * 1024), q1 = qa + (sb + (nh ^ 1) * 1024);
                    float sc[4] = {0.f, 0.f, 0.f, 0.f}, sd[4] = {0.f, 0.f, 0.f, 0.f};
                    uint32_t a[4][4], kb[2][4];
                    mbar_wait_w(sb + MB_KV + (~ui & 1) * 8, (s >> 1) & 1);
                    ldsm4(kb[0], kf + (kb0 + nh * 4096)); ldsm4(kb[1], (kf ^ 64) + (kb0 + nh * 4096));
                    mbar_wait_w(sb + MB_P, s & 1);
                    TL(12);
#pragma unroll
                    for (int k = 0; k < 4; k++) ldsm4t(a[k], q0 + k * 256);
#pragma unroll
                    for (int k = 0; k < 4; k++) mma16816v((k & 1) ? sd : sc, a[k], kb[k >> 1][2 * (k & 1)], kb[k >> 1][2 * (k & 1) + 1]);
                    ldsm4(kb[0], kf + (kb0 + (nh ^ 1) * 4096)); ldsm4(kb[1], (kf ^ 64) + (kb0 + (nh ^ 1) * 4096));
                    sched_fence(vf | yo);
                    bar_sync(BAR_QK, 224);
                    TLB(3);
#pragma unroll
                    for (int k = 0; k < 4; k++) ldsm4t(a[k], q1 + k * 256);
                    sched_fence(L);
#pragma unroll
                    for (int k = 0; k < 4; k++) mma16816v((k & 1) ? sd : sc, a[k], kb[k >> 1][2 * (k & 1)], kb[k >> 1][2 * (k & 1) + 1]);
                    ldsm4t(va[0][0], va0); ldsm4t(va[0][1], va0 + 2048);
                    sts32(sa, scale_scores(sc[0] + sd[0], sc[1] + sd[1]));
                    sts32(sa + 768, (scale_scores(sc[2] + sd[2], sc[3] + sd[3]) & keep) | (0xFF80FF80u & ~keep));
                    bar_arrive(BAR_SV, 352);
                    ldsm4t(va[1][0], va1); ldsm4t(va[1][1], va1 + 2048);
                }
                bar_sync(BAR_S, 160);
                TLB(4);
                uint32_t pw[6], vm[4];
                if (s + 1 < NSEG) {
                softmax40(pw, l4 + (sb + SM_S), [&]() {
                    bar_sync(BAR_V, 160);
                    ldsm4(vm, vma);
                });
                uint32_t a1[NP2][4];
                float inv[2];
                {
                    uint32_t w[4];
                    pv32<false>(w, inv, va, vm, pw, [&]() {
                        sched_fence(L);
#pragma unroll
                        for (int k = 0; k < NP2; k++) ldsm4t(a1[k], fo + SM_WO2 + k * 2048);
                    });
#pragma unroll
                    for (int i = 0; i < 4; i++) sts32(l4 + (sb + SM_O + g * 512) + i * 128, w[i]);
                }
                const uint32_t lo = L + (sb + SM_O);
                bar_arrive(BAR_O2, 256);
                bar_sync(BAR_O, 128);
                TLB(5);
                {
                    float y0[4] = {0.f, 0.f, 0.f, 0.f}, y1[4] = {0.f, 0.f, 0.f, 0.f}, y2[4] = {0.f, 0.f, 0.f, 0.f};
                    uint32_t b[4][4];
#pragma unroll
                    for (int p = 0; p < 4; p++) ldsm4t(b[p], lo + p * 512);
                    inv[0] = rcp_approx(inv[0]); inv[1] = rcp_approx(inv[1]);
                    asm volatile("st.shared.v2.f32 [%0], {%1, %2};" ::"r"(((L >> 1) & 0x18) + (sb + SM_INV + g * 32)), "f"(inv[0]), "f"(inv[1]) : "memory");
                    bar_arrive(BAR_INV, 256);
                    sched_fence(L);
#pragma unroll
                    for (int k = 0; k < 8; k++) {
                        const int p = k >> 1, u = k & 1;
                        mma16816v(y2, a1[k % NP2], b[p][2 * u], b[p][2 * u + 1]);
                        if (k + NP2 < 8) ldsm4t(a1[k % NP2], fo + SM_WO2 + (k + NP2) * 2048);
                        else if (k + NP2 < 16 - WO_RF1) ldsm4t(a1[k % NP2], fo + SM_WO1 + (k + NP2 - 8 + WO_RF1) * 2048);
                        mma16816v(y0, wo[k], b[p][2 * u], b[p][2 * u + 1]);
                        if (k < WO_RF1) mma16816v(y1, wo[8 + (k < WO_RF1 ? k : 0)], b[p][2 * u], b[p][2 * u + 1]);
                        else mma16816v(y1, a1[(k + 8 - WO_RF1) % NP2], b[p][2 * u], b[p][2 * u + 1]);
                        if (k < P2_FENCE) sched_fence(L);
                    }
                    char* yd = make_ptr(yo, mhi);
                    char* yd1 = make_ptr(yo ^ 4096, mhi);
                    st_relaxed_u32(yd1 + 0x80000, pack_bf16(y2[0] * inv[0], y2[1] * inv[1]));
                    st_relaxed_u32(yd + 0x82000, pack_bf16(y2[2] * inv[0], y2[3] * inv[1]));
                    st_relaxed_u32(yd, pack_bf16(y0[0] * inv[0], y0[1] * inv[1]));
                    st_relaxed_u32(yd1 + 0x2000, pack_bf16(y0[2] * inv[0], y0[3] * inv[1]));
                    st_relaxed_u32(yd + 0x40000, pack_bf16(y1[0] * inv[0], y1[1] * inv[1]));
                    st_relaxed_u32(yd1 + 0x42000, pack_bf16(y1[2] * inv[0], y1[3] * inv[1]));
                }
                bar_arrive(BAR_SENTC, 384);
                TL(13);
                bar_sync(BAR_SENT, 256);
                } else {
                    bar_sync(BAR_V, 160);
                }
            } else {
                bar_sync(BAR_PRO, 288);
            }
            float o[8];
            if (s + 3 < NSEG) {
                float d[16];
                const uint64_t da = make_desc(SB0 + SM_WV, 16, 1024);
                wg_fence();
                static_for<0, 32>([&](auto kc) {
                    constexpr int k = decltype(kc)::value, off = (k >> 2) * 256 + (k & 3) * 2;
                    if constexpr (k >= 24) wgmma_ss32u<off>(d, da + (k - 24) * 128, xtlo);
                    else wgmma_rs32u<off, k != 0>(d, wv[k], xtlo);
                });
                wg_commit();
                PHASE(1);
                const uint32_t rt = L + (rsb + SM_RT + 8192 + g * 1024);
                wg_wait<0>();
                TL(27);
#pragma unroll
                for (int i = 0; i < 2; i++)
                    st_async4(rt + i * 512, kh ? d[4 * i] : d[8 + 4 * i], kh ? d[4 * i + 1] : d[9 + 4 * i], kh ? d[4 * i + 2] : d[10 + 4 * i], kh ? d[4 * i + 3] : d[11 + 4 * i], rsb + MB_RT1);
#pragma unroll
                for (int i = 0; i < 8; i++) o[i] = kh ? d[8 + i] : d[i];
            } else {
#pragma unroll
                for (int i = 0; i < 8; i++) o[i] = 0.f;
            }
            if (s >= 0) {
                PHASE(2);
                const uint32_t vf = VFRAG(), va0 = vf + VBASE(), va1 = (vf ^ 32) + VBASE(), vma = L + (sb + SM_QKV + 4096 + g * 512), sa = (L >> 2) + (sb + SM_S + 768);
                uint32_t va[2][2][4], vm[4], pw[6], w[4];
                ldsm4t(va[0][0], va0); ldsm4t(va[0][1], va0 + 2048);
                ldsm4t(va[1][0], va1); ldsm4t(va[1][1], va1 + 2048);
                ldsm4(vm, vma);
                softmax40(pw, sa, [&]() {});
                float inv[2];
                pv32<true>(w, inv, va, vm, pw, [&]() {});
                stsm4t((L & 0x70) * 5 + ((L >> 3) & 0x30) + (sb + SM_TO + g * 640), w[0], w[1], w[2], w[3]);
                __syncwarp();
                stg128(reinterpret_cast<char*>(g_ox) + (((L & 0x1C0) << 7) + (L & 0x30) + (((ui - 3) * SEG + 8 * j) * HD + h * DH + 32 * g) * 2),
                       lds128(((L >> 2) & 0x70) * 5 + (L & 0x30) + (sb + SM_TO + g * 640)));
                TL(26);
            }
            if (s + 3 < NSEG) {
                PHASE(3);
                const uint32_t rt = L + (sb + SM_RT + 8192 + g * 1024), so = FRAG() + (sb + SM_STG + 4096);
                mbar_wait_w(sb + MB_RT1, it & 1);
                TL(28);
                uint32_t w[4];
#pragma unroll
                for (int i = 0; i < 2; i++) {
                    const uint4 v = lds128(rt + i * 512);
                    w[2 * i] = pack_bf16(o[4 * i] + __uint_as_float(v.x), o[4 * i + 1] + __uint_as_float(v.y));
                    w[2 * i + 1] = pack_bf16(o[4 * i + 2] + __uint_as_float(v.z), o[4 * i + 3] + __uint_as_float(v.w));
                }
                stsm4t(so, w[0], w[1], w[2], w[3]);
                __syncwarp();
                mbar_arrive_if0(L, sb + MB_STG);
                TL(15);
            }
        }
    }
    KT_END(2);
    asm volatile("barrier.cluster.arrive.relaxed; barrier.cluster.wait;" ::: "memory");
}
constexpr int B_UCH = 39 * 128 + 16;
constexpr int B_KLEN = 2128;
constexpr int B_KCH = 2 * B_KLEN * 2 + 64;
constexpr int B_SM_U = 0;
constexpr int B_SM_K = 16 * B_UCH;
constexpr int B_SM_BAR = B_SM_K + 16 * B_KCH;
constexpr int B_SMEM = B_SM_BAR + 16 + 128;
static_assert(16 * B_KCH >= 2 * 65536, "the k / v tiles alias the kernel copies");
#define PROBE_N 5
constexpr int B_C = 2056;

__device__ __forceinline__ uint32_t bf16_mul(uint32_t a, uint32_t b) {
    uint32_t d;
    asm("mul.rn.bf16x2 %0, %1, %2;" : "=r"(d) : "r"(a), "r"(b));
    return d;
}
__device__ __forceinline__ uint32_t bf16_add(uint32_t a, uint32_t b) {
    uint32_t d;
    asm("add.rn.bf16x2 %0, %1, %2;" : "=r"(d) : "r"(a), "r"(b));
    return d;
}

__device__ __forceinline__ uint32_t atomic_round_trip(char* p) {
    uint32_t t0, t1, v;
    asm volatile("{.reg .pred p;\n"
                 "mov.u32 %0, %%clock;\n"
                 "atom.relaxed.gpu.global.add.u32 %2, [%3], 1;\n"
                 "setp.ne.u32 p, %2, 0x7FFFFFFF;\n"
                 "mov.u32 %1, 0;\n"
                 "@p mov.u32 %1, %%clock;}" : "=&r"(t0), "=&r"(t1), "=&r"(v) : "l"(p) : "memory");
    return t1 - t0;
}
__device__ __forceinline__ uint32_t far_first(char* a, char* b, int lane) {
    if (lane < 16) stg128((lane < 8 ? a : b) + (lane & 7) * 16, make_uint4(0, 0, 0, 0));
    __syncwarp();
    uint32_t ta = ~0u, tb = ~0u;
    if (lane == 0) {
        __threadfence();
#pragma unroll 1
        for (int i = 0; i < PROBE_N; i++) { ta = min(ta, atomic_round_trip(a)); tb = min(tb, atomic_round_trip(b)); }
    }
    return ta > tb;
}
__device__ __forceinline__ void measure_distance(char* mbox, int lane) {
    const uint32_t b = blockIdx.x;
    unsigned smid;
    asm volatile("mov.u32 %0, %%smid;" : "=r"(smid));
    char* w1 = mbox + WIN + (b & 31) * 128;
    const uint32_t c = far_first(w1 + page_off(40 + (b >> 5), 0), w1 + page_off(40 + (b >> 5), 1), lane);
    if (lane == 0) g_cls[smid] = c;
    if (b == 0) {
        const uint32_t c0 = far_first(mbox + page_off(0, 0), mbox + page_off(0, 1), lane);
        if (lane == 0) { g_reg[2] = c0 ^ c; g_reg[0] = 0; g_reg[1] = 0; }
    }
    if (b == 1) for (int i = lane; i < 128; i += 32) g_xflag[i] = 0;
    __syncwarp();
}

#define SP(i)
__global__ void __launch_bounds__(512, 1)
ssm_kernel(const __grid_constant__ CUtensorMap mapK, const __grid_constant__ CUtensorMap mapV, const bf16* __restrict__ Q, const bf16* __restrict__ shiftk,
           const bf16* __restrict__ ssmk, const bf16* __restrict__ Dv, bf16* __restrict__ out, char* __restrict__ mbox) {
    extern __shared__ __align__(128) uint8_t smem_raw[];
    const uint32_t sb = (smem_u32(smem_raw) + 127) & ~127u;
    const int ch0 = (blockIdx.x >> 1) * 16, half = blockIdx.x & 1;
    const int t = threadIdx.x, warp = t >> 5, lane = t & 31;
    const int tmax = half ? 1536 : 2048;
    KT_START(1);
    SP(0);
    if (blockIdx.x >= 128) {
        if (warp == 15) measure_distance(mbox, lane);
        return;
    }
    const uint32_t stg_k = sb + B_SM_K, stg_v = stg_k + 65536, bar = sb + B_SM_BAR;
    if (t == 0) {
        mbar_init(bar, 1);
        asm volatile("fence.mbarrier_init.release.cluster;" ::: "memory");
        mbar_expect_tx(bar, 2 * tmax * 32);
        for (int r = 0; r < tmax; r += 256) {
            tma_load_2d(stg_k + r * 32, &mapK, ch0, r, bar);
            tma_load_2d(stg_v + r * 32, &mapV, ch0, r, bar);
        }
    }
    uint4 kr[8];
    {
        const uint4* src = reinterpret_cast<const uint4*>(ssmk + (size_t)(ch0 + warp) * S_LEN) + lane;
#pragma unroll
        for (int i = 0; i < 8; i++) kr[i] = __ldg(src + i * 32);
        const uint32_t ub = sb + B_SM_U + warp * B_UCH;
        for (int i = lane; i < 7 * 8; i += 32) sts128(ub + i * 16, make_uint4(0, 0, 0, 0));
    }
    const int hr = lane & 1, cc = ch0 + hr * 8;
    uint32_t w[4][4];
#pragma unroll
    for (int p = 0; p < 4; p++) {
        const uint4 sw = __ldg(reinterpret_cast<const uint4*>(shiftk + (size_t)cc * 4 + p * 8));
        w[0][p] = __byte_perm(sw.x, sw.z, 0x5410); w[1][p] = __byte_perm(sw.x, sw.z, 0x7632);
        w[2][p] = __byte_perm(sw.y, sw.w, 0x5410); w[3][p] = __byte_perm(sw.y, sw.w, 0x7632);
    }
    __syncthreads();
    if (warp == 15) measure_distance(mbox, lane);
    mbar_wait(bar, 0);
    SP(1);
    if (warp * 128 < tmax) {
#pragma unroll 2
        for (int i = 0; i < 8; i++) {
            const int tt = warp * 128 + i * 16 + (lane >> 1);
            const uint32_t ka = stg_k + tt * 32 + hr * 16;
            const uint4 z = make_uint4(0, 0, 0, 0);
            const uint4 k0 = lds128(ka), k1 = tt >= 1 ? lds128(ka - 32) : z, k2 = tt >= 2 ? lds128(ka - 64) : z, k3 = tt >= 3 ? lds128(ka - 96) : z;
            const uint4 vv = lds128(stg_v + tt * 32 + hr * 16);
            uint4 o;
#pragma unroll
            for (int p = 0; p < 4; p++) {
                uint32_t a = bf16_mul(((const uint32_t*)&k3)[p], w[3][p]);
                a = bf16_add(a, bf16_mul(((const uint32_t*)&k2)[p], w[2][p]));
                a = bf16_add(a, bf16_mul(((const uint32_t*)&k1)[p], w[1][p]));
                a = bf16_add(a, bf16_mul(((const uint32_t*)&k0)[p], w[0][p]));
                ((uint32_t*)&o)[p] = bf16_mul(a, ((const uint32_t*)&vv)[p]);
            }
            sts128(stg_v + tt * 32 + hr * 16, o);
        }
        __syncwarp();
#pragma unroll
        for (int i = 0; i < 8; i++) {
            const int tt = warp * 128 + i * 16;
            uint32_t r0, r1, r2, r3;
            ldsm4t(r0, r1, r2, r3, stg_v + (tt + (lane & 7) + (lane >> 4) * 8) * 32 + ((lane >> 3) & 1) * 16);
            const int chn = (lane & 7) + ((lane >> 3) & 1) * 8, ts = tt + (lane >> 4) * 8, row = 7 + (ts >> 6), unit = (ts & 63) >> 3;
            stsm4(sb + B_SM_U + chn * B_UCH + row * 128 + ((unit ^ (row & 7)) * 16), r0, r1, r2, r3);
        }
    }
    __syncthreads();
    {
        const uint32_t kb = sb + B_SM_K + warp * B_KCH;
#pragma unroll
        for (int i = 0; i < 8; i++) {
            const uint4 lo = kr[i];
            const uint32_t nx = __shfl_down_sync(~0u, lo.x, 1), n0 = (i < 7) ? __shfl_sync(~0u, kr[i < 7 ? i + 1 : 7].x, 0) : 0u;
            const uint32_t hix = (lane < 31) ? nx : n0;
            const int c = 256 - (lane + 32 * i);
            sts128(kb + c * 16, make_uint4(__byte_perm(hix, lo.w, 0x7610), __byte_perm(lo.w, lo.z, 0x7610), __byte_perm(lo.z, lo.y, 0x7610), __byte_perm(lo.y, lo.x, 0x7610)));
            sts128(kb + B_KLEN * 2 + 64 + c * 16, make_uint4(__byte_perm(lo.w, lo.w, 0x1032), __byte_perm(lo.z, lo.z, 0x1032), __byte_perm(lo.y, lo.y, 0x1032), __byte_perm(lo.x, lo.x, 0x1032)));
        }
        const uint32_t k0w = __shfl_sync(~0u, kr[0].x, 0);
        if (lane < 10) {
            const int c = (lane == 0) ? 0 : 256 + lane;
            sts128(kb + c * 16, make_uint4(c == 257 ? (k0w & 0xFFFFu) : 0u, 0u, 0u, 0u));
            sts128(kb + B_KLEN * 2 + 64 + c * 16, make_uint4(0u, 0u, 0u, 0u));
        }
    }
    __syncwarp();
    SP(2);
    SP(3);
    const int tA = half ? 1 : 0, tB = half ? 2 : 3;
    float accA[4][4], accB[4][4];
#pragma unroll
    for (int i = 0; i < 4; i++)
#pragma unroll
        for (int e = 0; e < 4; e++) { accA[i][e] = 0.f; accB[i][e] = 0.f; }
    const int g = lane >> 2, tq = lane & 3;
    const uint32_t kb = sb + B_SM_K + warp * B_KCH;
    const int e0 = B_C - g + 2 * tq;
    const uint32_t fbase = (e0 & 1) ? (kb + B_KLEN * 2 + 64 + (e0 - 1) * 2) : (kb + e0 * 2);
    const uint32_t ub = sb + B_SM_U + warp * B_UCH;
    uint32_t A[8][4];
    auto load_frag = [&](uint32_t (&a)[4], int q) {
        const uint32_t ad = fbase - 16 * q;
        a[0] = lds32(ad); a[1] = lds32(ad - 16); a[2] = lds32(ad + 16); a[3] = lds32(ad);
    };
#pragma unroll
    for (int i = 5; i < 8; i++) load_frag(A[i], 2 * (i - 8));
    const int mA = 8 * tA + 7, mB = 8 * tB + 7;
    auto tile_step = [&](float (&acc)[4][4], int tile, int m, auto mm_c) {
        constexpr int mm = decltype(mm_c)::value;
        const int row = 7 + 8 * tile - m + (lane & 7);
        const uint32_t ra = ub + row * 128;
#pragma unroll
        for (int p = 0; p < 2; p++) {
            uint32_t b[4];
            ldsm4(b[0], b[1], b[2], b[3], ra + (((p * 4 + (lane >> 3)) ^ (row & 7)) * 16));
#pragma unroll
            for (int u = 0; u < 2; u++) {
                const int k = 2 * p + u;
#pragma unroll
                for (int mt = 0; mt < 4; mt++) {
                    const int sl = (mm * 4 + (mt - k) + 8) & 7;
                    mma16816(acc[mt], A[sl][0], A[sl][1], A[sl][2], A[sl][3], b[2 * u], b[2 * u + 1]);
                }
            }
        }
    };
    int m = 0;
#pragma unroll 1
    for (; m <= mA; m += 2) {
#pragma unroll
        for (int i = 0; i < 4; i++) load_frag(A[i], 8 * m + 2 * i);
        tile_step(accB, tB, m, std::integral_constant<int, 0>());
        tile_step(accA, tA, m, std::integral_constant<int, 0>());
#pragma unroll
        for (int i = 0; i < 4; i++) load_frag(A[4 + i], 8 * m + 8 + 2 * i);
        tile_step(accB, tB, m + 1, std::integral_constant<int, 1>());
        tile_step(accA, tA, m + 1, std::integral_constant<int, 1>());
    }
#pragma unroll 1
    for (; m <= mB; m += 2) {
#pragma unroll
        for (int i = 0; i < 4; i++) load_frag(A[i], 8 * m + 2 * i);
        tile_step(accB, tB, m, std::integral_constant<int, 0>());
#pragma unroll
        for (int i = 0; i < 4; i++) load_frag(A[4 + i], 8 * m + 8 + 2 * i);
        tile_step(accB, tB, m + 1, std::integral_constant<int, 1>());
    }
    SP(4);
    {
        const uint32_t dw = (uint32_t)__ldg(reinterpret_cast<const uint16_t*>(Dv) + ch0 + warp) * 0x00010001u;
        __syncwarp();
#pragma unroll
        for (int tl = 0; tl < 2; tl++) {
            const int row = 7 + 8 * (tl ? tB : tA) + (lane & 7);
#pragma unroll
            for (int mp = 0; mp < 2; mp++) {
                const uint32_t a = ub + row * 128 + (((mp * 4 + (lane >> 3)) ^ (row & 7)) * 16);
                uint32_t u0, u1, u2, u3;
                ldsm4t(u0, u1, u2, u3, a);
                const float(&c0)[4] = tl ? accB[2 * mp] : accA[2 * mp];
                const float(&c1)[4] = tl ? accB[2 * mp + 1] : accA[2 * mp + 1];
                const uint32_t y0 = bf16_add(pack_bf16(c0[0], c0[1]), bf16_mul(u0, dw)), y1 = bf16_add(pack_bf16(c0[2], c0[3]), bf16_mul(u1, dw));
                const uint32_t y2 = bf16_add(pack_bf16(c1[0], c1[1]), bf16_mul(u2, dw)), y3 = bf16_add(pack_bf16(c1[2], c1[3]), bf16_mul(u3, dw));
                asm volatile("stmatrix.sync.aligned.m8n8.x4.trans.shared.b16 [%0], {%1,%2,%3,%4};" ::"r"(a), "r"(y0), "r"(y1), "r"(y2), "r"(y3) : "memory");
            }
        }
    }
    const int hh = lane >> 4, tbk = (warp & 7) * 16 + (lane & 15);
    const int tg = ((tbk < 64) ? tA : tB) * 512 + (tbk & 63) * 8;
    uint4 qv[8];
    if (t < 256) {
#pragma unroll
        for (int i = 0; i < 8; i++) qv[i] = __ldg(reinterpret_cast<const uint4*>(Q + (size_t)(tg + i) * DM + ch0 + hh * 8));
    }
    SP(5);
    __syncthreads();
    SP(6);
    if (t < 256) {
        const int row = 7 + (tg >> 6), unit = (tg & 63) >> 3;
        uint4 y[8];
#pragma unroll
        for (int c = 0; c < 8; c++) y[c] = lds128(sb + B_SM_U + (hh * 8 + c) * B_UCH + row * 128 + ((unit ^ (row & 7)) * 16));
#pragma unroll
        for (int i = 0; i < 8; i++) {
            const uint32_t sel = (i & 1) ? 0x7632 : 0x5410;
            uint4 o;
            o.x = bf16_mul(qv[i].x, __byte_perm(((const uint32_t*)&y[0])[i >> 1], ((const uint32_t*)&y[1])[i >> 1], sel));
            o.y = bf16_mul(qv[i].y, __byte_perm(((const uint32_t*)&y[2])[i >> 1], ((const uint32_t*)&y[3])[i >> 1], sel));
            o.z = bf16_mul(qv[i].z, __byte_perm(((const uint32_t*)&y[4])[i >> 1], ((const uint32_t*)&y[5])[i >> 1], sel));
            o.w = bf16_mul(qv[i].w, __byte_perm(((const uint32_t*)&y[6])[i >> 1], ((const uint32_t*)&y[7])[i >> 1], sel));
            stg128(out + (size_t)(tg + i) * OUT_LD + DM + ch0 + hh * 8, o);
        }
    } else {
        const uint4 sent = make_uint4(SENT, SENT, SENT, SENT);
        char* p0 = mbox + blockIdx.x * 16384 + (t - 256) * 16;
#pragma unroll
        for (int i = 0; i < 4; i++) stg128(p0 + i * 4096, sent);
        char* p1 = mbox + WIN + blockIdx.x * 8704 + (t - 256) * 16;
        stg128(p1, sent); stg128(p1 + 4096, sent);
        if (t < 256 + 32) stg128(p1 + 8192, sent);
    }
    KT_END(1);
}

typedef CUresult (*EncodeFn)(CUtensorMap*, CUtensorMapDataType, cuuint32_t, void*, const cuuint64_t*, const cuuint64_t*, const cuuint32_t*,
                             const cuuint32_t*, CUtensorMapInterleave, CUtensorMapSwizzle, CUtensorMapL2promotion, CUtensorMapFloatOOBfill);

static void make_map(EncodeFn fn, CUtensorMap* m, const void* ptr, uint64_t inner, uint64_t outer, uint32_t box_in, uint32_t box_out,
                     CUtensorMapL2promotion promo = CU_TENSOR_MAP_L2_PROMOTION_L2_256B) {
    cuuint64_t dims[2] = {inner, outer};
    cuuint64_t strides[1] = {inner * 2};
    cuuint32_t box[2] = {box_in, box_out};
    cuuint32_t es[2] = {1, 1};
    fn(m, CU_TENSOR_MAP_DATA_TYPE_BFLOAT16, 2, const_cast<void*>(ptr), dims, strides, box, es, CU_TENSOR_MAP_INTERLEAVE_NONE,
       CU_TENSOR_MAP_SWIZZLE_128B, promo, CU_TENSOR_MAP_FLOAT_OOB_FILL_NONE);
}

extern "C" void kernel_launch(void* const* d_in, const int* in_sizes, int n_in, void* d_out, int out_size) {
    const bf16* x = (const bf16*)d_in[0];
    const bf16* mem0 = (const bf16*)d_in[1];
    const bf16* Wq = (const bf16*)d_in[2];
    const bf16* Wk = (const bf16*)d_in[3];
    const bf16* Wv = (const bf16*)d_in[4];
    const bf16* Wo = (const bf16*)d_in[5];
    const bf16* Bq = (const bf16*)d_in[7];
    const bf16* Bk = (const bf16*)d_in[8];
    const bf16* Bv = (const bf16*)d_in[9];
    const bf16* Bsh = (const bf16*)d_in[10];
    const bf16* Bssm = (const bf16*)d_in[11];
    const bf16* BD = (const bf16*)d_in[12];
    bf16* out = (bf16*)d_out;

    static bool init = false;
    static EncodeFn enc = nullptr;
    static void *p_tok, *p_ox, *p_mbox;
    static int nclusters = 64;
    using G2 = GemmCfg<128, 5>;
    if (!init) {
        cudaDriverEntryPointQueryResult qr;
        cudaGetDriverEntryPoint("cuTensorMapEncodeTiled", (void**)&enc, cudaEnableDefault, &qr);
        cudaGetSymbolAddress(&p_tok, g_tok);
        cudaGetSymbolAddress(&p_ox, g_ox);
        cudaGetSymbolAddress(&p_mbox, g_mbox);
        cudaFuncSetAttribute(gemm_kernel<128, 5>, cudaFuncAttributeMaxDynamicSharedMemorySize, G2::SMEM);
        cudaFuncSetAttribute(chain_kernel, cudaFuncAttributeMaxDynamicSharedMemorySize, CHAIN_SMEM);
        cudaFuncSetAttribute(ssm_kernel, cudaFuncAttributeMaxDynamicSharedMemorySize, B_SMEM);
        cudaLaunchConfig_t cfg = {};
        cfg.gridDim = dim3(132); cfg.blockDim = dim3(384); cfg.dynamicSmemBytes = CHAIN_SMEM;
        cudaLaunchAttribute at[1];
        at[0].id = cudaLaunchAttributeClusterDimension; at[0].val.clusterDim.x = 2; at[0].val.clusterDim.y = 1; at[0].val.clusterDim.z = 1;
        cfg.attrs = at; cfg.numAttrs = 1;
        int n = 0;
        if (cudaOccupancyMaxActiveClusters(&n, chain_kernel, &cfg) == cudaSuccess && n > 64) nclusters = n < 66 ? n : 66;
        (void)cudaGetLastError();
        init = true;
    }
    char* mbox = (char*)(((uintptr_t)p_mbox + 2 * WIN - 1) & ~(uintptr_t)(2 * WIN - 1));
    CUtensorMap mX, mT32, mT16, mTQ, mKV, mWq, mWk, mWv, mWoC, mOx, mWo, mOut;
    {
        cuuint64_t dims[3] = {64, S_LEN, DM / 64};
        cuuint64_t strides[2] = {DM * 2, 128};
        cuuint32_t box[3] = {64, 32, 4};
        cuuint32_t es[3] = {1, 1, 1};
        enc(&mX, CU_TENSOR_MAP_DATA_TYPE_BFLOAT16, 3, const_cast<bf16*>(x), dims, strides, box, es, CU_TENSOR_MAP_INTERLEAVE_NONE,
            CU_TENSOR_MAP_SWIZZLE_128B, CU_TENSOR_MAP_L2_PROMOTION_L2_256B, CU_TENSOR_MAP_FLOAT_OOB_FILL_NONE);
    }
    make_map(enc, &mT32, p_tok, DH, 4 * NH * 3 * SEG, 64, 32, CU_TENSOR_MAP_L2_PROMOTION_L2_128B);
    make_map(enc, &mT16, p_tok, DH, 4 * NH * 3 * SEG, 64, 16, CU_TENSOR_MAP_L2_PROMOTION_L2_128B);
    {
        cuuint64_t dims[2] = {512, 4 * NH * 12};
        cuuint64_t strides[1] = {2048};
        cuuint32_t box[2] = {256, 4};
        cuuint32_t es[2] = {1, 1};
        enc(&mTQ, CU_TENSOR_MAP_DATA_TYPE_UINT32, 2, p_tok, dims, strides, box, es, CU_TENSOR_MAP_INTERLEAVE_NONE,
            CU_TENSOR_MAP_SWIZZLE_NONE, CU_TENSOR_MAP_L2_PROMOTION_L2_128B, CU_TENSOR_MAP_FLOAT_OOB_FILL_NONE);
    }
    {
        cuuint64_t dims[3] = {64, 4 * NH * 3 * SEG, 2};
        cuuint64_t strides[2] = {DH * 2, 128};
        cuuint32_t box[3] = {64, 32, 2};
        cuuint32_t es[3] = {1, 1, 1};
        enc(&mKV, CU_TENSOR_MAP_DATA_TYPE_BFLOAT16, 3, p_tok, dims, strides, box, es, CU_TENSOR_MAP_INTERLEAVE_NONE,
            CU_TENSOR_MAP_SWIZZLE_128B, CU_TENSOR_MAP_L2_PROMOTION_L2_128B, CU_TENSOR_MAP_FLOAT_OOB_FILL_NONE);
    }
    make_map(enc, &mWq, Wq, HD, DM, 64, 16, CU_TENSOR_MAP_L2_PROMOTION_L2_128B);
    make_map(enc, &mWk, Wk, HD, DM, 64, 16, CU_TENSOR_MAP_L2_PROMOTION_L2_128B);
    make_map(enc, &mWv, Wv, HD, DM, 64, 16, CU_TENSOR_MAP_L2_PROMOTION_L2_128B);
    make_map(enc, &mWoC, Wo, DM, HD, 64, 128, CU_TENSOR_MAP_L2_PROMOTION_L2_128B);
    make_map(enc, &mOx, p_ox, HD, S_LEN, 64, 128);
    make_map(enc, &mWo, Wo, DM, HD, 64, 64);
    make_map(enc, &mOut, out, OUT_LD, S_LEN, 64, 64);

    CUtensorMap mBk, mBv;
    for (int i = 0; i < 2; i++) {
        cuuint64_t dims[2] = {DM, S_LEN};
        cuuint64_t strides[1] = {DM * 2};
        cuuint32_t box[2] = {16, 256};
        cuuint32_t es[2] = {1, 1};
        enc(i ? &mBv : &mBk, CU_TENSOR_MAP_DATA_TYPE_BFLOAT16, 2, const_cast<bf16*>(i ? Bv : Bk), dims, strides, box, es, CU_TENSOR_MAP_INTERLEAVE_NONE,
            CU_TENSOR_MAP_SWIZZLE_NONE, CU_TENSOR_MAP_L2_PROMOTION_NONE, CU_TENSOR_MAP_FLOAT_OOB_FILL_NONE);
    }
    cudaStream_t st = cudaStreamPerThread;
    ssm_kernel<<<132, 512, B_SMEM, st>>>(mBk, mBv, Bq, Bsh, Bssm, BD, out, mbox);
    chain_kernel<<<2 * nclusters, 384, CHAIN_SMEM, st>>>(mX, mT32, mT16, mTQ, mKV, mWq, mWk, mWv, mWoC, mem0, mbox);
    gemm_kernel<128, 5><<<128, 288, G2::SMEM, st>>>(mOx, mWo, mWo, mWo, mOut, 16, 8, 64);
}
```

```cpp
#include <cuda_runtime.h>
#include <cuda_bf16.h>
#include <cuda.h>
#include <stdint.h>
#include <type_traits>

typedef __nv_bfloat16 bf16;

constexpr int S_LEN = 2048, DM = 1024, NH = 32, DH = 128, NSEG = 64, SEG = 32;
constexpr int HD = NH * DH;
constexpr int OUT_LD = 2048;
constexpr unsigned SENT = 0xFFFFFFFFu;

__device__ bf16 g_tok[4 * NH * 3 * SEG * DH];
__device__ bf16 g_ox[(size_t)S_LEN * HD];
__device__ uint4 g_mbox[4 * 131072];
__device__ unsigned g_xflag[128];
__device__ unsigned g_reg[4];
__device__ unsigned g_cls[256];
__device__ unsigned g_err;
constexpr uint32_t WIN = 2u << 20;
__host__ __device__ constexpr uint32_t page_off(uint32_t idx, uint32_t c) {
    return ((idx & 1) << 13) | ((idx >> 1) << 16) | (((c ^ idx ^ (idx >> 1) ^ (idx >> 2) ^ (idx >> 4)) & 1) << 12);
}
#define STAT(i, c) (void)(c)
#define KT_MARK(k)
#define KT_START(k)
#define KT_END(k)

__device__ __forceinline__ uint32_t smem_u32(const void* p) { return (uint32_t)__cvta_generic_to_shared(p); }
__device__ __forceinline__ void ldsm4(uint32_t& r0, uint32_t& r1, uint32_t& r2, uint32_t& r3, uint32_t a) {
    asm volatile("ldmatrix.sync.aligned.m8n8.x4.shared.b16 {%0,%1,%2,%3}, [%4];" : "=r"(r0), "=r"(r1), "=r"(r2), "=r"(r3) : "r"(a) : "memory");
}
__device__ __forceinline__ void ldsm4t(uint32_t& r0, uint32_t& r1, uint32_t& r2, uint32_t& r3, uint32_t a) {
    asm volatile("ldmatrix.sync.aligned.m8n8.x4.trans.shared.b16 {%0,%1,%2,%3}, [%4];" : "=r"(r0), "=r"(r1), "=r"(r2), "=r"(r3) : "r"(a) : "memory");
}
__device__ __forceinline__ void ldsm2(uint32_t& r0, uint32_t& r1, uint32_t a) {
    asm volatile("ldmatrix.sync.aligned.m8n8.x2.shared.b16 {%0,%1}, [%2];" : "=r"(r0), "=r"(r1) : "r"(a) : "memory");
}
__device__ __forceinline__ void stg128(void* p, uint4 v) {
    asm volatile("st.global.v4.u32 [%0], {%1,%2,%3,%4};" ::"l"(p), "r"(v.x), "r"(v.y), "r"(v.z), "r"(v.w) : "memory");
}
__device__ __forceinline__ void stsm4(uint32_t a, uint32_t r0, uint32_t r1, uint32_t r2, uint32_t r3) {
    asm volatile("stmatrix.sync.aligned.m8n8.x4.shared.b16 [%0], {%1,%2,%3,%4};" ::"r"(a), "r"(r0), "r"(r1), "r"(r2), "r"(r3) : "memory");
}
__device__ __forceinline__ void mma16816(float (&d)[4], uint32_t a0, uint32_t a1, uint32_t a2, uint32_t a3, uint32_t b0, uint32_t b1) {
    asm("mma.sync.aligned.m16n8k16.row.col.f32.bf16.bf16.f32 {%0,%1,%2,%3},{%4,%5,%6,%7},{%8,%9},{%0,%1,%2,%3};"
                 : "+f"(d[0]), "+f"(d[1]), "+f"(d[2]), "+f"(d[3])
                 : "r"(a0), "r"(a1), "r"(a2), "r"(a3), "r"(b0), "r"(b1));
}
__device__ __forceinline__ void mma1688(float (&d)[4], uint32_t a0, uint32_t a1, uint32_t b0) {
    asm("mma.sync.aligned.m16n8k8.row.col.f32.bf16.bf16.f32 {%0,%1,%2,%3},{%4,%5},{%6},{%0,%1,%2,%3};"
        : "+f"(d[0]), "+f"(d[1]), "+f"(d[2]), "+f"(d[3]) : "r"(a0), "r"(a1), "r"(b0));
}
__device__ __forceinline__ uint32_t movmat(uint32_t a) {
    uint32_t d;
    asm volatile("movmatrix.sync.aligned.m8n8.trans.b16 %0, %1;" : "=r"(d) : "r"(a));
    return d;
}
__device__ __forceinline__ uint32_t pack_bf16(float lo, float hi) {
    uint32_t r;
    asm("cvt.rn.bf16x2.f32 %0, %1, %2;" : "=r"(r) : "f"(hi), "f"(lo));
    return r;
}
__device__ __forceinline__ float bf16_round(float x) { return __bfloat162float(__float2bfloat16_rn(x)); }
__device__ __forceinline__ float bf_lo(uint32_t w) { return __uint_as_float(w << 16); }
__device__ __forceinline__ float bf_hi(uint32_t w) { return __uint_as_float(w & 0xFFFF0000u); }
__device__ __forceinline__ void bar_sync(int id, int n) { asm volatile("bar.sync %0, %1;" ::"r"(id), "r"(n) : "memory"); }
__device__ __forceinline__ void bar_sync_keep(int id, int n, uint32_t a, uint32_t b) {
    asm volatile("bar.sync %0, %1; // %2 %3" ::"r"(id), "r"(n), "r"(a), "r"(b) : "memory");
}
__device__ __forceinline__ bool bar_red_or(int id, int n, bool p) {
    uint32_t r;
    asm volatile("{.reg .pred p, q; setp.ne.u32 p, %3, 0; bar.red.or.pred q, %1, %2, p; selp.u32 %0, 1, 0, q;}" : "=r"(r) : "r"(id), "r"(n), "r"((uint32_t)p) : "memory");
    return r != 0;
}
__device__ __forceinline__ void bar_arrive(int id, int n) { asm volatile("bar.arrive %0, %1;" ::"r"(id), "r"(n) : "memory"); }
__device__ __forceinline__ void cp_async16(uint32_t dst, const void* src) {
    asm volatile("cp.async.cg.shared.global [%0], [%1], 16;" ::"r"(dst), "l"(src) : "memory");
}
__device__ __forceinline__ void cp_commit() { asm volatile("cp.async.commit_group;" ::: "memory"); }
template <int N> __device__ __forceinline__ void cp_wait() { asm volatile("cp.async.wait_group %0;" ::"n"(N) : "memory"); }
__device__ __forceinline__ uint4 ld_relaxed_v4(const void* p) {
    uint4 v;
    asm volatile("ld.relaxed.gpu.global.v4.u32 {%0,%1,%2,%3}, [%4];" : "=r"(v.x), "=r"(v.y), "=r"(v.z), "=r"(v.w) : "l"(p) : "memory");
    return v;
}
__device__ __forceinline__ void st_relaxed_u32(void* p, uint32_t v) { asm volatile("st.relaxed.gpu.global.u32 [%0], %1;" ::"l"(p), "r"(v) : "memory"); }
__device__ __forceinline__ void st_relaxed_v2(void* p, uint32_t a, uint32_t b) {
    asm volatile("st.relaxed.gpu.global.v2.u32 [%0], {%1,%2};" ::"l"(p), "r"(a), "r"(b) : "memory");
}
__device__ __forceinline__ void sts128(uint32_t a, uint4 v) {
    asm volatile("st.shared.v4.u32 [%0], {%1,%2,%3,%4};" ::"r"(a), "r"(v.x), "r"(v.y), "r"(v.z), "r"(v.w) : "memory");
}
__device__ __forceinline__ uint4 lds128(uint32_t a) {
    uint4 v;
    asm volatile("ld.shared.v4.u32 {%0,%1,%2,%3}, [%4];" : "=r"(v.x), "=r"(v.y), "=r"(v.z), "=r"(v.w) : "r"(a) : "memory");
    return v;
}
__device__ __forceinline__ void sts32(uint32_t a, uint32_t v) { asm volatile("st.shared.u32 [%0], %1;" ::"r"(a), "r"(v) : "memory"); }
__device__ __forceinline__ uint32_t lds32(uint32_t a) {
    uint32_t v;
    asm volatile("ld.shared.u32 %0, [%1];" : "=r"(v) : "r"(a) : "memory");
    return v;
}
__device__ __forceinline__ void mbar_init(uint32_t a, uint32_t c) { asm volatile("mbarrier.init.shared::cta.b64 [%0], %1;" ::"r"(a), "r"(c) : "memory"); }
__device__ __forceinline__ void mbar_expect_tx(uint32_t a, uint32_t bytes) {
    asm volatile("mbarrier.arrive.expect_tx.shared::cta.b64 _, [%0], %1;" ::"r"(a), "r"(bytes) : "memory");
}
__device__ __forceinline__ void mbar_arrive(uint32_t a) { asm volatile("mbarrier.arrive.shared::cta.b64 _, [%0];" ::"r"(a) : "memory"); }
__device__ __forceinline__ void mbar_wait(uint32_t a, uint32_t parity) {
    asm volatile("{.reg .pred p; .reg .u32 c;\n"
                 "mov.u32 c, 0;\n"
                 "MBW_LOOP:\n"
                 "add.u32 c, c, 1;\n"
                 "setp.gt.u32 p, c, 0x10000;\n"
                 "@!p mbarrier.try_wait.parity.shared::cta.b64 p, [%0], %1;\n"
                 "@!p bra.uni MBW_LOOP;}" ::"r"(a), "r"(parity) : "memory");
}
__device__ __forceinline__ void mbar_wait_w(uint32_t a, uint32_t parity) {
    asm volatile("{.reg .pred p; .reg .u32 c;\n"
                 "mov.u32 c, 0;\n"
                 "MBW_LOOP:\n"
                 "add.u32 c, c, 1;\n"
                 "setp.gt.u32 p, c, 0x10000;\n"
                 "@!p mbarrier.try_wait.parity.shared::cta.b64 p, [%0], %1;\n"
                 "vote.sync.all.pred p, p, 0xFFFFFFFF;\n"
                 "@!p bra.uni MBW_LOOP;}" ::"r"(a), "r"(parity) : "memory");
}
__device__ __forceinline__ void mbar_expect_tx_if0(uint32_t sel, uint32_t a, uint32_t bytes) {
    asm volatile("{.reg .pred p; setp.eq.u32 p, %2, 0; @p mbarrier.arrive.expect_tx.shared::cta.b64 _, [%0], %1;}" ::"r"(a), "r"(bytes), "r"(sel) : "memory");
}
__device__ __forceinline__ void mbar_arrive_if0(uint32_t sel, uint32_t a) {
    asm volatile("{.reg .pred p; setp.eq.u32 p, %1, 0; @p mbarrier.arrive.shared::cta.b64 _, [%0];}" ::"r"(a), "r"(sel) : "memory");
}
__device__ __forceinline__ void bulk_load(uint32_t dst, const void* src, uint32_t bytes, uint32_t bar) {
    asm volatile("cp.async.bulk.shared::cluster.global.mbarrier::complete_tx::bytes [%0], [%1], %2, [%3];" ::"r"(dst), "l"(src), "r"(bytes), "r"(bar) : "memory");
}
__device__ __forceinline__ void tma_load_2d(uint32_t dst, const CUtensorMap* map, int c0, int c1, uint32_t bar) {
    asm volatile("cp.async.bulk.tensor.2d.shared::cluster.global.mbarrier::complete_tx::bytes [%0], [%1, {%3, %4}], [%2];"
                 ::"r"(dst), "l"(map), "r"(bar), "r"(c0), "r"(c1) : "memory");
}
__device__ __forceinline__ uint64_t policy_evict_first() {
    uint64_t p;
    asm("createpolicy.fractional.L2::evict_first.b64 %0, 1.0;" : "=l"(p));
    return p;
}
__device__ __forceinline__ uint64_t policy_evict_normal() {
    uint64_t p;
    asm("createpolicy.fractional.L2::evict_normal.b64 %0, 1.0;" : "=l"(p));
    return p;
}
__device__ __forceinline__ void tma_load_2d(uint32_t dst, const CUtensorMap* map, int c0, int c1, uint32_t bar, uint64_t pol) {
    asm volatile("cp.async.bulk.tensor.2d.shared::cluster.global.mbarrier::complete_tx::bytes.L2::cache_hint [%0], [%1, {%3, %4}], [%2], %5;"
                 ::"r"(dst), "l"(map), "r"(bar), "r"(c0), "r"(c1), "l"(pol) : "memory");
}
__device__ __forceinline__ uint4 ldg128(const void* p, uint64_t pol) {
    uint4 v;
    asm("ld.global.nc.L2::cache_hint.v4.u32 {%0,%1,%2,%3}, [%4], %5;" : "=r"(v.x), "=r"(v.y), "=r"(v.z), "=r"(v.w) : "l"(p), "l"(pol));
    return v;
}
__device__ __forceinline__ void stg128(void* p, uint4 v, uint64_t pol) {
    asm volatile("st.global.L2::cache_hint.v4.u32 [%0], {%1,%2,%3,%4}, %5;" ::"l"(p), "r"(v.x), "r"(v.y), "r"(v.z), "r"(v.w), "l"(pol) : "memory");
}
__device__ __forceinline__ void tma_store_2d(const CUtensorMap* map, uint32_t src, int c0, int c1) {
    asm volatile("cp.async.bulk.tensor.2d.global.shared::cta.bulk_group [%0, {%2, %3}], [%1];" ::"l"(map), "r"(src), "r"(c0), "r"(c1) : "memory");
}
__device__ __forceinline__ char* make_ptr(uint32_t lo, uint32_t hi) {
    uint64_t p;
    asm("mov.b64 %0, {%1, %2};" : "=l"(p) : "r"(lo), "r"(hi));
    return reinterpret_cast<char*>(p);
}
__device__ __forceinline__ uint64_t make_desc(uint32_t saddr, uint32_t lbo, uint32_t sbo) {
    return (uint64_t)((saddr & 0x3FFFF) >> 4) | ((uint64_t)((lbo >> 4) & 0x3FFF) << 16) | ((uint64_t)((sbo >> 4) & 0x3FFF) << 32) | ((uint64_t)1 << 62);
}
__device__ __forceinline__ void wg_fence() { asm volatile("wgmma.fence.sync.aligned;" ::: "memory"); }
__device__ __forceinline__ void wg_commit() { asm volatile("wgmma.commit_group.sync.aligned;" ::: "memory"); }
template <int N> __device__ __forceinline__ void wg_wait() { asm volatile("wgmma.wait_group.sync.aligned %0;" ::"n"(N) : "memory"); }

#define R4(b) "+f"(d[b + 0]), "+f"(d[b + 1]), "+f"(d[b + 2]), "+f"(d[b + 3])
#define R16(b) R4(b), R4(b + 4), R4(b + 8), R4(b + 12)
__device__ __forceinline__ void wgmma_n128(float (&d)[64], uint64_t da, uint64_t db) {
    asm volatile(
        "wgmma.mma_async.sync.aligned.m64n128k16.f32.bf16.bf16 "
        "{%0,%1,%2,%3,%4,%5,%6,%7,%8,%9,%10,%11,%12,%13,%14,%15,%16,%17,%18,%19,%20,%21,%22,%23,%24,%25,%26,%27,%28,%29,%30,%31,"
        "%32,%33,%34,%35,%36,%37,%38,%39,%40,%41,%42,%43,%44,%45,%46,%47,%48,%49,%50,%51,%52,%53,%54,%55,%56,%57,%58,%59,%60,%61,%62,%63},"
        "%64,%65,1,1,1,0,1;"
        : R16(0), R16(16), R16(32), R16(48)
        : "l"(da), "l"(db));
}
__device__ __forceinline__ void wgmma_n256(float (&d)[128], uint64_t da, uint64_t db) {
    asm volatile(
        "wgmma.mma_async.sync.aligned.m64n256k16.f32.bf16.bf16 "
        "{%0,%1,%2,%3,%4,%5,%6,%7,%8,%9,%10,%11,%12,%13,%14,%15,%16,%17,%18,%19,%20,%21,%22,%23,%24,%25,%26,%27,%28,%29,%30,%31,"
        "%32,%33,%34,%35,%36,%37,%38,%39,%40,%41,%42,%43,%44,%45,%46,%47,%48,%49,%50,%51,%52,%53,%54,%55,%56,%57,%58,%59,%60,%61,%62,%63,"
        "%64,%65,%66,%67,%68,%69,%70,%71,%72,%73,%74,%75,%76,%77,%78,%79,%80,%81,%82,%83,%84,%85,%86,%87,%88,%89,%90,%91,%92,%93,%94,%95,"
        "%96,%97,%98,%99,%100,%101,%102,%103,%104,%105,%106,%107,%108,%109,%110,%111,%112,%113,%114,%115,%116,%117,%118,%119,%120,%121,%122,%123,%124,%125,%126,%127},"
        "%128,%129,1,1,1,0,1;"
        : R16(0), R16(16), R16(32), R16(48), R16(64), R16(80), R16(96), R16(112)
        : "l"(da), "l"(db));
}
template <int BN> struct WgAcc;
template <> struct WgAcc<128> { static __device__ __forceinline__ void mma(float (&d)[64], uint64_t a, uint64_t b) { wgmma_n128(d, a, b); } };
template <> struct WgAcc<256> { static __device__ __forceinline__ void mma(float (&d)[128], uint64_t a, uint64_t b) { wgmma_n256(d, a, b); } };

__device__ __forceinline__ void wgmma_rs32(float (&d)[16], const uint32_t (&a)[4], uint64_t db, bool acc) {
    asm volatile(
        "{.reg .pred p; setp.ne.b32 p, %21, 0;\n"
        "wgmma.mma_async.sync.aligned.m64n32k16.f32.bf16.bf16 {%0,%1,%2,%3,%4,%5,%6,%7,%8,%9,%10,%11,%12,%13,%14,%15}, {%16,%17,%18,%19}, %20, p, 1, 1, 0;}"
        : R16(0) : "r"(a[0]), "r"(a[1]), "r"(a[2]), "r"(a[3]), "l"(db), "n"(1) );
}
__device__ __forceinline__ void wgmma_rs32_first(float (&d)[16], const uint32_t (&a)[4], uint64_t db) {
    asm volatile(
        "{.reg .pred p; setp.ne.b32 p, %21, 0;\n"
        "wgmma.mma_async.sync.aligned.m64n32k16.f32.bf16.bf16 {%0,%1,%2,%3,%4,%5,%6,%7,%8,%9,%10,%11,%12,%13,%14,%15}, {%16,%17,%18,%19}, %20, p, 1, 1, 0;}"
        : R16(0) : "r"(a[0]), "r"(a[1]), "r"(a[2]), "r"(a[3]), "l"(db), "n"(0) );
}
__device__ __forceinline__ void wgmma_ss32(float (&d)[16], uint64_t da, uint64_t db) {
    asm volatile(
        "wgmma.mma_async.sync.aligned.m64n32k16.f32.bf16.bf16 {%0,%1,%2,%3,%4,%5,%6,%7,%8,%9,%10,%11,%12,%13,%14,%15}, %16, %17, 1, 1, 1, 1, 0;"
        : R16(0) : "l"(da), "l"(db));
}
template <int OFF, int ACC> __device__ __forceinline__ void wgmma_rs32u(float (&d)[16], const uint32_t (&a)[4], uint32_t lo) {
    asm volatile(
        "{.reg .pred p; .reg .b32 l; .reg .b64 e; setp.ne.b32 p, %22, 0; add.u32 l, %20, %21; mov.b64 e, {l, 0x40000040};\n"
        "wgmma.mma_async.sync.aligned.m64n32k16.f32.bf16.bf16 {%0,%1,%2,%3,%4,%5,%6,%7,%8,%9,%10,%11,%12,%13,%14,%15}, {%16,%17,%18,%19}, e, p, 1, 1, 0;}"
        : R16(0) : "r"(a[0]), "r"(a[1]), "r"(a[2]), "r"(a[3]), "r"(lo), "n"(OFF), "n"(ACC));
}
template <int OFF> __device__ __forceinline__ void wgmma_ss32u(float (&d)[16], uint64_t da, uint32_t lo) {
    asm volatile(
        "{.reg .b32 l; .reg .b64 e; add.u32 l, %17, %18; mov.b64 e, {l, 0x40000040};\n"
        "wgmma.mma_async.sync.aligned.m64n32k16.f32.bf16.bf16 {%0,%1,%2,%3,%4,%5,%6,%7,%8,%9,%10,%11,%12,%13,%14,%15}, %16, e, 1, 1, 1, 1, 0;}"
        : R16(0) : "l"(da), "r"(lo), "n"(OFF));
}
template <int K0, int K1, class F> __device__ __forceinline__ void static_for(F f) {
    if constexpr (K0 < K1) { f(std::integral_constant<int, K0>()); static_for<K0 + 1, K1>(f); }
}
__device__ __forceinline__ void st_async4(uint32_t a, float x, float y, float z, float w, uint32_t bar) {
    asm volatile("st.async.weak.shared::cluster.mbarrier::complete_tx::bytes.v4.f32 [%0], {%1,%2,%3,%4}, [%5];" ::"r"(a), "f"(x), "f"(y), "f"(z), "f"(w), "r"(bar) : "memory");
}
__device__ __forceinline__ void st_async2(uint32_t a, float x, float y, uint32_t bar) {
    asm volatile("st.async.weak.shared::cluster.mbarrier::complete_tx::bytes.v2.f32 [%0], {%1,%2}, [%3];" ::"r"(a), "f"(x), "f"(y), "r"(bar) : "memory");
}
__device__ __forceinline__ void st_async1(uint32_t a, uint32_t x, uint32_t bar) {
    asm volatile("st.async.weak.shared::cluster.mbarrier::complete_tx::bytes.b32 [%0], %1, [%2];" ::"r"(a), "r"(x), "r"(bar) : "memory");
}
__device__ __forceinline__ void stsm4t(uint32_t a, uint32_t r0, uint32_t r1, uint32_t r2, uint32_t r3) {
    asm volatile("stmatrix.sync.aligned.m8n8.x4.trans.shared.b16 [%0], {%1,%2,%3,%4};" ::"r"(a), "r"(r0), "r"(r1), "r"(r2), "r"(r3) : "memory");
}
__device__ __forceinline__ void ldsm4t(uint32_t (&r)[4], uint32_t a) { ldsm4t(r[0], r[1], r[2], r[3], a); }
__device__ __forceinline__ void ldsm4(uint32_t (&r)[4], uint32_t a) { ldsm4(r[0], r[1], r[2], r[3], a); }
__device__ __forceinline__ void mma16816(float (&d)[4], const uint32_t (&a)[4], uint32_t b0, uint32_t b1) { mma16816(d, a[0], a[1], a[2], a[3], b0, b1); }
__device__ __forceinline__ void sched_fence(uint32_t v) {
    asm volatile("{.reg .pred p; setp.ne.u32 p, %0, 0xFFFFFFFF; vote.sync.all.pred p, p, 0xFFFFFFFF; @p bra.uni SF_OK; exit; SF_OK:}" ::"r"(v) : "memory");
}
__device__ __forceinline__ void mma16816v(float (&d)[4], const uint32_t (&a)[4], uint32_t b0, uint32_t b1) {
    asm volatile("mma.sync.aligned.m16n8k16.row.col.f32.bf16.bf16.f32 {%0,%1,%2,%3},{%4,%5,%6,%7},{%8,%9},{%0,%1,%2,%3};"
                 : "+f"(d[0]), "+f"(d[1]), "+f"(d[2]), "+f"(d[3]) : "r"(a[0]), "r"(a[1]), "r"(a[2]), "r"(a[3]), "r"(b0), "r"(b1));
}
__device__ __forceinline__ uint32_t uniform(uint32_t v) { return __reduce_max_sync(~0u, v); }

template <int BN, int STAGES> struct GemmCfg {
    static constexpr int A_BYTES = 128 * 64 * 2;
    static constexpr int B_BYTES = BN * 64 * 2;
    static constexpr int STAGE_BYTES = A_BYTES + B_BYTES;
    static constexpr int EPI_BYTES = 128 * BN * 2;
    static constexpr int SMEM = STAGES * STAGE_BYTES + EPI_BYTES + 1024 + 256;
};

template <int BN, int STAGES>
__global__ void __cluster_dims__(2, 1, 1) __launch_bounds__(288, 1)
gemm_kernel(const __grid_constant__ CUtensorMap mapA, const __grid_constant__ CUtensorMap mapB0, const __grid_constant__ CUtensorMap mapB1,
            const __grid_constant__ CUtensorMap mapB2, const __grid_constant__ CUtensorMap mapC, int tiles_m, int tiles_n, int kblocks) {
    using Cfg = GemmCfg<BN, STAGES>;
    KT_START(BN == 256 ? 0 : 3);
    extern __shared__ uint8_t smem_raw[];
    const uint32_t sbase = (smem_u32(smem_raw) + 1023) & ~1023u;
    const uint32_t epi = sbase + STAGES * Cfg::STAGE_BYTES;
    const uint32_t bars = epi + Cfg::EPI_BYTES;
    const int warp = threadIdx.x >> 5, lane = threadIdx.x & 31;
    const uint32_t rank = blockIdx.x & 1;
    if (threadIdx.x == 0) {
        for (int i = 0; i < STAGES; i++) { mbar_init(bars + 8 * i, 1); mbar_init(bars + 8 * (STAGES + i), 16); }
        asm volatile("fence.mbarrier_init.release.cluster;" ::: "memory");
    }
    __syncthreads();
    asm volatile("barrier.cluster.arrive.release.aligned; barrier.cluster.wait.acquire.aligned;" ::: "memory");
    const int npairs = (tiles_m >> 1) * tiles_n, ncl = gridDim.x >> 1;
    if (warp == 8) {
        if (lane == 0) {
            int st = 0; uint32_t ph = 1;
            for (int pr = blockIdx.x >> 1; pr < npairs; pr += ncl) {
                const int tm = 2 * (pr % (tiles_m >> 1)) + rank, tn = pr / (tiles_m >> 1);
                const int n0 = tn * BN;
                const CUtensorMap* mb = (n0 < 4096) ? &mapB0 : (n0 < 8192 ? &mapB1 : &mapB2);
                const int nb = n0 & 4095;
                for (int kb = 0; kb < kblocks; kb++) {
                    mbar_wait(bars + 8 * (STAGES + st), ph);
                    const uint32_t full = bars + 8 * st;
                    mbar_expect_tx(full, Cfg::STAGE_BYTES);
                    const uint32_t sa = sbase + st * Cfg::STAGE_BYTES;
                    tma_load_2d(sa, &mapA, kb * 64, tm * 128, full);
#pragma unroll
                    for (int i = 0; i < BN / 128; i++) {
                        const int bx = rank * (BN / 128) + i;
                        asm volatile("cp.async.bulk.tensor.2d.shared::cluster.global.mbarrier::complete_tx::bytes.multicast::cluster [%0], [%1, {%3, %4}], [%2], %5;"
                                     ::"r"(sa + Cfg::A_BYTES + bx * 8192), "l"(mb), "r"(full), "r"(nb + bx * 64), "r"(kb * 64), "h"((uint16_t)3) : "memory");
                    }
                    if (++st == STAGES) { st = 0; ph ^= 1; }
                }
            }
        }
    } else {
        const int wg = warp >> 2;
        uint32_t peer_empty;
        asm volatile("mapa.shared::cluster.u32 %0, %1, %2;" : "=r"(peer_empty) : "r"(bars + 8 * STAGES), "r"(rank ^ 1));
        auto release = [&](int stg) {
            if (lane == 0) {
                mbar_arrive(bars + 8 * (STAGES + stg));
                asm volatile("mbarrier.arrive.shared::cluster.b64 _, [%0];" ::"r"(peer_empty + 8 * stg) : "memory");
            }
        };
        const uint32_t ew = epi + wg * (64 * BN * 2);
        int st = 0; uint32_t ph = 0;
        for (int pr = blockIdx.x >> 1; pr < npairs; pr += ncl) {
            const int tm = 2 * (pr % (tiles_m >> 1)) + rank, tn = pr / (tiles_m >> 1);
            float d[BN / 2];
#pragma unroll
            for (int i = 0; i < BN / 2; i++) d[i] = 0.f;
            int prev = -1;
            for (int kb = 0; kb < kblocks; kb++) {
                mbar_wait(bars + 8 * st, ph);
                const uint32_t sa = sbase + st * Cfg::STAGE_BYTES;
                const uint64_t da = make_desc(sa + wg * 8192, 16, 1024);
                const uint64_t db = make_desc(sa + Cfg::A_BYTES, 8192, 1024);
                wg_fence();
#pragma unroll
                for (int k = 0; k < 4; k++) WgAcc<BN>::mma(d, da + k * 2, db + k * 128);
                wg_commit();
                if (prev >= 0) { wg_wait<1>(); release(prev); }
                prev = st;
                if (++st == STAGES) { st = 0; ph ^= 1; }
            }
            wg_wait<0>();
            release(prev);
            if ((warp & 3) == 0 && lane == 0) asm volatile("cp.async.bulk.wait_group.read 0;" ::: "memory");
            bar_sync(1 + wg, 128);
            const int r = (warp & 3) * 16 + (lane & 7) + ((lane >> 3) & 1) * 8;
#pragma unroll
            for (int c = 0; c < BN / 64; c++)
#pragma unroll
                for (int i = 0; i < 4; i++) {
                    const int b = (c * 8 + i * 2) * 4;
                    stsm4(ew + c * 8192 + r * 128 + (((i * 2 + (lane >> 4)) ^ (r & 7)) * 16), pack_bf16(d[b], d[b + 1]), pack_bf16(d[b + 2], d[b + 3]),
                          pack_bf16(d[b + 4], d[b + 5]), pack_bf16(d[b + 6], d[b + 7]));
                }
            asm volatile("fence.proxy.async.shared::cta;" ::: "memory");
            bar_sync(1 + wg, 128);
            if ((warp & 3) == 0 && lane == 0) {
#pragma unroll
                for (int c = 0; c < BN / 64; c++)
                    asm volatile("cp.async.bulk.tensor.2d.global.shared::cta.bulk_group [%0, {%2, %3}], [%1];"
                                 ::"l"(&mapC), "r"(ew + c * 8192), "r"(tn * BN + c * 64), "r"(tm * 128 + wg * 64) : "memory");
                asm volatile("cp.async.bulk.commit_group;" ::: "memory");
            }
        }
        if ((warp & 3) == 0 && lane == 0) asm volatile("cp.async.bulk.wait_group 0;" ::: "memory");
    }
    __syncwarp();
    KT_END(BN == 256 ? 0 : 3);
    asm volatile("barrier.cluster.arrive.relaxed; barrier.cluster.wait;" ::: "memory");
}

#define WO_RF1 6
constexpr int SM_KV = 0, KV_BYTES = 18432;
constexpr int SM_XT = 2 * KV_BYTES;
constexpr int SM_STG = SM_XT + 65536;
constexpr int SM_Z = SM_STG + 6144;
constexpr int SM_RT = SM_Z + 8192;
constexpr int SM_QKV = SM_RT + 12288;
constexpr int SM_R1 = SM_QKV + 6144;
constexpr int SM_R2 = SM_R1 + 2048;
constexpr int SM_R3 = SM_R2 + 1024;
constexpr int SM_O = SM_R3 + 2048;
constexpr int SM_S = SM_O + 2048;
constexpr int SM_INV = SM_S + 1536;
constexpr int SM_TO = SM_R3;
constexpr int SM_WORK_END = SM_S + 2048;
constexpr int STG_QK = 0, STG_V = 98304;
constexpr int SM_WO1 = SM_WORK_END - WO_RF1 * 2048;
constexpr int STG_WO = SM_WO1 - 16384;
constexpr int SM_WQK = (SM_WO1 + 16384 > STG_V + 49152) ? SM_WO1 + 16384 : STG_V + 49152;
constexpr int SM_WV = SM_WQK + 32768;
constexpr int SM_WO2 = SM_WV + 16384;
constexpr int SM_BARS = SM_WO2 + 32768;
enum { MB_W0 = SM_BARS, MB_W1 = SM_BARS + 8, MB_W2 = SM_BARS + 16, MB_W3 = SM_BARS + 24, MB_XT = SM_BARS + 32  , MB_KV = SM_BARS + 48  ,
       MB_R3 = SM_BARS + 64, MB_R1 = SM_BARS + 72, MB_R2 = SM_BARS + 80, MB_RT0 = SM_BARS + 88, MB_RT1 = SM_BARS + 96, MB_FREE = SM_BARS + 104,
       MB_P = SM_BARS + 112, MB_V = SM_BARS + 120, MB_STG = SM_BARS + 128, SM_ROLE = SM_BARS + 136 };
constexpr int CHAIN_SMEM = SM_ROLE + 8;
static_assert(SM_WORK_END % 1024 == 0 && STG_WO >= STG_V, "work area");
static_assert(CHAIN_SMEM <= 232448 && WO_RF1 >= 6, "smem");

#define DLY_X 300
#define DLY_V 0
#define DLY_Y 150
#define DLY_Z 150
#define Q3_AT 9
#define NA 7
#define NP2 6
#define P2_FENCE 0
#define SPLIT 12
#define EF_W 1
#define XFLIP 0
#define YFLIP 0
#define ZFLIP 1
#define REG_A 240
#define REG_B 216
#define REG_C (3 * 168 - REG_A - REG_B)

enum { BAR_Y, BAR_MEM, BAR_PUB, BAR_QK, BAR_S, BAR_O, BAR_SENT, BAR_COMM, BAR_PUBV, BAR_PV, BAR_PDONE, BAR_VP, BAR_ZP, BAR_PRO, BAR_O2, BAR_SV,
       BAR_V = BAR_PV, BAR_SENTC = BAR_PDONE, BAR_Q3 = BAR_PRO, BAR_INV = BAR_PRO };

__device__ __forceinline__ uint32_t umax4(const uint4& v) { return max(max(v.x, v.y), max(v.z, v.w)); }
__device__ __forceinline__ unsigned gtime() { unsigned t; asm volatile("mov.u32 %0, %%globaltimer_lo;" : "=r"(t)::"memory"); return t; }
__device__ __forceinline__ unsigned clock32() { unsigned t; asm volatile("mov.u32 %0, %%clock;" : "=r"(t)::"memory"); return t; }
__device__ __forceinline__ void spin_cycles(int d) {
    if (d > 0) { const unsigned c0 = clock32(); while (clock32() - c0 < (unsigned)d) {} }
}
__device__ __forceinline__ float ex2_approx(float x) { float y; asm("ex2.approx.ftz.f32 %0, %1;" : "=f"(y) : "f"(x)); return y; }
__device__ __forceinline__ float rcp_approx(float x) { float y; asm("rcp.approx.ftz.f32 %0, %1;" : "=f"(y) : "f"(x)); return y; }
__device__ __forceinline__ void st_sent(const void* p) { asm volatile("st.relaxed.gpu.global.v4.u32 [%0], {%1,%1,%1,%1};" ::"l"(p), "r"(SENT) : "memory"); }
#define POLL_LD(p, a, b, c, d, addr) "@" p " ld.relaxed.gpu.global.v4.u32 {" a "," b "," c "," d "}, [" addr "];\n"
#define POLL_CK(p, a, b, c, d) "max.u32 m, " a "," b "; max.u32 n, " c "," d "; max.u32 m, m, n; setp.eq.u32 " p ", m, 0xFFFFFFFF;\n"
#define POLL_IO(v) "+r"(v.x), "+r"(v.y), "+r"(v.z), "+r"(v.w)
__device__ __forceinline__ void poll_init(uint4& v) { v = make_uint4(SENT, SENT, SENT, SENT); asm volatile("" : POLL_IO(v)); }
__device__ __forceinline__ int poll2(uint4 (&v)[2], const char* a) {
    int c = 0;
    asm volatile("{.reg .pred p0, p1, p; .reg .u32 m, n;\n"
                 "setp.eq.u32 p0, %8, 0; setp.eq.u32 p1, %8, 0;\n"
                 "POLL_LOOP:\n"
                 POLL_LD("p0", "%0", "%1", "%2", "%3", "%9") POLL_LD("p1", "%4", "%5", "%6", "%7", "%9+512")
                 "add.u32 %8, %8, 1;\n"
                 POLL_CK("p0", "%0", "%1", "%2", "%3") POLL_CK("p1", "%4", "%5", "%6", "%7")
                 "or.pred p, p0, p1; setp.lt.and.u32 p, %8, 0x10000, p; vote.sync.any.pred p, p, 0xFFFFFFFF;\n"
                 "@p bra.uni POLL_LOOP;}" : POLL_IO(v[0]), POLL_IO(v[1]), "+r"(c) : "l"(a) : "memory");
    return c;
}
__device__ __forceinline__ int poll4(uint4 (&v)[4], const char* a) {
    int c = 0;
    asm volatile("{.reg .pred p0, p1, p2, p3, p; .reg .u32 m, n;\n"
                 "setp.eq.u32 p0, %16, 0; setp.eq.u32 p1, %16, 0; setp.eq.u32 p2, %16, 0; setp.eq.u32 p3, %16, 0;\n"
                 "POLL_LOOP:\n"
                 POLL_LD("p0", "%0", "%1", "%2", "%3", "%17") POLL_LD("p1", "%4", "%5", "%6", "%7", "%17+2048")
                 POLL_LD("p2", "%8", "%9", "%10", "%11", "%17+4096") POLL_LD("p3", "%12", "%13", "%14", "%15", "%17+6144")
                 "add.u32 %16, %16, 1;\n"
                 POLL_CK("p0", "%0", "%1", "%2", "%3") POLL_CK("p1", "%4", "%5", "%6", "%7") POLL_CK("p2", "%8", "%9", "%10", "%11") POLL_CK("p3", "%12", "%13", "%14", "%15")
                 "or.pred p, p0, p1; or.pred p, p, p2; or.pred p, p, p3; setp.lt.and.u32 p, %16, 0x10000, p; vote.sync.any.pred p, p, 0xFFFFFFFF;\n"
                 "@p bra.uni POLL_LOOP;}" : POLL_IO(v[0]), POLL_IO(v[1]), POLL_IO(v[2]), POLL_IO(v[3]), "+r"(c) : "l"(a) : "memory");
    return c;
}
__device__ __forceinline__ uint32_t max_bf16x2(uint32_t a, uint32_t b) { uint32_t r; asm("max.bf16x2 %0, %1, %2;" : "=r"(r) : "r"(a), "r"(b)); return r; }
template <class F> __device__ __forceinline__ void softmax40(uint32_t (&pw)[6], uint32_t sa, F mid) {
    const float LOG2E = 1.4426950408889634f;
    uint32_t w[5];
    float e[10];
#pragma unroll
    for (int i = 0; i < 5; i++) w[i] = lds32(sa + i * 128);
    uint32_t m = max_bf16x2(max_bf16x2(max_bf16x2(w[0], w[1]), max_bf16x2(w[2], w[3])), w[4]);
    m = max_bf16x2(m, __shfl_xor_sync(~0u, m, 1));
    m = max_bf16x2(m, __shfl_xor_sync(~0u, m, 2));
    const float mb2 = fmaxf(bf_lo(m), bf_hi(m)) * LOG2E;
#pragma unroll
    for (int i = 0; i < 5; i++) {
        e[2 * i] = ex2_approx(fmaf(bf_lo(w[i]), LOG2E, -mb2));
        e[2 * i + 1] = ex2_approx(fmaf(bf_hi(w[i]), LOG2E, -mb2));
    }
    mid();
#pragma unroll
    for (int i = 0; i < 5; i++) pw[i] = pack_bf16(e[2 * i], e[2 * i + 1]);
    const float sum = (((e[0] + e[1]) + (e[2] + e[3])) + ((e[4] + e[5]) + (e[6] + e[7]))) + (e[8] + e[9]);
    const float hi = bf_hi(__float_as_uint(sum));
    pw[5] = pack_bf16(sum - hi, hi);
}
template <bool NORM, class F> __device__ __forceinline__ void pv32(uint32_t (&w)[4], float (&inv)[2], const uint32_t (&va)[2][2][4], const uint32_t (&vm)[4], const uint32_t (&pw)[6], F mid) {
    float o[2][3][4], t[4] = {0.f, 0.f, 0.f, 0.f};
#pragma unroll
    for (int i = 0; i < 3; i++)
#pragma unroll
        for (int m = 0; m < 2; m++) {
            o[m][i][0] = o[m][i][1] = o[m][i][2] = o[m][i][3] = 0.f;
            if (i < 2) mma16816(o[m][i], va[m][i & 1], pw[2 * i], pw[2 * i + 1]);
            else mma1688(o[m][i], vm[2 * m], vm[2 * m + 1], pw[4]);
        }
    mma1688(t, 0x3F803F80u, 0x3F803F80u, pw[5]);
    mid();
    if (NORM) { inv[0] = rcp_approx(t[0]); inv[1] = rcp_approx(t[1]); }
#pragma unroll
    for (int i = 0; i < 4; i++) {
        const float a = (o[i >> 1][0][2 * (i & 1)] + o[i >> 1][1][2 * (i & 1)]) + o[i >> 1][2][2 * (i & 1)];
        const float b = (o[i >> 1][0][2 * (i & 1) + 1] + o[i >> 1][1][2 * (i & 1) + 1]) + o[i >> 1][2][2 * (i & 1) + 1];
        w[i] = NORM ? pack_bf16(a * inv[0], b * inv[1]) : pack_bf16(a, b);
    }
    if (!NORM) { inv[0] = t[0]; inv[1] = t[1]; }
}
__device__ __forceinline__ uint32_t scale_scores(float a, float b) {
    const float scale = 0.08838834764831845f;
    const uint32_t w = pack_bf16(a, b);
    return pack_bf16(bf_lo(w) * scale, bf_hi(w) * scale);
}

__device__ __forceinline__ uint32_t peer_addr(uint32_t a, uint32_t rank) {
    uint32_t r;
    asm("mapa.shared::cluster.u32 %0, %1, %2;" : "=r"(r) : "r"(a), "r"(rank));
    return r;
}

#define TL(i) do {} while (0)
#define TLB(i) do {} while (0)
#define TLC(i) do {} while (0)

__global__ void __cluster_dims__(2, 1, 1) __launch_bounds__(384, 1)
chain_kernel(const __grid_constant__ CUtensorMap mapX, const __grid_constant__ CUtensorMap mapT32, const __grid_constant__ CUtensorMap mapT16,
             const __grid_constant__ CUtensorMap mapTQ, const __grid_constant__ CUtensorMap mapKV,
             const __grid_constant__ CUtensorMap mapWq, const __grid_constant__ CUtensorMap mapWk, const __grid_constant__ CUtensorMap mapWv,
             const __grid_constant__ CUtensorMap mapWo, const bf16* __restrict__ mem0, char* __restrict__ mbox) {
    KT_START(2);
    extern __shared__ __align__(1024) uint8_t smem_chain[];
    constexpr uint32_t SB0 = 1024;
    if (smem_u32(smem_chain) != (SB0 | ((blockIdx.x & 1) << 24))) __trap();
    const int kh = blockIdx.x & 1;
    if (threadIdx.x == 0) {
        const uint32_t sb = smem_u32(smem_chain);
        for (int i = 0; i < 14; i++) mbar_init(sb + SM_BARS + 8 * i, 1);
        mbar_init(sb + MB_P, 4); mbar_init(sb + MB_V, 4); mbar_init(sb + MB_STG, 8);
        asm volatile("fence.mbarrier_init.release.cluster;" ::: "memory");
        if (kh == 0) {
            unsigned smid, ncl = gridDim.x >> 1;
            asm volatile("mov.u32 %0, %%smid;" : "=r"(smid));
            const unsigned r = __vminu2(g_cls[smid], g_cls[smid ^ 1]), c = (r & 0xFFFF) > (r >> 16), i = atomicAdd(&g_reg[c], 1u);
            unsigned p = c * 32 + i;
            if (i >= 32) {
                unsigned n0, n1; int guard = 0;
                do {
                    asm volatile("ld.relaxed.gpu.global.u32 %0, [%1];" : "=r"(n0) : "l"(g_reg) : "memory");
                    asm volatile("ld.relaxed.gpu.global.u32 %0, [%1];" : "=r"(n1) : "l"(g_reg + 1) : "memory");
                } while (n0 + n1 < ncl && ++guard < (1 << 20));
                const unsigned k = (c ? n0 : n1) + i - 32;
                p = k < 32 ? (c ^ 1) * 32 + k : 64;
            }
            p |= g_reg[2] << 8;
            uint32_t ra;
            asm volatile("mapa.shared::cluster.u32 %0, %1, 1;" : "=r"(ra) : "r"(sb + SM_ROLE));
            asm volatile("st.shared::cluster.u32 [%0], %1;" ::"r"(ra), "r"(p) : "memory");
            sts32(sb + SM_ROLE, p);
        }
    }
    __syncthreads();
    asm volatile("barrier.cluster.arrive.release.aligned; barrier.cluster.wait.acquire.aligned;" ::: "memory");
    const uint32_t rw = uniform(lds32(smem_u32(smem_chain) + SM_ROLE));
    const int pair = rw & 255, yflip = (rw >> 8) ^ YFLIP;
    if (pair >= 64) return;
    if (threadIdx.x == 0) KT_MARK(5);
    const int h = pair >> 1, nh = pair & 1, j = 2 * nh + kh, role = 2 * pair + kh;
#define WG_ORDER 0x210
    const int warp = uniform(((WG_ORDER >> (4 * (threadIdx.x >> 7))) & 3) * 4 + ((threadIdx.x >> 5) & 3));
    const uint32_t g = warp & 3, sb = SB0 | (kh << 24), rsb = sb ^ (1u << 24), cls = pair >> 5, kflip = ZFLIP ^ kh;
    const uint32_t mlo = (uint32_t)(uintptr_t)mbox, mhi = (uint32_t)((uintptr_t)mbox >> 32);
    auto lane16 = [&]() {
        uint32_t t;
        asm volatile("mov.u32 %0, %%laneid; shl.b32 %0, %0, 4;" : "=r"(t));
        return t;
    };
#define PHASE(k) uint32_t L; asm volatile("{.reg .u32 t; shr.u32 t, %1, %3; add.u32 %0, %2, t;}" : "=r"(L) : "r"(it), "r"(l16), "n"(8 + (k)))
#define ROWPAT() ((((L << 3) & 0x380) | ((L << 2) & 0x400)) | ((L ^ (L >> 3)) & 0x10) | (L & 0x60))
#define FRAG() (ROWPAT() ^ (g << 5))
#define QFRAG() ((((L >> 1) & 0x80) | (L & 0x70)) + ((L & 0x80) ? SM_KV + 16384 + kvo : SM_QKV))
#define VFRAG() (ROWPAT() ^ ((g & 1) << 6))
#define VBASE() (sb + SM_KV + 8192 + (g >> 1) * 4096 + kvo)
#define XTLO() ((uint32_t)make_desc(SB0 + SM_XT, 16, 1024) + (ui & 1) * 2048)
    if (warp >= 8) {
        asm volatile("setmaxnreg.dec.sync.aligned.u32 %0;" ::"n"(REG_C));
        const uint32_t l16 = lane16(), lane = l16 >> 4;
        const int ct = g * 32 + lane;
        if (warp == 8) {
            const CUtensorMap* ws = kh ? &mapWq : &mapWk;
            const CUtensorMap* wn = kh ? &mapWk : &mapWq;
            const uint64_t pol = EF_W ? policy_evict_first() : policy_evict_normal();
            const int col = h * DH + 64 * nh, row = 512 * kh;
            if (lane == 0) { mbar_expect_tx(sb + MB_W0, 49152); mbar_expect_tx(sb + MB_W1, 98304); mbar_expect_tx(sb + MB_W2, 81920); mbar_expect_tx(sb + MB_W3, 32768); }
            __syncwarp();
            if (lane < 24) {
                const int k = lane ^ (16 * kflip);
                tma_load_2d(sb + STG_V + lane * 2048, &mapWv, col, row + 16 * k, sb + MB_W0, pol);
                tma_load_2d(sb + STG_QK + lane * 2048, ws, col, row + 16 * k, sb + MB_W1, pol);
                tma_load_2d(sb + STG_QK + (24 + lane) * 2048, wn, col, row + 16 * k, sb + MB_W1, pol);
            }
            if (lane < 8) {
                const int k = (24 + lane) ^ (16 * kflip);
                tma_load_2d(sb + SM_WQK + lane * 4096, ws, col, row + 16 * k, sb + MB_W2, pol);
                tma_load_2d(sb + SM_WQK + lane * 4096 + 2048, wn, col, row + 16 * k, sb + MB_W2, pol);
                tma_load_2d(sb + SM_WV + lane * 2048, &mapWv, col, row + 16 * k, sb + MB_W2, pol);
            }
            if (lane < 2) tma_load_2d(sb + SM_WO2 + lane * 16384, &mapWo, 256 * j + 128 + 64 * lane, h * DH, sb + MB_W2, pol);
            __syncwarp();
            bar_sync(BAR_PV, 160);
            if (lane < 2) tma_load_2d(sb + STG_WO + lane * 16384, &mapWo, 256 * j + 64 * lane, h * DH, sb + MB_W3, pol);
            __syncwarp();
        }
        bar_sync(BAR_PDONE, 384);
        KT_MARK(9);
        for (int c = ct; c < 512; c += 128) {
            uint32_t w[4];
#pragma unroll
            for (int r = 0; r < 4; r++) {
                const uint32_t lo = reinterpret_cast<const uint16_t*>(mem0)[(2 * r) * DM + 512 * kh + c], hi = reinterpret_cast<const uint16_t*>(mem0)[(2 * r + 1) * DM + 512 * kh + c];
                w[r] = lo | (hi << 16);
            }
            sts128(sb + SM_Z + (c ^ (256 * kflip)) * 16, make_uint4(w[0], w[1], w[2], w[3]));
        }
        auto load_xt = [&](int seg, int half) {
            const uint32_t bar = sb + MB_XT + (seg & 1) * 8;
            if (half == 0) mbar_expect_tx(bar, 32768);
            asm volatile("cp.async.bulk.tensor.3d.shared::cluster.global.mbarrier::complete_tx::bytes [%0], [%1, {%3, %4, %5}], [%2];"
                         ::"r"(sb + SM_XT + (seg & 1) * 32768 + half * 16384), "l"(&mapX), "r"(bar), "r"(0), "r"(seg * SEG), "r"(8 * kh + 4 * (half ^ kflip)) : "memory");
        };
        auto tok_start = [&](int s) {
            if (lane == 0) {
                if (s > -3 && s + 2 < NSEG) {
                    mbar_wait(sb + MB_STG, (s + 2) & 1);
                    asm volatile("fence.proxy.async.shared::cta;" ::: "memory");
                    const int r = ((s + 2) & 3) * NH + h;
                    tma_store_2d(kh ? &mapT32 : &mapTQ, sb + SM_STG, kh ? 64 * nh : 256 * nh, kh ? r * 96 + 32 : r * 12);
                    tma_store_2d(&mapT16, sb + SM_STG + 4096, 64 * nh, r * 96 + 64 + 16 * kh);
                    asm volatile("cp.async.bulk.commit_group;" ::: "memory");
                }
                if (s + 4 < NSEG) load_xt(s + 4, 0);
                asm volatile("cp.async.bulk.wait_group.read 0;" ::: "memory");
                if (s < 0) {
                    asm volatile("mbarrier.arrive.shared::cluster.b64 _, [%0];" ::"r"(rsb + MB_FREE) : "memory");
                    mbar_wait(sb + MB_FREE, (s + 3) & 1);
                }
            }
            __syncwarp();
        };
        auto tok_mid = [&](int s) {
            if (lane == 0) {
                if (s + 4 < NSEG) load_xt(s + 4, 1);
                if (s > -3 && s + 2 < NSEG) {
                    asm volatile("cp.async.bulk.wait_group 0;" ::: "memory");
                    st_relaxed_u32(g_xflag + role, s + 3);
                }
            }
            __syncwarp();
        };
        auto kv_check = [&](int s) {
            if (s + 1 < NSEG) {
                if (lane < 4) {
                    unsigned f; int guard = 0;
                    do {
                        asm volatile("ld.acquire.gpu.global.u32 %0, [%1];" : "=r"(f) : "l"(g_xflag + h * 4 + lane) : "memory");
                        if (++guard > (1 << 20)) __trap();
                    } while (f <= (unsigned)(s + 1));
                }
                __syncwarp();
                asm volatile("fence.proxy.async.global;" ::: "memory");
            }
        };
        auto kv_load = [&](int s) {
            if (lane == 0 && s + 1 < NSEG) {
                const uint32_t bar = sb + MB_KV + ((s + 1) & 1) * 8, dst = sb + SM_KV + ((s + 1) & 1) * KV_BYTES;
                const int row = (((s + 1) & 3) * NH + h) * 96;
                mbar_expect_tx(bar, KV_BYTES);
                asm volatile("cp.async.bulk.tensor.3d.shared::cluster.global.mbarrier::complete_tx::bytes.multicast::cluster [%0], [%1, {%3, %4, %3}], [%2], %5;"
                             ::"r"(dst + kh * 8192), "l"(&mapKV), "r"(bar), "r"(0), "r"(row + 32 + 32 * kh), "h"((uint16_t)3) : "memory");
                bulk_load(dst + 16384, g_tok + row * DH + j * 1024, 2048, bar);
            }
            __syncwarp();
        };
        if (warp == 9) {
            if (lane == 0) { load_xt(0, 0); load_xt(0, 1); }
#pragma unroll 1
            for (int s = -3; s < 0; s++) { tok_start(s); KT_MARK(13 + s); bar_arrive(BAR_PRO, 288); tok_mid(s); }
        }
        if (warp == 11) { kv_check(-1); kv_load(-1); }
        bar_arrive(BAR_MEM, 384);
        const uint32_t ybox = mlo + page_off(role & 63, cls ^ yflip), xoth = mlo + WIN + page_off((pair & 31) ^ 1, cls ^ XFLIP);
        const uint32_t zline = mlo + WIN + page_off(32 + ((role >> 5) & 1), cls ^ ZFLIP) + (role & 31) * 128, zbox = mlo + WIN + (page_off(32 + kh, 0) & ~4096u);
        const uint32_t xtype = g == 0 ? 2 : (g & 1);
        const uint32_t ydst = (lane >> 3) * 128 + ((lane & 7) ^ (lane >> 3)) * 16, ysrc = lane * 128 + ((2 * g) ^ (lane & 7)) * 16;
#pragma unroll 1
        for (int s = 0; s < NSEG; s++) {
            const uint32_t slot = (s & 3) << 14;
            if (g == 3) {
                kv_check(s);
                const uint32_t L = l16, kvo = (s & 1) * KV_BYTES, qa = QFRAG(), sa = sb + SM_S + 512 + (L >> 2);
                float sc[4] = {0.f, 0.f, 0.f, 0.f}, sd[4] = {0.f, 0.f, 0.f, 0.f};
                uint32_t a[4][4], kb[2][4];
                mbar_wait_w(sb + MB_KV + (s & 1) * 8, (s >> 1) & 1);
                mbar_wait_w(sb + MB_P, s & 1);
#pragma unroll
                for (int c = 0; c < 2; c++) {
                    const uint32_t qc = qa + (sb + (nh ^ c) * 1024), kc = L + (sb + SM_QKV + 2048 + (nh ^ c) * 1024);
                    if (c) bar_sync(BAR_QK, 224);
                    ldsm4t(kb[0], kc); ldsm4t(a[0], qc); ldsm4t(a[1], qc + 256);
                    ldsm4t(kb[1], kc + 512); ldsm4t(a[2], qc + 512); ldsm4t(a[3], qc + 768);
                    mma16816v(sc, a[0], kb[0][0], kb[0][1]);
                    mma16816v(sd, a[1], kb[0][2], kb[0][3]);
                    mma16816v(sc, a[2], kb[1][0], kb[1][1]);
                    mma16816v(sd, a[3], kb[1][2], kb[1][3]);
                }
                sts32(sa, scale_scores(sc[0] + sd[0], sc[1] + sd[1]));
                sts32(sa + 768, scale_scores(sc[2] + sd[2], sc[3] + sd[3]));
                bar_arrive(BAR_S, 160);
                TL(25);
                bar_sync(BAR_SV, 352);
                kv_load(s);
            } else {
                if (g == 1) { tok_start(s); TL(21); if (s == 0) KT_MARK(13); }
                const char* p = make_ptr(l16 + (xoth + xtype * 1024 + slot), mhi);
                const uint32_t dst = l16 + (sb + SM_QKV + xtype * 2048 + (nh ^ 1) * 1024);
                asm volatile("" ::"l"(p));
                uint4 v[2];
                poll_init(v[0]); poll_init(v[1]);
                if (g == 0) {
                    bar_sync(BAR_PUBV, 160);
                    mbar_wait_w(sb + MB_V, s & 1);
                    spin_cycles(DLY_V);
                } else {
                    bar_sync(BAR_PUB, 192);
                    spin_cycles(DLY_X);
                }
                const int r = poll2(v, p);
                STAT(1, r > 1 && warp == 10);
                sts128(dst, v[0]); sts128(dst + 512, v[1]);
                if (g != 0) bar_arrive(BAR_QK, 224);
                if (g == 0) { bar_arrive(BAR_V, 160); bar_arrive(BAR_SV, 352); TL(17); }
                if (g == 1) {
                    TL(31);
                    bar_sync(BAR_SV, 352);
                    tok_mid(s);
                    TL(22);
                }
                if (g == 2 && s >= 1) {
                    TL(16);
                    const uint32_t prev = (slot - 0x4000) & 0xC000;
                    const char* y = make_ptr(l16 + (ybox + prev), mhi);
                    const char* x = make_ptr(l16 + (xoth + prev + kh * 1536), mhi);
#pragma unroll
                    for (int i = 0; i < 8; i++) st_sent(y + i * 512);
#pragma unroll
                    for (int i = 0; i < 3; i++) st_sent(x + i * 512);
                    st_relaxed_u32(make_ptr(lane * 4 + (zline + (slot ^ 0x8000)), mhi), SENT);
                    TL(23);
                }
            }
            if (s + 1 == NSEG) break;
            {
                const char* p = make_ptr(l16 + (ybox + g * 1024 + slot), mhi);
                char* zdst = make_ptr(lane * 4 + (zline + g * 32 + slot), mhi);
                const uint32_t dst = ydst + (sb + SM_Z + g * 1024), dst1 = (ydst ^ 64) + (sb + SM_Z + g * 1024 + 512), src = ysrc + (sb + SM_Z), src1 = (ysrc ^ 16) + (sb + SM_Z);
                asm volatile("" ::"l"(p), "l"(zdst));
                uint4 v[2];
                poll_init(v[0]); poll_init(v[1]);
                bar_sync(BAR_SENTC, 384);
                spin_cycles(DLY_Y);
                const int r = poll2(v, p);
                STAT(2, r > 1 && warp == 8);
                sts128(dst, v[0]); sts128(dst1, v[1]);
                bar_sync(BAR_Y, 128);
                TL(18);
                uint32_t b[2][4];
                ldsm4t(b[0], src); ldsm4t(b[1], src1);
                const uint32_t one = 0x3F803F80u;
                float d0[4] = {0.f, 0.f, 0.f, 0.f}, d1[4] = {0.f, 0.f, 0.f, 0.f};
                mma16816(d0, one, one, one, one, b[0][0], b[0][1]);
                mma16816(d1, one, one, one, one, b[1][0], b[1][1]);
                mma16816(d0, one, one, one, one, b[0][2], b[0][3]);
                mma16816(d1, one, one, one, one, b[1][2], b[1][3]);
                const uint32_t w = (lane & 4) ? pack_bf16(d1[0], d1[1]) : pack_bf16(d0[0], d0[1]);
                asm volatile("{.reg .pred p; setp.lt.u32 p, %2, 128; @p st.relaxed.gpu.global.u32 [%0], %1;}" ::"l"(zdst), "r"(w), "r"(l16) : "memory");
                if (s + 3 < NSEG) bar_arrive(BAR_ZP, 256);
                TL(19);
            }
            {
                const char* p = make_ptr(l16 + (zbox + g * 512 + slot), mhi);
                const uint32_t dst = l16 + (sb + SM_Z + g * 512);
                asm volatile("" ::"l"(p));
                uint4 v[4];
                poll_init(v[0]); poll_init(v[1]); poll_init(v[2]); poll_init(v[3]);
                bar_sync(BAR_COMM, 128);
                spin_cycles(DLY_Z);
                const int r = poll4(v, p);
                STAT(0, r > 1 && warp == 8);
#pragma unroll
                for (int i = 0; i < 4; i++) sts128(dst + i * 2048, v[i]);
                bar_arrive(BAR_MEM, 384);
                TL(20);
            }
        }
    } else if (warp < 4) {
        asm volatile("setmaxnreg.inc.sync.aligned.u32 %0;" ::"n"(REG_A));
        const uint32_t l16 = lane16();
        uint32_t wa[2][24][4];
        {
            const uint32_t L = l16, fa = sb + FRAG();
            mbar_wait_w(sb + MB_W1, 0);
            KT_MARK(7);
#pragma unroll
            for (int t = 0; t < 2; t++)
#pragma unroll
                for (int r = 0; r < 24; r++) ldsm4t(wa[t][r], fa + STG_QK + (t * 24 + r) * 2048);
            mbar_wait_w(sb + MB_W2, 0);
            bar_arrive(BAR_PDONE, 384);
        }
        auto batch1 = [&](float (&d)[16], uint32_t lo, auto tc, auto k0c, auto k1c) {
            constexpr int t = decltype(tc)::value;
            const uint64_t da = make_desc(SB0 + SM_WQK, 16, 1024);
            wg_fence();
            static_for<decltype(k0c)::value, decltype(k1c)::value>([&](auto kc) {
                constexpr int k = decltype(kc)::value, off = (k >> 2) * 256 + (k & 3) * 2;
                if constexpr (k >= 24) wgmma_ss32u<off>(d, da + ((k - 24) * 2 + t) * 128, lo);
                else wgmma_rs32u<off, k != 0 || t != 0>(d, wa[t][k], lo);
            });
            wg_commit();
        };
        const uint32_t xbox = mlo + WIN + page_off(pair & 31, cls ^ XFLIP);
        const uint32_t ybox = mlo + page_off(24 + 2 * g + 32 * nh, kh ^ yflip) + h * 128;
#pragma unroll 1
        for (uint32_t it = 0; it < NSEG + 3; it++) {
            const int s = (int)it - 3;
            const uint32_t ui = uniform(it), slot = ((ui + 1) & 3) << 14, kvo = (~ui & 1) * KV_BYTES, xtlo = XTLO();
            {
                PHASE(5);
                const uint32_t first = L | (g << 9);
                if (s >= 0) mbar_expect_tx_if0(first, sb + MB_R1, 2048);
                if (s + 3 < NSEG) {
                    mbar_expect_tx_if0(first, sb + MB_RT0, 8192);
                    mbar_wait_w(sb + MB_XT + (ui & 1) * 8, (it >> 1) & 1);
                }
            }
            if (s >= 0) {
                PHASE(0);
                const uint32_t mb = L + (sb + SM_Z), ra = L + (sb + g * 512), r1 = L + (rsb + SM_R1 + g * 512), r1b = rsb + MB_R1;
                sched_fence(r1 | r1b);
                bar_sync(BAR_MEM, 384);
                TLB(0);
                float acc[2][2][4];
#pragma unroll
                for (int t = 0; t < 4; t++) { acc[t >> 1][t & 1][0] = acc[t >> 1][t & 1][1] = acc[t >> 1][t & 1][2] = acc[t >> 1][t & 1][3] = 0.f; }
                uint32_t b[4][4];
                uint4 u0, u1;
#pragma unroll
                for (int p = 0; p < 4; p++) ldsm4t(b[p], mb + p * 512);
#pragma unroll
                for (int p = 0; p < 12; p++) {
#pragma unroll
                    for (int u = 0; u < 2; u++) {
                        mma16816v(acc[0][u], wa[0][2 * p + u], b[p & 3][2 * u], b[p & 3][2 * u + 1]);
                        mma16816v(acc[1][u], wa[1][2 * p + u], b[p & 3][2 * u], b[p & 3][2 * u + 1]);
                    }
                    if (p + 4 < 12) ldsm4t(b[p & 3], mb + (p + 4) * 512);
                    if (p == Q3_AT) {
                        bar_sync(BAR_Q3, 256);
                        u0 = lds128(ra + SM_R3); u1 = lds128(ra + SM_O);
                    }
                }
                st_async4(r1, (acc[0][0][0] + __uint_as_float(u0.x)) + acc[0][1][0], (acc[0][0][1] + __uint_as_float(u0.y)) + acc[0][1][1],
                          (acc[0][0][2] + __uint_as_float(u0.z)) + acc[0][1][2], (acc[0][0][3] + __uint_as_float(u0.w)) + acc[0][1][3], r1b);
                TL(1);
                const float o0 = (acc[1][0][0] + __uint_as_float(u1.x)) + acc[1][1][0], o1 = (acc[1][0][1] + __uint_as_float(u1.y)) + acc[1][1][1];
                const float o2 = (acc[1][0][2] + __uint_as_float(u1.z)) + acc[1][1][2], o3 = (acc[1][0][3] + __uint_as_float(u1.w)) + acc[1][1][3];
                const uint32_t l4 = L >> 2, qo = SM_QKV + kh * 2048 + nh * 1024 + g * 256, qr = l4 + (rsb + qo), ql = l4 + (sb + qo), pb = rsb + MB_P;
                char* xd = make_ptr(l4 + (xbox + kh * 1024 + g * 256 + slot), mhi);
                asm volatile("" ::"l"(xd), "r"(qr), "r"(pb), "r"(qr + 128), "f"(o0), "f"(o1), "f"(o2), "f"(o3));
                mbar_wait_w(sb + MB_R1, s & 1);
                const uint4 v = lds128(ra + SM_R1);
                const uint32_t w0 = pack_bf16(o0 + __uint_as_float(v.x), o1 + __uint_as_float(v.y)), w1 = pack_bf16(o2 + __uint_as_float(v.z), o3 + __uint_as_float(v.w));
                st_relaxed_u32(xd, w0);
                st_relaxed_u32(xd + 128, w1);
                bar_arrive(BAR_PUB, 192);
                st_async1(qr, w0, pb);
                st_async1(qr + 128, w1, pb);
                sts32(ql, w0);
                sts32(ql + 128, w1);
                __syncwarp();
                mbar_expect_tx_if0(L, sb + MB_P, 256);
                TL(2);
                if (s + 3 < NSEG) bar_sync(BAR_VP, 256);
            } else {
                bar_sync(BAR_PRO, 288);
            }
            if (s + 3 < NSEG) {
                float d[16];
                batch1(d, xtlo, std::integral_constant<int, 0>(), std::integral_constant<int, 0>(), std::integral_constant<int, 32>());
                PHASE(1);
                const uint32_t rt = L + (rsb + SM_RT + g * 2048);
                wg_wait<0>();
                TL(7);
#pragma unroll
                for (int i = 0; i < 4; i++) st_async4(rt + i * 512, d[4 * i], d[4 * i + 1], d[4 * i + 2], d[4 * i + 3], rsb + MB_RT0);
            }
            if (s + 1 == NSEG) { bar_arrive(BAR_SV, 352); break; }
            if (s >= 0) {
                PHASE(2);
                const uint32_t fo = FRAG() + (sb + SM_WO2 + 16384), lo = L + (sb + SM_O), yo = (L >> 2) + (ybox + slot);
                uint32_t a1[8][4];
                bar_sync(BAR_SV, 352);
#pragma unroll
                for (int k = 0; k < 8; k++) ldsm4t(a1[k], fo + k * 2048);
                sched_fence(yo);
                bar_sync(BAR_O2, 256);
                TLB(14);
                float y0[4] = {0.f, 0.f, 0.f, 0.f}, y1[4] = {0.f, 0.f, 0.f, 0.f};
                uint32_t b[2][4];
                ldsm4t(b[0], lo); ldsm4t(b[1], lo + 512);
                sched_fence(L);
#pragma unroll
                for (int p = 0; p < 4; p++) {
                    mma16816v(y0, a1[2 * p], b[p & 1][0], b[p & 1][1]);
                    mma16816v(y1, a1[2 * p + 1], b[p & 1][2], b[p & 1][3]);
                    if (p < 2) ldsm4t(b[p & 1], lo + (p + 2) * 512);
                }
                bar_sync(BAR_INV, 256);
                float i0, i1;
                asm volatile("ld.shared.v2.f32 {%0, %1}, [%2];" : "=f"(i0), "=f"(i1) : "r"(((L >> 1) & 0x18) + (sb + SM_INV + g * 32)) : "memory");
                st_relaxed_u32(make_ptr(yo, mhi), pack_bf16((y0[0] + y1[0]) * i0, (y0[1] + y1[1]) * i1));
                st_relaxed_u32(make_ptr(yo ^ 4096, mhi) + 0x2000, pack_bf16((y0[2] + y1[2]) * i0, (y0[3] + y1[3]) * i1));
                bar_arrive(BAR_SENTC, 384);
                TL(6);
            }
            if (s + 3 < NSEG) {
                PHASE(4);
                float d[16];
                const uint32_t rt = L + (sb + SM_RT + g * 2048);
                mbar_wait_w(sb + MB_RT0, it & 1);
#pragma unroll
                for (int i = 0; i < 4; i++) {
                    const uint4 v = lds128(rt + i * 512);
                    d[4 * i] = __uint_as_float(v.x); d[4 * i + 1] = __uint_as_float(v.y); d[4 * i + 2] = __uint_as_float(v.z); d[4 * i + 3] = __uint_as_float(v.w);
                }
                if (s >= 0) bar_sync(BAR_SENT, 256);
                if (SPLIT > 0) batch1(d, xtlo, std::integral_constant<int, 1>(), std::integral_constant<int, 0>(), std::integral_constant<int, SPLIT>());
                if (s >= 0) bar_sync(BAR_ZP, 256);
                TLB(30);
                batch1(d, xtlo, std::integral_constant<int, 1>(), std::integral_constant<int, SPLIT>(), std::integral_constant<int, 32>());
                const uint32_t so = (kh ? FRAG() : ((L & 0x100) << 2) + (L & 0xF0) + g * 256) + (sb + SM_STG);
                wg_wait<0>();
                TL(8);
                uint32_t w[8];
#pragma unroll
                for (int i = 0; i < 8; i++) w[i] = pack_bf16(d[2 * i], d[2 * i + 1]);
                if (kh) {
                    stsm4t(so, w[0], w[1], w[2], w[3]);
                    stsm4t(so + 2048, w[4], w[5], w[6], w[7]);
                } else {
                    stsm4(so, w[0], w[1], w[2], w[3]);
                    stsm4(so + 2048, w[4], w[5], w[6], w[7]);
                }
                __syncwarp();
                mbar_arrive_if0(L, sb + MB_STG);
                TL(9);
            } else {
                bar_arrive(BAR_SENT, 256);
            }
        }
    } else {
        asm volatile("setmaxnreg.inc.sync.aligned.u32 %0;" ::"n"(REG_B));
        const uint32_t l16 = lane16();
        uint32_t wv[24][4], wo[8 + WO_RF1][4];
        {
            const uint32_t L = l16, fa = sb + FRAG();
            mbar_wait_w(sb + MB_W0, 0);
            KT_MARK(6);
#pragma unroll
            for (int r = 0; r < 24; r++) ldsm4t(wv[r], fa + STG_V + r * 2048);
            bar_arrive(BAR_PV, 160);
            mbar_wait_w(sb + MB_W3, 0);
            KT_MARK(8);
#pragma unroll
            for (int r = 0; r < 8 + WO_RF1; r++) ldsm4t(wo[r], fa + STG_WO + r * 2048);
            mbar_wait_w(sb + MB_W2, 0);
            bar_arrive(BAR_PDONE, 384);
        }
        const uint32_t xbox = mlo + WIN + page_off(pair & 31, cls ^ XFLIP);
        const uint32_t ybox = mlo + page_off(2 * g + 32 * nh, kh ^ yflip) + h * 128;
#pragma unroll 1
        for (uint32_t it = 0; it < NSEG + 3; it++) {
            const int s = (int)it - 3;
            const uint32_t ui = uniform(it), slot = ((ui + 1) & 3) << 14, kvo = (~ui & 1) * KV_BYTES, xtlo = XTLO();
            {
                PHASE(5);
                const uint32_t first = L | (g << 9);
                if (s >= 0) mbar_expect_tx_if0(first, sb + MB_R2, 1024);
                if (s + 3 < NSEG) {
                    mbar_expect_tx_if0(first, sb + MB_RT1, 4096);
                    mbar_wait_w(sb + MB_XT + (ui & 1) * 8, (it >> 1) & 1);
                }
            }
            if (s >= 0) {
                PHASE(0);
                const uint32_t fo = FRAG() + sb, l4 = L >> 2;
                {
                    const uint32_t mb = L + (sb + SM_Z), aw = fo + SM_WQK, ra = L + (sb + g * 512), r2 = (L >> 1) + (rsb + SM_R2 + g * 256), r2b = rsb + MB_R2;
                    uint32_t a[NA][4], b[4][4];
#pragma unroll
                    for (int i = 0; i < NA; i++) ldsm4t(a[i], aw + i * 2048);
                    sched_fence(L);
                    bar_sync(BAR_MEM, 384);
#pragma unroll
                    for (int p = 0; p < 4; p++) ldsm4t(b[p], mb + (12 + p) * 512);
                    sched_fence(L);
                    float c[2][4] = {{0.f, 0.f, 0.f, 0.f}, {0.f, 0.f, 0.f, 0.f}};
#pragma unroll
                    for (int i = 0; i < 16; i++) {
                        mma16816v(c[i & 1], a[i % NA], b[i >> 2][i & 2], b[i >> 2][(i & 2) + 1]);
                        ldsm4t(a[i % NA], aw + (i + NA) * 2048);
                    }
                    sts128(ra + SM_R3, make_uint4(__float_as_uint(c[0][0]), __float_as_uint(c[0][1]), __float_as_uint(c[0][2]), __float_as_uint(c[0][3])));
                    sts128(ra + SM_O, make_uint4(__float_as_uint(c[1][0]), __float_as_uint(c[1][1]), __float_as_uint(c[1][2]), __float_as_uint(c[1][3])));
                    bar_arrive(BAR_Q3, 256);
                    TL(29);
                    float acc[4][4];
#pragma unroll
                    for (int t = 0; t < 4; t++) { acc[t][0] = acc[t][1] = acc[t][2] = acc[t][3] = 0.f; }
#pragma unroll
                    for (int i = 16; i < 24; i++) {
                        mma16816v(acc[i & 1], a[i % NA], b[(i - 16) >> 1][2 * (i & 1)], b[(i - 16) >> 1][2 * (i & 1) + 1]);
                        if (i + NA < 24) ldsm4t(a[i % NA], aw + (i + NA) * 2048);
                        else ldsm4t(a[i % NA], mb + (i + NA - 24) * 512);
                    }
#pragma unroll
                    for (int p = 0; p < 12; p++) {
                        mma16816v(acc[(2 * p) & 3], wv[2 * p], a[(24 + p) % NA][0], a[(24 + p) % NA][1]);
                        mma16816v(acc[(2 * p + 1) & 3], wv[2 * p + 1], a[(24 + p) % NA][2], a[(24 + p) % NA][3]);
                        if (p + NA < 12) ldsm4t(a[(24 + p) % NA], mb + (p + NA) * 512);
                    }
                    if (s + 3 < NSEG) bar_arrive(BAR_VP, 256);
                    float o[4];
#pragma unroll
                    for (int i = 0; i < 4; i++) o[i] = (acc[0][i] + acc[1][i]) + (acc[2][i] + acc[3][i]);
                    st_async2(r2, kh ? o[0] : o[2], kh ? o[1] : o[3], r2b);
                    TL(10);
                    const float o0 = kh ? o[2] : o[0], o1 = kh ? o[3] : o[1];
                    const uint32_t qo = SM_QKV + 4096 + nh * 1024 + (2 * g + kh) * 128, qr = l4 + (rsb + qo), ql = l4 + (sb + qo), vb = rsb + MB_V, rl = (L >> 1) + (sb + SM_R2 + g * 256);
                    char* xd = make_ptr(l4 + (xbox + 2048 + (2 * g + kh) * 128 + slot), mhi);
                    asm volatile("" ::"l"(xd), "r"(qr), "r"(vb), "f"(o0), "f"(o1));
                    mbar_wait_w(sb + MB_R2, s & 1);
                    uint32_t vx, vy;
                    asm volatile("ld.shared.v2.u32 {%0,%1}, [%2];" : "=r"(vx), "=r"(vy) : "r"(rl) : "memory");
                    const uint32_t w0 = pack_bf16(o0 + __uint_as_float(vx), o1 + __uint_as_float(vy));
                    st_relaxed_u32(xd, w0);
                    bar_arrive(BAR_PUBV, 160);
                    st_async1(qr, w0, vb);
                    sts32(ql, w0);
                    __syncwarp();
                    mbar_expect_tx_if0(L, sb + MB_V, 128);
                    TL(11);
                }
                const uint32_t vma = L + (sb + SM_QKV + 4096 + g * 512), yo = l4 + (ybox + slot);
                uint32_t va[2][2][4];
                {
                    const uint32_t qa = QFRAG(), vf = VFRAG(), va0 = vf + VBASE(), va1 = (vf ^ 32) + VBASE();
                    const uint32_t kf = ((L << 3) & 0x380) | ((L ^ (L >> 3)) & 0x30) | (L & 0x40), kb0 = sb + SM_KV + kvo + g * 1024;
                    const int d = (int)(L >> 6) - (int)((L >> 3) & 6) + 8 * (j - (int)g);
                    const uint32_t keep = (d < 0 ? 0u : 0xFFFFu) | (d < 1 ? 0u : 0xFFFF0000u), sa = l4 + (sb + SM_S + g * 128);
                    const uint32_t q0 = qa + (sb + nh * 1024), q1 = qa + (sb + (nh ^ 1) * 1024);
                    float sc[4] = {0.f, 0.f, 0.f, 0.f}, sd[4] = {0.f, 0.f, 0.f, 0.f};
                    uint32_t a[4][4], kb[2][4];
                    mbar_wait_w(sb + MB_KV + (~ui & 1) * 8, (s >> 1) & 1);
                    ldsm4(kb[0], kf + (kb0 + nh * 4096)); ldsm4(kb[1], (kf ^ 64) + (kb0 + nh * 4096));
                    mbar_wait_w(sb + MB_P, s & 1);
                    TL(12);
#pragma unroll
                    for (int k = 0; k < 4; k++) ldsm4t(a[k], q0 + k * 256);
#pragma unroll
                    for (int k = 0; k < 4; k++) mma16816v((k & 1) ? sd : sc, a[k], kb[k >> 1][2 * (k & 1)], kb[k >> 1][2 * (k & 1) + 1]);
                    ldsm4(kb[0], kf + (kb0 + (nh ^ 1) * 4096)); ldsm4(kb[1], (kf ^ 64) + (kb0 + (nh ^ 1) * 4096));
                    sched_fence(vf | yo);
                    bar_sync(BAR_QK, 224);
                    TLB(3);
#pragma unroll
                    for (int k = 0; k < 4; k++) ldsm4t(a[k], q1 + k * 256);
                    sched_fence(L);
#pragma unroll
                    for (int k = 0; k < 4; k++) mma16816v((k & 1) ? sd : sc, a[k], kb[k >> 1][2 * (k & 1)], kb[k >> 1][2 * (k & 1) + 1]);
                    ldsm4t(va[0][0], va0); ldsm4t(va[0][1], va0 + 2048);
                    sts32(sa, scale_scores(sc[0] + sd[0], sc[1] + sd[1]));
                    sts32(sa + 768, (scale_scores(sc[2] + sd[2], sc[3] + sd[3]) & keep) | (0xFF80FF80u & ~keep));
                    bar_arrive(BAR_SV, 352);
                    ldsm4t(va[1][0], va1); ldsm4t(va[1][1], va1 + 2048);
                }
                bar_sync(BAR_S, 160);
                TLB(4);
                uint32_t pw[6], vm[4];
                if (s + 1 < NSEG) {
                softmax40(pw, l4 + (sb + SM_S), [&]() {
                    bar_sync(BAR_V, 160);
                    ldsm4(vm, vma);
                });
                uint32_t a1[NP2][4];
                float inv[2];
                {
                    uint32_t w[4];
                    pv32<false>(w, inv, va, vm, pw, [&]() {
                        sched_fence(L);
#pragma unroll
                        for (int k = 0; k < NP2; k++) ldsm4t(a1[k], fo + SM_WO2 + k * 2048);
                    });
#pragma unroll
                    for (int i = 0; i < 4; i++) sts32(l4 + (sb + SM_O + g * 512) + i * 128, w[i]);
                }
                const uint32_t lo = L + (sb + SM_O);
                bar_arrive(BAR_O2, 256);
                bar_sync(BAR_O, 128);
                TLB(5);
                {
                    float y0[4] = {0.f, 0.f, 0.f, 0.f}, y1[4] = {0.f, 0.f, 0.f, 0.f}, y2[4] = {0.f, 0.f, 0.f, 0.f};
                    uint32_t b[4][4];
#pragma unroll
                    for (int p = 0; p < 4; p++) ldsm4t(b[p], lo + p * 512);
                    inv[0] = rcp_approx(inv[0]); inv[1] = rcp_approx(inv[1]);
                    asm volatile("st.shared.v2.f32 [%0], {%1, %2};" ::"r"(((L >> 1) & 0x18) + (sb + SM_INV + g * 32)), "f"(inv[0]), "f"(inv[1]) : "memory");
                    bar_arrive(BAR_INV, 256);
                    sched_fence(L);
#pragma unroll
                    for (int k = 0; k < 8; k++) {
                        const int p = k >> 1, u = k & 1;
                        mma16816v(y2, a1[k % NP2], b[p][2 * u], b[p][2 * u + 1]);
                        if (k + NP2 < 8) ldsm4t(a1[k % NP2], fo + SM_WO2 + (k + NP2) * 2048);
                        else if (k + NP2 < 16 - WO_RF1) ldsm4t(a1[k % NP2], fo + SM_WO1 + (k + NP2 - 8 + WO_RF1) * 2048);
                        mma16816v(y0, wo[k], b[p][2 * u], b[p][2 * u + 1]);
                        if (k < WO_RF1) mma16816v(y1, wo[8 + (k < WO_RF1 ? k : 0)], b[p][2 * u], b[p][2 * u + 1]);
                        else mma16816v(y1, a1[(k + 8 - WO_RF1) % NP2], b[p][2 * u], b[p][2 * u + 1]);
                        if (k < P2_FENCE) sched_fence(L);
                    }
                    char* yd = make_ptr(yo, mhi);
                    char* yd1 = make_ptr(yo ^ 4096, mhi);
                    st_relaxed_u32(yd1 + 0x80000, pack_bf16(y2[0] * inv[0], y2[1] * inv[1]));
                    st_relaxed_u32(yd + 0x82000, pack_bf16(y2[2] * inv[0], y2[3] * inv[1]));
                    st_relaxed_u32(yd, pack_bf16(y0[0] * inv[0], y0[1] * inv[1]));
                    st_relaxed_u32(yd1 + 0x2000, pack_bf16(y0[2] * inv[0], y0[3] * inv[1]));
                    st_relaxed_u32(yd + 0x40000, pack_bf16(y1[0] * inv[0], y1[1] * inv[1]));
                    st_relaxed_u32(yd1 + 0x42000, pack_bf16(y1[2] * inv[0], y1[3] * inv[1]));
                }
                bar_arrive(BAR_SENTC, 384);
                TL(13);
                bar_sync(BAR_SENT, 256);
                } else {
                    bar_sync(BAR_V, 160);
                }
            } else {
                bar_sync(BAR_PRO, 288);
            }
            float o[8];
            if (s + 3 < NSEG) {
                float d[16];
                const uint64_t da = make_desc(SB0 + SM_WV, 16, 1024);
                wg_fence();
                static_for<0, 32>([&](auto kc) {
                    constexpr int k = decltype(kc)::value, off = (k >> 2) * 256 + (k & 3) * 2;
                    if constexpr (k >= 24) wgmma_ss32u<off>(d, da + (k - 24) * 128, xtlo);
                    else wgmma_rs32u<off, k != 0>(d, wv[k], xtlo);
                });
                wg_commit();
                PHASE(1);
                const uint32_t rt = L + (rsb + SM_RT + 8192 + g * 1024);
                wg_wait<0>();
                TL(27);
#pragma unroll
                for (int i = 0; i < 2; i++)
                    st_async4(rt + i * 512, kh ? d[4 * i] : d[8 + 4 * i], kh ? d[4 * i + 1] : d[9 + 4 * i], kh ? d[4 * i + 2] : d[10 + 4 * i], kh ? d[4 * i + 3] : d[11 + 4 * i], rsb + MB_RT1);
#pragma unroll
                for (int i = 0; i < 8; i++) o[i] = kh ? d[8 + i] : d[i];
            } else {
#pragma unroll
                for (int i = 0; i < 8; i++) o[i] = 0.f;
            }
            if (s >= 0) {
                PHASE(2);
                const uint32_t vf = VFRAG(), va0 = vf + VBASE(), va1 = (vf ^ 32) + VBASE(), vma = L + (sb + SM_QKV + 4096 + g * 512), sa = (L >> 2) + (sb + SM_S + 768);
                uint32_t va[2][2][4], vm[4], pw[6], w[4];
                ldsm4t(va[0][0], va0); ldsm4t(va[0][1], va0 + 2048);
                ldsm4t(va[1][0], va1); ldsm4t(va[1][1], va1 + 2048);
                ldsm4(vm, vma);
                softmax40(pw, sa, [&]() {});
                float inv[2];
                pv32<true>(w, inv, va, vm, pw, [&]() {});
                stsm4t((L & 0x70) * 5 + ((L >> 3) & 0x30) + (sb + SM_TO + g * 640), w[0], w[1], w[2], w[3]);
                __syncwarp();
                stg128(reinterpret_cast<char*>(g_ox) + (((L & 0x1C0) << 7) + (L & 0x30) + (((ui - 3) * SEG + 8 * j) * HD + h * DH + 32 * g) * 2),
                       lds128(((L >> 2) & 0x70) * 5 + (L & 0x30) + (sb + SM_TO + g * 640)));
                TL(26);
            }
            if (s + 3 < NSEG) {
                PHASE(3);
                const uint32_t rt = L + (sb + SM_RT + 8192 + g * 1024), so = FRAG() + (sb + SM_STG + 4096);
                mbar_wait_w(sb + MB_RT1, it & 1);
                TL(28);
                uint32_t w[4];
#pragma unroll
                for (int i = 0; i < 2; i++) {
                    const uint4 v = lds128(rt + i * 512);
                    w[2 * i] = pack_bf16(o[4 * i] + __uint_as_float(v.x), o[4 * i + 1] + __uint_as_float(v.y));
                    w[2 * i + 1] = pack_bf16(o[4 * i + 2] + __uint_as_float(v.z), o[4 * i + 3] + __uint_as_float(v.w));
                }
                stsm4t(so, w[0], w[1], w[2], w[3]);
                __syncwarp();
                mbar_arrive_if0(L, sb + MB_STG);
                TL(15);
            }
        }
    }
    KT_END(2);
    asm volatile("barrier.cluster.arrive.relaxed; barrier.cluster.wait;" ::: "memory");
}
constexpr int B_UCH = 73 * 64;
constexpr int B_SCH = 33 * 64;
constexpr int B_KLEN = 2128;
constexpr int B_KCH = 2 * B_KLEN * 2 + 64;
constexpr int B_KBOX = 136 * 32;
constexpr int B_SM_U = 0;
constexpr int B_SM_S = 8 * B_UCH;
constexpr int B_SM_K = B_SM_S + 8 * B_SCH;
constexpr int B_SM_KT = B_SM_K + 8 * B_KCH;
constexpr int B_SM_VT = B_SM_KT + 8 * B_KBOX;
constexpr int B_SM_QT = B_SM_VT + 32768;
constexpr int B_SM_BAR = B_SM_QT + 32768;
constexpr int B_SMEM = B_SM_BAR + 128 + 512;
static_assert(B_SM_KT % 256 == 0 && B_SM_S % 512 == 0 && B_SMEM <= 232448, "tiles");
constexpr int PROBE_N = 4;
#define PROBE_R 2
constexpr int B_C = 2056;

__device__ __forceinline__ uint32_t bf16_mul(uint32_t a, uint32_t b) {
    uint32_t d;
    asm("mul.rn.bf16x2 %0, %1, %2;" : "=r"(d) : "r"(a), "r"(b));
    return d;
}
__device__ __forceinline__ uint32_t bf16_add(uint32_t a, uint32_t b) {
    uint32_t d;
    asm("add.rn.bf16x2 %0, %1, %2;" : "=r"(d) : "r"(a), "r"(b));
    return d;
}

__device__ __forceinline__ uint32_t atomic_round_trip(char* p) {
    uint32_t t0, t1, v;
    asm volatile("{.reg .pred p;\n"
                 "mov.u32 %0, %%clock;\n"
                 "atom.relaxed.gpu.global.add.u32 %2, [%3], 1;\n"
                 "setp.ne.u32 p, %2, 0x7FFFFFFF;\n"
                 "mov.u32 %1, 0;\n"
                 "@p mov.u32 %1, %%clock;}" : "=&r"(t0), "=&r"(t1), "=&r"(v) : "l"(p) : "memory");
    return t1 - t0;
}
__device__ __forceinline__ uint32_t round_trips(char* a, char* b, uint32_t stride, int lane) {
    for (int i = lane >> 3; i < 2 * PROBE_N; i += 4) stg128(((i & 1) ? b : a) + (i >> 1) * stride + (lane & 7) * 16, make_uint4(0, 0, 0, 0));
    __syncwarp();
    uint32_t ta = 0xFFFF, tb = 0xFFFF;
    if (lane == 0) {
        __threadfence();
#pragma unroll 1
        for (int i = 0; i < PROBE_N; i++) { ta = min(ta, atomic_round_trip(a + i * stride)); tb = min(tb, atomic_round_trip(b + i * stride)); }
    }
    __syncwarp();
    return ta | (tb << 16);
}
__device__ __forceinline__ void measure_distance(char* mbox, int lane) {
    const uint32_t b = blockIdx.x;
    unsigned smid;
    asm volatile("mov.u32 %0, %%smid;" : "=r"(smid));
    char* w1 = mbox + WIN + (b & 31) * 128;
    uint32_t r = 0xFFFFFFFF;
#pragma unroll 1
    for (int i = 0; i < PROBE_R; i++) r = __vminu2(r, round_trips(w1 + page_off(40 + 5 * i + (b >> 5), 0), w1 + page_off(40 + 5 * i + (b >> 5), 1), 16384, lane));
    if (lane == 0) g_cls[smid] = r;
    if (b == 128) {
        char *p = mbox + page_off(0, 0), *q = mbox + page_off(0, 1);
        uint32_t r0 = 0xFFFFFFFF;
#pragma unroll 1
        for (int i = 0; i < PROBE_R; i++) r0 = __vminu2(r0, round_trips(p, q, 128, lane));
        if (lane == 0) { g_reg[2] = ((r0 & 0xFFFF) > (r0 >> 16)) != ((r & 0xFFFF) > (r >> 16)); g_reg[0] = 0; g_reg[1] = 0; }
        const uint4 sent = make_uint4(SENT, SENT, SENT, SENT);
        stg128(p + lane * 16, sent); stg128(q + lane * 16, sent);
    }
    if (b == 129) for (int i = lane; i < 128; i += 32) g_xflag[i] = 0;
}

#define SP(i)
#define SP2(i)
#define PF_STOP 1
#define SENT_AT 3
#define Q_LATE 1
#define PF_DEPTH 4
#define PF_STRIDE 256
struct ChainInputs { const char* w[4]; const char *x, *mem0; };
#define EF_MASK 15
#define EF(i) (((EF_MASK >> (i)) & 1) ? policy_evict_first() : policy_evict_normal())
__device__ __forceinline__ void l2_prefetch(const char* p, uint32_t bytes) {
    asm volatile("cp.async.bulk.prefetch.L2.global [%0], %1;" ::"l"(p), "r"(bytes) : "memory");
}
#define WG_CONV(N, LIST, A0, A1, A2, A3, LO, OF, ...) \
    if constexpr (NN == N) asm volatile("{.reg .b32 l; .reg .b64 e; add.u32 l, %" #LO ", %" #OF "; mov.b64 e, {l, 0x80000020};\n" \
        "wgmma.mma_async.sync.aligned.m64n" #N "k16.f32.bf16.bf16 {" LIST "}, {%" #A0 ",%" #A1 ",%" #A2 ",%" #A3 "}, e, 1, 1, 1, 0;}" \
        : __VA_ARGS__ : "r"(a[0]), "r"(a[1]), "r"(a[2]), "r"(a[3]), "r"(lo), "n"(OFF));
#define WL4 "%0,%1,%2,%3"
#define WL8 WL4 ",%4,%5,%6,%7"
#define WL12 WL8 ",%8,%9,%10,%11"
#define WL16 WL12 ",%12,%13,%14,%15"
#define WL20 WL16 ",%16,%17,%18,%19"
#define WL24 WL20 ",%20,%21,%22,%23"
#define WL28 WL24 ",%24,%25,%26,%27"
#define WL32 WL28 ",%28,%29,%30,%31"
template <int NN, int OFF> __device__ __forceinline__ void wgmma_conv(float (&d)[32], const uint32_t (&a)[4], uint32_t lo) {
    WG_CONV(8, WL4, 4, 5, 6, 7, 8, 9, R4(0))
    WG_CONV(16, WL8, 8, 9, 10, 11, 12, 13, R4(0), R4(4))
    WG_CONV(24, WL12, 12, 13, 14, 15, 16, 17, R4(0), R4(4), R4(8))
    WG_CONV(32, WL16, 16, 17, 18, 19, 20, 21, R16(0))
    WG_CONV(40, WL20, 20, 21, 22, 23, 24, 25, R16(0), R4(16))
    WG_CONV(48, WL24, 24, 25, 26, 27, 28, 29, R16(0), R4(16), R4(20))
    WG_CONV(56, WL28, 28, 29, 30, 31, 32, 33, R16(0), R4(16), R4(20), R4(24))
    WG_CONV(64, WL32, 32, 33, 34, 35, 36, 37, R16(0), R16(16))
}
__device__ __forceinline__ void copy_to_peer(uint32_t dst, uint32_t src, uint32_t bytes, uint32_t bar) {
    asm volatile("cp.async.bulk.shared::cluster.shared::cta.mbarrier::complete_tx::bytes [%0], [%1], %2, [%3];" ::"r"(dst), "r"(src), "r"(bytes), "r"(bar) : "memory");
}
__device__ __forceinline__ uint32_t lds_volatile(uint32_t a) {
    uint32_t v;
    asm volatile("ld.volatile.shared.u32 %0, [%1];" : "=r"(v) : "r"(a) : "memory");
    return v;
}
__device__ __forceinline__ uint32_t swz64(uint32_t a) { return a ^ ((a >> 3) & 0x30); }
__device__ __forceinline__ void fence_async() { asm volatile("fence.proxy.async.shared::cta;" ::: "memory"); }

__global__ void __cluster_dims__(2, 1, 1) __launch_bounds__(576, 1)
ssm_kernel(const __grid_constant__ CUtensorMap mapK, const __grid_constant__ CUtensorMap mapV, const __grid_constant__ CUtensorMap mapQ,
           const __grid_constant__ CUtensorMap mapO, const bf16* __restrict__ shiftk, const bf16* __restrict__ ssmk, const bf16* __restrict__ Dv,
           char* __restrict__ mbox, const __grid_constant__ ChainInputs ci) {
    extern __shared__ __align__(128) uint8_t smem_raw[];
    const uint32_t sb = (smem_u32(smem_raw) + 511) & ~511u;
    const int rank = blockIdx.x & 1, ch0 = blockIdx.x * 8, c16 = ch0 & ~15, t0 = rank * 1024;
    const int t = threadIdx.x, warp = t >> 5, lane = t & 31;
    const uint32_t bar = sb + B_SM_BAR, barQ = bar + 64, barU = bar + 72, barY = bar + 80, flag = bar + 88;
    SP(0);
    if (lane == 0 && warp < 16 && blockIdx.x < 128) {
        const int i = warp >> 1;
        if (warp & 1) {
            if (i < 3) { mbar_init(barQ + i * 8, 1); mbar_expect_tx(barQ + i * 8, i ? 16384 : 32768); }
            if (i == 3) sts32(flag, 0);
        } else {
            mbar_init(bar + i * 8, 1);
            asm volatile("fence.mbarrier_init.release.cluster;" ::: "memory");
            mbar_expect_tx(bar + i * 8, B_KBOX + 4096);
            tma_load_2d(sb + B_SM_KT + i * B_KBOX, &mapK, c16, t0 + i * 128 - 8, bar + i * 8, EF(0));
            tma_load_2d(sb + B_SM_VT + i * 4096, &mapV, c16, t0 + i * 128, bar + i * 8, EF(0));
        }
        asm volatile("fence.mbarrier_init.release.cluster;" ::: "memory");
    }
    __syncwarp();
    if (warp == 14) SP2(14);
    KT_START(1);
    if (warp == 17) {
        asm volatile("barrier.cluster.arrive.relaxed.aligned;" ::: "memory");
        measure_distance(mbox, lane);
        asm volatile("barrier.cluster.wait.aligned;" ::: "memory");
        KT_MARK(14);
        return;
    }
    if (blockIdx.x >= 128) return;
    if (warp == 16) {
        asm volatile("barrier.cluster.arrive.relaxed.aligned; barrier.cluster.wait.aligned;" ::: "memory");
        SP2(8);
        if (Q_LATE) for (int i = 0; i < 8; i++) { mbar_wait_w(bar + i * 8, 0); SP2(i); }
        if (lane < 8) tma_load_2d(sb + B_SM_QT + lane * 4096, &mapQ, c16, t0 + lane * 128, barQ, EF(3));
        if (!Q_LATE) for (int i = 0; i < 8; i++) mbar_wait_w(bar + i * 8, 0);
        if (lane == 0) {
            l2_prefetch(ci.x + blockIdx.x * 2048, 2048);
            if (blockIdx.x < 8) l2_prefetch(ci.mem0 + blockIdx.x * 2048, 2048);
        }
        uint32_t v[PF_DEPTH], acc = 0;
#pragma unroll
        for (int u = 0; u < PF_DEPTH; u++) v[u] = 0;
        constexpr int PER = 32 * PF_STRIDE, NW = 65536 / PER;
#pragma unroll 1
        for (int i = 0; i < 4 * NW && lds_volatile(flag) == 0; i += PF_DEPTH) {
#pragma unroll
            for (int u = 0; u < PF_DEPTH; u++) {
                const char* a = ci.w[(i + u) / NW] + blockIdx.x * 65536 + ((i + u) % NW) * PER + lane * PF_STRIDE;
                acc |= v[u];
                asm volatile("ld.global.cg.L2::256B.u32 %0, [%1];" : "=r"(v[u]) : "l"(a) : "memory");
            }
        }
#pragma unroll
        for (int u = 0; u < PF_DEPTH; u++) acc |= v[u];
        if (acc == 0x7FFF7FFFu && v[0] == 0x7FFEu) g_err = 1;
        SP2(12);
        KT_MARK(15);
        return;
    }
    asm volatile("barrier.cluster.arrive.relaxed.aligned;" ::: "memory");
    const int far = warp & 1, unit = rank ^ far;
    uint32_t w[4];
    uint32_t d2;
    asm volatile("ld.global.nc.u32 %0, [%1];" : "=r"(d2) : "l"(Dv + ch0 + (warp >> 2) * 2));
    {
        const int ch = warp & 7, half = warp >> 3;
        const uint32_t kb = sb + B_SM_K + ch * B_KCH;
        const uint4* src = reinterpret_cast<const uint4*>(ssmk + (size_t)(ch0 + ch) * S_LEN);
        uint4 kr[4];
#pragma unroll
        for (int i = 0; i < 4; i++) kr[i] = ldg128(src + half * 128 + i * 32 + lane, EF(1));
        const uint32_t edge = half ? 0u : __ldg(reinterpret_cast<const uint32_t*>(src + 128));
        const uint2 sw = __ldg(reinterpret_cast<const uint2*>(shiftk + (size_t)(c16 + unit * 8 + (lane >> 2)) * 4));
        w[0] = __byte_perm(sw.x, 0, 0x1010); w[1] = __byte_perm(sw.x, 0, 0x3232); w[2] = __byte_perm(sw.y, 0, 0x1010); w[3] = __byte_perm(sw.y, 0, 0x3232);
        if (half) sts128(sb + B_SM_U + ch * B_UCH + 4096 + lane * 16, make_uint4(0, 0, 0, 0));
#pragma unroll
        for (int i = 0; i < 4; i++) {
            const uint4 lo = kr[i];
            const uint32_t nx = __shfl_down_sync(~0u, lo.x, 1), n0 = (i < 3) ? __shfl_sync(~0u, kr[i < 3 ? i + 1 : 3].x, 0) : edge;
            const uint32_t hix = (lane < 31) ? nx : n0;
            const int c = 256 - (half * 128 + 32 * i + lane);
            sts128(kb + c * 16, make_uint4(__byte_perm(hix, lo.w, 0x7610), __byte_perm(lo.w, lo.z, 0x7610), __byte_perm(lo.z, lo.y, 0x7610), __byte_perm(lo.y, lo.x, 0x7610)));
            sts128(kb + B_KLEN * 2 + 64 + c * 16, make_uint4(__byte_perm(lo.w, lo.w, 0x1032), __byte_perm(lo.z, lo.z, 0x1032), __byte_perm(lo.y, lo.y, 0x1032), __byte_perm(lo.x, lo.x, 0x1032)));
        }
        const uint32_t k0w = __shfl_sync(~0u, kr[0].x, 0);
        if (half == 0 && lane < 8) {
            sts128(kb + (257 + lane) * 16, make_uint4(lane == 0 ? (k0w & 0xFFFFu) : 0u, 0u, 0u, 0u));
            sts128(kb + B_KLEN * 2 + 64 + (257 + lane) * 16, make_uint4(0u, 0u, 0u, 0u));
        }
    }
    auto sentinels = [&]() {
        const uint4 sent = make_uint4(SENT, SENT, SENT, SENT);
        char* p0 = mbox + blockIdx.x * 16384 + t * 16;
        if (blockIdx.x != 0 || (t & 255) >= 32) stg128(p0, sent);
        stg128(p0 + 8192, sent);
        char* p1 = mbox + WIN + blockIdx.x * 8704 + t * 16;
        stg128(p1, sent);
        if (t < 32) stg128(p1 + 8192, sent);
    };
    if (SENT_AT == 1) sentinels();
    asm volatile("barrier.cluster.wait.acquire.aligned;" ::: "memory");
    SP(1);
    {
        const int box = warp >> 1, row0 = 63 - 32 * rank - 4 * box;
        const uint32_t kt = sb + B_SM_KT + box * B_KBOX + 256 + lane * 32, s0 = (unit ^ ((lane >> 2) & 1)) * 16;
        const uint32_t a0 = kt + s0, a2 = kt - 64 + (unit ^ (((lane + 6) >> 2) & 1)) * 16, a4 = kt - 128 + (s0 ^ 16), av = sb + B_SM_VT + box * 4096 + lane * 32 + s0;
        const uint32_t ul = (lane & 7) * B_UCH + row0 * 64 + (lane >> 3) * 16;
        const uint32_t ud = sb + (far ? B_SM_S + (lane & 7) * (B_SCH - B_UCH) - (1 - rank) * 2048 : B_SM_U);
        mbar_wait_w(bar + box * 8, 0);
        SP(2);
#pragma unroll
        for (int i = 0; i < 4; i++) {
            uint32_t k0[4], k2[4], k4[4], vv[4], o[4];
            ldsm4t(k0, a0 + i * 1024); ldsm4t(k2, a2 + i * 1024); ldsm4t(k4, a4 + i * 1024); ldsm4t(vv, av + i * 1024);
#pragma unroll
            for (int j = 0; j < 4; j++) {
                uint32_t a = bf16_mul(__byte_perm(k4[j], k2[j], 0x5432), w[3]);
                a = bf16_add(a, bf16_mul(k2[j], w[2]));
                a = bf16_add(a, bf16_mul(__byte_perm(k2[j], k0[j], 0x5432), w[1]));
                a = bf16_add(a, bf16_mul(k0[j], w[0]));
                o[j] = bf16_mul(a, vv[j]);
            }
            stsm4(ud + swz64(ul - i * 64), o[0], o[1], o[2], o[3]);
        }
        fence_async();
        __syncwarp();
        if (far && lane < 8) {
            const uint32_t o = lane * B_UCH + (row0 - 3) * 64;
            copy_to_peer(peer_addr(sb + B_SM_U + o, rank ^ 1), ud + o, 256, peer_addr(barU, rank ^ 1));
        }
    }
    bar_sync(1, 512);
    mbar_wait_w(barU, 0);
    if (SENT_AT == 2) sentinels();
    SP(3);
    const int wg = warp >> 2, wq = warp & 3, hi = wq >> 1, g = lane >> 2, tq = lane & 3;
    const uint32_t zero = lds32(sb + B_SM_U + 4096);
#pragma unroll 1
    for (int cc = 0; cc < 2; cc++) {
        const int ch = 2 * wg + cc;
        const uint32_t kb = sb + B_SM_K + ch * B_KCH, ub = sb + B_SM_U + ch * B_UCH;
        const uint32_t dw = __byte_perm(d2, 0, cc ? 0x3232 : 0x1010);
        const int e0 = B_C - g + 2 * tq;
        const uint32_t f0 = ((e0 & 1) ? (kb + B_KLEN * 2 + 64 + (e0 - 1) * 2) : (kb + e0 * 2)) - 32 * wq;
        const uint32_t lo = uniform((ub >> 4) | 0x10000);
        float d[32];
#pragma unroll
        for (int i = 0; i < 32; i++) d[i] = 0.f;
        uint32_t A[2][2][4];
        static_for<0, 32>([&](auto jc) {
            constexpr int j = decltype(jc)::value, N = 64 - 8 * (j / 4);
            if (j >= 2) wg_wait<1>();
            uint32_t(&a)[4] = A[j & 1][0];
            uint32_t(&b)[4] = A[j & 1][1];
            a[0] = lds32(f0 - 128 * j); a[1] = lds32(f0 - 128 * j - 16); a[2] = lds32(f0 - 128 * j + 16);
            b[0] = lds32(f0 - 128 * j + 32); b[2] = lds32(f0 - 128 * j + 48);
            a[3] = a[0] ^ zero; b[1] = a[2] ^ zero; b[3] = b[0] ^ zero;
            wg_fence();
            wgmma_conv<N, 8 * j>(d, a, lo);
            wgmma_conv<N, 8 * j + 2>(d, b, lo);
            wg_commit();
        });
        wg_wait<0>();
        if (cc) SP(4);
        if (PF_STOP == 1 && cc && t == 0) sts32(flag, 1);
        bar_sync(2 + wg, 128);
        if (!hi && tq == 3) { float x = d[13]; d[13] = d[29]; d[29] = x; x = d[15]; d[15] = d[31]; d[31] = x; }
        if (hi && tq == 0) { d[0] = 0.f; d[2] = 0.f; }
        {
            const uint32_t xs = kb + (wq ^ 2) * 2048 + lane * 4;
            const uint32_t xn = hi ? xs + (tq ? 124 : 140) : xs + (tq < 3 ? 4 : -12), wrap = hi ? (tq ? 0 : -1) : (tq < 3 ? 0 : 1);
#pragma unroll
            for (int nb = 0; nb < 4; nb++) {
                const uint32_t xw = xn + ((nb + wrap) & 3) * 512;
#pragma unroll
                for (int i = 0; i < 2; i++) {
                    const float e0v = hi ? d[4 * nb + 2 * i] : d[16 + 4 * nb + 2 * i], e1v = hi ? d[4 * nb + 2 * i + 1] : d[16 + 4 * nb + 2 * i + 1];
                    sts32(hi ? xw + i * 256 : xs + nb * 512 + i * 256 + 128, __float_as_uint(e0v));
                    sts32(hi ? xs + nb * 512 + i * 256 : xw + i * 256, __float_as_uint(e1v));
                }
            }
        }
        bar_sync(2 + wg, 128);
#pragma unroll
        for (int p = 0; p < 2; p++) {
            int row = 16 * p + (lane >> 4) * 8 + (lane & 7);
            row = hi ? row + 31 : row == 31 ? 63 : row;
            const uint32_t a = sb + B_SM_U + swz64(ch * B_UCH + row * 64 + ((wq & 1) * 2 + ((lane >> 3) & 1)) * 16);
            uint32_t u[4];
            ldsm4t(u, a);
#pragma unroll
            for (int b = 0; b < 4; b++) {
                const int r = 8 * p + 2 * b;
                const float y0 = (hi ? d[16 + r] : d[r]) + __uint_as_float(lds32(kb + wq * 2048 + r * 128 + lane * 4));
                const float y1 = (hi ? d[17 + r] : d[r + 1]) + __uint_as_float(lds32(kb + wq * 2048 + r * 128 + 128 + lane * 4));
                u[b] = bf16_add(pack_bf16(y0, y1), bf16_mul(u[b], dw));
            }
            stsm4t(a, u[0], u[1], u[2], u[3]);
        }
        fence_async();
        bar_sync(2 + wg, 128);
        if (SENT_AT == 3 && cc == 0) sentinels();
        if (wq == 0 && lane == 0) copy_to_peer(peer_addr(sb + B_SM_S + ch * B_SCH, rank ^ 1), ub + rank * 2048, 2048, peer_addr(barY, rank ^ 1));
    }
    if (PF_STOP == 2 && t == 0) sts32(flag, 1);
    SP(5);
    mbar_wait_w(barQ, 0);
    bar_sync(1, 512);
    mbar_wait_w(barY, 0);
    asm volatile("barrier.cluster.arrive.relaxed.aligned;" ::: "memory");
    SP(6);
#pragma unroll
    for (int i = 0; i < 4; i++) {
        const int fr = i & 1, row = 63 - 32 * rank - 2 * warp - (i >> 1);
        const uint32_t qa = sb + B_SM_QT + warp * 2048 + (i >> 1) * 1024 + lane * 32 + ((rank ^ fr ^ (lane >> 2)) & 1) * 16;
        uint32_t y[4], q[4];
        ldsm4t(y, sb + (fr ? B_SM_S + (lane & 7) * (B_SCH - B_UCH) - (1 - rank) * 2048 : B_SM_U) + swz64((lane & 7) * B_UCH + row * 64 + (lane >> 3) * 16));
        ldsm4(q, qa);
        stsm4(qa, bf16_mul(q[0], y[0]), bf16_mul(q[1], y[1]), bf16_mul(q[2], y[2]), bf16_mul(q[3], y[3]));
    }
    fence_async();
    __syncwarp();
    if (lane == 0) {
        asm volatile("cp.async.bulk.tensor.2d.global.shared::cta.bulk_group.L2::cache_hint [%0, {%2, %3}], [%1], %4;"
                     ::"l"(&mapO), "r"(sb + B_SM_QT + warp * 2048), "r"(DM + c16), "r"(t0 + warp * 64), "l"(EF(4)) : "memory");
        asm volatile("cp.async.bulk.commit_group;" ::: "memory");
    }
    if (SENT_AT == 0) sentinels();
    if (warp == 0) SP2(10);
    if (lane == 0) asm volatile("cp.async.bulk.wait_group.read 0;" ::: "memory");
    __syncwarp();
    if (warp == 0) SP2(11);
    asm volatile("barrier.cluster.wait.aligned;" ::: "memory");
    SP(7);
    KT_END(1);
}

typedef CUresult (*EncodeFn)(CUtensorMap*, CUtensorMapDataType, cuuint32_t, void*, const cuuint64_t*, const cuuint64_t*, const cuuint32_t*,
                             const cuuint32_t*, CUtensorMapInterleave, CUtensorMapSwizzle, CUtensorMapL2promotion, CUtensorMapFloatOOBfill);

static void make_map(EncodeFn fn, CUtensorMap* m, const void* ptr, uint64_t inner, uint64_t outer, uint32_t box_in, uint32_t box_out,
                     CUtensorMapL2promotion promo = CU_TENSOR_MAP_L2_PROMOTION_L2_256B) {
    cuuint64_t dims[2] = {inner, outer};
    cuuint64_t strides[1] = {inner * 2};
    cuuint32_t box[2] = {box_in, box_out};
    cuuint32_t es[2] = {1, 1};
    fn(m, CU_TENSOR_MAP_DATA_TYPE_BFLOAT16, 2, const_cast<void*>(ptr), dims, strides, box, es, CU_TENSOR_MAP_INTERLEAVE_NONE,
       CU_TENSOR_MAP_SWIZZLE_128B, promo, CU_TENSOR_MAP_FLOAT_OOB_FILL_NONE);
}

#define SSM_PROMO CU_TENSOR_MAP_L2_PROMOTION_NONE
extern "C" void kernel_launch(void* const* d_in, const int* in_sizes, int n_in, void* d_out, int out_size) {
    const bf16* x = (const bf16*)d_in[0];
    const bf16* mem0 = (const bf16*)d_in[1];
    const bf16* Wq = (const bf16*)d_in[2];
    const bf16* Wk = (const bf16*)d_in[3];
    const bf16* Wv = (const bf16*)d_in[4];
    const bf16* Wo = (const bf16*)d_in[5];
    const bf16* Bq = (const bf16*)d_in[7];
    const bf16* Bk = (const bf16*)d_in[8];
    const bf16* Bv = (const bf16*)d_in[9];
    const bf16* Bsh = (const bf16*)d_in[10];
    const bf16* Bssm = (const bf16*)d_in[11];
    const bf16* BD = (const bf16*)d_in[12];
    bf16* out = (bf16*)d_out;

    static bool init = false;
    static EncodeFn enc = nullptr;
    static void *p_tok, *p_ox, *p_mbox;
    static int nclusters = 64;
    using G2 = GemmCfg<128, 5>;
    if (!init) {
        cudaDriverEntryPointQueryResult qr;
        cudaGetDriverEntryPoint("cuTensorMapEncodeTiled", (void**)&enc, cudaEnableDefault, &qr);
        cudaGetSymbolAddress(&p_tok, g_tok);
        cudaGetSymbolAddress(&p_ox, g_ox);
        cudaGetSymbolAddress(&p_mbox, g_mbox);
        cudaFuncSetAttribute(gemm_kernel<128, 5>, cudaFuncAttributeMaxDynamicSharedMemorySize, G2::SMEM);
        cudaFuncSetAttribute(chain_kernel, cudaFuncAttributeMaxDynamicSharedMemorySize, CHAIN_SMEM);
        cudaFuncSetAttribute(ssm_kernel, cudaFuncAttributeMaxDynamicSharedMemorySize, B_SMEM);
        cudaLaunchConfig_t cfg = {};
        cfg.gridDim = dim3(132); cfg.blockDim = dim3(384); cfg.dynamicSmemBytes = CHAIN_SMEM;
        cudaLaunchAttribute at[1];
        at[0].id = cudaLaunchAttributeClusterDimension; at[0].val.clusterDim.x = 2; at[0].val.clusterDim.y = 1; at[0].val.clusterDim.z = 1;
        cfg.attrs = at; cfg.numAttrs = 1;
        int n = 0;
        if (cudaOccupancyMaxActiveClusters(&n, chain_kernel, &cfg) == cudaSuccess && n > 64) nclusters = n < 66 ? n : 66;
        (void)cudaGetLastError();
        init = true;
    }
    char* mbox = (char*)(((uintptr_t)p_mbox + 2 * WIN - 1) & ~(uintptr_t)(2 * WIN - 1));
    CUtensorMap mX, mT32, mT16, mTQ, mKV, mWq, mWk, mWv, mWoC, mOx, mWo, mOut;
    {
        cuuint64_t dims[3] = {64, S_LEN, DM / 64};
        cuuint64_t strides[2] = {DM * 2, 128};
        cuuint32_t box[3] = {64, 32, 4};
        cuuint32_t es[3] = {1, 1, 1};
        enc(&mX, CU_TENSOR_MAP_DATA_TYPE_BFLOAT16, 3, const_cast<bf16*>(x), dims, strides, box, es, CU_TENSOR_MAP_INTERLEAVE_NONE,
            CU_TENSOR_MAP_SWIZZLE_128B, CU_TENSOR_MAP_L2_PROMOTION_L2_256B, CU_TENSOR_MAP_FLOAT_OOB_FILL_NONE);
    }
    make_map(enc, &mT32, p_tok, DH, 4 * NH * 3 * SEG, 64, 32, CU_TENSOR_MAP_L2_PROMOTION_L2_128B);
    make_map(enc, &mT16, p_tok, DH, 4 * NH * 3 * SEG, 64, 16, CU_TENSOR_MAP_L2_PROMOTION_L2_128B);
    {
        cuuint64_t dims[2] = {512, 4 * NH * 12};
        cuuint64_t strides[1] = {2048};
        cuuint32_t box[2] = {256, 4};
        cuuint32_t es[2] = {1, 1};
        enc(&mTQ, CU_TENSOR_MAP_DATA_TYPE_UINT32, 2, p_tok, dims, strides, box, es, CU_TENSOR_MAP_INTERLEAVE_NONE,
            CU_TENSOR_MAP_SWIZZLE_NONE, CU_TENSOR_MAP_L2_PROMOTION_L2_128B, CU_TENSOR_MAP_FLOAT_OOB_FILL_NONE);
    }
    {
        cuuint64_t dims[3] = {64, 4 * NH * 3 * SEG, 2};
        cuuint64_t strides[2] = {DH * 2, 128};
        cuuint32_t box[3] = {64, 32, 2};
        cuuint32_t es[3] = {1, 1, 1};
        enc(&mKV, CU_TENSOR_MAP_DATA_TYPE_BFLOAT16, 3, p_tok, dims, strides, box, es, CU_TENSOR_MAP_INTERLEAVE_NONE,
            CU_TENSOR_MAP_SWIZZLE_128B, CU_TENSOR_MAP_L2_PROMOTION_L2_128B, CU_TENSOR_MAP_FLOAT_OOB_FILL_NONE);
    }
    make_map(enc, &mWq, Wq, HD, DM, 64, 16, CU_TENSOR_MAP_L2_PROMOTION_L2_128B);
    make_map(enc, &mWk, Wk, HD, DM, 64, 16, CU_TENSOR_MAP_L2_PROMOTION_L2_128B);
    make_map(enc, &mWv, Wv, HD, DM, 64, 16, CU_TENSOR_MAP_L2_PROMOTION_L2_128B);
    make_map(enc, &mWoC, Wo, DM, HD, 64, 128, CU_TENSOR_MAP_L2_PROMOTION_L2_128B);
    make_map(enc, &mOx, p_ox, HD, S_LEN, 64, 128);
    make_map(enc, &mWo, Wo, DM, HD, 64, 64);
    make_map(enc, &mOut, out, OUT_LD, S_LEN, 64, 64);

    CUtensorMap mB[4];
    for (int i = 0; i < 4; i++) {
        cuuint64_t dims[2] = {(cuuint64_t)(i < 3 ? DM : OUT_LD), S_LEN};
        cuuint64_t strides[1] = {dims[0] * 2};
        cuuint32_t box[2] = {16, i == 0 ? 136u : i < 3 ? 128u : 64u};
        cuuint32_t es[2] = {1, 1};
        enc(&mB[i], CU_TENSOR_MAP_DATA_TYPE_BFLOAT16, 2, const_cast<bf16*>(i == 0 ? Bk : i == 1 ? Bv : i == 2 ? Bq : out), dims, strides, box, es,
            CU_TENSOR_MAP_INTERLEAVE_NONE, CU_TENSOR_MAP_SWIZZLE_32B, SSM_PROMO, CU_TENSOR_MAP_FLOAT_OOB_FILL_NONE);
    }
    cudaStream_t st = cudaStreamPerThread;
    const ChainInputs ci = {{(const char*)Wv, (const char*)Wk, (const char*)Wq, (const char*)Wo}, (const char*)x, (const char*)mem0};
    ssm_kernel<<<132, 576, B_SMEM, st>>>(mB[0], mB[1], mB[2], mB[3], Bsh, Bssm, BD, mbox, ci);
    chain_kernel<<<2 * nclusters, 384, CHAIN_SMEM, st>>>(mX, mT32, mT16, mTQ, mKV, mWq, mWk, mWv, mWoC, mem0, mbox);
    gemm_kernel<128, 5><<<128, 288, G2::SMEM, st>>>(mOx, mWo, mWo, mWo, mOut, 16, 8, 64);
}
```

```cpp
#include <cuda_runtime.h>
#include <cuda_bf16.h>
#include <cuda.h>
#include <stdint.h>
#include <type_traits>

typedef __nv_bfloat16 bf16;

constexpr int S_LEN = 2048, DM = 1024, NH = 32, DH = 128, NSEG = 64, SEG = 32;
constexpr int HD = NH * DH;
constexpr int OUT_LD = 2048;
constexpr unsigned SENT = 0xFFFFFFFFu;

__device__ bf16 g_tok[4 * NH * 3 * SEG * DH];
__device__ bf16 g_ox[(size_t)S_LEN * HD];
__device__ uint4 g_mbox[4 * 131072];
__device__ unsigned g_xflag[128];
__device__ unsigned g_reg[4];
__device__ unsigned g_cls[256];
__device__ unsigned g_err;
constexpr uint32_t WIN = 2u << 20;
__host__ __device__ constexpr uint32_t page_off(uint32_t idx, uint32_t c) {
    return ((idx & 1) << 13) | ((idx >> 1) << 16) | (((c ^ idx ^ (idx >> 1) ^ (idx >> 2) ^ (idx >> 4)) & 1) << 12);
}
#define STAT(i, c) (void)(c)
#define KT_MARK(k)
#define KT_START(k)
#define KT_END(k)

__device__ __forceinline__ uint32_t smem_u32(const void* p) { return (uint32_t)__cvta_generic_to_shared(p); }
__device__ __forceinline__ void ldsm4(uint32_t& r0, uint32_t& r1, uint32_t& r2, uint32_t& r3, uint32_t a) {
    asm volatile("ldmatrix.sync.aligned.m8n8.x4.shared.b16 {%0,%1,%2,%3}, [%4];" : "=r"(r0), "=r"(r1), "=r"(r2), "=r"(r3) : "r"(a) : "memory");
}
__device__ __forceinline__ void ldsm4t(uint32_t& r0, uint32_t& r1, uint32_t& r2, uint32_t& r3, uint32_t a) {
    asm volatile("ldmatrix.sync.aligned.m8n8.x4.trans.shared.b16 {%0,%1,%2,%3}, [%4];" : "=r"(r0), "=r"(r1), "=r"(r2), "=r"(r3) : "r"(a) : "memory");
}
__device__ __forceinline__ void ldsm2(uint32_t& r0, uint32_t& r1, uint32_t a) {
    asm volatile("ldmatrix.sync.aligned.m8n8.x2.shared.b16 {%0,%1}, [%2];" : "=r"(r0), "=r"(r1) : "r"(a) : "memory");
}
__device__ __forceinline__ void stg128(void* p, uint4 v) {
    asm volatile("st.global.v4.u32 [%0], {%1,%2,%3,%4};" ::"l"(p), "r"(v.x), "r"(v.y), "r"(v.z), "r"(v.w) : "memory");
}
__device__ __forceinline__ void stsm4(uint32_t a, uint32_t r0, uint32_t r1, uint32_t r2, uint32_t r3) {
    asm volatile("stmatrix.sync.aligned.m8n8.x4.shared.b16 [%0], {%1,%2,%3,%4};" ::"r"(a), "r"(r0), "r"(r1), "r"(r2), "r"(r3) : "memory");
}
__device__ __forceinline__ void mma16816(float (&d)[4], uint32_t a0, uint32_t a1, uint32_t a2, uint32_t a3, uint32_t b0, uint32_t b1) {
    asm("mma.sync.aligned.m16n8k16.row.col.f32.bf16.bf16.f32 {%0,%1,%2,%3},{%4,%5,%6,%7},{%8,%9},{%0,%1,%2,%3};"
                 : "+f"(d[0]), "+f"(d[1]), "+f"(d[2]), "+f"(d[3])
                 : "r"(a0), "r"(a1), "r"(a2), "r"(a3), "r"(b0), "r"(b1));
}
__device__ __forceinline__ void mma1688(float (&d)[4], uint32_t a0, uint32_t a1, uint32_t b0) {
    asm("mma.sync.aligned.m16n8k8.row.col.f32.bf16.bf16.f32 {%0,%1,%2,%3},{%4,%5},{%6},{%0,%1,%2,%3};"
        : "+f"(d[0]), "+f"(d[1]), "+f"(d[2]), "+f"(d[3]) : "r"(a0), "r"(a1), "r"(b0));
}
__device__ __forceinline__ uint32_t movmat(uint32_t a) {
    uint32_t d;
    asm volatile("movmatrix.sync.aligned.m8n8.trans.b16 %0, %1;" : "=r"(d) : "r"(a));
    return d;
}
__device__ __forceinline__ uint32_t pack_bf16(float lo, float hi) {
    uint32_t r;
    asm("cvt.rn.bf16x2.f32 %0, %1, %2;" : "=r"(r) : "f"(hi), "f"(lo));
    return r;
}
__device__ __forceinline__ uint32_t bf16_mul(uint32_t a, uint32_t b) {
    uint32_t d;
    asm("mul.rn.bf16x2 %0, %1, %2;" : "=r"(d) : "r"(a), "r"(b));
    return d;
}
__device__ __forceinline__ uint32_t bf16_add(uint32_t a, uint32_t b) {
    uint32_t d;
    asm("add.rn.bf16x2 %0, %1, %2;" : "=r"(d) : "r"(a), "r"(b));
    return d;
}

__device__ __forceinline__ float bf16_round(float x) { return __bfloat162float(__float2bfloat16_rn(x)); }
__device__ __forceinline__ float bf_lo(uint32_t w) { return __uint_as_float(w << 16); }
__device__ __forceinline__ float bf_hi(uint32_t w) { return __uint_as_float(w & 0xFFFF0000u); }
__device__ __forceinline__ void bar_sync(int id, int n) { asm volatile("bar.sync %0, %1;" ::"r"(id), "r"(n) : "memory"); }
__device__ __forceinline__ void bar_sync_keep(int id, int n, uint32_t a, uint32_t b) {
    asm volatile("bar.sync %0, %1; // %2 %3" ::"r"(id), "r"(n), "r"(a), "r"(b) : "memory");
}
__device__ __forceinline__ bool bar_red_or(int id, int n, bool p) {
    uint32_t r;
    asm volatile("{.reg .pred p, q; setp.ne.u32 p, %3, 0; bar.red.or.pred q, %1, %2, p; selp.u32 %0, 1, 0, q;}" : "=r"(r) : "r"(id), "r"(n), "r"((uint32_t)p) : "memory");
    return r != 0;
}
__device__ __forceinline__ void bar_arrive(int id, int n) { asm volatile("bar.arrive %0, %1;" ::"r"(id), "r"(n) : "memory"); }
__device__ __forceinline__ void cp_async16(uint32_t dst, const void* src) {
    asm volatile("cp.async.cg.shared.global [%0], [%1], 16;" ::"r"(dst), "l"(src) : "memory");
}
__device__ __forceinline__ void cp_commit() { asm volatile("cp.async.commit_group;" ::: "memory"); }
template <int N> __device__ __forceinline__ void cp_wait() { asm volatile("cp.async.wait_group %0;" ::"n"(N) : "memory"); }
__device__ __forceinline__ uint4 ld_relaxed_v4(const void* p) {
    uint4 v;
    asm volatile("ld.relaxed.gpu.global.v4.u32 {%0,%1,%2,%3}, [%4];" : "=r"(v.x), "=r"(v.y), "=r"(v.z), "=r"(v.w) : "l"(p) : "memory");
    return v;
}
__device__ __forceinline__ void st_relaxed_u32(void* p, uint32_t v) { asm volatile("st.relaxed.gpu.global.u32 [%0], %1;" ::"l"(p), "r"(v) : "memory"); }
__device__ __forceinline__ void st_relaxed_v2(void* p, uint32_t a, uint32_t b) {
    asm volatile("st.relaxed.gpu.global.v2.u32 [%0], {%1,%2};" ::"l"(p), "r"(a), "r"(b) : "memory");
}
__device__ __forceinline__ void sts128(uint32_t a, uint4 v) {
    asm volatile("st.shared.v4.u32 [%0], {%1,%2,%3,%4};" ::"r"(a), "r"(v.x), "r"(v.y), "r"(v.z), "r"(v.w) : "memory");
}
__device__ __forceinline__ uint4 lds128(uint32_t a) {
    uint4 v;
    asm volatile("ld.shared.v4.u32 {%0,%1,%2,%3}, [%4];" : "=r"(v.x), "=r"(v.y), "=r"(v.z), "=r"(v.w) : "r"(a) : "memory");
    return v;
}
__device__ __forceinline__ void sts32(uint32_t a, uint32_t v) { asm volatile("st.shared.u32 [%0], %1;" ::"r"(a), "r"(v) : "memory"); }
__device__ __forceinline__ uint32_t lds32(uint32_t a) {
    uint32_t v;
    asm volatile("ld.shared.u32 %0, [%1];" : "=r"(v) : "r"(a) : "memory");
    return v;
}
__device__ __forceinline__ void mbar_init(uint32_t a, uint32_t c) { asm volatile("mbarrier.init.shared::cta.b64 [%0], %1;" ::"r"(a), "r"(c) : "memory"); }
__device__ __forceinline__ void mbar_expect_tx(uint32_t a, uint32_t bytes) {
    asm volatile("mbarrier.arrive.expect_tx.shared::cta.b64 _, [%0], %1;" ::"r"(a), "r"(bytes) : "memory");
}
__device__ __forceinline__ void mbar_arrive(uint32_t a) { asm volatile("mbarrier.arrive.shared::cta.b64 _, [%0];" ::"r"(a) : "memory"); }
__device__ __forceinline__ void mbar_wait(uint32_t a, uint32_t parity) {
    asm volatile("{.reg .pred p; .reg .u32 c;\n"
                 "mov.u32 c, 0;\n"
                 "MBW_LOOP:\n"
                 "add.u32 c, c, 1;\n"
                 "setp.gt.u32 p, c, 0x10000;\n"
                 "@!p mbarrier.try_wait.parity.shared::cta.b64 p, [%0], %1;\n"
                 "@!p bra.uni MBW_LOOP;}" ::"r"(a), "r"(parity) : "memory");
}
__device__ __forceinline__ void mbar_wait_w(uint32_t a, uint32_t parity) {
    asm volatile("{.reg .pred p; .reg .u32 c;\n"
                 "mov.u32 c, 0;\n"
                 "MBW_LOOP:\n"
                 "add.u32 c, c, 1;\n"
                 "setp.gt.u32 p, c, 0x10000;\n"
                 "@!p mbarrier.try_wait.parity.shared::cta.b64 p, [%0], %1;\n"
                 "vote.sync.all.pred p, p, 0xFFFFFFFF;\n"
                 "@!p bra.uni MBW_LOOP;}" ::"r"(a), "r"(parity) : "memory");
}
__device__ __forceinline__ void mbar_expect_tx_if0(uint32_t sel, uint32_t a, uint32_t bytes) {
    asm volatile("{.reg .pred p; setp.eq.u32 p, %2, 0; @p mbarrier.arrive.expect_tx.shared::cta.b64 _, [%0], %1;}" ::"r"(a), "r"(bytes), "r"(sel) : "memory");
}
__device__ __forceinline__ void mbar_arrive_if0(uint32_t sel, uint32_t a) {
    asm volatile("{.reg .pred p; setp.eq.u32 p, %1, 0; @p mbarrier.arrive.shared::cta.b64 _, [%0];}" ::"r"(a), "r"(sel) : "memory");
}
__device__ __forceinline__ void bulk_load(uint32_t dst, const void* src, uint32_t bytes, uint32_t bar) {
    asm volatile("cp.async.bulk.shared::cluster.global.mbarrier::complete_tx::bytes [%0], [%1], %2, [%3];" ::"r"(dst), "l"(src), "r"(bytes), "r"(bar) : "memory");
}
__device__ __forceinline__ void tma_load_2d(uint32_t dst, const CUtensorMap* map, int c0, int c1, uint32_t bar) {
    asm volatile("cp.async.bulk.tensor.2d.shared::cluster.global.mbarrier::complete_tx::bytes [%0], [%1, {%3, %4}], [%2];"
                 ::"r"(dst), "l"(map), "r"(bar), "r"(c0), "r"(c1) : "memory");
}
__device__ __forceinline__ uint64_t policy_evict_first() {
    uint64_t p;
    asm("createpolicy.fractional.L2::evict_first.b64 %0, 1.0;" : "=l"(p));
    return p;
}
__device__ __forceinline__ uint64_t policy_evict_normal() {
    uint64_t p;
    asm("createpolicy.fractional.L2::evict_normal.b64 %0, 1.0;" : "=l"(p));
    return p;
}
__device__ __forceinline__ void tma_load_2d(uint32_t dst, const CUtensorMap* map, int c0, int c1, uint32_t bar, uint64_t pol) {
    asm volatile("cp.async.bulk.tensor.2d.shared::cluster.global.mbarrier::complete_tx::bytes.L2::cache_hint [%0], [%1, {%3, %4}], [%2], %5;"
                 ::"r"(dst), "l"(map), "r"(bar), "r"(c0), "r"(c1), "l"(pol) : "memory");
}
__device__ __forceinline__ uint4 ldg128(const void* p, uint64_t pol) {
    uint4 v;
    asm("ld.global.nc.L2::cache_hint.v4.u32 {%0,%1,%2,%3}, [%4], %5;" : "=r"(v.x), "=r"(v.y), "=r"(v.z), "=r"(v.w) : "l"(p), "l"(pol));
    return v;
}
__device__ __forceinline__ void stg128(void* p, uint4 v, uint64_t pol) {
    asm volatile("st.global.L2::cache_hint.v4.u32 [%0], {%1,%2,%3,%4}, %5;" ::"l"(p), "r"(v.x), "r"(v.y), "r"(v.z), "r"(v.w), "l"(pol) : "memory");
}
__device__ __forceinline__ void tma_store_2d(const CUtensorMap* map, uint32_t src, int c0, int c1) {
    asm volatile("cp.async.bulk.tensor.2d.global.shared::cta.bulk_group [%0, {%2, %3}], [%1];" ::"l"(map), "r"(src), "r"(c0), "r"(c1) : "memory");
}
__device__ __forceinline__ char* make_ptr(uint32_t lo, uint32_t hi) {
    uint64_t p;
    asm("mov.b64 %0, {%1, %2};" : "=l"(p) : "r"(lo), "r"(hi));
    return reinterpret_cast<char*>(p);
}
__device__ __forceinline__ uint64_t make_desc(uint32_t saddr, uint32_t lbo, uint32_t sbo) {
    return (uint64_t)((saddr & 0x3FFFF) >> 4) | ((uint64_t)((lbo >> 4) & 0x3FFF) << 16) | ((uint64_t)((sbo >> 4) & 0x3FFF) << 32) | ((uint64_t)1 << 62);
}
__device__ __forceinline__ void wg_fence() { asm volatile("wgmma.fence.sync.aligned;" ::: "memory"); }
__device__ __forceinline__ void wg_commit() { asm volatile("wgmma.commit_group.sync.aligned;" ::: "memory"); }
template <int N> __device__ __forceinline__ void wg_wait() { asm volatile("wgmma.wait_group.sync.aligned %0;" ::"n"(N) : "memory"); }

#define R4(b) "+f"(d[b + 0]), "+f"(d[b + 1]), "+f"(d[b + 2]), "+f"(d[b + 3])
#define R16(b) R4(b), R4(b + 4), R4(b + 8), R4(b + 12)
__device__ __forceinline__ void wgmma_n128(float (&d)[64], uint64_t da, uint64_t db) {
    asm volatile(
        "wgmma.mma_async.sync.aligned.m64n128k16.f32.bf16.bf16 "
        "{%0,%1,%2,%3,%4,%5,%6,%7,%8,%9,%10,%11,%12,%13,%14,%15,%16,%17,%18,%19,%20,%21,%22,%23,%24,%25,%26,%27,%28,%29,%30,%31,"
        "%32,%33,%34,%35,%36,%37,%38,%39,%40,%41,%42,%43,%44,%45,%46,%47,%48,%49,%50,%51,%52,%53,%54,%55,%56,%57,%58,%59,%60,%61,%62,%63},"
        "%64,%65,1,1,1,0,1;"
        : R16(0), R16(16), R16(32), R16(48)
        : "l"(da), "l"(db));
}
__device__ __forceinline__ void wgmma_n256(float (&d)[128], uint64_t da, uint64_t db) {
    asm volatile(
        "wgmma.mma_async.sync.aligned.m64n256k16.f32.bf16.bf16 "
        "{%0,%1,%2,%3,%4,%5,%6,%7,%8,%9,%10,%11,%12,%13,%14,%15,%16,%17,%18,%19,%20,%21,%22,%23,%24,%25,%26,%27,%28,%29,%30,%31,"
        "%32,%33,%34,%35,%36,%37,%38,%39,%40,%41,%42,%43,%44,%45,%46,%47,%48,%49,%50,%51,%52,%53,%54,%55,%56,%57,%58,%59,%60,%61,%62,%63,"
        "%64,%65,%66,%67,%68,%69,%70,%71,%72,%73,%74,%75,%76,%77,%78,%79,%80,%81,%82,%83,%84,%85,%86,%87,%88,%89,%90,%91,%92,%93,%94,%95,"
        "%96,%97,%98,%99,%100,%101,%102,%103,%104,%105,%106,%107,%108,%109,%110,%111,%112,%113,%114,%115,%116,%117,%118,%119,%120,%121,%122,%123,%124,%125,%126,%127},"
        "%128,%129,1,1,1,0,1;"
        : R16(0), R16(16), R16(32), R16(48), R16(64), R16(80), R16(96), R16(112)
        : "l"(da), "l"(db));
}
template <int BN> struct WgAcc;
template <> struct WgAcc<128> { static __device__ __forceinline__ void mma(float (&d)[64], uint64_t a, uint64_t b) { wgmma_n128(d, a, b); } };
template <> struct WgAcc<256> { static __device__ __forceinline__ void mma(float (&d)[128], uint64_t a, uint64_t b) { wgmma_n256(d, a, b); } };

__device__ __forceinline__ void wgmma_rs32(float (&d)[16], const uint32_t (&a)[4], uint64_t db, bool acc) {
    asm volatile(
        "{.reg .pred p; setp.ne.b32 p, %21, 0;\n"
        "wgmma.mma_async.sync.aligned.m64n32k16.f32.bf16.bf16 {%0,%1,%2,%3,%4,%5,%6,%7,%8,%9,%10,%11,%12,%13,%14,%15}, {%16,%17,%18,%19}, %20, p, 1, 1, 0;}"
        : R16(0) : "r"(a[0]), "r"(a[1]), "r"(a[2]), "r"(a[3]), "l"(db), "n"(1) );
}
__device__ __forceinline__ void wgmma_rs32_first(float (&d)[16], const uint32_t (&a)[4], uint64_t db) {
    asm volatile(
        "{.reg .pred p; setp.ne.b32 p, %21, 0;\n"
        "wgmma.mma_async.sync.aligned.m64n32k16.f32.bf16.bf16 {%0,%1,%2,%3,%4,%5,%6,%7,%8,%9,%10,%11,%12,%13,%14,%15}, {%16,%17,%18,%19}, %20, p, 1, 1, 0;}"
        : R16(0) : "r"(a[0]), "r"(a[1]), "r"(a[2]), "r"(a[3]), "l"(db), "n"(0) );
}
__device__ __forceinline__ void wgmma_ss32(float (&d)[16], uint64_t da, uint64_t db) {
    asm volatile(
        "wgmma.mma_async.sync.aligned.m64n32k16.f32.bf16.bf16 {%0,%1,%2,%3,%4,%5,%6,%7,%8,%9,%10,%11,%12,%13,%14,%15}, %16, %17, 1, 1, 1, 1, 0;"
        : R16(0) : "l"(da), "l"(db));
}
template <int OFF, int ACC> __device__ __forceinline__ void wgmma_rs32u(float (&d)[16], const uint32_t (&a)[4], uint32_t lo) {
    asm volatile(
        "{.reg .pred p; .reg .b32 l; .reg .b64 e; setp.ne.b32 p, %22, 0; add.u32 l, %20, %21; mov.b64 e, {l, 0x40000040};\n"
        "wgmma.mma_async.sync.aligned.m64n32k16.f32.bf16.bf16 {%0,%1,%2,%3,%4,%5,%6,%7,%8,%9,%10,%11,%12,%13,%14,%15}, {%16,%17,%18,%19}, e, p, 1, 1, 0;}"
        : R16(0) : "r"(a[0]), "r"(a[1]), "r"(a[2]), "r"(a[3]), "r"(lo), "n"(OFF), "n"(ACC));
}
template <int OFF> __device__ __forceinline__ void wgmma_ss32u(float (&d)[16], uint64_t da, uint32_t lo) {
    asm volatile(
        "{.reg .b32 l; .reg .b64 e; add.u32 l, %17, %18; mov.b64 e, {l, 0x40000040};\n"
        "wgmma.mma_async.sync.aligned.m64n32k16.f32.bf16.bf16 {%0,%1,%2,%3,%4,%5,%6,%7,%8,%9,%10,%11,%12,%13,%14,%15}, %16, e, 1, 1, 1, 1, 0;}"
        : R16(0) : "l"(da), "r"(lo), "n"(OFF));
}
template <int K0, int K1, class F> __device__ __forceinline__ void static_for(F f) {
    if constexpr (K0 < K1) { f(std::integral_constant<int, K0>()); static_for<K0 + 1, K1>(f); }
}
__device__ __forceinline__ void st_async4(uint32_t a, float x, float y, float z, float w, uint32_t bar) {
    asm volatile("st.async.weak.shared::cluster.mbarrier::complete_tx::bytes.v4.f32 [%0], {%1,%2,%3,%4}, [%5];" ::"r"(a), "f"(x), "f"(y), "f"(z), "f"(w), "r"(bar) : "memory");
}
__device__ __forceinline__ void st_async2(uint32_t a, float x, float y, uint32_t bar) {
    asm volatile("st.async.weak.shared::cluster.mbarrier::complete_tx::bytes.v2.f32 [%0], {%1,%2}, [%3];" ::"r"(a), "f"(x), "f"(y), "r"(bar) : "memory");
}
__device__ __forceinline__ void st_async1(uint32_t a, uint32_t x, uint32_t bar) {
    asm volatile("st.async.weak.shared::cluster.mbarrier::complete_tx::bytes.b32 [%0], %1, [%2];" ::"r"(a), "r"(x), "r"(bar) : "memory");
}
__device__ __forceinline__ void stsm4t(uint32_t a, uint32_t r0, uint32_t r1, uint32_t r2, uint32_t r3) {
    asm volatile("stmatrix.sync.aligned.m8n8.x4.trans.shared.b16 [%0], {%1,%2,%3,%4};" ::"r"(a), "r"(r0), "r"(r1), "r"(r2), "r"(r3) : "memory");
}
__device__ __forceinline__ void ldsm4t(uint32_t (&r)[4], uint32_t a) { ldsm4t(r[0], r[1], r[2], r[3], a); }
__device__ __forceinline__ void ldsm4(uint32_t (&r)[4], uint32_t a) { ldsm4(r[0], r[1], r[2], r[3], a); }
__device__ __forceinline__ void mma16816(float (&d)[4], const uint32_t (&a)[4], uint32_t b0, uint32_t b1) { mma16816(d, a[0], a[1], a[2], a[3], b0, b1); }
__device__ __forceinline__ void sched_fence(uint32_t v) {
    asm volatile("{.reg .pred p; setp.ne.u32 p, %0, 0xFFFFFFFF; vote.sync.all.pred p, p, 0xFFFFFFFF; @p bra.uni SF_OK; exit; SF_OK:}" ::"r"(v) : "memory");
}
__device__ __forceinline__ void mma16816v(float (&d)[4], const uint32_t (&a)[4], uint32_t b0, uint32_t b1) {
    asm volatile("mma.sync.aligned.m16n8k16.row.col.f32.bf16.bf16.f32 {%0,%1,%2,%3},{%4,%5,%6,%7},{%8,%9},{%0,%1,%2,%3};"
                 : "+f"(d[0]), "+f"(d[1]), "+f"(d[2]), "+f"(d[3]) : "r"(a[0]), "r"(a[1]), "r"(a[2]), "r"(a[3]), "r"(b0), "r"(b1));
}
__device__ __forceinline__ uint32_t uniform(uint32_t v) { return __reduce_max_sync(~0u, v); }

template <int BN, int STAGES> struct GemmCfg {
    static constexpr int A_BYTES = 128 * 64 * 2;
    static constexpr int B_BYTES = BN * 64 * 2;
    static constexpr int STAGE_BYTES = A_BYTES + B_BYTES;
    static constexpr int EPI_BYTES = 128 * BN * 2;
    static constexpr int SMEM = STAGES * STAGE_BYTES + EPI_BYTES + 1024 + 256;
};

template <int BN, int STAGES>
__global__ void __cluster_dims__(2, 1, 1) __launch_bounds__(288, 1)
gemm_kernel(const __grid_constant__ CUtensorMap mapA, const __grid_constant__ CUtensorMap mapB0, const __grid_constant__ CUtensorMap mapB1,
            const __grid_constant__ CUtensorMap mapB2, const __grid_constant__ CUtensorMap mapC, int tiles_m, int tiles_n, int kblocks) {
    using Cfg = GemmCfg<BN, STAGES>;
    KT_START(BN == 256 ? 0 : 3);
    extern __shared__ uint8_t smem_raw[];
    const uint32_t sbase = (smem_u32(smem_raw) + 1023) & ~1023u;
    const uint32_t epi = sbase + STAGES * Cfg::STAGE_BYTES;
    const uint32_t bars = epi + Cfg::EPI_BYTES;
    const int warp = threadIdx.x >> 5, lane = threadIdx.x & 31;
    const uint32_t rank = blockIdx.x & 1;
    if (threadIdx.x == 0) {
        for (int i = 0; i < STAGES; i++) { mbar_init(bars + 8 * i, 1); mbar_init(bars + 8 * (STAGES + i), 16); }
        asm volatile("fence.mbarrier_init.release.cluster;" ::: "memory");
    }
    __syncthreads();
    asm volatile("barrier.cluster.arrive.release.aligned; barrier.cluster.wait.acquire.aligned;" ::: "memory");
    const int npairs = (tiles_m >> 1) * tiles_n, ncl = gridDim.x >> 1;
    if (warp == 8) {
        if (lane == 0) {
            int st = 0; uint32_t ph = 1;
            for (int pr = blockIdx.x >> 1; pr < npairs; pr += ncl) {
                const int tm = 2 * (pr % (tiles_m >> 1)) + rank, tn = pr / (tiles_m >> 1);
                const int n0 = tn * BN;
                const CUtensorMap* mb = (n0 < 4096) ? &mapB0 : (n0 < 8192 ? &mapB1 : &mapB2);
                const int nb = n0 & 4095;
                for (int kb = 0; kb < kblocks; kb++) {
                    mbar_wait(bars + 8 * (STAGES + st), ph);
                    const uint32_t full = bars + 8 * st;
                    mbar_expect_tx(full, Cfg::STAGE_BYTES);
                    const uint32_t sa = sbase + st * Cfg::STAGE_BYTES;
                    tma_load_2d(sa, &mapA, kb * 64, tm * 128, full);
#pragma unroll
                    for (int i = 0; i < BN / 128; i++) {
                        const int bx = rank * (BN / 128) + i;
                        asm volatile("cp.async.bulk.tensor.2d.shared::cluster.global.mbarrier::complete_tx::bytes.multicast::cluster [%0], [%1, {%3, %4}], [%2], %5;"
                                     ::"r"(sa + Cfg::A_BYTES + bx * 8192), "l"(mb), "r"(full), "r"(nb + bx * 64), "r"(kb * 64), "h"((uint16_t)3) : "memory");
                    }
                    if (++st == STAGES) { st = 0; ph ^= 1; }
                }
            }
        }
    } else {
        const int wg = warp >> 2;
        uint32_t peer_empty;
        asm volatile("mapa.shared::cluster.u32 %0, %1, %2;" : "=r"(peer_empty) : "r"(bars + 8 * STAGES), "r"(rank ^ 1));
        auto release = [&](int stg) {
            if (lane == 0) {
                mbar_arrive(bars + 8 * (STAGES + stg));
                asm volatile("mbarrier.arrive.shared::cluster.b64 _, [%0];" ::"r"(peer_empty + 8 * stg) : "memory");
            }
        };
        const uint32_t ew = epi + wg * (64 * BN * 2);
        int st = 0; uint32_t ph = 0;
        for (int pr = blockIdx.x >> 1; pr < npairs; pr += ncl) {
            const int tm = 2 * (pr % (tiles_m >> 1)) + rank, tn = pr / (tiles_m >> 1);
            float d[BN / 2];
#pragma unroll
            for (int i = 0; i < BN / 2; i++) d[i] = 0.f;
            int prev = -1;
            for (int kb = 0; kb < kblocks; kb++) {
                mbar_wait(bars + 8 * st, ph);
                const uint32_t sa = sbase + st * Cfg::STAGE_BYTES;
                const uint64_t da = make_desc(sa + wg * 8192, 16, 1024);
                const uint64_t db = make_desc(sa + Cfg::A_BYTES, 8192, 1024);
                wg_fence();
#pragma unroll
                for (int k = 0; k < 4; k++) WgAcc<BN>::mma(d, da + k * 2, db + k * 128);
                wg_commit();
                if (prev >= 0) { wg_wait<1>(); release(prev); }
                prev = st;
                if (++st == STAGES) { st = 0; ph ^= 1; }
            }
            wg_wait<0>();
            release(prev);
            if ((warp & 3) == 0 && lane == 0) asm volatile("cp.async.bulk.wait_group.read 0;" ::: "memory");
            bar_sync(1 + wg, 128);
            const int r = (warp & 3) * 16 + (lane & 7) + ((lane >> 3) & 1) * 8;
#pragma unroll
            for (int c = 0; c < BN / 64; c++)
#pragma unroll
                for (int i = 0; i < 4; i++) {
                    const int b = (c * 8 + i * 2) * 4;
                    stsm4(ew + c * 8192 + r * 128 + (((i * 2 + (lane >> 4)) ^ (r & 7)) * 16), pack_bf16(d[b], d[b + 1]), pack_bf16(d[b + 2], d[b + 3]),
                          pack_bf16(d[b + 4], d[b + 5]), pack_bf16(d[b + 6], d[b + 7]));
                }
            asm volatile("fence.proxy.async.shared::cta;" ::: "memory");
            bar_sync(1 + wg, 128);
            if ((warp & 3) == 0 && lane == 0) {
#pragma unroll
                for (int c = 0; c < BN / 64; c++)
                    asm volatile("cp.async.bulk.tensor.2d.global.shared::cta.bulk_group [%0, {%2, %3}], [%1];"
                                 ::"l"(&mapC), "r"(ew + c * 8192), "r"(tn * BN + c * 64), "r"(tm * 128 + wg * 64) : "memory");
                asm volatile("cp.async.bulk.commit_group;" ::: "memory");
            }
        }
        if ((warp & 3) == 0 && lane == 0) asm volatile("cp.async.bulk.wait_group 0;" ::: "memory");
    }
    __syncwarp();
    KT_END(BN == 256 ? 0 : 3);
    asm volatile("barrier.cluster.arrive.relaxed; barrier.cluster.wait;" ::: "memory");
}

#define WO_RF1 6
constexpr int SM_KV = 0, KV_BYTES = 18432;
constexpr int SM_XT = 2 * KV_BYTES;
constexpr int SM_STG = SM_XT + 65536;
constexpr int SM_Z = SM_STG + 6144;
constexpr int SM_RT = SM_Z + 8192;
constexpr int SM_QKV = SM_RT + 12288;
constexpr int SM_R1 = SM_QKV + 6144;
constexpr int SM_R2 = SM_R1 + 2048;
constexpr int SM_R3 = SM_R2 + 1024;
constexpr int SM_O = SM_R3 + 2048;
constexpr int SM_S = SM_O + 2048;
constexpr int SM_INV = SM_S + 1536;
constexpr int SM_TO = SM_R3;
constexpr int SM_WORK_END = SM_S + 2048;
constexpr int STG_QK = 0, STG_V = 98304;
constexpr int SM_WO1 = SM_WORK_END - WO_RF1 * 2048;
constexpr int STG_WO = SM_WO1 - 16384;
constexpr int SM_WQK = (SM_WO1 + 16384 > STG_V + 49152) ? SM_WO1 + 16384 : STG_V + 49152;
constexpr int SM_WV = SM_WQK + 32768;
constexpr int SM_WO2 = SM_WV + 16384;
constexpr int SM_BARS = SM_WO2 + 32768;
enum { MB_W0 = SM_BARS, MB_W1 = SM_BARS + 8, MB_W2 = SM_BARS + 16, MB_W3 = SM_BARS + 24, MB_XT = SM_BARS + 32  , MB_KV = SM_BARS + 48  ,
       MB_R3 = SM_BARS + 64, MB_R1 = SM_BARS + 72, MB_R2 = SM_BARS + 80, MB_RT0 = SM_BARS + 88, MB_RT1 = SM_BARS + 96, MB_FREE = SM_BARS + 104,
       MB_P = SM_BARS + 112, MB_V = SM_BARS + 120, MB_STG = SM_BARS + 128, SM_ROLE = SM_BARS + 136 };
constexpr int CHAIN_SMEM = SM_ROLE + 8;
static_assert(SM_WORK_END % 1024 == 0 && STG_WO >= STG_V, "work area");
static_assert(CHAIN_SMEM <= 232448 && WO_RF1 >= 6, "smem");

#define DLY_X 250
#define DLY_V 0
#define DLY_Y 250
#define DLY_Z 300
#define Q3_AT 9
#define NA 7
#define NP2 6
#define P2_FENCE 0
#define SPLIT 10
#define TA0 16
#define SENT_EARLY 1
#define Y_CHAIN 1
#define EF_W 1
#define XFLIP 0
#define YFLIP 0
#define ZFLIP 1
#define REG_A 240
#define REG_B 216
#define REG_C (3 * 168 - REG_A - REG_B)

enum { BAR_Y, BAR_MEM, BAR_PUB, BAR_QK, BAR_S, BAR_O, BAR_SENT, BAR_COMM, BAR_PUBV, BAR_PV, BAR_PDONE, BAR_VP, BAR_ZP, BAR_PRO, BAR_O2, BAR_SV,
       BAR_V = BAR_PV, BAR_SENTC = BAR_PDONE, BAR_Q3 = BAR_PRO, BAR_INV = BAR_PRO };

__device__ __forceinline__ uint32_t umax4(const uint4& v) { return max(max(v.x, v.y), max(v.z, v.w)); }
__device__ __forceinline__ unsigned gtime() { unsigned t; asm volatile("mov.u32 %0, %%globaltimer_lo;" : "=r"(t)::"memory"); return t; }
__device__ __forceinline__ unsigned clock32() { unsigned t; asm volatile("mov.u32 %0, %%clock;" : "=r"(t)::"memory"); return t; }
__device__ __forceinline__ void spin_cycles(int d) {
    if (d > 0) { const unsigned c0 = clock32(); while (clock32() - c0 < (unsigned)d) {} }
}
__device__ __forceinline__ float ex2_approx(float x) { float y; asm("ex2.approx.ftz.f32 %0, %1;" : "=f"(y) : "f"(x)); return y; }
__device__ __forceinline__ float rcp_approx(float x) { float y; asm("rcp.approx.ftz.f32 %0, %1;" : "=f"(y) : "f"(x)); return y; }
__device__ __forceinline__ void st_sent(const void* p) { asm volatile("st.relaxed.gpu.global.v4.u32 [%0], {%1,%1,%1,%1};" ::"l"(p), "r"(SENT) : "memory"); }
#define POLL_LD(p, a, b, c, d, addr) "@" p " ld.relaxed.gpu.global.v4.u32 {" a "," b "," c "," d "}, [" addr "];\n"
#define POLL_CK(p, a, b, c, d) "max.u32 m, " a "," b "; max.u32 n, " c "," d "; max.u32 m, m, n; setp.eq.u32 " p ", m, 0xFFFFFFFF;\n"
#define POLL_IO(v) "+r"(v.x), "+r"(v.y), "+r"(v.z), "+r"(v.w)
__device__ __forceinline__ void poll_init(uint4& v) { v = make_uint4(SENT, SENT, SENT, SENT); asm volatile("" : POLL_IO(v)); }
__device__ __forceinline__ int poll2(uint4 (&v)[2], const char* a) {
    int c = 0;
    asm volatile("{.reg .pred p0, p1, p; .reg .u32 m, n;\n"
                 "setp.eq.u32 p0, %8, 0; setp.eq.u32 p1, %8, 0;\n"
                 "POLL_LOOP:\n"
                 POLL_LD("p0", "%0", "%1", "%2", "%3", "%9") POLL_LD("p1", "%4", "%5", "%6", "%7", "%9+512")
                 "add.u32 %8, %8, 1;\n"
                 POLL_CK("p0", "%0", "%1", "%2", "%3") POLL_CK("p1", "%4", "%5", "%6", "%7")
                 "or.pred p, p0, p1; setp.lt.and.u32 p, %8, 0x10000, p; vote.sync.any.pred p, p, 0xFFFFFFFF;\n"
                 "@p bra.uni POLL_LOOP;}" : POLL_IO(v[0]), POLL_IO(v[1]), "+r"(c) : "l"(a) : "memory");
    return c;
}
__device__ __forceinline__ int poll4(uint4 (&v)[4], const char* a) {
    int c = 0;
    asm volatile("{.reg .pred p0, p1, p2, p3, p; .reg .u32 m, n;\n"
                 "setp.eq.u32 p0, %16, 0; setp.eq.u32 p1, %16, 0; setp.eq.u32 p2, %16, 0; setp.eq.u32 p3, %16, 0;\n"
                 "POLL_LOOP:\n"
                 POLL_LD("p0", "%0", "%1", "%2", "%3", "%17") POLL_LD("p1", "%4", "%5", "%6", "%7", "%17+2048")
                 POLL_LD("p2", "%8", "%9", "%10", "%11", "%17+4096") POLL_LD("p3", "%12", "%13", "%14", "%15", "%17+6144")
                 "add.u32 %16, %16, 1;\n"
                 POLL_CK("p0", "%0", "%1", "%2", "%3") POLL_CK("p1", "%4", "%5", "%6", "%7") POLL_CK("p2", "%8", "%9", "%10", "%11") POLL_CK("p3", "%12", "%13", "%14", "%15")
                 "or.pred p, p0, p1; or.pred p, p, p2; or.pred p, p, p3; setp.lt.and.u32 p, %16, 0x10000, p; vote.sync.any.pred p, p, 0xFFFFFFFF;\n"
                 "@p bra.uni POLL_LOOP;}" : POLL_IO(v[0]), POLL_IO(v[1]), POLL_IO(v[2]), POLL_IO(v[3]), "+r"(c) : "l"(a) : "memory");
    return c;
}
__device__ __forceinline__ uint32_t max_bf16x2(uint32_t a, uint32_t b) { uint32_t r; asm("max.bf16x2 %0, %1, %2;" : "=r"(r) : "r"(a), "r"(b)); return r; }
template <class F> __device__ __forceinline__ void softmax40(uint32_t (&pw)[6], uint32_t sa, F mid) {
    const float LOG2E = 1.4426950408889634f;
    uint32_t w[5];
    float e[10];
#pragma unroll
    for (int i = 0; i < 5; i++) w[i] = lds32(sa + i * 128);
    uint32_t m = max_bf16x2(max_bf16x2(max_bf16x2(w[0], w[1]), max_bf16x2(w[2], w[3])), w[4]);
    m = max_bf16x2(m, __shfl_xor_sync(~0u, m, 1));
    m = max_bf16x2(m, __shfl_xor_sync(~0u, m, 2));
    const float mb2 = fmaxf(bf_lo(m), bf_hi(m)) * LOG2E;
#pragma unroll
    for (int i = 0; i < 5; i++) {
        e[2 * i] = ex2_approx(fmaf(bf_lo(w[i]), LOG2E, -mb2));
        e[2 * i + 1] = ex2_approx(fmaf(bf_hi(w[i]), LOG2E, -mb2));
    }
    mid();
#pragma unroll
    for (int i = 0; i < 5; i++) pw[i] = pack_bf16(e[2 * i], e[2 * i + 1]);
    const float sum = (((e[0] + e[1]) + (e[2] + e[3])) + ((e[4] + e[5]) + (e[6] + e[7]))) + (e[8] + e[9]);
    const float hi = bf_hi(__float_as_uint(sum));
    pw[5] = pack_bf16(sum - hi, hi);
}
template <bool NORM, class F> __device__ __forceinline__ void pv32(uint32_t (&w)[4], float (&inv)[2], const uint32_t (&va)[2][2][4], const uint32_t (&vm)[4], const uint32_t (&pw)[6], F mid) {
    float o[2][3][4], t[4] = {0.f, 0.f, 0.f, 0.f};
#pragma unroll
    for (int i = 0; i < 3; i++)
#pragma unroll
        for (int m = 0; m < 2; m++) {
            o[m][i][0] = o[m][i][1] = o[m][i][2] = o[m][i][3] = 0.f;
            if (i < 2) mma16816(o[m][i], va[m][i & 1], pw[2 * i], pw[2 * i + 1]);
            else mma1688(o[m][i], vm[2 * m], vm[2 * m + 1], pw[4]);
        }
    mma1688(t, 0x3F803F80u, 0x3F803F80u, pw[5]);
    mid();
    if (NORM) { inv[0] = rcp_approx(t[0]); inv[1] = rcp_approx(t[1]); }
#pragma unroll
    for (int i = 0; i < 4; i++) {
        const float a = (o[i >> 1][0][2 * (i & 1)] + o[i >> 1][1][2 * (i & 1)]) + o[i >> 1][2][2 * (i & 1)];
        const float b = (o[i >> 1][0][2 * (i & 1) + 1] + o[i >> 1][1][2 * (i & 1) + 1]) + o[i >> 1][2][2 * (i & 1) + 1];
        w[i] = NORM ? pack_bf16(a * inv[0], b * inv[1]) : pack_bf16(a, b);
    }
    if (!NORM) { inv[0] = t[0]; inv[1] = t[1]; }
}
__device__ __forceinline__ uint32_t scale_scores(float a, float b) {
    const float scale = 0.08838834764831845f;
    const uint32_t w = pack_bf16(a, b);
    return pack_bf16(bf_lo(w) * scale, bf_hi(w) * scale);
}

__device__ __forceinline__ uint32_t peer_addr(uint32_t a, uint32_t rank) {
    uint32_t r;
    asm("mapa.shared::cluster.u32 %0, %1, %2;" : "=r"(r) : "r"(a), "r"(rank));
    return r;
}

#define TL(i) do {} while (0)
#define TLB(i) do {} while (0)
#define TLC(i) do {} while (0)

__global__ void __cluster_dims__(2, 1, 1) __launch_bounds__(384, 1)
chain_kernel(const __grid_constant__ CUtensorMap mapX, const __grid_constant__ CUtensorMap mapT32, const __grid_constant__ CUtensorMap mapT16,
             const __grid_constant__ CUtensorMap mapTQ, const __grid_constant__ CUtensorMap mapKV,
             const __grid_constant__ CUtensorMap mapWq, const __grid_constant__ CUtensorMap mapWk, const __grid_constant__ CUtensorMap mapWv,
             const __grid_constant__ CUtensorMap mapWo, const bf16* __restrict__ mem0, char* __restrict__ mbox) {
    KT_START(2);
    extern __shared__ __align__(1024) uint8_t smem_chain[];
    constexpr uint32_t SB0 = 1024;
    if (smem_u32(smem_chain) != (SB0 | ((blockIdx.x & 1) << 24))) __trap();
    const int kh = blockIdx.x & 1;
    if (threadIdx.x == 0) {
        const uint32_t sb = smem_u32(smem_chain);
        for (int i = 0; i < 14; i++) mbar_init(sb + SM_BARS + 8 * i, 1);
        mbar_init(sb + MB_P, 4); mbar_init(sb + MB_V, 4); mbar_init(sb + MB_STG, 8);
        asm volatile("fence.mbarrier_init.release.cluster;" ::: "memory");
        if (kh == 0) {
            unsigned smid, ncl = gridDim.x >> 1;
            asm volatile("mov.u32 %0, %%smid;" : "=r"(smid));
            const unsigned r = __vminu2(g_cls[smid], g_cls[smid ^ 1]), c = (r & 0xFFFF) > (r >> 16), i = atomicAdd(&g_reg[c], 1u);
            unsigned p = c * 32 + i;
            if (i >= 32) {
                unsigned n0, n1; int guard = 0;
                do {
                    asm volatile("ld.relaxed.gpu.global.u32 %0, [%1];" : "=r"(n0) : "l"(g_reg) : "memory");
                    asm volatile("ld.relaxed.gpu.global.u32 %0, [%1];" : "=r"(n1) : "l"(g_reg + 1) : "memory");
                } while (n0 + n1 < ncl && ++guard < (1 << 20));
                const unsigned k = (c ? n0 : n1) + i - 32;
                p = k < 32 ? (c ^ 1) * 32 + k : 64;
            }
            p |= g_reg[2] << 8;
            uint32_t ra;
            asm volatile("mapa.shared::cluster.u32 %0, %1, 1;" : "=r"(ra) : "r"(sb + SM_ROLE));
            asm volatile("st.shared::cluster.u32 [%0], %1;" ::"r"(ra), "r"(p) : "memory");
            sts32(sb + SM_ROLE, p);
        }
    }
    __syncthreads();
    asm volatile("barrier.cluster.arrive.release.aligned; barrier.cluster.wait.acquire.aligned;" ::: "memory");
    const uint32_t rw = uniform(lds32(smem_u32(smem_chain) + SM_ROLE));
    const int pair = rw & 255, yflip = (rw >> 8) ^ YFLIP;
    if (pair >= 64) return;
    if (threadIdx.x == 0) KT_MARK(5);
    const int h = pair >> 1, nh = pair & 1, j = 2 * nh + kh, role = 2 * pair + kh;
#define WG_ORDER 0x210
    const int warp = uniform(((WG_ORDER >> (4 * (threadIdx.x >> 7))) & 3) * 4 + ((threadIdx.x >> 5) & 3));
    const uint32_t g = warp & 3, sb = SB0 | (kh << 24), rsb = sb ^ (1u << 24), cls = pair >> 5, kflip = ZFLIP ^ kh;
    const uint32_t mlo = (uint32_t)(uintptr_t)mbox, mhi = (uint32_t)((uintptr_t)mbox >> 32);
    auto lane16 = [&]() {
        uint32_t t;
        asm volatile("mov.u32 %0, %%laneid; shl.b32 %0, %0, 4;" : "=r"(t));
        return t;
    };
#define PHASE(k) uint32_t L; asm volatile("{.reg .u32 t; shr.u32 t, %1, %3; add.u32 %0, %2, t;}" : "=r"(L) : "r"(it), "r"(l16), "n"(8 + (k)))
#define ROWPAT() ((((L << 3) & 0x380) | ((L << 2) & 0x400)) | ((L ^ (L >> 3)) & 0x10) | (L & 0x60))
#define FRAG() (ROWPAT() ^ (g << 5))
#define QFRAG() ((((L >> 1) & 0x80) | (L & 0x70)) + ((L & 0x80) ? SM_KV + 16384 + kvo : SM_QKV))
#define VFRAG() (ROWPAT() ^ ((g & 1) << 6))
#define VBASE() (sb + SM_KV + 8192 + (g >> 1) * 4096 + kvo)
#define XTLO() ((uint32_t)make_desc(SB0 + SM_XT, 16, 1024) + (ui & 1) * 2048)
    if (warp >= 8) {
        asm volatile("setmaxnreg.dec.sync.aligned.u32 %0;" ::"n"(REG_C));
        const uint32_t l16 = lane16(), lane = l16 >> 4;
        const int ct = g * 32 + lane;
        if (warp == 8) {
            const CUtensorMap* ws = kh ? &mapWq : &mapWk;
            const CUtensorMap* wn = kh ? &mapWk : &mapWq;
            const uint64_t pol = EF_W ? policy_evict_first() : policy_evict_normal();
            const int col = h * DH + 64 * nh, row = 512 * kh;
            if (lane == 0) { mbar_expect_tx(sb + MB_W0, 49152); mbar_expect_tx(sb + MB_W1, 98304); mbar_expect_tx(sb + MB_W2, 81920); mbar_expect_tx(sb + MB_W3, 32768); }
            __syncwarp();
            if (lane < 24) {
                const int k = lane ^ (16 * kflip);
                tma_load_2d(sb + STG_V + lane * 2048, &mapWv, col, row + 16 * k, sb + MB_W0, pol);
                tma_load_2d(sb + STG_QK + lane * 2048, ws, col, row + 16 * k, sb + MB_W1, pol);
                tma_load_2d(sb + STG_QK + (24 + lane) * 2048, wn, col, row + 16 * k, sb + MB_W1, pol);
            }
            if (lane < 8) {
                const int k = (24 + lane) ^ (16 * kflip);
                tma_load_2d(sb + SM_WQK + lane * 4096, ws, col, row + 16 * k, sb + MB_W2, pol);
                tma_load_2d(sb + SM_WQK + lane * 4096 + 2048, wn, col, row + 16 * k, sb + MB_W2, pol);
                tma_load_2d(sb + SM_WV + lane * 2048, &mapWv, col, row + 16 * k, sb + MB_W2, pol);
            }
            if (lane < 2) tma_load_2d(sb + SM_WO2 + lane * 16384, &mapWo, 256 * j + 128 + 64 * lane, h * DH, sb + MB_W2, pol);
            __syncwarp();
            bar_sync(BAR_PV, 160);
            if (lane < 2) tma_load_2d(sb + STG_WO + lane * 16384, &mapWo, 256 * j + 64 * lane, h * DH, sb + MB_W3, pol);
            __syncwarp();
        }
        bar_sync(BAR_PDONE, 384);
        KT_MARK(9);
        for (int c = ct; c < 512; c += 128) {
            uint32_t w[4];
#pragma unroll
            for (int r = 0; r < 4; r++) {
                const uint32_t lo = reinterpret_cast<const uint16_t*>(mem0)[(2 * r) * DM + 512 * kh + c], hi = reinterpret_cast<const uint16_t*>(mem0)[(2 * r + 1) * DM + 512 * kh + c];
                w[r] = lo | (hi << 16);
            }
            sts128(sb + SM_Z + (c ^ (256 * kflip)) * 16, make_uint4(w[0], w[1], w[2], w[3]));
        }
        auto load_xt = [&](int seg, int half) {
            const uint32_t bar = sb + MB_XT + (seg & 1) * 8;
            if (half == 0) mbar_expect_tx(bar, 32768);
            asm volatile("cp.async.bulk.tensor.3d.shared::cluster.global.mbarrier::complete_tx::bytes [%0], [%1, {%3, %4, %5}], [%2];"
                         ::"r"(sb + SM_XT + (seg & 1) * 32768 + half * 16384), "l"(&mapX), "r"(bar), "r"(0), "r"(seg * SEG), "r"(8 * kh + 4 * (half ^ kflip)) : "memory");
        };
        auto tok_start = [&](int s) {
            if (lane == 0) {
                if (s > -3 && s + 2 < NSEG) {
                    mbar_wait(sb + MB_STG, (s + 2) & 1);
                    asm volatile("fence.proxy.async.shared::cta;" ::: "memory");
                    const int r = ((s + 2) & 3) * NH + h;
                    tma_store_2d(kh ? &mapT32 : &mapTQ, sb + SM_STG, kh ? 64 * nh : 256 * nh, kh ? r * 96 + 32 : r * 12);
                    tma_store_2d(&mapT16, sb + SM_STG + 4096, 64 * nh, r * 96 + 64 + 16 * kh);
                    asm volatile("cp.async.bulk.commit_group;" ::: "memory");
                }
                if (s + 4 < NSEG) load_xt(s + 4, 0);
                asm volatile("cp.async.bulk.wait_group.read 0;" ::: "memory");
                if (s < 0) {
                    asm volatile("mbarrier.arrive.shared::cluster.b64 _, [%0];" ::"r"(rsb + MB_FREE) : "memory");
                    mbar_wait(sb + MB_FREE, (s + 3) & 1);
                }
            }
            __syncwarp();
        };
        auto tok_mid = [&](int s) {
            if (lane == 0) {
                if (s + 4 < NSEG) load_xt(s + 4, 1);
                if (s > -3 && s + 2 < NSEG) {
                    asm volatile("cp.async.bulk.wait_group 0;" ::: "memory");
                    st_relaxed_u32(g_xflag + role, s + 3);
                }
            }
            __syncwarp();
        };
        auto kv_check = [&](int s) {
            if (s + 1 < NSEG) {
                if (lane < 4) {
                    unsigned f; int guard = 0;
                    do {
                        asm volatile("ld.acquire.gpu.global.u32 %0, [%1];" : "=r"(f) : "l"(g_xflag + h * 4 + lane) : "memory");
                        if (++guard > (1 << 20)) __trap();
                    } while (f <= (unsigned)(s + 1));
                }
                __syncwarp();
                asm volatile("fence.proxy.async.global;" ::: "memory");
            }
        };
        auto kv_load = [&](int s) {
            if (lane == 0 && s + 1 < NSEG) {
                const uint32_t bar = sb + MB_KV + ((s + 1) & 1) * 8, dst = sb + SM_KV + ((s + 1) & 1) * KV_BYTES;
                const int row = (((s + 1) & 3) * NH + h) * 96;
                mbar_expect_tx(bar, KV_BYTES);
                asm volatile("cp.async.bulk.tensor.3d.shared::cluster.global.mbarrier::complete_tx::bytes.multicast::cluster [%0], [%1, {%3, %4, %3}], [%2], %5;"
                             ::"r"(dst + kh * 8192), "l"(&mapKV), "r"(bar), "r"(0), "r"(row + 32 + 32 * kh), "h"((uint16_t)3) : "memory");
                bulk_load(dst + 16384, g_tok + row * DH + j * 1024, 2048, bar);
            }
            __syncwarp();
        };
        if (warp == 9) {
            if (lane == 0) { load_xt(0, 0); load_xt(0, 1); }
#pragma unroll 1
            for (int s = -3; s < 0; s++) { tok_start(s); KT_MARK(13 + s); bar_arrive(BAR_PRO, 288); tok_mid(s); }
        }
        if (warp == 11) { kv_check(-1); kv_load(-1); }
        bar_arrive(BAR_MEM, 384);
        const uint32_t ybox = mlo + page_off(role & 63, cls ^ yflip), xoth = mlo + WIN + page_off((pair & 31) ^ 1, cls ^ XFLIP);
        const uint32_t zline = mlo + WIN + page_off(32 + ((role >> 5) & 1), cls ^ ZFLIP) + (role & 31) * 128, zbox = mlo + WIN + (page_off(32 + kh, 0) & ~4096u);
        const uint32_t xtype = g == 0 ? 2 : (g & 1);
        const uint32_t ydst = (lane >> 3) * 128 + ((lane & 7) ^ (lane >> 3)) * 16, ysrc = lane * 128 + ((2 * g) ^ (lane & 7)) * 16;
#pragma unroll 1
        for (int s = 0; s < NSEG; s++) {
            const uint32_t slot = (s & 3) << 14;
            if (g == 3) {
                kv_check(s);
                const uint32_t L = l16, kvo = (s & 1) * KV_BYTES, qa = QFRAG(), sa = sb + SM_S + 512 + (L >> 2);
                float sc[4] = {0.f, 0.f, 0.f, 0.f}, sd[4] = {0.f, 0.f, 0.f, 0.f};
                uint32_t a[4][4], kb[2][4];
                mbar_wait_w(sb + MB_KV + (s & 1) * 8, (s >> 1) & 1);
                mbar_wait_w(sb + MB_P, s & 1);
#pragma unroll
                for (int c = 0; c < 2; c++) {
                    const uint32_t qc = qa + (sb + (nh ^ c) * 1024), kc = L + (sb + SM_QKV + 2048 + (nh ^ c) * 1024);
                    if (c) bar_sync(BAR_QK, 224);
                    ldsm4t(kb[0], kc); ldsm4t(a[0], qc); ldsm4t(a[1], qc + 256);
                    ldsm4t(kb[1], kc + 512); ldsm4t(a[2], qc + 512); ldsm4t(a[3], qc + 768);
                    mma16816v(sc, a[0], kb[0][0], kb[0][1]);
                    mma16816v(sd, a[1], kb[0][2], kb[0][3]);
                    mma16816v(sc, a[2], kb[1][0], kb[1][1]);
                    mma16816v(sd, a[3], kb[1][2], kb[1][3]);
                }
                sts32(sa, scale_scores(sc[0] + sd[0], sc[1] + sd[1]));
                sts32(sa + 768, scale_scores(sc[2] + sd[2], sc[3] + sd[3]));
                bar_arrive(BAR_S, 160);
                TL(25);
                bar_sync(BAR_SV, 352);
                kv_load(s);
            } else {
                if (g == 1) { tok_start(s); TL(21); if (s == 0) KT_MARK(13); }
                const char* p = make_ptr(l16 + (xoth + xtype * 1024 + slot), mhi);
                const uint32_t dst = l16 + (sb + SM_QKV + xtype * 2048 + (nh ^ 1) * 1024);
                asm volatile("" ::"l"(p));
                uint4 v[2];
                poll_init(v[0]); poll_init(v[1]);
                if (g == 0) {
                    bar_sync(BAR_PUBV, 160);
                    mbar_wait_w(sb + MB_V, s & 1);
                    spin_cycles(DLY_V);
                } else {
                    bar_sync(BAR_PUB, 192);
                    spin_cycles(DLY_X);
                }
                const int r = poll2(v, p);
                STAT(1, r > 1 && warp == 10);
                sts128(dst, v[0]); sts128(dst + 512, v[1]);
                if (g != 0) bar_arrive(BAR_QK, 224);
                if (g == 0) { bar_arrive(BAR_V, 160); bar_arrive(BAR_SV, 352); TL(17); }
                if (g == 1) {
                    TL(31);
                    bar_sync(BAR_SV, 352);
                    tok_mid(s);
                    TL(22);
                }
                if (g == 2 && s >= 1) {
                    TL(16);
                    const uint32_t prev = (slot - 0x4000) & 0xC000;
                    const char* y = make_ptr(l16 + (ybox + prev), mhi);
                    const char* x = make_ptr(l16 + (xoth + prev + kh * 1536), mhi);
#pragma unroll
                    for (int i = 0; i < 8; i++) st_sent(y + i * 512);
#pragma unroll
                    for (int i = 0; i < 3; i++) st_sent(x + i * 512);
                    st_relaxed_u32(make_ptr(lane * 4 + (zline + (slot ^ 0x8000)), mhi), SENT);
                    TL(23);
                }
            }
            if (s + 1 == NSEG) break;
            {
                const char* p = make_ptr(l16 + (ybox + g * 1024 + slot), mhi);
                char* zdst = make_ptr(lane * 4 + (zline + g * 32 + slot), mhi);
                const uint32_t dst = ydst + (sb + SM_Z + g * 1024), dst1 = (ydst ^ 64) + (sb + SM_Z + g * 1024 + 512), src = ysrc + (sb + SM_Z), src1 = (ysrc ^ 16) + (sb + SM_Z);
                asm volatile("" ::"l"(p), "l"(zdst));
                uint4 v[2];
                poll_init(v[0]); poll_init(v[1]);
                bar_sync(BAR_SENTC, 384);
                spin_cycles(DLY_Y);
                const int r = poll2(v, p);
                STAT(2, r > 1 && warp == 8);
                sts128(dst, v[0]); sts128(dst1, v[1]);
                bar_sync(BAR_Y, 128);
                TL(18);
                uint32_t b[2][4];
                ldsm4t(b[0], src); ldsm4t(b[1], src1);
                const uint32_t one = 0x3F803F80u;
                float d0[4] = {0.f, 0.f, 0.f, 0.f}, d1[4] = {0.f, 0.f, 0.f, 0.f};
                mma16816(d0, one, one, one, one, b[0][0], b[0][1]);
                mma16816(d1, one, one, one, one, b[1][0], b[1][1]);
                mma16816(d0, one, one, one, one, b[0][2], b[0][3]);
                mma16816(d1, one, one, one, one, b[1][2], b[1][3]);
                const uint32_t w = (lane & 4) ? pack_bf16(d1[0], d1[1]) : pack_bf16(d0[0], d0[1]);
                asm volatile("{.reg .pred p; setp.lt.u32 p, %2, 128; @p st.relaxed.gpu.global.u32 [%0], %1;}" ::"l"(zdst), "r"(w), "r"(l16) : "memory");
                if (s + 3 < NSEG) bar_arrive(BAR_ZP, 256);
                TL(19);
            }
            {
                const char* p = make_ptr(l16 + (zbox + g * 512 + slot), mhi);
                const uint32_t dst = l16 + (sb + SM_Z + g * 512);
                asm volatile("" ::"l"(p));
                uint4 v[4];
                poll_init(v[0]); poll_init(v[1]); poll_init(v[2]); poll_init(v[3]);
                bar_sync(BAR_COMM, 128);
                spin_cycles(DLY_Z);
                const int r = poll4(v, p);
                STAT(0, r > 1 && warp == 8);
#pragma unroll
                for (int i = 0; i < 4; i++) sts128(dst + i * 2048, v[i]);
                bar_arrive(BAR_MEM, 384);
                TL(20);
            }
        }
    } else if (warp < 4) {
        asm volatile("setmaxnreg.inc.sync.aligned.u32 %0;" ::"n"(REG_A));
        const uint32_t l16 = lane16();
        uint32_t wa[2][24][4];
        {
            const uint32_t L = l16, fa = sb + FRAG();
            mbar_wait_w(sb + MB_W1, 0);
            KT_MARK(7);
#pragma unroll
            for (int t = 0; t < 2; t++)
#pragma unroll
                for (int r = 0; r < 24; r++) ldsm4t(wa[t][r], fa + STG_QK + (t * 24 + r) * 2048);
            mbar_wait_w(sb + MB_W2, 0);
            bar_arrive(BAR_PDONE, 384);
        }
        auto batch1 = [&](float (&d)[16], uint32_t lo, auto tc, auto k0c, auto k1c) {
            constexpr int t = decltype(tc)::value;
            const uint64_t da = make_desc(SB0 + SM_WQK, 16, 1024);
            wg_fence();
            static_for<decltype(k0c)::value, decltype(k1c)::value>([&](auto kc) {
                constexpr int k = decltype(kc)::value, off = (k >> 2) * 256 + (k & 3) * 2;
                if constexpr (k >= 24) wgmma_ss32u<off>(d, da + ((k - 24) * 2 + t) * 128, lo);
                else wgmma_rs32u<off, k != 0 || t != 0>(d, wa[t][k], lo);
            });
            wg_commit();
        };
        const uint32_t xbox = mlo + WIN + page_off(pair & 31, cls ^ XFLIP);
        const uint32_t ybox = mlo + page_off(24 + 2 * g + 32 * nh, kh ^ yflip) + h * 128;
#pragma unroll 1
        for (uint32_t it = 0; it < NSEG + 3; it++) {
            const int s = (int)it - 3;
            const uint32_t ui = uniform(it), slot = ((ui + 1) & 3) << 14, kvo = (~ui & 1) * KV_BYTES, xtlo = XTLO();
            {
                PHASE(5);
                const uint32_t first = L | (g << 9);
                if (s >= 0) mbar_expect_tx_if0(first, sb + MB_R1, 2048);
                if (s + 3 < NSEG) {
                    mbar_expect_tx_if0(first, sb + MB_RT0, 8192);
                    mbar_wait_w(sb + MB_XT + (ui & 1) * 8, (it >> 1) & 1);
                }
            }
            if (s >= 0) {
                PHASE(0);
                const uint32_t mb = L + (sb + SM_Z), ra = L + (sb + g * 512), r1 = L + (rsb + SM_R1 + g * 512), r1b = rsb + MB_R1;
                sched_fence(r1 | r1b);
                bar_sync(BAR_MEM, 384);
                TLB(0);
                float acc[2][2][4];
#pragma unroll
                for (int t = 0; t < 4; t++) { acc[t >> 1][t & 1][0] = acc[t >> 1][t & 1][1] = acc[t >> 1][t & 1][2] = acc[t >> 1][t & 1][3] = 0.f; }
                uint32_t b[4][4];
                uint4 u0, u1;
#pragma unroll
                for (int p = 0; p < 4; p++) ldsm4t(b[p], mb + p * 512);
#pragma unroll
                for (int p = 0; p < 12; p++) {
#pragma unroll
                    for (int u = 0; u < 2; u++) {
                        mma16816v(acc[0][u], wa[0][2 * p + u], b[p & 3][2 * u], b[p & 3][2 * u + 1]);
                        mma16816v(acc[1][u], wa[1][2 * p + u], b[p & 3][2 * u], b[p & 3][2 * u + 1]);
                    }
                    if (p + 4 < 12) ldsm4t(b[p & 3], mb + (p + 4) * 512);
                    if (p == Q3_AT) {
                        bar_sync(BAR_Q3, 256);
                        u0 = lds128(ra + SM_R3); u1 = lds128(ra + SM_O);
                    }
                }
                st_async4(r1, (acc[0][0][0] + __uint_as_float(u0.x)) + acc[0][1][0], (acc[0][0][1] + __uint_as_float(u0.y)) + acc[0][1][1],
                          (acc[0][0][2] + __uint_as_float(u0.z)) + acc[0][1][2], (acc[0][0][3] + __uint_as_float(u0.w)) + acc[0][1][3], r1b);
                TL(1);
                const float o0 = (acc[1][0][0] + __uint_as_float(u1.x)) + acc[1][1][0], o1 = (acc[1][0][1] + __uint_as_float(u1.y)) + acc[1][1][1];
                const float o2 = (acc[1][0][2] + __uint_as_float(u1.z)) + acc[1][1][2], o3 = (acc[1][0][3] + __uint_as_float(u1.w)) + acc[1][1][3];
                const uint32_t l4 = L >> 2, qo = SM_QKV + kh * 2048 + nh * 1024 + g * 256, qr = l4 + (rsb + qo), ql = l4 + (sb + qo), pb = rsb + MB_P;
                char* xd = make_ptr(l4 + (xbox + kh * 1024 + g * 256 + slot), mhi);
                asm volatile("" ::"l"(xd), "r"(qr), "r"(pb), "r"(qr + 128), "f"(o0), "f"(o1), "f"(o2), "f"(o3));
                mbar_wait_w(sb + MB_R1, s & 1);
                const uint4 v = lds128(ra + SM_R1);
                const uint32_t w0 = pack_bf16(o0 + __uint_as_float(v.x), o1 + __uint_as_float(v.y)), w1 = pack_bf16(o2 + __uint_as_float(v.z), o3 + __uint_as_float(v.w));
                st_relaxed_u32(xd, w0);
                st_relaxed_u32(xd + 128, w1);
                bar_arrive(BAR_PUB, 192);
                st_async1(qr, w0, pb);
                st_async1(qr + 128, w1, pb);
                sts32(ql, w0);
                sts32(ql + 128, w1);
                __syncwarp();
                mbar_expect_tx_if0(L, sb + MB_P, 256);
                TL(2);
                if (s + 3 < NSEG) bar_sync(BAR_VP, 256);
            } else {
                bar_sync(BAR_PRO, 288);
            }
            if (s + 3 < NSEG) {
                float d[16];
                batch1(d, xtlo, std::integral_constant<int, 0>(), std::integral_constant<int, 0>(), std::integral_constant<int, 32>());
                PHASE(1);
                const uint32_t rt = L + (rsb + SM_RT + g * 2048);
                wg_wait<0>();
                TL(7);
#pragma unroll
                for (int i = 0; i < 4; i++) st_async4(rt + i * 512, d[4 * i], d[4 * i + 1], d[4 * i + 2], d[4 * i + 3], rsb + MB_RT0);
            }
            if (s + 1 == NSEG) { bar_arrive(BAR_SV, 352); break; }
            if (s >= 0) {
                PHASE(2);
                const uint32_t fo = FRAG() + (sb + SM_WO2 + 16384), lo = L + (sb + SM_O), yo = (L >> 2) + (ybox + slot);
                uint32_t a1[8][4];
                bar_sync(BAR_SV, 352);
#pragma unroll
                for (int k = 0; k < 8; k++) ldsm4t(a1[k], fo + k * 2048);
                sched_fence(yo);
                bar_sync(BAR_O2, 256);
                TLB(14);
                float y0[4] = {0.f, 0.f, 0.f, 0.f}, y1[4] = {0.f, 0.f, 0.f, 0.f};
                uint32_t b[2][4];
                ldsm4t(b[0], lo); ldsm4t(b[1], lo + 512);
                sched_fence(L);
#pragma unroll
                for (int p = 0; p < 4; p++) {
                    mma16816v(y0, a1[2 * p], b[p & 1][0], b[p & 1][1]);
                    mma16816v(y1, a1[2 * p + 1], b[p & 1][2], b[p & 1][3]);
                    if (p < 2) ldsm4t(b[p & 1], lo + (p + 2) * 512);
                }
                bar_sync(BAR_INV, 256);
                float i0, i1;
                asm volatile("ld.shared.v2.f32 {%0, %1}, [%2];" : "=f"(i0), "=f"(i1) : "r"(((L >> 1) & 0x18) + (sb + SM_INV + g * 32)) : "memory");
                st_relaxed_u32(make_ptr(yo, mhi), pack_bf16((y0[0] + y1[0]) * i0, (y0[1] + y1[1]) * i1));
                st_relaxed_u32(make_ptr(yo ^ 4096, mhi) + 0x2000, pack_bf16((y0[2] + y1[2]) * i0, (y0[3] + y1[3]) * i1));
                bar_arrive(BAR_SENTC, 384);
                TL(6);
            }
            if (s + 3 < NSEG) {
                PHASE(4);
                float d[16];
                const uint32_t rt = L + (sb + SM_RT + g * 2048);
                if (SENT_EARLY && s >= 0) bar_sync(BAR_SENT, 256);
                mbar_wait_w(sb + MB_RT0, it & 1);
#pragma unroll
                for (int i = 0; i < 4; i++) {
                    const uint4 v = lds128(rt + i * 512);
                    d[4 * i] = __uint_as_float(v.x); d[4 * i + 1] = __uint_as_float(v.y); d[4 * i + 2] = __uint_as_float(v.z); d[4 * i + 3] = __uint_as_float(v.w);
                }
                if (!SENT_EARLY && s >= 0) bar_sync(BAR_SENT, 256);
                if (SPLIT > 0) batch1(d, xtlo, std::integral_constant<int, 1>(), std::integral_constant<int, 0>(), std::integral_constant<int, SPLIT>());
                if (s >= 0) bar_sync(BAR_ZP, 256);
                TLB(30);
                batch1(d, xtlo, std::integral_constant<int, 1>(), std::integral_constant<int, SPLIT>(), std::integral_constant<int, 32>());
                const uint32_t so = (kh ? FRAG() : ((L & 0x100) << 2) + (L & 0xF0) + g * 256) + (sb + SM_STG);
                wg_wait<0>();
                TL(8);
                uint32_t w[8];
#pragma unroll
                for (int i = 0; i < 8; i++) w[i] = pack_bf16(d[2 * i], d[2 * i + 1]);
                if (kh) {
                    stsm4t(so, w[0], w[1], w[2], w[3]);
                    stsm4t(so + 2048, w[4], w[5], w[6], w[7]);
                } else {
                    stsm4(so, w[0], w[1], w[2], w[3]);
                    stsm4(so + 2048, w[4], w[5], w[6], w[7]);
                }
                __syncwarp();
                mbar_arrive_if0(L, sb + MB_STG);
                TL(9);
            } else {
                bar_arrive(BAR_SENT, 256);
            }
        }
    } else {
        asm volatile("setmaxnreg.inc.sync.aligned.u32 %0;" ::"n"(REG_B));
        const uint32_t l16 = lane16();
        uint32_t wv[24][4], wo[8 + WO_RF1][4];
        {
            const uint32_t L = l16, fa = sb + FRAG();
            mbar_wait_w(sb + MB_W0, 0);
            KT_MARK(6);
#pragma unroll
            for (int r = 0; r < 24; r++) ldsm4t(wv[r], fa + STG_V + r * 2048);
            bar_arrive(BAR_PV, 160);
            mbar_wait_w(sb + MB_W3, 0);
            KT_MARK(8);
#pragma unroll
            for (int r = 0; r < 8 + WO_RF1; r++) ldsm4t(wo[r], fa + STG_WO + r * 2048);
            mbar_wait_w(sb + MB_W2, 0);
            bar_arrive(BAR_PDONE, 384);
        }
        const uint32_t xbox = mlo + WIN + page_off(pair & 31, cls ^ XFLIP);
        const uint32_t ybox = mlo + page_off(2 * g + 32 * nh, kh ^ yflip) + h * 128;
#pragma unroll 1
        for (uint32_t it = 0; it < NSEG + 3; it++) {
            const int s = (int)it - 3;
            const uint32_t ui = uniform(it), slot = ((ui + 1) & 3) << 14, kvo = (~ui & 1) * KV_BYTES, xtlo = XTLO();
            {
                PHASE(5);
                const uint32_t first = L | (g << 9);
                if (s >= 0) mbar_expect_tx_if0(first, sb + MB_R2, 1024);
                if (s + 3 < NSEG) {
                    mbar_expect_tx_if0(first, sb + MB_RT1, 4096);
                    mbar_wait_w(sb + MB_XT + (ui & 1) * 8, (it >> 1) & 1);
                }
            }
            if (s >= 0) {
                PHASE(0);
                const uint32_t fo = FRAG() + sb, l4 = L >> 2;
                {
                    const uint32_t mb = L + (sb + SM_Z), aw = fo + SM_WQK, ra = L + (sb + g * 512), r2 = (L >> 1) + (rsb + SM_R2 + g * 256), r2b = rsb + MB_R2;
                    uint32_t a[NA][4], b[4][4];
#pragma unroll
                    for (int i = 0; i < NA; i++) ldsm4t(a[i], aw + i * 2048);
                    sched_fence(L);
                    TL(24);
                    bar_sync(BAR_MEM, 384);
#pragma unroll
                    for (int p = 0; p < 4; p++) ldsm4t(b[p], mb + (12 + p) * 512);
                    sched_fence(L);
                    float c[2][4] = {{0.f, 0.f, 0.f, 0.f}, {0.f, 0.f, 0.f, 0.f}};
#pragma unroll
                    for (int i = 0; i < 16; i++) {
                        mma16816v(c[i & 1], a[i % NA], b[i >> 2][i & 2], b[i >> 2][(i & 2) + 1]);
                        ldsm4t(a[i % NA], aw + (i + NA) * 2048);
                    }
                    sts128(ra + SM_R3, make_uint4(__float_as_uint(c[0][0]), __float_as_uint(c[0][1]), __float_as_uint(c[0][2]), __float_as_uint(c[0][3])));
                    sts128(ra + SM_O, make_uint4(__float_as_uint(c[1][0]), __float_as_uint(c[1][1]), __float_as_uint(c[1][2]), __float_as_uint(c[1][3])));
                    bar_arrive(BAR_Q3, 256);
                    TL(29);
                    float acc[4][4];
#pragma unroll
                    for (int t = 0; t < 4; t++) { acc[t][0] = acc[t][1] = acc[t][2] = acc[t][3] = 0.f; }
#pragma unroll
                    for (int i = 16; i < 24; i++) {
                        mma16816v(acc[i & 1], a[i % NA], b[(i - 16) >> 1][2 * (i & 1)], b[(i - 16) >> 1][2 * (i & 1) + 1]);
                        if (i + NA < 24) ldsm4t(a[i % NA], aw + (i + NA) * 2048);
                        else ldsm4t(a[i % NA], mb + (i + NA - 24) * 512);
                    }
#pragma unroll
                    for (int p = 0; p < 12; p++) {
                        mma16816v(acc[(2 * p) & 3], wv[2 * p], a[(24 + p) % NA][0], a[(24 + p) % NA][1]);
                        mma16816v(acc[(2 * p + 1) & 3], wv[2 * p + 1], a[(24 + p) % NA][2], a[(24 + p) % NA][3]);
                        if (p + NA < 12) ldsm4t(a[(24 + p) % NA], mb + (p + NA) * 512);
                    }
                    if (s + 3 < NSEG) bar_arrive(BAR_VP, 256);
                    float o[4];
#pragma unroll
                    for (int i = 0; i < 4; i++) o[i] = (acc[0][i] + acc[1][i]) + (acc[2][i] + acc[3][i]);
                    st_async2(r2, kh ? o[0] : o[2], kh ? o[1] : o[3], r2b);
                    TL(10);
                    const float o0 = kh ? o[2] : o[0], o1 = kh ? o[3] : o[1];
                    const uint32_t qo = SM_QKV + 4096 + nh * 1024 + (2 * g + kh) * 128, qr = l4 + (rsb + qo), ql = l4 + (sb + qo), vb = rsb + MB_V, rl = (L >> 1) + (sb + SM_R2 + g * 256);
                    char* xd = make_ptr(l4 + (xbox + 2048 + (2 * g + kh) * 128 + slot), mhi);
                    asm volatile("" ::"l"(xd), "r"(qr), "r"(vb), "f"(o0), "f"(o1));
                    mbar_wait_w(sb + MB_R2, s & 1);
                    uint32_t vx, vy;
                    asm volatile("ld.shared.v2.u32 {%0,%1}, [%2];" : "=r"(vx), "=r"(vy) : "r"(rl) : "memory");
                    const uint32_t w0 = pack_bf16(o0 + __uint_as_float(vx), o1 + __uint_as_float(vy));
                    st_relaxed_u32(xd, w0);
                    bar_arrive(BAR_PUBV, 160);
                    st_async1(qr, w0, vb);
                    sts32(ql, w0);
                    __syncwarp();
                    mbar_expect_tx_if0(L, sb + MB_V, 128);
                    TL(11);
                }
                const uint32_t vma = L + (sb + SM_QKV + 4096 + g * 512), yo = l4 + (ybox + slot);
                uint32_t va[2][2][4];
                {
                    const uint32_t qa = QFRAG(), vf = VFRAG(), va0 = vf + VBASE(), va1 = (vf ^ 32) + VBASE();
                    const uint32_t kf = ((L << 3) & 0x380) | ((L ^ (L >> 3)) & 0x30) | (L & 0x40), kb0 = sb + SM_KV + kvo + g * 1024;
                    const int d = (int)(L >> 6) - (int)((L >> 3) & 6) + 8 * (j - (int)g);
                    const uint32_t keep = (d < 0 ? 0u : 0xFFFFu) | (d < 1 ? 0u : 0xFFFF0000u), sa = l4 + (sb + SM_S + g * 128);
                    const uint32_t q0 = qa + (sb + nh * 1024), q1 = qa + (sb + (nh ^ 1) * 1024);
                    float sc[4] = {0.f, 0.f, 0.f, 0.f}, sd[4] = {0.f, 0.f, 0.f, 0.f};
                    uint32_t a[4][4], kb[2][4];
                    mbar_wait_w(sb + MB_KV + (~ui & 1) * 8, (s >> 1) & 1);
                    ldsm4(kb[0], kf + (kb0 + nh * 4096)); ldsm4(kb[1], (kf ^ 64) + (kb0 + nh * 4096));
                    mbar_wait_w(sb + MB_P, s & 1);
                    TL(12);
#pragma unroll
                    for (int k = 0; k < 4; k++) ldsm4t(a[k], q0 + k * 256);
#pragma unroll
                    for (int k = 0; k < 4; k++) mma16816v((k & 1) ? sd : sc, a[k], kb[k >> 1][2 * (k & 1)], kb[k >> 1][2 * (k & 1) + 1]);
                    ldsm4(kb[0], kf + (kb0 + (nh ^ 1) * 4096)); ldsm4(kb[1], (kf ^ 64) + (kb0 + (nh ^ 1) * 4096));
                    sched_fence(vf | yo);
                    bar_sync(BAR_QK, 224);
                    TLB(3);
#pragma unroll
                    for (int k = 0; k < 4; k++) ldsm4t(a[k], q1 + k * 256);
                    sched_fence(L);
#pragma unroll
                    for (int k = 0; k < 4; k++) mma16816v((k & 1) ? sd : sc, a[k], kb[k >> 1][2 * (k & 1)], kb[k >> 1][2 * (k & 1) + 1]);
                    ldsm4t(va[0][0], va0); ldsm4t(va[0][1], va0 + 2048);
                    sts32(sa, scale_scores(sc[0] + sd[0], sc[1] + sd[1]));
                    sts32(sa + 768, (scale_scores(sc[2] + sd[2], sc[3] + sd[3]) & keep) | (0xFF80FF80u & ~keep));
                    bar_arrive(BAR_SV, 352);
                    ldsm4t(va[1][0], va1); ldsm4t(va[1][1], va1 + 2048);
                }
                bar_sync(BAR_S, 160);
                TLB(4);
                uint32_t pw[6], vm[4];
                if (s + 1 < NSEG) {
                softmax40(pw, l4 + (sb + SM_S), [&]() {
                    bar_sync(BAR_V, 160);
                    ldsm4(vm, vma);
                });
                uint32_t a1[NP2][4];
                float inv[2];
                {
                    uint32_t w[4];
                    pv32<false>(w, inv, va, vm, pw, [&]() {
                        sched_fence(L);
#pragma unroll
                        for (int k = 0; k < NP2; k++) ldsm4t(a1[k], fo + SM_WO2 + k * 2048);
                    });
#pragma unroll
                    for (int i = 0; i < 4; i++) sts32(l4 + (sb + SM_O + g * 512) + i * 128, w[i]);
                }
                const uint32_t lo = L + (sb + SM_O);
                bar_arrive(BAR_O2, 256);
                bar_sync(BAR_O, 128);
                TLB(5);
                {
                    float y0[4] = {0.f, 0.f, 0.f, 0.f}, y1[4] = {0.f, 0.f, 0.f, 0.f}, y2[4] = {0.f, 0.f, 0.f, 0.f};
                    uint32_t b[4][4];
#pragma unroll
                    for (int p = 0; p < 4; p++) ldsm4t(b[p], lo + p * 512);
                    inv[0] = rcp_approx(inv[0]); inv[1] = rcp_approx(inv[1]);
                    asm volatile("st.shared.v2.f32 [%0], {%1, %2};" ::"r"(((L >> 1) & 0x18) + (sb + SM_INV + g * 32)), "f"(inv[0]), "f"(inv[1]) : "memory");
                    bar_arrive(BAR_INV, 256);
                    sched_fence(L);
#pragma unroll
                    for (int k = 0; k < 8; k++) {
                        const int p = k >> 1, u = k & 1;
                        mma16816v(y2, a1[k % NP2], b[p][2 * u], b[p][2 * u + 1]);
                        if (k + NP2 < 8) ldsm4t(a1[k % NP2], fo + SM_WO2 + (k + NP2) * 2048);
                        else if (k + NP2 < 16 - WO_RF1) ldsm4t(a1[k % NP2], fo + SM_WO1 + (k + NP2 - 8 + WO_RF1) * 2048);
                        mma16816v(y0, wo[k], b[p][2 * u], b[p][2 * u + 1]);
                        if (k < WO_RF1) mma16816v(y1, wo[8 + (k < WO_RF1 ? k : 0)], b[p][2 * u], b[p][2 * u + 1]);
                        else mma16816v(y1, a1[(k + 8 - WO_RF1) % NP2], b[p][2 * u], b[p][2 * u + 1]);
                        if (k < P2_FENCE) sched_fence(L);
                    }
                    char* yd = make_ptr(yo, mhi);
                    char* yd1 = make_ptr(yo ^ 4096, mhi);
                    st_relaxed_u32(yd1 + 0x80000, pack_bf16(y2[0] * inv[0], y2[1] * inv[1]));
                    st_relaxed_u32(yd + 0x82000, pack_bf16(y2[2] * inv[0], y2[3] * inv[1]));
                    st_relaxed_u32(yd, pack_bf16(y0[0] * inv[0], y0[1] * inv[1]));
                    st_relaxed_u32(yd1 + 0x2000, pack_bf16(y0[2] * inv[0], y0[3] * inv[1]));
                    st_relaxed_u32(yd + 0x40000, pack_bf16(y1[0] * inv[0], y1[1] * inv[1]));
                    st_relaxed_u32(yd1 + 0x42000, pack_bf16(y1[2] * inv[0], y1[3] * inv[1]));
                }
                bar_arrive(BAR_SENTC, 384);
                TL(13);
                bar_sync(BAR_SENT, 256);
                } else {
                    bar_sync(BAR_V, 160);
                }
            } else {
                bar_sync(BAR_PRO, 288);
            }
            float o[8];
            {
                PHASE(1);
                float d[16];
                const uint64_t da = make_desc(SB0 + SM_WV, 16, 1024);
                auto batch = [&](auto k0c, auto k1c) {
                    static_for<decltype(k0c)::value, decltype(k1c)::value>([&](auto kc) {
                        constexpr int k = decltype(kc)::value, off = (k >> 2) * 256 + (k & 3) * 2;
                        if constexpr (k >= 24) wgmma_ss32u<off>(d, da + (k - 24) * 128, xtlo);
                        else wgmma_rs32u<off, k != 0>(d, wv[k], xtlo);
                    });
                };
                const uint32_t vf = VFRAG(), va0 = vf + VBASE(), va1 = (vf ^ 32) + VBASE(), vma = L + (sb + SM_QKV + 4096 + g * 512), sa = (L >> 2) + (sb + SM_S + 768);
                const uint32_t rt = L + (rsb + SM_RT + 8192 + g * 1024);
                uint32_t va[2][2][4], vm[4], pw[6], w[4];
                wg_fence();
                batch(std::integral_constant<int, 0>(), std::integral_constant<int, TA0>());
                wg_commit();
                batch(std::integral_constant<int, TA0>(), std::integral_constant<int, 32>());
                wg_commit();
                wg_wait<1>();
                softmax40(pw, sa, [&]() {});
                ldsm4t(va[0][0], va0); ldsm4t(va[0][1], va0 + 2048);
                ldsm4t(va[1][0], va1); ldsm4t(va[1][1], va1 + 2048);
                ldsm4(vm, vma);
                wg_wait<0>();
                TL(27);
                float inv[2];
                pv32<true>(w, inv, va, vm, pw, [&]() {
                    if (s + 3 < NSEG) {
#pragma unroll
                        for (int i = 0; i < 2; i++)
                            st_async4(rt + i * 512, kh ? d[4 * i] : d[8 + 4 * i], kh ? d[4 * i + 1] : d[9 + 4 * i], kh ? d[4 * i + 2] : d[10 + 4 * i], kh ? d[4 * i + 3] : d[11 + 4 * i], rsb + MB_RT1);
                    }
#pragma unroll
                    for (int i = 0; i < 8; i++) o[i] = kh ? d[8 + i] : d[i];
                });
                stsm4t((L & 0x70) * 5 + ((L >> 3) & 0x30) + (sb + SM_TO + g * 640), w[0], w[1], w[2], w[3]);
                __syncwarp();
                const uint4 r = lds128(((L >> 2) & 0x70) * 5 + (L & 0x30) + (sb + SM_TO + g * 640));
                if (s >= 0) stg128(reinterpret_cast<char*>(g_ox) + (((L & 0x1C0) << 7) + (L & 0x30) + (((ui - 3) * SEG + 8 * j) * HD + h * DH + 32 * g) * 2), r);
                TL(26);
            }
            if (s + 3 < NSEG) {
                PHASE(3);
                const uint32_t rt = L + (sb + SM_RT + 8192 + g * 1024), so = FRAG() + (sb + SM_STG + 4096);
                mbar_wait_w(sb + MB_RT1, it & 1);
                TL(28);
                uint32_t w[4];
#pragma unroll
                for (int i = 0; i < 2; i++) {
                    const uint4 v = lds128(rt + i * 512);
                    w[2 * i] = pack_bf16(o[4 * i] + __uint_as_float(v.x), o[4 * i + 1] + __uint_as_float(v.y));
                    w[2 * i + 1] = pack_bf16(o[4 * i + 2] + __uint_as_float(v.z), o[4 * i + 3] + __uint_as_float(v.w));
                }
                stsm4t(so, w[0], w[1], w[2], w[3]);
                __syncwarp();
                mbar_arrive_if0(L, sb + MB_STG);
                TL(15);
            }
        }
    }
    KT_END(2);
    asm volatile("barrier.cluster.arrive.relaxed; barrier.cluster.wait;" ::: "memory");
}
constexpr int B_UCH = 73 * 64;
constexpr int B_SCH = 33 * 64;
constexpr int B_KLEN = 2128;
constexpr int B_KCH = 2 * B_KLEN * 2 + 64;
constexpr int B_KBOX = 136 * 32;
constexpr int B_SM_U = 0;
constexpr int B_SM_S = 8 * B_UCH;
constexpr int B_SM_K = B_SM_S + 8 * B_SCH;
constexpr int B_SM_KT = B_SM_K + 8 * B_KCH;
constexpr int B_SM_VT = B_SM_KT + 8 * B_KBOX;
constexpr int B_SM_QT = B_SM_VT + 32768;
constexpr int B_SM_BAR = B_SM_QT + 32768;
constexpr int B_SMEM = B_SM_BAR + 128 + 512;
static_assert(B_SM_KT % 256 == 0 && B_SM_S % 512 == 0 && B_SMEM <= 232448, "tiles");
constexpr int PROBE_N = 4;
#define PROBE_R 2
constexpr int B_C = 2056;

__device__ __forceinline__ uint32_t atomic_round_trip(char* p) {
    uint32_t t0, t1, v;
    asm volatile("{.reg .pred p;\n"
                 "mov.u32 %0, %%clock;\n"
                 "atom.relaxed.gpu.global.add.u32 %2, [%3], 1;\n"
                 "setp.ne.u32 p, %2, 0x7FFFFFFF;\n"
                 "mov.u32 %1, 0;\n"
                 "@p mov.u32 %1, %%clock;}" : "=&r"(t0), "=&r"(t1), "=&r"(v) : "l"(p) : "memory");
    return t1 - t0;
}
__device__ __forceinline__ uint32_t round_trips(char* a, char* b, uint32_t stride, int lane) {
    for (int i = lane >> 3; i < 2 * PROBE_N; i += 4) stg128(((i & 1) ? b : a) + (i >> 1) * stride + (lane & 7) * 16, make_uint4(0, 0, 0, 0));
    __syncwarp();
    uint32_t ta = 0xFFFF, tb = 0xFFFF;
    if (lane == 0) {
        __threadfence();
#pragma unroll 1
        for (int i = 0; i < PROBE_N; i++) { ta = min(ta, atomic_round_trip(a + i * stride)); tb = min(tb, atomic_round_trip(b + i * stride)); }
    }
    __syncwarp();
    return ta | (tb << 16);
}
__device__ __forceinline__ void measure_distance(char* mbox, int lane) {
    const uint32_t b = blockIdx.x;
    unsigned smid;
    asm volatile("mov.u32 %0, %%smid;" : "=r"(smid));
    char* w1 = mbox + WIN + (b & 31) * 128;
    uint32_t r = 0xFFFFFFFF;
#pragma unroll 1
    for (int i = 0; i < PROBE_R; i++) r = __vminu2(r, round_trips(w1 + page_off(50 + 5 * i + (b >> 5), 0), w1 + page_off(50 + 5 * i + (b >> 5), 1), 16384, lane));
    if (lane == 0) g_cls[smid] = r;
    if (b == 128) {
        char *p = mbox + page_off(0, 0), *q = mbox + page_off(0, 1);
        uint32_t r0 = 0xFFFFFFFF;
#pragma unroll 1
        for (int i = 0; i < PROBE_R; i++) r0 = __vminu2(r0, round_trips(p, q, 128, lane));
        if (lane == 0) { g_reg[2] = ((r0 & 0xFFFF) > (r0 >> 16)) != ((r & 0xFFFF) > (r >> 16)); g_reg[0] = 0; g_reg[1] = 0; }
        const uint4 sent = make_uint4(SENT, SENT, SENT, SENT);
        stg128(p + lane * 16, sent); stg128(q + lane * 16, sent);
    }
    if (b == 129) for (int i = lane; i < 128; i += 32) g_xflag[i] = 0;
}

#define SP(i)
#define SP2(i)
#define PF_STOP 1
#define SENT_AT 3
#define Q_LATE 1
#define PF_DEPTH 4
#define PF_STRIDE 256
struct ChainInputs { const char* w[4]; const char *x, *mem0; };
#define EF_MASK 15
#define EF(i) (((EF_MASK >> (i)) & 1) ? policy_evict_first() : policy_evict_normal())
__device__ __forceinline__ void l2_prefetch(const char* p, uint32_t bytes) {
    asm volatile("cp.async.bulk.prefetch.L2.global [%0], %1;" ::"l"(p), "r"(bytes) : "memory");
}
#define WG_CONV(N, LIST, A0, A1, A2, A3, LO, OF, ...) \
    if constexpr (NN == N) asm volatile("{.reg .b32 l; .reg .b64 e; add.u32 l, %" #LO ", %" #OF "; mov.b64 e, {l, 0x80000020};\n" \
        "wgmma.mma_async.sync.aligned.m64n" #N "k16.f32.bf16.bf16 {" LIST "}, {%" #A0 ",%" #A1 ",%" #A2 ",%" #A3 "}, e, 1, 1, 1, 0;}" \
        : __VA_ARGS__ : "r"(a[0]), "r"(a[1]), "r"(a[2]), "r"(a[3]), "r"(lo), "n"(OFF));
#define WL4 "%0,%1,%2,%3"
#define WL8 WL4 ",%4,%5,%6,%7"
#define WL12 WL8 ",%8,%9,%10,%11"
#define WL16 WL12 ",%12,%13,%14,%15"
#define WL20 WL16 ",%16,%17,%18,%19"
#define WL24 WL20 ",%20,%21,%22,%23"
#define WL28 WL24 ",%24,%25,%26,%27"
#define WL32 WL28 ",%28,%29,%30,%31"
template <int NN, int OFF> __device__ __forceinline__ void wgmma_conv(float (&d)[32], const uint32_t (&a)[4], uint32_t lo) {
    WG_CONV(8, WL4, 4, 5, 6, 7, 8, 9, R4(0))
    WG_CONV(16, WL8, 8, 9, 10, 11, 12, 13, R4(0), R4(4))
    WG_CONV(24, WL12, 12, 13, 14, 15, 16, 17, R4(0), R4(4), R4(8))
    WG_CONV(32, WL16, 16, 17, 18, 19, 20, 21, R16(0))
    WG_CONV(40, WL20, 20, 21, 22, 23, 24, 25, R16(0), R4(16))
    WG_CONV(48, WL24, 24, 25, 26, 27, 28, 29, R16(0), R4(16), R4(20))
    WG_CONV(56, WL28, 28, 29, 30, 31, 32, 33, R16(0), R4(16), R4(20), R4(24))
    WG_CONV(64, WL32, 32, 33, 34, 35, 36, 37, R16(0), R16(16))
}
__device__ __forceinline__ void copy_to_peer(uint32_t dst, uint32_t src, uint32_t bytes, uint32_t bar) {
    asm volatile("cp.async.bulk.shared::cluster.shared::cta.mbarrier::complete_tx::bytes [%0], [%1], %2, [%3];" ::"r"(dst), "r"(src), "r"(bytes), "r"(bar) : "memory");
}
__device__ __forceinline__ uint32_t lds_volatile(uint32_t a) {
    uint32_t v;
    asm volatile("ld.volatile.shared.u32 %0, [%1];" : "=r"(v) : "r"(a) : "memory");
    return v;
}
__device__ __forceinline__ uint32_t swz64(uint32_t a) { return a ^ ((a >> 3) & 0x30); }
__device__ __forceinline__ void fence_async() { asm volatile("fence.proxy.async.shared::cta;" ::: "memory"); }

__global__ void __cluster_dims__(2, 1, 1) __launch_bounds__(576, 1)
ssm_kernel(const __grid_constant__ CUtensorMap mapK, const __grid_constant__ CUtensorMap mapV, const __grid_constant__ CUtensorMap mapQ,
           const __grid_constant__ CUtensorMap mapO, const bf16* __restrict__ shiftk, const bf16* __restrict__ ssmk, const bf16* __restrict__ Dv,
           char* __restrict__ mbox, const __grid_constant__ ChainInputs ci) {
    extern __shared__ __align__(128) uint8_t smem_raw[];
    const uint32_t sb = (smem_u32(smem_raw) + 511) & ~511u;
    const int rank = blockIdx.x & 1, ch0 = blockIdx.x * 8, c16 = ch0 & ~15, t0 = rank * 1024;
    const int t = threadIdx.x, warp = t >> 5, lane = t & 31;
    const uint32_t bar = sb + B_SM_BAR, barQ = bar + 64, barU = bar + 72, barY = bar + 80, flag = bar + 88;
    SP(0);
    if (lane == 0 && warp < 16 && blockIdx.x < 128) {
        const int i = warp >> 1;
        if (warp & 1) {
            if (i < 3) { mbar_init(barQ + i * 8, 1); mbar_expect_tx(barQ + i * 8, i ? 16384 : 32768); }
            if (i == 3) sts32(flag, 0);
        } else {
            mbar_init(bar + i * 8, 1);
            asm volatile("fence.mbarrier_init.release.cluster;" ::: "memory");
            mbar_expect_tx(bar + i * 8, B_KBOX + 4096);
            tma_load_2d(sb + B_SM_KT + i * B_KBOX, &mapK, c16, t0 + i * 128 - 8, bar + i * 8, EF(0));
            tma_load_2d(sb + B_SM_VT + i * 4096, &mapV, c16, t0 + i * 128, bar + i * 8, EF(0));
        }
        asm volatile("fence.mbarrier_init.release.cluster;" ::: "memory");
    }
    __syncwarp();
    if (warp == 14) SP2(14);
    KT_START(1);
    if (warp == 17) {
        asm volatile("barrier.cluster.arrive.relaxed.aligned;" ::: "memory");
        measure_distance(mbox, lane);
        asm volatile("barrier.cluster.wait.aligned;" ::: "memory");
        KT_MARK(14);
        return;
    }
    if (blockIdx.x >= 128) return;
    if (warp == 16) {
        asm volatile("barrier.cluster.arrive.relaxed.aligned; barrier.cluster.wait.aligned;" ::: "memory");
        SP2(8);
        if (Q_LATE) for (int i = 0; i < 8; i++) { mbar_wait_w(bar + i * 8, 0); SP2(i); }
        if (lane < 8) tma_load_2d(sb + B_SM_QT + lane * 4096, &mapQ, c16, t0 + lane * 128, barQ, EF(3));
        if (!Q_LATE) for (int i = 0; i < 8; i++) mbar_wait_w(bar + i * 8, 0);
        if (lane == 0) {
            l2_prefetch(ci.x + blockIdx.x * 2048, 2048);
            if (blockIdx.x < 8) l2_prefetch(ci.mem0 + blockIdx.x * 2048, 2048);
        }
        uint32_t v[PF_DEPTH], acc = 0;
#pragma unroll
        for (int u = 0; u < PF_DEPTH; u++) v[u] = 0;
        constexpr int PER = 32 * PF_STRIDE, NW = 65536 / PER;
#pragma unroll 1
        for (int i = 0; i < 4 * NW && lds_volatile(flag) == 0; i += PF_DEPTH) {
#pragma unroll
            for (int u = 0; u < PF_DEPTH; u++) {
                const char* a = ci.w[(i + u) / NW] + blockIdx.x * 65536 + ((i + u) % NW) * PER + lane * PF_STRIDE;
                acc |= v[u];
                asm volatile("ld.global.cg.L2::256B.u32 %0, [%1];" : "=r"(v[u]) : "l"(a) : "memory");
            }
        }
#pragma unroll
        for (int u = 0; u < PF_DEPTH; u++) acc |= v[u];
        if (acc == 0x7FFF7FFFu && v[0] == 0x7FFEu) g_err = 1;
        SP2(12);
        KT_MARK(15);
        return;
    }
    asm volatile("barrier.cluster.arrive.relaxed.aligned;" ::: "memory");
    const int far = warp & 1, unit = rank ^ far;
    uint32_t w[4];
    uint32_t d2;
    asm volatile("ld.global.nc.u32 %0, [%1];" : "=r"(d2) : "l"(Dv + ch0 + (warp >> 2) * 2));
    {
        const int ch = warp & 7, half = warp >> 3;
        const uint32_t kb = sb + B_SM_K + ch * B_KCH;
        const uint4* src = reinterpret_cast<const uint4*>(ssmk + (size_t)(ch0 + ch) * S_LEN);
        uint4 kr[4];
#pragma unroll
        for (int i = 0; i < 4; i++) kr[i] = ldg128(src + half * 128 + i * 32 + lane, EF(1));
        const uint32_t edge = half ? 0u : __ldg(reinterpret_cast<const uint32_t*>(src + 128));
        const uint2 sw = __ldg(reinterpret_cast<const uint2*>(shiftk + (size_t)(c16 + unit * 8 + (lane >> 2)) * 4));
        w[0] = __byte_perm(sw.x, 0, 0x1010); w[1] = __byte_perm(sw.x, 0, 0x3232); w[2] = __byte_perm(sw.y, 0, 0x1010); w[3] = __byte_perm(sw.y, 0, 0x3232);
        if (half) sts128(sb + B_SM_U + ch * B_UCH + 4096 + lane * 16, make_uint4(0, 0, 0, 0));
#pragma unroll
        for (int i = 0; i < 4; i++) {
            const uint4 lo = kr[i];
            const uint32_t nx = __shfl_down_sync(~0u, lo.x, 1), n0 = (i < 3) ? __shfl_sync(~0u, kr[i < 3 ? i + 1 : 3].x, 0) : edge;
            const uint32_t hix = (lane < 31) ? nx : n0;
            const int c = 256 - (half * 128 + 32 * i + lane);
            sts128(kb + c * 16, make_uint4(__byte_perm(hix, lo.w, 0x7610), __byte_perm(lo.w, lo.z, 0x7610), __byte_perm(lo.z, lo.y, 0x7610), __byte_perm(lo.y, lo.x, 0x7610)));
            sts128(kb + B_KLEN * 2 + 64 + c * 16, make_uint4(__byte_perm(lo.w, lo.w, 0x1032), __byte_perm(lo.z, lo.z, 0x1032), __byte_perm(lo.y, lo.y, 0x1032), __byte_perm(lo.x, lo.x, 0x1032)));
        }
        const uint32_t k0w = __shfl_sync(~0u, kr[0].x, 0);
        if (half == 0 && lane < 8) {
            sts128(kb + (257 + lane) * 16, make_uint4(lane == 0 ? (k0w & 0xFFFFu) : 0u, 0u, 0u, 0u));
            sts128(kb + B_KLEN * 2 + 64 + (257 + lane) * 16, make_uint4(0u, 0u, 0u, 0u));
        }
    }
    auto sentinels = [&]() {
        const uint4 sent = make_uint4(SENT, SENT, SENT, SENT);
        char* p0 = mbox + blockIdx.x * 16384 + t * 16;
        if (blockIdx.x != 0 || (t & 255) >= 32) stg128(p0, sent);
        stg128(p0 + 8192, sent);
        char* p1 = mbox + WIN + blockIdx.x * 12800 + t * 16;
        stg128(p1, sent);
        if (t < 288) stg128(p1 + 8192, sent);
    };
    if (SENT_AT == 1) sentinels();
    asm volatile("barrier.cluster.wait.acquire.aligned;" ::: "memory");
    SP(1);
    {
        const int box = warp >> 1, row0 = 63 - 32 * rank - 4 * box;
        const uint32_t kt = sb + B_SM_KT + box * B_KBOX + 256 + lane * 32, s0 = (unit ^ ((lane >> 2) & 1)) * 16;
        const uint32_t a0 = kt + s0, a2 = kt - 64 + (unit ^ (((lane + 6) >> 2) & 1)) * 16, a4 = kt - 128 + (s0 ^ 16), av = sb + B_SM_VT + box * 4096 + lane * 32 + s0;
        const uint32_t ul = (lane & 7) * B_UCH + row0 * 64 + (lane >> 3) * 16;
        const uint32_t ud = sb + (far ? B_SM_S + (lane & 7) * (B_SCH - B_UCH) - (1 - rank) * 2048 : B_SM_U);
        mbar_wait_w(bar + box * 8, 0);
        SP(2);
#pragma unroll
        for (int i = 0; i < 4; i++) {
            uint32_t k0[4], k2[4], k4[4], vv[4], o[4];
            ldsm4t(k0, a0 + i * 1024); ldsm4t(k2, a2 + i * 1024); ldsm4t(k4, a4 + i * 1024); ldsm4t(vv, av + i * 1024);
#pragma unroll
            for (int j = 0; j < 4; j++) {
                uint32_t a = bf16_mul(__byte_perm(k4[j], k2[j], 0x5432), w[3]);
                a = bf16_add(a, bf16_mul(k2[j], w[2]));
                a = bf16_add(a, bf16_mul(__byte_perm(k2[j], k0[j], 0x5432), w[1]));
                a = bf16_add(a, bf16_mul(k0[j], w[0]));
                o[j] = bf16_mul(a, vv[j]);
            }
            stsm4(ud + swz64(ul - i * 64), o[0], o[1], o[2], o[3]);
        }
        fence_async();
        __syncwarp();
        if (far && lane < 8) {
            const uint32_t o = lane * B_UCH + (row0 - 3) * 64;
            copy_to_peer(peer_addr(sb + B_SM_U + o, rank ^ 1), ud + o, 256, peer_addr(barU, rank ^ 1));
        }
    }
    bar_sync(1, 512);
    mbar_wait_w(barU, 0);
    if (SENT_AT == 2) sentinels();
    SP(3);
    const int wg = warp >> 2, wq = warp & 3, hi = wq >> 1, g = lane >> 2, tq = lane & 3;
    const uint32_t zero = lds32(sb + B_SM_U + 4096);
#pragma unroll 1
    for (int cc = 0; cc < 2; cc++) {
        const int ch = 2 * wg + cc;
        const uint32_t kb = sb + B_SM_K + ch * B_KCH, ub = sb + B_SM_U + ch * B_UCH;
        const uint32_t dw = __byte_perm(d2, 0, cc ? 0x3232 : 0x1010);
        const int e0 = B_C - g + 2 * tq;
        const uint32_t f0 = ((e0 & 1) ? (kb + B_KLEN * 2 + 64 + (e0 - 1) * 2) : (kb + e0 * 2)) - 32 * wq;
        const uint32_t lo = uniform((ub >> 4) | 0x10000);
        float d[32];
#pragma unroll
        for (int i = 0; i < 32; i++) d[i] = 0.f;
        uint32_t A[2][2][4];
        static_for<0, 32>([&](auto jc) {
            constexpr int j = decltype(jc)::value, N = 64 - 8 * (j / 4);
            if (j >= 2) wg_wait<1>();
            uint32_t(&a)[4] = A[j & 1][0];
            uint32_t(&b)[4] = A[j & 1][1];
            a[0] = lds32(f0 - 128 * j); a[1] = lds32(f0 - 128 * j - 16); a[2] = lds32(f0 - 128 * j + 16);
            b[0] = lds32(f0 - 128 * j + 32); b[2] = lds32(f0 - 128 * j + 48);
            a[3] = a[0] ^ zero; b[1] = a[2] ^ zero; b[3] = b[0] ^ zero;
            wg_fence();
            wgmma_conv<N, 8 * j>(d, a, lo);
            wgmma_conv<N, 8 * j + 2>(d, b, lo);
            wg_commit();
        });
        wg_wait<0>();
        if (cc) SP(4);
        if (PF_STOP == 1 && cc && t == 0) sts32(flag, 1);
        bar_sync(2 + wg, 128);
        if (!hi && tq == 3) { float x = d[13]; d[13] = d[29]; d[29] = x; x = d[15]; d[15] = d[31]; d[31] = x; }
        if (hi && tq == 0) { d[0] = 0.f; d[2] = 0.f; }
        {
            const uint32_t xs = kb + (wq ^ 2) * 2048 + lane * 4;
            const uint32_t xn = hi ? xs + (tq ? 124 : 140) : xs + (tq < 3 ? 4 : -12), wrap = hi ? (tq ? 0 : -1) : (tq < 3 ? 0 : 1);
#pragma unroll
            for (int nb = 0; nb < 4; nb++) {
                const uint32_t xw = xn + ((nb + wrap) & 3) * 512;
#pragma unroll
                for (int i = 0; i < 2; i++) {
                    const float e0v = hi ? d[4 * nb + 2 * i] : d[16 + 4 * nb + 2 * i], e1v = hi ? d[4 * nb + 2 * i + 1] : d[16 + 4 * nb + 2 * i + 1];
                    sts32(hi ? xw + i * 256 : xs + nb * 512 + i * 256 + 128, __float_as_uint(e0v));
                    sts32(hi ? xs + nb * 512 + i * 256 : xw + i * 256, __float_as_uint(e1v));
                }
            }
        }
        bar_sync(2 + wg, 128);
#pragma unroll
        for (int p = 0; p < 2; p++) {
            int row = 16 * p + (lane >> 4) * 8 + (lane & 7);
            row = hi ? row + 31 : row == 31 ? 63 : row;
            const uint32_t a = sb + B_SM_U + swz64(ch * B_UCH + row * 64 + ((wq & 1) * 2 + ((lane >> 3) & 1)) * 16);
            uint32_t u[4];
            ldsm4t(u, a);
#pragma unroll
            for (int b = 0; b < 4; b++) {
                const int r = 8 * p + 2 * b;
                const float y0 = (hi ? d[16 + r] : d[r]) + __uint_as_float(lds32(kb + wq * 2048 + r * 128 + lane * 4));
                const float y1 = (hi ? d[17 + r] : d[r + 1]) + __uint_as_float(lds32(kb + wq * 2048 + r * 128 + 128 + lane * 4));
                u[b] = bf16_add(pack_bf16(y0, y1), bf16_mul(u[b], dw));
            }
            stsm4t(a, u[0], u[1], u[2], u[3]);
        }
        fence_async();
        bar_sync(2 + wg, 128);
        if (SENT_AT == 3 && cc == 0) sentinels();
        if (wq == 0 && lane == 0) copy_to_peer(peer_addr(sb + B_SM_S + ch * B_SCH, rank ^ 1), ub + rank * 2048, 2048, peer_addr(barY, rank ^ 1));
    }
    if (PF_STOP == 2 && t == 0) sts32(flag, 1);
    SP(5);
    mbar_wait_w(barQ, 0);
    bar_sync(1, 512);
    mbar_wait_w(barY, 0);
    asm volatile("barrier.cluster.arrive.relaxed.aligned;" ::: "memory");
    SP(6);
#pragma unroll
    for (int i = 0; i < 4; i++) {
        const int fr = i & 1, row = 63 - 32 * rank - 2 * warp - (i >> 1);
        const uint32_t qa = sb + B_SM_QT + warp * 2048 + (i >> 1) * 1024 + lane * 32 + ((rank ^ fr ^ (lane >> 2)) & 1) * 16;
        uint32_t y[4], q[4];
        ldsm4t(y, sb + (fr ? B_SM_S + (lane & 7) * (B_SCH - B_UCH) - (1 - rank) * 2048 : B_SM_U) + swz64((lane & 7) * B_UCH + row * 64 + (lane >> 3) * 16));
        ldsm4(q, qa);
        stsm4(qa, bf16_mul(q[0], y[0]), bf16_mul(q[1], y[1]), bf16_mul(q[2], y[2]), bf16_mul(q[3], y[3]));
    }
    fence_async();
    __syncwarp();
    if (lane == 0) {
        asm volatile("cp.async.bulk.tensor.2d.global.shared::cta.bulk_group.L2::cache_hint [%0, {%2, %3}], [%1], %4;"
                     ::"l"(&mapO), "r"(sb + B_SM_QT + warp * 2048), "r"(DM + c16), "r"(t0 + warp * 64), "l"(EF(4)) : "memory");
        asm volatile("cp.async.bulk.commit_group;" ::: "memory");
    }
    if (SENT_AT == 0) sentinels();
    if (warp == 0) SP2(10);
    if (lane == 0) asm volatile("cp.async.bulk.wait_group.read 0;" ::: "memory");
    __syncwarp();
    if (warp == 0) SP2(11);
    asm volatile("barrier.cluster.wait.aligned;" ::: "memory");
    SP(7);
    KT_END(1);
}

typedef CUresult (*EncodeFn)(CUtensorMap*, CUtensorMapDataType, cuuint32_t, void*, const cuuint64_t*, const cuuint64_t*, const cuuint32_t*,
                             const cuuint32_t*, CUtensorMapInterleave, CUtensorMapSwizzle, CUtensorMapL2promotion, CUtensorMapFloatOOBfill);

static void make_map(EncodeFn fn, CUtensorMap* m, const void* ptr, uint64_t inner, uint64_t outer, uint32_t box_in, uint32_t box_out,
                     CUtensorMapL2promotion promo = CU_TENSOR_MAP_L2_PROMOTION_L2_256B) {
    cuuint64_t dims[2] = {inner, outer};
    cuuint64_t strides[1] = {inner * 2};
    cuuint32_t box[2] = {box_in, box_out};
    cuuint32_t es[2] = {1, 1};
    fn(m, CU_TENSOR_MAP_DATA_TYPE_BFLOAT16, 2, const_cast<void*>(ptr), dims, strides, box, es, CU_TENSOR_MAP_INTERLEAVE_NONE,
       CU_TENSOR_MAP_SWIZZLE_128B, promo, CU_TENSOR_MAP_FLOAT_OOB_FILL_NONE);
}

#define SSM_PROMO CU_TENSOR_MAP_L2_PROMOTION_NONE
extern "C" void kernel_launch(void* const* d_in, const int* in_sizes, int n_in, void* d_out, int out_size) {
    const bf16* x = (const bf16*)d_in[0];
    const bf16* mem0 = (const bf16*)d_in[1];
    const bf16* Wq = (const bf16*)d_in[2];
    const bf16* Wk = (const bf16*)d_in[3];
    const bf16* Wv = (const bf16*)d_in[4];
    const bf16* Wo = (const bf16*)d_in[5];
    const bf16* Bq = (const bf16*)d_in[7];
    const bf16* Bk = (const bf16*)d_in[8];
    const bf16* Bv = (const bf16*)d_in[9];
    const bf16* Bsh = (const bf16*)d_in[10];
    const bf16* Bssm = (const bf16*)d_in[11];
    const bf16* BD = (const bf16*)d_in[12];
    bf16* out = (bf16*)d_out;

    static bool init = false;
    static EncodeFn enc = nullptr;
    static void *p_tok, *p_ox, *p_mbox;
    static int nclusters = 64;
    using G2 = GemmCfg<128, 5>;
    if (!init) {
        cudaDriverEntryPointQueryResult qr;
        cudaGetDriverEntryPoint("cuTensorMapEncodeTiled", (void**)&enc, cudaEnableDefault, &qr);
        cudaGetSymbolAddress(&p_tok, g_tok);
        cudaGetSymbolAddress(&p_ox, g_ox);
        cudaGetSymbolAddress(&p_mbox, g_mbox);
        cudaFuncSetAttribute(gemm_kernel<128, 5>, cudaFuncAttributeMaxDynamicSharedMemorySize, G2::SMEM);
        cudaFuncSetAttribute(chain_kernel, cudaFuncAttributeMaxDynamicSharedMemorySize, CHAIN_SMEM);
        cudaFuncSetAttribute(ssm_kernel, cudaFuncAttributeMaxDynamicSharedMemorySize, B_SMEM);
        cudaLaunchConfig_t cfg = {};
        cfg.gridDim = dim3(132); cfg.blockDim = dim3(384); cfg.dynamicSmemBytes = CHAIN_SMEM;
        cudaLaunchAttribute at[1];
        at[0].id = cudaLaunchAttributeClusterDimension; at[0].val.clusterDim.x = 2; at[0].val.clusterDim.y = 1; at[0].val.clusterDim.z = 1;
        cfg.attrs = at; cfg.numAttrs = 1;
        int n = 0;
        if (cudaOccupancyMaxActiveClusters(&n, chain_kernel, &cfg) == cudaSuccess && n > 64) nclusters = n < 66 ? n : 66;
        (void)cudaGetLastError();
        init = true;
    }
    char* mbox = (char*)(((uintptr_t)p_mbox + 2 * WIN - 1) & ~(uintptr_t)(2 * WIN - 1));
    CUtensorMap mX, mT32, mT16, mTQ, mKV, mWq, mWk, mWv, mWoC, mOx, mWo, mOut;
    {
        cuuint64_t dims[3] = {64, S_LEN, DM / 64};
        cuuint64_t strides[2] = {DM * 2, 128};
        cuuint32_t box[3] = {64, 32, 4};
        cuuint32_t es[3] = {1, 1, 1};
        enc(&mX, CU_TENSOR_MAP_DATA_TYPE_BFLOAT16, 3, const_cast<bf16*>(x), dims, strides, box, es, CU_TENSOR_MAP_INTERLEAVE_NONE,
            CU_TENSOR_MAP_SWIZZLE_128B, CU_TENSOR_MAP_L2_PROMOTION_L2_256B, CU_TENSOR_MAP_FLOAT_OOB_FILL_NONE);
    }
    make_map(enc, &mT32, p_tok, DH, 4 * NH * 3 * SEG, 64, 32, CU_TENSOR_MAP_L2_PROMOTION_L2_128B);
    make_map(enc, &mT16, p_tok, DH, 4 * NH * 3 * SEG, 64, 16, CU_TENSOR_MAP_L2_PROMOTION_L2_128B);
    {
        cuuint64_t dims[2] = {512, 4 * NH * 12};
        cuuint64_t strides[1] = {2048};
        cuuint32_t box[2] = {256, 4};
        cuuint32_t es[2] = {1, 1};
        enc(&mTQ, CU_TENSOR_MAP_DATA_TYPE_UINT32, 2, p_tok, dims, strides, box, es, CU_TENSOR_MAP_INTERLEAVE_NONE,
            CU_TENSOR_MAP_SWIZZLE_NONE, CU_TENSOR_MAP_L2_PROMOTION_L2_128B, CU_TENSOR_MAP_FLOAT_OOB_FILL_NONE);
    }
    {
        cuuint64_t dims[3] = {64, 4 * NH * 3 * SEG, 2};
        cuuint64_t strides[2] = {DH * 2, 128};
        cuuint32_t box[3] = {64, 32, 2};
        cuuint32_t es[3] = {1, 1, 1};
        enc(&mKV, CU_TENSOR_MAP_DATA_TYPE_BFLOAT16, 3, p_tok, dims, strides, box, es, CU_TENSOR_MAP_INTERLEAVE_NONE,
            CU_TENSOR_MAP_SWIZZLE_128B, CU_TENSOR_MAP_L2_PROMOTION_L2_128B, CU_TENSOR_MAP_FLOAT_OOB_FILL_NONE);
    }
    make_map(enc, &mWq, Wq, HD, DM, 64, 16, CU_TENSOR_MAP_L2_PROMOTION_L2_128B);
    make_map(enc, &mWk, Wk, HD, DM, 64, 16, CU_TENSOR_MAP_L2_PROMOTION_L2_128B);
    make_map(enc, &mWv, Wv, HD, DM, 64, 16, CU_TENSOR_MAP_L2_PROMOTION_L2_128B);
    make_map(enc, &mWoC, Wo, DM, HD, 64, 128, CU_TENSOR_MAP_L2_PROMOTION_L2_128B);
    make_map(enc, &mOx, p_ox, HD, S_LEN, 64, 128);
    make_map(enc, &mWo, Wo, DM, HD, 64, 64);
    make_map(enc, &mOut, out, OUT_LD, S_LEN, 64, 64);

    CUtensorMap mB[4];
    for (int i = 0; i < 4; i++) {
        cuuint64_t dims[2] = {(cuuint64_t)(i < 3 ? DM : OUT_LD), S_LEN};
        cuuint64_t strides[1] = {dims[0] * 2};
        cuuint32_t box[2] = {16, i == 0 ? 136u : i < 3 ? 128u : 64u};
        cuuint32_t es[2] = {1, 1};
        enc(&mB[i], CU_TENSOR_MAP_DATA_TYPE_BFLOAT16, 2, const_cast<bf16*>(i == 0 ? Bk : i == 1 ? Bv : i == 2 ? Bq : out), dims, strides, box, es,
            CU_TENSOR_MAP_INTERLEAVE_NONE, CU_TENSOR_MAP_SWIZZLE_32B, SSM_PROMO, CU_TENSOR_MAP_FLOAT_OOB_FILL_NONE);
    }
    cudaStream_t st = cudaStreamPerThread;
    const ChainInputs ci = {{(const char*)Wv, (const char*)Wk, (const char*)Wq, (const char*)Wo}, (const char*)x, (const char*)mem0};
    ssm_kernel<<<132, 576, B_SMEM, st>>>(mB[0], mB[1], mB[2], mB[3], Bsh, Bssm, BD, mbox, ci);
    chain_kernel<<<2 * nclusters, 384, CHAIN_SMEM, st>>>(mX, mT32, mT16, mTQ, mKV, mWq, mWk, mWv, mWoC, mem0, mbox);
    gemm_kernel<128, 5><<<128, 288, G2::SMEM, st>>>(mOx, mWo, mWo, mWo, mOut, 16, 8, 64);
}
```

```cpp
#include <cuda_runtime.h>
#include <cuda_bf16.h>
#include <cuda.h>
#include <stdint.h>
#include <type_traits>

typedef __nv_bfloat16 bf16;

constexpr int S_LEN = 2048, DM = 1024, NH = 32, DH = 128, NSEG = 64, SEG = 32;
constexpr int HD = NH * DH;
constexpr int OUT_LD = 2048;
constexpr unsigned SENT = 0xFFFFFFFFu;

__device__ bf16 g_tok[4 * NH * 3 * SEG * DH];
__device__ bf16 g_ox[(size_t)S_LEN * HD];
__device__ uint4 g_mbox[4 * 131072];
__device__ unsigned g_xflag[128];
__device__ unsigned g_reg[4];
__device__ unsigned g_cls[256];
__device__ unsigned g_err;
constexpr uint32_t WIN = 2u << 20;
__host__ __device__ constexpr uint32_t page_off(uint32_t idx, uint32_t c) {
    return ((idx & 1) << 13) | ((idx >> 1) << 16) | (((c ^ idx ^ (idx >> 1) ^ (idx >> 2) ^ (idx >> 4)) & 1) << 12);
}
#define STAT(i, c) (void)(c)
#define PDL 3

__device__ __forceinline__ void launch_dependents() { asm volatile("griddepcontrol.launch_dependents;" ::: "memory"); }
__device__ __forceinline__ void wait_prerequisites() { asm volatile("griddepcontrol.wait;" ::: "memory"); }
#define KT_MARK(k)
#define KT_START(k)
#define KT_END(k)

__device__ __forceinline__ uint32_t smem_u32(const void* p) { return (uint32_t)__cvta_generic_to_shared(p); }
__device__ __forceinline__ void ldsm4(uint32_t& r0, uint32_t& r1, uint32_t& r2, uint32_t& r3, uint32_t a) {
    asm volatile("ldmatrix.sync.aligned.m8n8.x4.shared.b16 {%0,%1,%2,%3}, [%4];" : "=r"(r0), "=r"(r1), "=r"(r2), "=r"(r3) : "r"(a) : "memory");
}
__device__ __forceinline__ void ldsm4t(uint32_t& r0, uint32_t& r1, uint32_t& r2, uint32_t& r3, uint32_t a) {
    asm volatile("ldmatrix.sync.aligned.m8n8.x4.trans.shared.b16 {%0,%1,%2,%3}, [%4];" : "=r"(r0), "=r"(r1), "=r"(r2), "=r"(r3) : "r"(a) : "memory");
}
__device__ __forceinline__ void ldsm2(uint32_t& r0, uint32_t& r1, uint32_t a) {
    asm volatile("ldmatrix.sync.aligned.m8n8.x2.shared.b16 {%0,%1}, [%2];" : "=r"(r0), "=r"(r1) : "r"(a) : "memory");
}
__device__ __forceinline__ void stg128(void* p, uint4 v) {
    asm volatile("st.global.v4.u32 [%0], {%1,%2,%3,%4};" ::"l"(p), "r"(v.x), "r"(v.y), "r"(v.z), "r"(v.w) : "memory");
}
__device__ __forceinline__ void stsm4(uint32_t a, uint32_t r0, uint32_t r1, uint32_t r2, uint32_t r3) {
    asm volatile("stmatrix.sync.aligned.m8n8.x4.shared.b16 [%0], {%1,%2,%3,%4};" ::"r"(a), "r"(r0), "r"(r1), "r"(r2), "r"(r3) : "memory");
}
__device__ __forceinline__ void mma16816(float (&d)[4], uint32_t a0, uint32_t a1, uint32_t a2, uint32_t a3, uint32_t b0, uint32_t b1) {
    asm("mma.sync.aligned.m16n8k16.row.col.f32.bf16.bf16.f32 {%0,%1,%2,%3},{%4,%5,%6,%7},{%8,%9},{%0,%1,%2,%3};"
                 : "+f"(d[0]), "+f"(d[1]), "+f"(d[2]), "+f"(d[3])
                 : "r"(a0), "r"(a1), "r"(a2), "r"(a3), "r"(b0), "r"(b1));
}
__device__ __forceinline__ void mma1688(float (&d)[4], uint32_t a0, uint32_t a1, uint32_t b0) {
    asm("mma.sync.aligned.m16n8k8.row.col.f32.bf16.bf16.f32 {%0,%1,%2,%3},{%4,%5},{%6},{%0,%1,%2,%3};"
        : "+f"(d[0]), "+f"(d[1]), "+f"(d[2]), "+f"(d[3]) : "r"(a0), "r"(a1), "r"(b0));
}
__device__ __forceinline__ uint32_t movmat(uint32_t a) {
    uint32_t d;
    asm volatile("movmatrix.sync.aligned.m8n8.trans.b16 %0, %1;" : "=r"(d) : "r"(a));
    return d;
}
__device__ __forceinline__ uint32_t pack_bf16(float lo, float hi) {
    uint32_t r;
    asm("cvt.rn.bf16x2.f32 %0, %1, %2;" : "=r"(r) : "f"(hi), "f"(lo));
    return r;
}
__device__ __forceinline__ uint32_t bf16_mul(uint32_t a, uint32_t b) {
    uint32_t d;
    asm("mul.rn.bf16x2 %0, %1, %2;" : "=r"(d) : "r"(a), "r"(b));
    return d;
}
__device__ __forceinline__ uint32_t bf16_add(uint32_t a, uint32_t b) {
    uint32_t d;
    asm("add.rn.bf16x2 %0, %1, %2;" : "=r"(d) : "r"(a), "r"(b));
    return d;
}

__device__ __forceinline__ float bf16_round(float x) { return __bfloat162float(__float2bfloat16_rn(x)); }
__device__ __forceinline__ float bf_lo(uint32_t w) { return __uint_as_float(w << 16); }
__device__ __forceinline__ float bf_hi(uint32_t w) { return __uint_as_float(w & 0xFFFF0000u); }
__device__ __forceinline__ void bar_sync(int id, int n) { asm volatile("bar.sync %0, %1;" ::"r"(id), "r"(n) : "memory"); }
__device__ __forceinline__ void bar_sync_keep(int id, int n, uint32_t a, uint32_t b) {
    asm volatile("bar.sync %0, %1; // %2 %3" ::"r"(id), "r"(n), "r"(a), "r"(b) : "memory");
}
__device__ __forceinline__ bool bar_red_or(int id, int n, bool p) {
    uint32_t r;
    asm volatile("{.reg .pred p, q; setp.ne.u32 p, %3, 0; bar.red.or.pred q, %1, %2, p; selp.u32 %0, 1, 0, q;}" : "=r"(r) : "r"(id), "r"(n), "r"((uint32_t)p) : "memory");
    return r != 0;
}
__device__ __forceinline__ void bar_arrive(int id, int n) { asm volatile("bar.arrive %0, %1;" ::"r"(id), "r"(n) : "memory"); }
__device__ __forceinline__ void cp_async16(uint32_t dst, const void* src) {
    asm volatile("cp.async.cg.shared.global [%0], [%1], 16;" ::"r"(dst), "l"(src) : "memory");
}
__device__ __forceinline__ void cp_commit() { asm volatile("cp.async.commit_group;" ::: "memory"); }
template <int N> __device__ __forceinline__ void cp_wait() { asm volatile("cp.async.wait_group %0;" ::"n"(N) : "memory"); }
__device__ __forceinline__ uint4 ld_relaxed_v4(const void* p) {
    uint4 v;
    asm volatile("ld.relaxed.gpu.global.v4.u32 {%0,%1,%2,%3}, [%4];" : "=r"(v.x), "=r"(v.y), "=r"(v.z), "=r"(v.w) : "l"(p) : "memory");
    return v;
}
__device__ __forceinline__ void st_relaxed_u32(void* p, uint32_t v) { asm volatile("st.relaxed.gpu.global.u32 [%0], %1;" ::"l"(p), "r"(v) : "memory"); }
__device__ __forceinline__ void st_relaxed_v2(void* p, uint32_t a, uint32_t b) {
    asm volatile("st.relaxed.gpu.global.v2.u32 [%0], {%1,%2};" ::"l"(p), "r"(a), "r"(b) : "memory");
}
__device__ __forceinline__ void sts128(uint32_t a, uint4 v) {
    asm volatile("st.shared.v4.u32 [%0], {%1,%2,%3,%4};" ::"r"(a), "r"(v.x), "r"(v.y), "r"(v.z), "r"(v.w) : "memory");
}
__device__ __forceinline__ uint4 lds128(uint32_t a) {
    uint4 v;
    asm volatile("ld.shared.v4.u32 {%0,%1,%2,%3}, [%4];" : "=r"(v.x), "=r"(v.y), "=r"(v.z), "=r"(v.w) : "r"(a) : "memory");
    return v;
}
__device__ __forceinline__ void sts32(uint32_t a, uint32_t v) { asm volatile("st.shared.u32 [%0], %1;" ::"r"(a), "r"(v) : "memory"); }
__device__ __forceinline__ uint32_t lds32(uint32_t a) {
    uint32_t v;
    asm volatile("ld.shared.u32 %0, [%1];" : "=r"(v) : "r"(a) : "memory");
    return v;
}
__device__ __forceinline__ void mbar_init(uint32_t a, uint32_t c) { asm volatile("mbarrier.init.shared::cta.b64 [%0], %1;" ::"r"(a), "r"(c) : "memory"); }
__device__ __forceinline__ void mbar_expect_tx(uint32_t a, uint32_t bytes) {
    asm volatile("mbarrier.arrive.expect_tx.shared::cta.b64 _, [%0], %1;" ::"r"(a), "r"(bytes) : "memory");
}
__device__ __forceinline__ void mbar_arrive(uint32_t a) { asm volatile("mbarrier.arrive.shared::cta.b64 _, [%0];" ::"r"(a) : "memory"); }
__device__ __forceinline__ void mbar_wait(uint32_t a, uint32_t parity) {
    asm volatile("{.reg .pred p; .reg .u32 c;\n"
                 "mov.u32 c, 0;\n"
                 "MBW_LOOP:\n"
                 "add.u32 c, c, 1;\n"
                 "setp.gt.u32 p, c, 0x10000;\n"
                 "@!p mbarrier.try_wait.parity.shared::cta.b64 p, [%0], %1;\n"
                 "@!p bra.uni MBW_LOOP;}" ::"r"(a), "r"(parity) : "memory");
}
__device__ __forceinline__ void mbar_wait_w(uint32_t a, uint32_t parity) {
    asm volatile("{.reg .pred p; .reg .u32 c;\n"
                 "mov.u32 c, 0;\n"
                 "MBW_LOOP:\n"
                 "add.u32 c, c, 1;\n"
                 "setp.gt.u32 p, c, 0x10000;\n"
                 "@!p mbarrier.try_wait.parity.shared::cta.b64 p, [%0], %1;\n"
                 "vote.sync.all.pred p, p, 0xFFFFFFFF;\n"
                 "@!p bra.uni MBW_LOOP;}" ::"r"(a), "r"(parity) : "memory");
}
__device__ __forceinline__ void mbar_expect_tx_if0(uint32_t sel, uint32_t a, uint32_t bytes) {
    asm volatile("{.reg .pred p; setp.eq.u32 p, %2, 0; @p mbarrier.arrive.expect_tx.shared::cta.b64 _, [%0], %1;}" ::"r"(a), "r"(bytes), "r"(sel) : "memory");
}
__device__ __forceinline__ void mbar_arrive_if0(uint32_t sel, uint32_t a) {
    asm volatile("{.reg .pred p; setp.eq.u32 p, %1, 0; @p mbarrier.arrive.shared::cta.b64 _, [%0];}" ::"r"(a), "r"(sel) : "memory");
}
__device__ __forceinline__ void bulk_load(uint32_t dst, const void* src, uint32_t bytes, uint32_t bar) {
    asm volatile("cp.async.bulk.shared::cluster.global.mbarrier::complete_tx::bytes [%0], [%1], %2, [%3];" ::"r"(dst), "l"(src), "r"(bytes), "r"(bar) : "memory");
}
__device__ __forceinline__ void tma_load_2d(uint32_t dst, const CUtensorMap* map, int c0, int c1, uint32_t bar) {
    asm volatile("cp.async.bulk.tensor.2d.shared::cluster.global.mbarrier::complete_tx::bytes [%0], [%1, {%3, %4}], [%2];"
                 ::"r"(dst), "l"(map), "r"(bar), "r"(c0), "r"(c1) : "memory");
}
__device__ __forceinline__ void tma_load_2d_both(uint32_t dst, const CUtensorMap* map, int c0, int c1, uint32_t bar) {
    asm volatile("cp.async.bulk.tensor.2d.shared::cluster.global.mbarrier::complete_tx::bytes.multicast::cluster [%0], [%1, {%3, %4}], [%2], %5;"
                 ::"r"(dst), "l"(map), "r"(bar), "r"(c0), "r"(c1), "h"((uint16_t)3) : "memory");
}
__device__ __forceinline__ uint64_t policy_evict_first() {
    uint64_t p;
    asm("createpolicy.fractional.L2::evict_first.b64 %0, 1.0;" : "=l"(p));
    return p;
}
__device__ __forceinline__ uint64_t policy_evict_normal() {
    uint64_t p;
    asm("createpolicy.fractional.L2::evict_normal.b64 %0, 1.0;" : "=l"(p));
    return p;
}
__device__ __forceinline__ void tma_load_2d(uint32_t dst, const CUtensorMap* map, int c0, int c1, uint32_t bar, uint64_t pol) {
    asm volatile("cp.async.bulk.tensor.2d.shared::cluster.global.mbarrier::complete_tx::bytes.L2::cache_hint [%0], [%1, {%3, %4}], [%2], %5;"
                 ::"r"(dst), "l"(map), "r"(bar), "r"(c0), "r"(c1), "l"(pol) : "memory");
}
__device__ __forceinline__ uint4 ldg128(const void* p, uint64_t pol) {
    uint4 v;
    asm("ld.global.nc.L2::cache_hint.v4.u32 {%0,%1,%2,%3}, [%4], %5;" : "=r"(v.x), "=r"(v.y), "=r"(v.z), "=r"(v.w) : "l"(p), "l"(pol));
    return v;
}
__device__ __forceinline__ void stg128(void* p, uint4 v, uint64_t pol) {
    asm volatile("st.global.L2::cache_hint.v4.u32 [%0], {%1,%2,%3,%4}, %5;" ::"l"(p), "r"(v.x), "r"(v.y), "r"(v.z), "r"(v.w), "l"(pol) : "memory");
}
__device__ __forceinline__ void tma_store_2d(const CUtensorMap* map, uint32_t src, int c0, int c1) {
    asm volatile("cp.async.bulk.tensor.2d.global.shared::cta.bulk_group [%0, {%2, %3}], [%1];" ::"l"(map), "r"(src), "r"(c0), "r"(c1) : "memory");
}
__device__ __forceinline__ char* make_ptr(uint32_t lo, uint32_t hi) {
    uint64_t p;
    asm("mov.b64 %0, {%1, %2};" : "=l"(p) : "r"(lo), "r"(hi));
    return reinterpret_cast<char*>(p);
}
__device__ __forceinline__ uint64_t make_desc(uint32_t saddr, uint32_t lbo, uint32_t sbo) {
    return (uint64_t)((saddr & 0x3FFFF) >> 4) | ((uint64_t)((lbo >> 4) & 0x3FFF) << 16) | ((uint64_t)((sbo >> 4) & 0x3FFF) << 32) | ((uint64_t)1 << 62);
}
__device__ __forceinline__ void wg_fence() { asm volatile("wgmma.fence.sync.aligned;" ::: "memory"); }
__device__ __forceinline__ void wg_commit() { asm volatile("wgmma.commit_group.sync.aligned;" ::: "memory"); }
template <int N> __device__ __forceinline__ void wg_wait() { asm volatile("wgmma.wait_group.sync.aligned %0;" ::"n"(N) : "memory"); }

#define R4(b) "+f"(d[b + 0]), "+f"(d[b + 1]), "+f"(d[b + 2]), "+f"(d[b + 3])
#define R16(b) R4(b), R4(b + 4), R4(b + 8), R4(b + 12)
template <int N> __device__ __forceinline__ void wgmma_proj(float (&d)[N / 2], uint64_t da, uint64_t db) {
    if constexpr (N == 96)
        asm volatile("wgmma.mma_async.sync.aligned.m64n96k16.f32.bf16.bf16 {"
            "%0,%1,%2,%3,%4,%5,%6,%7,%8,%9,%10,%11,%12,%13,%14,%15,%16,%17,%18,%19,%20,%21,%22,%23,%24,%25,%26,%27,%28,%29,%30,%31,%32,%33,%34,%35,%36,%37,%38,%39,"
            "%40,%41,%42,%43,%44,%45,%46,%47"
            "}, %48, %49, 1, 1, 1, 1, 0;" : R16(0), R16(16), R16(32) : "l"(da), "l"(db));
    if constexpr (N == 128)
        asm volatile("wgmma.mma_async.sync.aligned.m64n128k16.f32.bf16.bf16 {"
            "%0,%1,%2,%3,%4,%5,%6,%7,%8,%9,%10,%11,%12,%13,%14,%15,%16,%17,%18,%19,%20,%21,%22,%23,%24,%25,%26,%27,%28,%29,%30,%31,%32,%33,%34,%35,%36,%37,%38,%39,"
            "%40,%41,%42,%43,%44,%45,%46,%47,%48,%49,%50,%51,%52,%53,%54,%55,%56,%57,%58,%59,%60,%61,%62,%63"
            "}, %64, %65, 1, 1, 1, 1, 0;" : R16(0), R16(16), R16(32), R16(48) : "l"(da), "l"(db));
    if constexpr (N == 256)
        asm volatile("wgmma.mma_async.sync.aligned.m64n256k16.f32.bf16.bf16 {"
            "%0,%1,%2,%3,%4,%5,%6,%7,%8,%9,%10,%11,%12,%13,%14,%15,%16,%17,%18,%19,%20,%21,%22,%23,%24,%25,%26,%27,%28,%29,%30,%31,%32,%33,%34,%35,%36,%37,%38,%39,"
            "%40,%41,%42,%43,%44,%45,%46,%47,%48,%49,%50,%51,%52,%53,%54,%55,%56,%57,%58,%59,%60,%61,%62,%63,%64,%65,%66,%67,%68,%69,%70,%71,%72,%73,%74,%75,%76,%7"
            "7,%78,%79,%80,%81,%82,%83,%84,%85,%86,%87,%88,%89,%90,%91,%92,%93,%94,%95,%96,%97,%98,%99,%100,%101,%102,%103,%104,%105,%106,%107,%108,%109,%110,%111,"
            "%112,%113,%114,%115,%116,%117,%118,%119,%120,%121,%122,%123,%124,%125,%126,%127"
            "}, %128, %129, 1, 1, 1, 1, 0;" : R16(0), R16(16), R16(32), R16(48), R16(64), R16(80), R16(96), R16(112) : "l"(da), "l"(db));
}

__device__ __forceinline__ void wgmma_rs32(float (&d)[16], const uint32_t (&a)[4], uint64_t db, bool acc) {
    asm volatile(
        "{.reg .pred p; setp.ne.b32 p, %21, 0;\n"
        "wgmma.mma_async.sync.aligned.m64n32k16.f32.bf16.bf16 {%0,%1,%2,%3,%4,%5,%6,%7,%8,%9,%10,%11,%12,%13,%14,%15}, {%16,%17,%18,%19}, %20, p, 1, 1, 0;}"
        : R16(0) : "r"(a[0]), "r"(a[1]), "r"(a[2]), "r"(a[3]), "l"(db), "n"(1) );
}
__device__ __forceinline__ void wgmma_rs32_first(float (&d)[16], const uint32_t (&a)[4], uint64_t db) {
    asm volatile(
        "{.reg .pred p; setp.ne.b32 p, %21, 0;\n"
        "wgmma.mma_async.sync.aligned.m64n32k16.f32.bf16.bf16 {%0,%1,%2,%3,%4,%5,%6,%7,%8,%9,%10,%11,%12,%13,%14,%15}, {%16,%17,%18,%19}, %20, p, 1, 1, 0;}"
        : R16(0) : "r"(a[0]), "r"(a[1]), "r"(a[2]), "r"(a[3]), "l"(db), "n"(0) );
}
__device__ __forceinline__ void wgmma_ss32(float (&d)[16], uint64_t da, uint64_t db) {
    asm volatile(
        "wgmma.mma_async.sync.aligned.m64n32k16.f32.bf16.bf16 {%0,%1,%2,%3,%4,%5,%6,%7,%8,%9,%10,%11,%12,%13,%14,%15}, %16, %17, 1, 1, 1, 1, 0;"
        : R16(0) : "l"(da), "l"(db));
}
template <int OFF, int ACC> __device__ __forceinline__ void wgmma_rs32u(float (&d)[16], const uint32_t (&a)[4], uint32_t lo) {
    asm volatile(
        "{.reg .pred p; .reg .b32 l; .reg .b64 e; setp.ne.b32 p, %22, 0; add.u32 l, %20, %21; mov.b64 e, {l, 0x40000040};\n"
        "wgmma.mma_async.sync.aligned.m64n32k16.f32.bf16.bf16 {%0,%1,%2,%3,%4,%5,%6,%7,%8,%9,%10,%11,%12,%13,%14,%15}, {%16,%17,%18,%19}, e, p, 1, 1, 0;}"
        : R16(0) : "r"(a[0]), "r"(a[1]), "r"(a[2]), "r"(a[3]), "r"(lo), "n"(OFF), "n"(ACC));
}
template <int OFF> __device__ __forceinline__ void wgmma_ss32u(float (&d)[16], uint64_t da, uint32_t lo) {
    asm volatile(
        "{.reg .b32 l; .reg .b64 e; add.u32 l, %17, %18; mov.b64 e, {l, 0x40000040};\n"
        "wgmma.mma_async.sync.aligned.m64n32k16.f32.bf16.bf16 {%0,%1,%2,%3,%4,%5,%6,%7,%8,%9,%10,%11,%12,%13,%14,%15}, %16, e, 1, 1, 1, 1, 0;}"
        : R16(0) : "l"(da), "r"(lo), "n"(OFF));
}
template <int K0, int K1, class F> __device__ __forceinline__ void static_for(F f) {
    if constexpr (K0 < K1) { f(std::integral_constant<int, K0>()); static_for<K0 + 1, K1>(f); }
}
__device__ __forceinline__ void st_async4(uint32_t a, float x, float y, float z, float w, uint32_t bar) {
    asm volatile("st.async.weak.shared::cluster.mbarrier::complete_tx::bytes.v4.f32 [%0], {%1,%2,%3,%4}, [%5];" ::"r"(a), "f"(x), "f"(y), "f"(z), "f"(w), "r"(bar) : "memory");
}
__device__ __forceinline__ void st_async2(uint32_t a, float x, float y, uint32_t bar) {
    asm volatile("st.async.weak.shared::cluster.mbarrier::complete_tx::bytes.v2.f32 [%0], {%1,%2}, [%3];" ::"r"(a), "f"(x), "f"(y), "r"(bar) : "memory");
}
__device__ __forceinline__ void st_async1(uint32_t a, uint32_t x, uint32_t bar) {
    asm volatile("st.async.weak.shared::cluster.mbarrier::complete_tx::bytes.b32 [%0], %1, [%2];" ::"r"(a), "r"(x), "r"(bar) : "memory");
}
__device__ __forceinline__ void stsm4t(uint32_t a, uint32_t r0, uint32_t r1, uint32_t r2, uint32_t r3) {
    asm volatile("stmatrix.sync.aligned.m8n8.x4.trans.shared.b16 [%0], {%1,%2,%3,%4};" ::"r"(a), "r"(r0), "r"(r1), "r"(r2), "r"(r3) : "memory");
}
__device__ __forceinline__ void ldsm4t(uint32_t (&r)[4], uint32_t a) { ldsm4t(r[0], r[1], r[2], r[3], a); }
__device__ __forceinline__ void ldsm4(uint32_t (&r)[4], uint32_t a) { ldsm4(r[0], r[1], r[2], r[3], a); }
__device__ __forceinline__ void mma16816(float (&d)[4], const uint32_t (&a)[4], uint32_t b0, uint32_t b1) { mma16816(d, a[0], a[1], a[2], a[3], b0, b1); }
__device__ __forceinline__ void sched_fence(uint32_t v) {
    asm volatile("{.reg .pred p; setp.ne.u32 p, %0, 0xFFFFFFFF; vote.sync.all.pred p, p, 0xFFFFFFFF; @p bra.uni SF_OK; exit; SF_OK:}" ::"r"(v) : "memory");
}
__device__ __forceinline__ void mma16816v(float (&d)[4], const uint32_t (&a)[4], uint32_t b0, uint32_t b1) {
    asm volatile("mma.sync.aligned.m16n8k16.row.col.f32.bf16.bf16.f32 {%0,%1,%2,%3},{%4,%5,%6,%7},{%8,%9},{%0,%1,%2,%3};"
                 : "+f"(d[0]), "+f"(d[1]), "+f"(d[2]), "+f"(d[3]) : "r"(a[0]), "r"(a[1]), "r"(a[2]), "r"(a[3]), "r"(b0), "r"(b1));
}
__device__ __forceinline__ uint32_t uniform(uint32_t v) { return __reduce_max_sync(~0u, v); }

#define WPRE 0
#define G2_X 0
#define G2_K 4
#define FIN_SO 0
#define KROT 0
#define WFIRST 0
template <int NT, int STAGES> struct ProjCfg {
    static constexpr int STAGE_BYTES = 16384 + NT * 128;
    static constexpr int EPI = NT == 256 ? STAGES * STAGE_BYTES : 0;
    static constexpr int BARS = 229376 + (NT == 256 ? 192 : 0);
    static_assert(STAGES * STAGE_BYTES <= 229376 && EPI + NT * 256 <= 229376 && STAGES <= 12, "smem");
};
constexpr int PROJ_ROLE = 229376 + 384, PROJ_SMEM = PROJ_ROLE + 16;
__device__ __forceinline__ unsigned claim_pair(unsigned* reg) {
    unsigned smid, ncl = gridDim.x >> 1;
    asm volatile("mov.u32 %0, %%smid;" : "=r"(smid));
    const unsigned r = __vminu2(g_cls[smid], g_cls[smid ^ 1]), c = (r & 0xFFFF) > (r >> 16);
    unsigned n = atomicAdd(reg, c ? 0x10000u : 1u);
    const unsigned i = c ? n >> 16 : n & 0xFFFF, order = ((n >> 16) + (n & 0xFFFF)) << 8;
    if (i < 32) return c * 32 + i + order;
    for (int guard = 0; guard < (1 << 20); guard++) {
        asm volatile("ld.relaxed.gpu.global.u32 %0, [%1];" : "=r"(n) : "l"(reg) : "memory");
        if ((n >> 16) + (n & 0xFFFF) >= ncl) break;
    }
    const unsigned k = (c ? n & 0xFFFF : n >> 16) + i - 32;
    return (k < 32 ? (c ^ 1) * 32 + k : 64) + order;
}
template <int NT, int STAGES> __device__ __forceinline__ void proj_init(uint32_t sb) {
    for (int i = 0; i < STAGES; i++) { mbar_init(sb + ProjCfg<NT, STAGES>::BARS + 8 * i, 1); mbar_init(sb + ProjCfg<NT, STAGES>::BARS + 8 * (STAGES + i), 16); }
    asm volatile("fence.mbarrier_init.release.cluster;" ::: "memory");
}
template <int NT, int STAGES, bool SHARE_O, class T, class R>
__device__ __forceinline__ void proj_tiles(uint32_t sb, int warp, uint32_t rank, int ntiles, const CUtensorMap* mapW, const CUtensorMap* mapO,
                                           const CUtensorMap* mapOut, T tile, R ready, int rot = 0) {
    using Cfg = ProjCfg<NT, STAGES>;
    const uint32_t bars = sb + Cfg::BARS;
    const int lane = threadIdx.x & 31;
    if (warp == 8) {
        int st = 0; uint32_t ph = 1;
        for (int i = 0; i < ntiles; i++) {
            int col, tok;
            tile(i, col, tok);
            constexpr bool PRE = WPRE && !SHARE_O;
            if (PRE && lane == 0)
                for (int kb = 0; kb < STAGES; kb++) {
                    mbar_expect_tx(bars + 8 * kb, Cfg::STAGE_BYTES);
                    tma_load_2d_both(sb + kb * Cfg::STAGE_BYTES + rank * 8192, mapW, col + rank * 64, kb * 64, bars + 8 * kb);
                }
            ready(i);
            if (lane == 0) {
                if (PRE) {
                    for (int kb = 0; kb < STAGES; kb++) tma_load_2d(sb + kb * Cfg::STAGE_BYTES + 16384, mapO, kb * 64, tok, bars + 8 * kb);
                    ph = 0;
                }
                for (int kb = PRE ? STAGES : 0; kb < HD / 64; kb++) {
                    mbar_wait(bars + 8 * (STAGES + st), ph);
                    const uint32_t full = bars + 8 * st, sa = sb + st * Cfg::STAGE_BYTES;
                    mbar_expect_tx(full, SHARE_O ? Cfg::STAGE_BYTES : G2_X == 1 ? 16384 : G2_X == 2 ? NT * 128 : Cfg::STAGE_BYTES);
                    if (SHARE_O) {
                        tma_load_2d(sa, mapW, col, kb * 64, full);
                        tma_load_2d(sa + 8192, mapW, col + 64, kb * 64, full);
                        tma_load_2d_both(sa + 16384 + rank * (NT * 64), mapO, kb * 64, tok + rank * (NT / 2), full);
                    } else {
                        const int k0 = ((kb + rot) & 63) * 64;
                        if (WFIRST) tma_load_2d_both(sa + rank * 8192, mapW, col + rank * 64, k0, full);
                        if (G2_X != 1) tma_load_2d(sa + 16384, mapO, k0, G2_X == 3 ? tok & 511 : tok, full);
                        if (!WFIRST && G2_X != 2) tma_load_2d_both(sa + rank * 8192, mapW, col + rank * 64, k0, full);
                    }
                    if (++st == STAGES) { st = 0; ph ^= 1; }
                }
            }
            __syncwarp();
        }
    } else if (warp < 8) {
        const int wg = warp >> 2;
        uint32_t peer_empty;
        asm volatile("mapa.shared::cluster.u32 %0, %1, %2;" : "=r"(peer_empty) : "r"(bars + 8 * STAGES), "r"(rank ^ 1));
        auto release = [&](int stg) {
            if (lane == 0) {
                mbar_arrive(bars + 8 * (STAGES + stg));
                asm volatile("mbarrier.arrive.shared::cluster.b64 _, [%0];" ::"r"(peer_empty + 8 * stg) : "memory");
            }
        };
        const uint32_t ew = sb + Cfg::EPI + wg * (NT * 128);
        int st = 0; uint32_t ph = 0;
        for (int i = 0; i < ntiles; i++) {
            int col, tok;
            tile(i, col, tok);
            float d[NT / 2];
#pragma unroll
            for (int r = 0; r < NT / 2; r++) d[r] = 0.f;
            int prev = -1;
            for (int kb = 0; kb < HD / 64; kb++) {
                mbar_wait(bars + 8 * st, ph);
                const uint32_t sa = sb + st * Cfg::STAGE_BYTES;
                const uint64_t da = make_desc(sa + wg * 8192, 16, 1024), db = make_desc(sa + 16384, 16, 1024);
                wg_fence();
#pragma unroll
                for (int k = 0; k < (NT == 256 ? 4 : G2_K); k++) wgmma_proj<NT>(d, da + k * 128, db + k * 2);
                wg_commit();
                if (prev >= 0) { wg_wait<1>(); release(prev); }
                prev = st;
                if (++st == STAGES) { st = 0; ph ^= 1; }
            }
            wg_wait<0>();
            release(prev);
            if ((warp & 3) == 0 && lane == 0) asm volatile("cp.async.bulk.wait_group.read 0;" ::: "memory");
            if (Cfg::EPI) bar_sync(1 + wg, 128); else bar_sync(3, 256);
            const uint32_t ea = ew + ((lane >> 4) * 8 + (lane & 7)) * 128 + ((((warp & 3) * 2 + ((lane >> 3) & 1)) ^ (lane & 7)) * 16);
#pragma unroll
            for (int r = 0; r < NT / 16; r++)
                stsm4t(ea + r * 2048, pack_bf16(d[8 * r], d[8 * r + 1]), pack_bf16(d[8 * r + 2], d[8 * r + 3]), pack_bf16(d[8 * r + 4], d[8 * r + 5]), pack_bf16(d[8 * r + 6], d[8 * r + 7]));
            asm volatile("fence.proxy.async.shared::cta;" ::: "memory");
            bar_sync(1 + wg, 128);
            if ((warp & 3) == 0 && lane == 0) {
                tma_store_2d(mapOut, ew, col + wg * 64, tok);
                asm volatile("cp.async.bulk.commit_group;" ::: "memory");
            }
        }
        if ((warp & 3) == 0 && lane == 0) asm volatile("cp.async.bulk.wait_group 0;" ::: "memory");
    }
    __syncwarp();
}
constexpr int EARLY_NT = 256, EARLY_STAGES = 3;

template <int NT, int STAGES>
__global__ void __cluster_dims__(2, 1, 1) __launch_bounds__(288, 1)
proj_kernel(const __grid_constant__ CUtensorMap mapW, const __grid_constant__ CUtensorMap mapO, const __grid_constant__ CUtensorMap mapOut,
            const __grid_constant__ CUtensorMap mapOE, const __grid_constant__ CUtensorMap mapOutE) {
    KT_START(3);
    extern __shared__ __align__(1024) uint8_t smem_proj[];
    const uint32_t sb = smem_u32(smem_proj), role = sb + PROJ_ROLE;
    if (sb & 1023) __trap();
    const uint32_t rank = blockIdx.x & 1;
    const int warp = threadIdx.x >> 5;
    if (threadIdx.x == 0) {
        proj_init<NT, STAGES>(sb);
        proj_init<EARLY_NT, EARLY_STAGES>(sb);
        if (rank == 0) {
            const unsigned p = claim_pair(g_reg + 2);
            uint32_t ra;
            asm volatile("mapa.shared::cluster.u32 %0, %1, 1;" : "=r"(ra) : "r"(role));
            asm volatile("st.shared::cluster.u32 [%0], %1;" ::"r"(ra), "r"(p) : "memory");
            sts32(role, p);
        }
    }
    __syncthreads();
    asm volatile("barrier.cluster.arrive.release.aligned; barrier.cluster.wait.acquire.aligned;" ::: "memory");
    const int p = lds32(role) & 255, order = lds32(role) >> 8;
    if (NT == 96 && order < 2) {
        proj_tiles<EARLY_NT, EARLY_STAGES, true>(sb, warp, rank, 4, &mapW, &mapOE, &mapOutE,
            [&](int i, int& col, int& tok) { col = ((i & 1) * 4 + order * 2 + rank) * 128; tok = (i >> 1) * EARLY_NT; },
            [&](int i) {
                const unsigned need = 8 * (i >> 1) + 8 + 3;
                for (int guard = 0; guard < (1 << 16); guard++) {
                    const uint4 f = ld_relaxed_v4(g_xflag + (threadIdx.x & 31) * 4);
                    if (__all_sync(~0u, min(min(f.x, f.y), min(f.z, f.w)) >= need)) break;
                    __nanosleep(1000);
                }
                asm volatile("fence.acq_rel.gpu; fence.proxy.async.global;" ::: "memory");
            });
        __syncthreads();
        asm volatile("barrier.cluster.arrive.relaxed.aligned; barrier.cluster.wait.aligned;" ::: "memory");
    }
    if (p >= 64) return;
    proj_tiles<NT, STAGES, false>(sb, warp, rank, 1, &mapW, &mapO, &mapOut,
                                  [&](int, int& col, int& tok) { col = (p & 7) * 128; tok = S_LEN - 16 * NT + ((p >> 3) * 2 + rank) * NT; },
                                  [&](int) { wait_prerequisites(); }, KROT == 0 ? 0 : KROT == 1 ? (p & 7) * 8 : KROT == 2 ? (p >> 3) * 8 : KROT == 3 ? ((p & 7) + (p >> 3)) * 8 : (p >> 5) * 32);
    KT_END(3);
    asm volatile("barrier.cluster.arrive.relaxed; barrier.cluster.wait;" ::: "memory");
}

#define WO_RF1 6
constexpr int SM_KV = 0, KV_BYTES = 18432;
constexpr int SM_XT = 2 * KV_BYTES;
constexpr int SM_STG = SM_XT + 65536;
constexpr int SM_Z = SM_STG + 6144;
constexpr int SM_RT = SM_Z + 8192;
constexpr int SM_QKV = SM_RT + 12288;
constexpr int SM_R1 = SM_QKV + 6144;
constexpr int SM_R2 = SM_R1 + 2048;
constexpr int SM_R3 = SM_R2 + 1024;
constexpr int SM_O = SM_R3 + 2048;
constexpr int SM_S = SM_O + 2048;
constexpr int SM_INV = SM_S + 1536;
constexpr int SM_TO = SM_R3;
constexpr int SM_WORK_END = SM_S + 2048;
constexpr int STG_QK = 0, STG_V = 98304;
constexpr int SM_WO1 = SM_WORK_END - WO_RF1 * 2048;
constexpr int STG_WO = SM_WO1 - 16384;
constexpr int SM_WQK = (SM_WO1 + 16384 > STG_V + 49152) ? SM_WO1 + 16384 : STG_V + 49152;
constexpr int SM_WV = SM_WQK + 32768;
constexpr int SM_WO2 = SM_WV + 16384;
constexpr int SM_BARS = SM_WO2 + 32768;
enum { MB_W0 = SM_BARS, MB_W1 = SM_BARS + 8, MB_W2 = SM_BARS + 16, MB_W3 = SM_BARS + 24, MB_XT = SM_BARS + 32  , MB_KV = SM_BARS + 48  ,
       MB_R3 = SM_BARS + 64, MB_R1 = SM_BARS + 72, MB_R2 = SM_BARS + 80, MB_RT0 = SM_BARS + 88, MB_RT1 = SM_BARS + 96, MB_FREE = SM_BARS + 104,
       MB_P = SM_BARS + 112, MB_V = SM_BARS + 120, MB_STG = SM_BARS + 128, SM_ROLE = SM_BARS + 136 };
constexpr int CHAIN_SMEM = SM_ROLE + 8;
static_assert(SM_WORK_END % 1024 == 0 && STG_WO >= STG_V, "work area");
static_assert(CHAIN_SMEM <= 232448 && WO_RF1 >= 6, "smem");

#define DLY_X 250
#define DLY_V 0
#define DLY_Y 250
#define DLY_Z 300
#define Q3_AT 9
#define NA 7
#define NP2 6
#define P2_FENCE 0
#define SPLIT 10
#define TA0 16
#define SENT_EARLY 1
#define Y_CHAIN 1
#define EF_W 1
#define XFLIP 0
#define YFLIP 0
#define ZFLIP 1
#define OFENCE 2
#define REG_A 240
#define REG_B 216
#define REG_C (3 * 168 - REG_A - REG_B)

enum { BAR_Y, BAR_MEM, BAR_PUB, BAR_QK, BAR_S, BAR_O, BAR_SENT, BAR_COMM, BAR_PUBV, BAR_PV, BAR_PDONE, BAR_VP, BAR_ZP, BAR_PRO, BAR_O2, BAR_SV,
       BAR_V = BAR_PV, BAR_SENTC = BAR_PDONE, BAR_Q3 = BAR_PRO, BAR_INV = BAR_PRO };

__device__ __forceinline__ uint32_t umax4(const uint4& v) { return max(max(v.x, v.y), max(v.z, v.w)); }
__device__ __forceinline__ unsigned gtime() { unsigned t; asm volatile("mov.u32 %0, %%globaltimer_lo;" : "=r"(t)::"memory"); return t; }
__device__ __forceinline__ unsigned clock32() { unsigned t; asm volatile("mov.u32 %0, %%clock;" : "=r"(t)::"memory"); return t; }
__device__ __forceinline__ void spin_cycles(int d) {
    if (d > 0) { const unsigned c0 = clock32(); while (clock32() - c0 < (unsigned)d) {} }
}
__device__ __forceinline__ float ex2_approx(float x) { float y; asm("ex2.approx.ftz.f32 %0, %1;" : "=f"(y) : "f"(x)); return y; }
__device__ __forceinline__ float rcp_approx(float x) { float y; asm("rcp.approx.ftz.f32 %0, %1;" : "=f"(y) : "f"(x)); return y; }
__device__ __forceinline__ void st_sent(const void* p) { asm volatile("st.relaxed.gpu.global.v4.u32 [%0], {%1,%1,%1,%1};" ::"l"(p), "r"(SENT) : "memory"); }
#define POLL_LD(p, a, b, c, d, addr) "@" p " ld.relaxed.gpu.global.v4.u32 {" a "," b "," c "," d "}, [" addr "];\n"
#define POLL_CK(p, a, b, c, d) "max.u32 m, " a "," b "; max.u32 n, " c "," d "; max.u32 m, m, n; setp.eq.u32 " p ", m, 0xFFFFFFFF;\n"
#define POLL_IO(v) "+r"(v.x), "+r"(v.y), "+r"(v.z), "+r"(v.w)
__device__ __forceinline__ void poll_init(uint4& v) { v = make_uint4(SENT, SENT, SENT, SENT); asm volatile("" : POLL_IO(v)); }
__device__ __forceinline__ int poll2(uint4 (&v)[2], const char* a) {
    int c = 0;
    asm volatile("{.reg .pred p0, p1, p; .reg .u32 m, n;\n"
                 "setp.eq.u32 p0, %8, 0; setp.eq.u32 p1, %8, 0;\n"
                 "POLL_LOOP:\n"
                 POLL_LD("p0", "%0", "%1", "%2", "%3", "%9") POLL_LD("p1", "%4", "%5", "%6", "%7", "%9+512")
                 "add.u32 %8, %8, 1;\n"
                 POLL_CK("p0", "%0", "%1", "%2", "%3") POLL_CK("p1", "%4", "%5", "%6", "%7")
                 "or.pred p, p0, p1; setp.lt.and.u32 p, %8, 0x10000, p; vote.sync.any.pred p, p, 0xFFFFFFFF;\n"
                 "@p bra.uni POLL_LOOP;}" : POLL_IO(v[0]), POLL_IO(v[1]), "+r"(c) : "l"(a) : "memory");
    return c;
}
__device__ __forceinline__ int poll4(uint4 (&v)[4], const char* a) {
    int c = 0;
    asm volatile("{.reg .pred p0, p1, p2, p3, p; .reg .u32 m, n;\n"
                 "setp.eq.u32 p0, %16, 0; setp.eq.u32 p1, %16, 0; setp.eq.u32 p2, %16, 0; setp.eq.u32 p3, %16, 0;\n"
                 "POLL_LOOP:\n"
                 POLL_LD("p0", "%0", "%1", "%2", "%3", "%17") POLL_LD("p1", "%4", "%5", "%6", "%7", "%17+2048")
                 POLL_LD("p2", "%8", "%9", "%10", "%11", "%17+4096") POLL_LD("p3", "%12", "%13", "%14", "%15", "%17+6144")
                 "add.u32 %16, %16, 1;\n"
                 POLL_CK("p0", "%0", "%1", "%2", "%3") POLL_CK("p1", "%4", "%5", "%6", "%7") POLL_CK("p2", "%8", "%9", "%10", "%11") POLL_CK("p3", "%12", "%13", "%14", "%15")
                 "or.pred p, p0, p1; or.pred p, p, p2; or.pred p, p, p3; setp.lt.and.u32 p, %16, 0x10000, p; vote.sync.any.pred p, p, 0xFFFFFFFF;\n"
                 "@p bra.uni POLL_LOOP;}" : POLL_IO(v[0]), POLL_IO(v[1]), POLL_IO(v[2]), POLL_IO(v[3]), "+r"(c) : "l"(a) : "memory");
    return c;
}
__device__ __forceinline__ uint32_t max_bf16x2(uint32_t a, uint32_t b) { uint32_t r; asm("max.bf16x2 %0, %1, %2;" : "=r"(r) : "r"(a), "r"(b)); return r; }
template <class F> __device__ __forceinline__ void softmax40(uint32_t (&pw)[6], uint32_t sa, F mid) {
    const float LOG2E = 1.4426950408889634f;
    uint32_t w[5];
    float e[10];
#pragma unroll
    for (int i = 0; i < 5; i++) w[i] = lds32(sa + i * 128);
    uint32_t m = max_bf16x2(max_bf16x2(max_bf16x2(w[0], w[1]), max_bf16x2(w[2], w[3])), w[4]);
    m = max_bf16x2(m, __shfl_xor_sync(~0u, m, 1));
    m = max_bf16x2(m, __shfl_xor_sync(~0u, m, 2));
    const float mb2 = fmaxf(bf_lo(m), bf_hi(m)) * LOG2E;
#pragma unroll
    for (int i = 0; i < 5; i++) {
        e[2 * i] = ex2_approx(fmaf(bf_lo(w[i]), LOG2E, -mb2));
        e[2 * i + 1] = ex2_approx(fmaf(bf_hi(w[i]), LOG2E, -mb2));
    }
    mid();
#pragma unroll
    for (int i = 0; i < 5; i++) pw[i] = pack_bf16(e[2 * i], e[2 * i + 1]);
    const float sum = (((e[0] + e[1]) + (e[2] + e[3])) + ((e[4] + e[5]) + (e[6] + e[7]))) + (e[8] + e[9]);
    const float hi = bf_hi(__float_as_uint(sum));
    pw[5] = pack_bf16(sum - hi, hi);
}
template <bool NORM, class F> __device__ __forceinline__ void pv32(uint32_t (&w)[4], float (&inv)[2], const uint32_t (&va)[2][2][4], const uint32_t (&vm)[4], const uint32_t (&pw)[6], F mid) {
    float o[2][3][4], t[4] = {0.f, 0.f, 0.f, 0.f};
#pragma unroll
    for (int i = 0; i < 3; i++)
#pragma unroll
        for (int m = 0; m < 2; m++) {
            o[m][i][0] = o[m][i][1] = o[m][i][2] = o[m][i][3] = 0.f;
            if (i < 2) mma16816(o[m][i], va[m][i & 1], pw[2 * i], pw[2 * i + 1]);
            else mma1688(o[m][i], vm[2 * m], vm[2 * m + 1], pw[4]);
        }
    mma1688(t, 0x3F803F80u, 0x3F803F80u, pw[5]);
    mid();
    if (NORM) { inv[0] = rcp_approx(t[0]); inv[1] = rcp_approx(t[1]); }
#pragma unroll
    for (int i = 0; i < 4; i++) {
        const float a = (o[i >> 1][0][2 * (i & 1)] + o[i >> 1][1][2 * (i & 1)]) + o[i >> 1][2][2 * (i & 1)];
        const float b = (o[i >> 1][0][2 * (i & 1) + 1] + o[i >> 1][1][2 * (i & 1) + 1]) + o[i >> 1][2][2 * (i & 1) + 1];
        w[i] = NORM ? pack_bf16(a * inv[0], b * inv[1]) : pack_bf16(a, b);
    }
    if (!NORM) { inv[0] = t[0]; inv[1] = t[1]; }
}
__device__ __forceinline__ uint32_t scale_scores(float a, float b) {
    const float scale = 0.08838834764831845f;
    const uint32_t w = pack_bf16(a, b);
    return pack_bf16(bf_lo(w) * scale, bf_hi(w) * scale);
}

__device__ __forceinline__ uint32_t peer_addr(uint32_t a, uint32_t rank) {
    uint32_t r;
    asm("mapa.shared::cluster.u32 %0, %1, %2;" : "=r"(r) : "r"(a), "r"(rank));
    return r;
}

#define TL(i) do {} while (0)
#define TLB(i) do {} while (0)
#define TLC(i) do {} while (0)

__global__ void __cluster_dims__(2, 1, 1) __launch_bounds__(384, 1)
chain_kernel(const __grid_constant__ CUtensorMap mapX, const __grid_constant__ CUtensorMap mapT32, const __grid_constant__ CUtensorMap mapT16,
             const __grid_constant__ CUtensorMap mapTQ, const __grid_constant__ CUtensorMap mapKV,
             const __grid_constant__ CUtensorMap mapWq, const __grid_constant__ CUtensorMap mapWk, const __grid_constant__ CUtensorMap mapWv,
             const __grid_constant__ CUtensorMap mapWo, const bf16* __restrict__ mem0, char* __restrict__ mbox) {
    KT_START(2);
    extern __shared__ __align__(1024) uint8_t smem_chain[];
    constexpr uint32_t SB0 = 1024;
    if (smem_u32(smem_chain) != (SB0 | ((blockIdx.x & 1) << 24))) __trap();
    const int kh = blockIdx.x & 1;
    if (threadIdx.x == 0) {
        const uint32_t sb = smem_u32(smem_chain);
        for (int i = 0; i < 14; i++) mbar_init(sb + SM_BARS + 8 * i, 1);
        mbar_init(sb + MB_P, 4); mbar_init(sb + MB_V, 4); mbar_init(sb + MB_STG, 8);
        asm volatile("fence.mbarrier_init.release.cluster;" ::: "memory");
        wait_prerequisites();
        launch_dependents();
        if (kh == 0) {
            unsigned p = claim_pair(g_reg) & 255;
            p |= g_reg[1] << 8;
            uint32_t ra;
            asm volatile("mapa.shared::cluster.u32 %0, %1, 1;" : "=r"(ra) : "r"(sb + SM_ROLE));
            asm volatile("st.shared::cluster.u32 [%0], %1;" ::"r"(ra), "r"(p) : "memory");
            sts32(sb + SM_ROLE, p);
        }
    }
    __syncthreads();
    asm volatile("barrier.cluster.arrive.release.aligned; barrier.cluster.wait.acquire.aligned;" ::: "memory");
    const uint32_t rw = uniform(lds32(smem_u32(smem_chain) + SM_ROLE));
    const int pair = rw & 255, yflip = (rw >> 8) ^ YFLIP;
    if (pair >= 64) return;
    if (threadIdx.x == 0) KT_MARK(5);
    const int h = pair >> 1, nh = pair & 1, j = 2 * nh + kh, role = 2 * pair + kh;
#define WG_ORDER 0x210
    const int warp = uniform(((WG_ORDER >> (4 * (threadIdx.x >> 7))) & 3) * 4 + ((threadIdx.x >> 5) & 3));
    const uint32_t g = warp & 3, sb = SB0 | (kh << 24), rsb = sb ^ (1u << 24), cls = pair >> 5, kflip = ZFLIP ^ kh;
    const uint32_t mlo = (uint32_t)(uintptr_t)mbox, mhi = (uint32_t)((uintptr_t)mbox >> 32);
    auto lane16 = [&]() {
        uint32_t t;
        asm volatile("mov.u32 %0, %%laneid; shl.b32 %0, %0, 4;" : "=r"(t));
        return t;
    };
#define PHASE(k) uint32_t L; asm volatile("{.reg .u32 t; shr.u32 t, %1, %3; add.u32 %0, %2, t;}" : "=r"(L) : "r"(it), "r"(l16), "n"(8 + (k)))
#define ROWPAT() ((((L << 3) & 0x380) | ((L << 2) & 0x400)) | ((L ^ (L >> 3)) & 0x10) | (L & 0x60))
#define FRAG() (ROWPAT() ^ (g << 5))
#define QFRAG() ((((L >> 1) & 0x80) | (L & 0x70)) + ((L & 0x80) ? SM_KV + 16384 + kvo : SM_QKV))
#define VFRAG() (ROWPAT() ^ ((g & 1) << 6))
#define VBASE() (sb + SM_KV + 8192 + (g >> 1) * 4096 + kvo)
#define XTLO() ((uint32_t)make_desc(SB0 + SM_XT, 16, 1024) + (ui & 1) * 2048)
    if (warp >= 8) {
        asm volatile("setmaxnreg.dec.sync.aligned.u32 %0;" ::"n"(REG_C));
        const uint32_t l16 = lane16(), lane = l16 >> 4;
        const int ct = g * 32 + lane;
        if (warp == 8) {
            const CUtensorMap* ws = kh ? &mapWq : &mapWk;
            const CUtensorMap* wn = kh ? &mapWk : &mapWq;
            const uint64_t pol = EF_W ? policy_evict_first() : policy_evict_normal();
            const int col = h * DH + 64 * nh, row = 512 * kh;
            if (lane == 0) { mbar_expect_tx(sb + MB_W0, 49152); mbar_expect_tx(sb + MB_W1, 98304); mbar_expect_tx(sb + MB_W2, 81920); mbar_expect_tx(sb + MB_W3, 32768); }
            __syncwarp();
            if (lane < 24) {
                const int k = lane ^ (16 * kflip);
                tma_load_2d(sb + STG_V + lane * 2048, &mapWv, col, row + 16 * k, sb + MB_W0, pol);
                tma_load_2d(sb + STG_QK + lane * 2048, ws, col, row + 16 * k, sb + MB_W1, pol);
                tma_load_2d(sb + STG_QK + (24 + lane) * 2048, wn, col, row + 16 * k, sb + MB_W1, pol);
            }
            if (lane < 8) {
                const int k = (24 + lane) ^ (16 * kflip);
                tma_load_2d(sb + SM_WQK + lane * 4096, ws, col, row + 16 * k, sb + MB_W2, pol);
                tma_load_2d(sb + SM_WQK + lane * 4096 + 2048, wn, col, row + 16 * k, sb + MB_W2, pol);
                tma_load_2d(sb + SM_WV + lane * 2048, &mapWv, col, row + 16 * k, sb + MB_W2, pol);
            }
            if (lane < 2) tma_load_2d(sb + SM_WO2 + lane * 16384, &mapWo, 256 * j + 128 + 64 * lane, h * DH, sb + MB_W2, pol);
            __syncwarp();
            bar_sync(BAR_PV, 160);
            if (lane < 2) tma_load_2d(sb + STG_WO + lane * 16384, &mapWo, 256 * j + 64 * lane, h * DH, sb + MB_W3, pol);
            __syncwarp();
        }
        bar_sync(BAR_PDONE, 384);
        KT_MARK(9);
        for (int c = ct; c < 512; c += 128) {
            uint32_t w[4];
#pragma unroll
            for (int r = 0; r < 4; r++) {
                const uint32_t lo = reinterpret_cast<const uint16_t*>(mem0)[(2 * r) * DM + 512 * kh + c], hi = reinterpret_cast<const uint16_t*>(mem0)[(2 * r + 1) * DM + 512 * kh + c];
                w[r] = lo | (hi << 16);
            }
            sts128(sb + SM_Z + (c ^ (256 * kflip)) * 16, make_uint4(w[0], w[1], w[2], w[3]));
        }
        auto load_xt = [&](int seg, int half) {
            const uint32_t bar = sb + MB_XT + (seg & 1) * 8;
            if (half == 0) mbar_expect_tx(bar, 32768);
            asm volatile("cp.async.bulk.tensor.3d.shared::cluster.global.mbarrier::complete_tx::bytes [%0], [%1, {%3, %4, %5}], [%2];"
                         ::"r"(sb + SM_XT + (seg & 1) * 32768 + half * 16384), "l"(&mapX), "r"(bar), "r"(0), "r"(seg * SEG), "r"(8 * kh + 4 * (half ^ kflip)) : "memory");
        };
        auto tok_start = [&](int s) {
            if (lane == 0) {
                if (s > -3 && s + 2 < NSEG) {
                    mbar_wait(sb + MB_STG, (s + 2) & 1);
                    asm volatile("fence.proxy.async.shared::cta;" ::: "memory");
                    const int r = ((s + 2) & 3) * NH + h;
                    tma_store_2d(kh ? &mapT32 : &mapTQ, sb + SM_STG, kh ? 64 * nh : 256 * nh, kh ? r * 96 + 32 : r * 12);
                    tma_store_2d(&mapT16, sb + SM_STG + 4096, 64 * nh, r * 96 + 64 + 16 * kh);
                    asm volatile("cp.async.bulk.commit_group;" ::: "memory");
                }
                if (s + 4 < NSEG) load_xt(s + 4, 0);
                asm volatile("cp.async.bulk.wait_group.read 0;" ::: "memory");
                if (s < 0) {
                    asm volatile("mbarrier.arrive.shared::cluster.b64 _, [%0];" ::"r"(rsb + MB_FREE) : "memory");
                    mbar_wait(sb + MB_FREE, (s + 3) & 1);
                }
            }
            __syncwarp();
        };
        auto tok_mid = [&](int s) {
            if (lane == 0) {
                if (s + 4 < NSEG) load_xt(s + 4, 1);
                if (s > -3 && s + 2 < NSEG) {
                    asm volatile("cp.async.bulk.wait_group 0;" ::: "memory");
                    if (s == 8 || s == 16) asm volatile("fence.acq_rel.gpu;" ::: "memory");
                    st_relaxed_u32(g_xflag + role, s + 3);
                }
            }
            __syncwarp();
        };
        auto kv_check = [&](int s) {
            if (s + 1 < NSEG) {
                if (lane < 4) {
                    unsigned f; int guard = 0;
                    do {
                        asm volatile("ld.acquire.gpu.global.u32 %0, [%1];" : "=r"(f) : "l"(g_xflag + h * 4 + lane) : "memory");
                        if (++guard > (1 << 20)) __trap();
                    } while (f <= (unsigned)(s + 1));
                }
                __syncwarp();
                asm volatile("fence.proxy.async.global;" ::: "memory");
            }
        };
        auto kv_load = [&](int s) {
            if (lane == 0 && s + 1 < NSEG) {
                const uint32_t bar = sb + MB_KV + ((s + 1) & 1) * 8, dst = sb + SM_KV + ((s + 1) & 1) * KV_BYTES;
                const int row = (((s + 1) & 3) * NH + h) * 96;
                mbar_expect_tx(bar, KV_BYTES);
                asm volatile("cp.async.bulk.tensor.3d.shared::cluster.global.mbarrier::complete_tx::bytes.multicast::cluster [%0], [%1, {%3, %4, %3}], [%2], %5;"
                             ::"r"(dst + kh * 8192), "l"(&mapKV), "r"(bar), "r"(0), "r"(row + 32 + 32 * kh), "h"((uint16_t)3) : "memory");
                bulk_load(dst + 16384, g_tok + row * DH + j * 1024, 2048, bar);
            }
            __syncwarp();
        };
        if (warp == 9) {
            if (lane == 0) { load_xt(0, 0); load_xt(0, 1); }
#pragma unroll 1
            for (int s = -3; s < 0; s++) { tok_start(s); KT_MARK(13 + s); bar_arrive(BAR_PRO, 288); tok_mid(s); }
        }
        if (warp == 11) { kv_check(-1); kv_load(-1); }
        bar_arrive(BAR_MEM, 384);
        const uint32_t ybox = mlo + page_off(role & 63, cls ^ yflip), xoth = mlo + WIN + page_off((pair & 31) ^ 1, cls ^ XFLIP);
        const uint32_t zline = mlo + WIN + page_off(32 + ((role >> 5) & 1), cls ^ ZFLIP) + (role & 31) * 128, zbox = mlo + WIN + (page_off(32 + kh, 0) & ~4096u);
        const uint32_t xtype = g == 0 ? 2 : (g & 1);
        const uint32_t ydst = (lane >> 3) * 128 + ((lane & 7) ^ (lane >> 3)) * 16, ysrc = lane * 128 + ((2 * g) ^ (lane & 7)) * 16;
#pragma unroll 1
        for (int s = 0; s < NSEG; s++) {
            const uint32_t slot = (s & 3) << 14;
            if (g == 3) {
                kv_check(s);
                const uint32_t L = l16, kvo = (s & 1) * KV_BYTES, qa = QFRAG(), sa = sb + SM_S + 512 + (L >> 2);
                float sc[4] = {0.f, 0.f, 0.f, 0.f}, sd[4] = {0.f, 0.f, 0.f, 0.f};
                uint32_t a[4][4], kb[2][4];
                mbar_wait_w(sb + MB_KV + (s & 1) * 8, (s >> 1) & 1);
                mbar_wait_w(sb + MB_P, s & 1);
#pragma unroll
                for (int c = 0; c < 2; c++) {
                    const uint32_t qc = qa + (sb + (nh ^ c) * 1024), kc = L + (sb + SM_QKV + 2048 + (nh ^ c) * 1024);
                    if (c) bar_sync(BAR_QK, 224);
                    ldsm4t(kb[0], kc); ldsm4t(a[0], qc); ldsm4t(a[1], qc + 256);
                    ldsm4t(kb[1], kc + 512); ldsm4t(a[2], qc + 512); ldsm4t(a[3], qc + 768);
                    mma16816v(sc, a[0], kb[0][0], kb[0][1]);
                    mma16816v(sd, a[1], kb[0][2], kb[0][3]);
                    mma16816v(sc, a[2], kb[1][0], kb[1][1]);
                    mma16816v(sd, a[3], kb[1][2], kb[1][3]);
                }
                sts32(sa, scale_scores(sc[0] + sd[0], sc[1] + sd[1]));
                sts32(sa + 768, scale_scores(sc[2] + sd[2], sc[3] + sd[3]));
                bar_arrive(BAR_S, 160);
                TL(25);
                bar_sync(BAR_SV, 352);
                kv_load(s);
            } else {
                if (g == 1) { tok_start(s); TL(21); if (s == 0) KT_MARK(13); }
                const char* p = make_ptr(l16 + (xoth + xtype * 1024 + slot), mhi);
                const uint32_t dst = l16 + (sb + SM_QKV + xtype * 2048 + (nh ^ 1) * 1024);
                asm volatile("" ::"l"(p));
                uint4 v[2];
                poll_init(v[0]); poll_init(v[1]);
                if (g == 0) {
                    bar_sync(BAR_PUBV, 160);
                    mbar_wait_w(sb + MB_V, s & 1);
                    spin_cycles(DLY_V);
                } else {
                    bar_sync(BAR_PUB, 192);
                    spin_cycles(DLY_X);
                }
                const int r = poll2(v, p);
                STAT(1, r > 1 && warp == 10);
                sts128(dst, v[0]); sts128(dst + 512, v[1]);
                if (g != 0) bar_arrive(BAR_QK, 224);
                if (g == 0) { bar_arrive(BAR_V, 160); bar_arrive(BAR_SV, 352); TL(17); }
                if (g == 1) {
                    TL(31);
                    bar_sync(BAR_SV, 352);
                    tok_mid(s);
                    TL(22);
                }
                if (g == 2 && s >= 1) {
                    TL(16);
                    const uint32_t prev = (slot - 0x4000) & 0xC000;
                    const char* y = make_ptr(l16 + (ybox + prev), mhi);
                    const char* x = make_ptr(l16 + (xoth + prev + kh * 1536), mhi);
#pragma unroll
                    for (int i = 0; i < 8; i++) st_sent(y + i * 512);
#pragma unroll
                    for (int i = 0; i < 3; i++) st_sent(x + i * 512);
                    st_relaxed_u32(make_ptr(lane * 4 + (zline + (slot ^ 0x8000)), mhi), SENT);
                    TL(23);
                }
            }
            if (s + 1 == NSEG) break;
            {
                const char* p = make_ptr(l16 + (ybox + g * 1024 + slot), mhi);
                char* zdst = make_ptr(lane * 4 + (zline + g * 32 + slot), mhi);
                const uint32_t dst = ydst + (sb + SM_Z + g * 1024), dst1 = (ydst ^ 64) + (sb + SM_Z + g * 1024 + 512), src = ysrc + (sb + SM_Z), src1 = (ysrc ^ 16) + (sb + SM_Z);
                asm volatile("" ::"l"(p), "l"(zdst));
                uint4 v[2];
                poll_init(v[0]); poll_init(v[1]);
                bar_sync(BAR_SENTC, 384);
                spin_cycles(DLY_Y);
                const int r = poll2(v, p);
                STAT(2, r > 1 && warp == 8);
                sts128(dst, v[0]); sts128(dst1, v[1]);
                bar_sync(BAR_Y, 128);
                TL(18);
                uint32_t b[2][4];
                ldsm4t(b[0], src); ldsm4t(b[1], src1);
                const uint32_t one = 0x3F803F80u;
                float d0[4] = {0.f, 0.f, 0.f, 0.f}, d1[4] = {0.f, 0.f, 0.f, 0.f};
                mma16816(d0, one, one, one, one, b[0][0], b[0][1]);
                mma16816(d1, one, one, one, one, b[1][0], b[1][1]);
                mma16816(d0, one, one, one, one, b[0][2], b[0][3]);
                mma16816(d1, one, one, one, one, b[1][2], b[1][3]);
                const uint32_t w = (lane & 4) ? pack_bf16(d1[0], d1[1]) : pack_bf16(d0[0], d0[1]);
                asm volatile("{.reg .pred p; setp.lt.u32 p, %2, 128; @p st.relaxed.gpu.global.u32 [%0], %1;}" ::"l"(zdst), "r"(w), "r"(l16) : "memory");
                if (s + 3 < NSEG) bar_arrive(BAR_ZP, 256);
                TL(19);
            }
            {
                const char* p = make_ptr(l16 + (zbox + g * 512 + slot), mhi);
                const uint32_t dst = l16 + (sb + SM_Z + g * 512);
                asm volatile("" ::"l"(p));
                uint4 v[4];
                poll_init(v[0]); poll_init(v[1]); poll_init(v[2]); poll_init(v[3]);
                bar_sync(BAR_COMM, 128);
                spin_cycles(DLY_Z);
                const int r = poll4(v, p);
                STAT(0, r > 1 && warp == 8);
#pragma unroll
                for (int i = 0; i < 4; i++) sts128(dst + i * 2048, v[i]);
                bar_arrive(BAR_MEM, 384);
                TL(20);
            }
        }
    } else if (warp < 4) {
        asm volatile("setmaxnreg.inc.sync.aligned.u32 %0;" ::"n"(REG_A));
        const uint32_t l16 = lane16();
        uint32_t wa[2][24][4];
        {
            const uint32_t L = l16, fa = sb + FRAG();
            mbar_wait_w(sb + MB_W1, 0);
            KT_MARK(7);
#pragma unroll
            for (int t = 0; t < 2; t++)
#pragma unroll
                for (int r = 0; r < 24; r++) ldsm4t(wa[t][r], fa + STG_QK + (t * 24 + r) * 2048);
            mbar_wait_w(sb + MB_W2, 0);
            bar_arrive(BAR_PDONE, 384);
        }
        auto batch1 = [&](float (&d)[16], uint32_t lo, auto tc, auto k0c, auto k1c) {
            constexpr int t = decltype(tc)::value;
            const uint64_t da = make_desc(SB0 + SM_WQK, 16, 1024);
            wg_fence();
            static_for<decltype(k0c)::value, decltype(k1c)::value>([&](auto kc) {
                constexpr int k = decltype(kc)::value, off = (k >> 2) * 256 + (k & 3) * 2;
                if constexpr (k >= 24) wgmma_ss32u<off>(d, da + ((k - 24) * 2 + t) * 128, lo);
                else wgmma_rs32u<off, k != 0 || t != 0>(d, wa[t][k], lo);
            });
            wg_commit();
        };
        const uint32_t xbox = mlo + WIN + page_off(pair & 31, cls ^ XFLIP);
        const uint32_t ybox = mlo + page_off(24 + 2 * g + 32 * nh, kh ^ yflip) + h * 128;
#pragma unroll 1
        for (uint32_t it = 0; it < NSEG + 3; it++) {
            const int s = (int)it - 3;
            const uint32_t ui = uniform(it), slot = ((ui + 1) & 3) << 14, kvo = (~ui & 1) * KV_BYTES, xtlo = XTLO();
            {
                PHASE(5);
                const uint32_t first = L | (g << 9);
                if (s >= 0) mbar_expect_tx_if0(first, sb + MB_R1, 2048);
                if (s + 3 < NSEG) {
                    mbar_expect_tx_if0(first, sb + MB_RT0, 8192);
                    mbar_wait_w(sb + MB_XT + (ui & 1) * 8, (it >> 1) & 1);
                }
            }
            if (s >= 0) {
                PHASE(0);
                const uint32_t mb = L + (sb + SM_Z), ra = L + (sb + g * 512), r1 = L + (rsb + SM_R1 + g * 512), r1b = rsb + MB_R1;
                sched_fence(r1 | r1b);
                bar_sync(BAR_MEM, 384);
                TLB(0);
                float acc[2][2][4];
#pragma unroll
                for (int t = 0; t < 4; t++) { acc[t >> 1][t & 1][0] = acc[t >> 1][t & 1][1] = acc[t >> 1][t & 1][2] = acc[t >> 1][t & 1][3] = 0.f; }
                uint32_t b[4][4];
                uint4 u0, u1;
#pragma unroll
                for (int p = 0; p < 4; p++) ldsm4t(b[p], mb + p * 512);
#pragma unroll
                for (int p = 0; p < 12; p++) {
#pragma unroll
                    for (int u = 0; u < 2; u++) {
                        mma16816v(acc[0][u], wa[0][2 * p + u], b[p & 3][2 * u], b[p & 3][2 * u + 1]);
                        mma16816v(acc[1][u], wa[1][2 * p + u], b[p & 3][2 * u], b[p & 3][2 * u + 1]);
                    }
                    if (p + 4 < 12) ldsm4t(b[p & 3], mb + (p + 4) * 512);
                    if (p == Q3_AT) {
                        bar_sync(BAR_Q3, 256);
                        u0 = lds128(ra + SM_R3); u1 = lds128(ra + SM_O);
                    }
                }
                st_async4(r1, (acc[0][0][0] + __uint_as_float(u0.x)) + acc[0][1][0], (acc[0][0][1] + __uint_as_float(u0.y)) + acc[0][1][1],
                          (acc[0][0][2] + __uint_as_float(u0.z)) + acc[0][1][2], (acc[0][0][3] + __uint_as_float(u0.w)) + acc[0][1][3], r1b);
                TL(1);
                const float o0 = (acc[1][0][0] + __uint_as_float(u1.x)) + acc[1][1][0], o1 = (acc[1][0][1] + __uint_as_float(u1.y)) + acc[1][1][1];
                const float o2 = (acc[1][0][2] + __uint_as_float(u1.z)) + acc[1][1][2], o3 = (acc[1][0][3] + __uint_as_float(u1.w)) + acc[1][1][3];
                const uint32_t l4 = L >> 2, qo = SM_QKV + kh * 2048 + nh * 1024 + g * 256, qr = l4 + (rsb + qo), ql = l4 + (sb + qo), pb = rsb + MB_P;
                char* xd = make_ptr(l4 + (xbox + kh * 1024 + g * 256 + slot), mhi);
                asm volatile("" ::"l"(xd), "r"(qr), "r"(pb), "r"(qr + 128), "f"(o0), "f"(o1), "f"(o2), "f"(o3));
                mbar_wait_w(sb + MB_R1, s & 1);
                const uint4 v = lds128(ra + SM_R1);
                const uint32_t w0 = pack_bf16(o0 + __uint_as_float(v.x), o1 + __uint_as_float(v.y)), w1 = pack_bf16(o2 + __uint_as_float(v.z), o3 + __uint_as_float(v.w));
                st_relaxed_u32(xd, w0);
                st_relaxed_u32(xd + 128, w1);
                bar_arrive(BAR_PUB, 192);
                st_async1(qr, w0, pb);
                st_async1(qr + 128, w1, pb);
                sts32(ql, w0);
                sts32(ql + 128, w1);
                __syncwarp();
                mbar_expect_tx_if0(L, sb + MB_P, 256);
                TL(2);
                if (s + 3 < NSEG) bar_sync(BAR_VP, 256);
            } else {
                bar_sync(BAR_PRO, 288);
            }
            if (s + 3 < NSEG) {
                float d[16];
                batch1(d, xtlo, std::integral_constant<int, 0>(), std::integral_constant<int, 0>(), std::integral_constant<int, 32>());
                PHASE(1);
                const uint32_t rt = L + (rsb + SM_RT + g * 2048);
                wg_wait<0>();
                TL(7);
#pragma unroll
                for (int i = 0; i < 4; i++) st_async4(rt + i * 512, d[4 * i], d[4 * i + 1], d[4 * i + 2], d[4 * i + 3], rsb + MB_RT0);
            }
            if (s + 1 == NSEG) { bar_arrive(BAR_SV, 352); break; }
            if (s >= 0) {
                PHASE(2);
                const uint32_t fo = FRAG() + (sb + SM_WO2 + 16384), lo = L + (sb + SM_O), yo = (L >> 2) + (ybox + slot);
                uint32_t a1[8][4];
                bar_sync(BAR_SV, 352);
#pragma unroll
                for (int k = 0; k < 8; k++) ldsm4t(a1[k], fo + k * 2048);
                sched_fence(yo);
                bar_sync(BAR_O2, 256);
                TLB(14);
                float y0[4] = {0.f, 0.f, 0.f, 0.f}, y1[4] = {0.f, 0.f, 0.f, 0.f};
                uint32_t b[2][4];
                ldsm4t(b[0], lo); ldsm4t(b[1], lo + 512);
                sched_fence(L);
#pragma unroll
                for (int p = 0; p < 4; p++) {
                    mma16816v(y0, a1[2 * p], b[p & 1][0], b[p & 1][1]);
                    mma16816v(y1, a1[2 * p + 1], b[p & 1][2], b[p & 1][3]);
                    if (p < 2) ldsm4t(b[p & 1], lo + (p + 2) * 512);
                }
                bar_sync(BAR_INV, 256);
                float i0, i1;
                asm volatile("ld.shared.v2.f32 {%0, %1}, [%2];" : "=f"(i0), "=f"(i1) : "r"(((L >> 1) & 0x18) + (sb + SM_INV + g * 32)) : "memory");
                st_relaxed_u32(make_ptr(yo, mhi), pack_bf16((y0[0] + y1[0]) * i0, (y0[1] + y1[1]) * i1));
                st_relaxed_u32(make_ptr(yo ^ 4096, mhi) + 0x2000, pack_bf16((y0[2] + y1[2]) * i0, (y0[3] + y1[3]) * i1));
                bar_arrive(BAR_SENTC, 384);
                TL(6);
            }
            if (s + 3 < NSEG) {
                PHASE(4);
                float d[16];
                const uint32_t rt = L + (sb + SM_RT + g * 2048);
                if (SENT_EARLY && s >= 0) bar_sync(BAR_SENT, 256);
                mbar_wait_w(sb + MB_RT0, it & 1);
#pragma unroll
                for (int i = 0; i < 4; i++) {
                    const uint4 v = lds128(rt + i * 512);
                    d[4 * i] = __uint_as_float(v.x); d[4 * i + 1] = __uint_as_float(v.y); d[4 * i + 2] = __uint_as_float(v.z); d[4 * i + 3] = __uint_as_float(v.w);
                }
                if (!SENT_EARLY && s >= 0) bar_sync(BAR_SENT, 256);
                if (SPLIT > 0) batch1(d, xtlo, std::integral_constant<int, 1>(), std::integral_constant<int, 0>(), std::integral_constant<int, SPLIT>());
                if (s >= 0) bar_sync(BAR_ZP, 256);
                TLB(30);
                batch1(d, xtlo, std::integral_constant<int, 1>(), std::integral_constant<int, SPLIT>(), std::integral_constant<int, 32>());
                const uint32_t so = (kh ? FRAG() : ((L & 0x100) << 2) + (L & 0xF0) + g * 256) + (sb + SM_STG);
                wg_wait<0>();
                TL(8);
                uint32_t w[8];
#pragma unroll
                for (int i = 0; i < 8; i++) w[i] = pack_bf16(d[2 * i], d[2 * i + 1]);
                if (kh) {
                    stsm4t(so, w[0], w[1], w[2], w[3]);
                    stsm4t(so + 2048, w[4], w[5], w[6], w[7]);
                } else {
                    stsm4(so, w[0], w[1], w[2], w[3]);
                    stsm4(so + 2048, w[4], w[5], w[6], w[7]);
                }
                __syncwarp();
                mbar_arrive_if0(L, sb + MB_STG);
                TL(9);
            } else {
                bar_arrive(BAR_SENT, 256);
            }
        }
    } else {
        asm volatile("setmaxnreg.inc.sync.aligned.u32 %0;" ::"n"(REG_B));
        const uint32_t l16 = lane16();
        uint32_t wv[24][4], wo[8 + WO_RF1][4];
        {
            const uint32_t L = l16, fa = sb + FRAG();
            mbar_wait_w(sb + MB_W0, 0);
            KT_MARK(6);
#pragma unroll
            for (int r = 0; r < 24; r++) ldsm4t(wv[r], fa + STG_V + r * 2048);
            bar_arrive(BAR_PV, 160);
            mbar_wait_w(sb + MB_W3, 0);
            KT_MARK(8);
#pragma unroll
            for (int r = 0; r < 8 + WO_RF1; r++) ldsm4t(wo[r], fa + STG_WO + r * 2048);
            mbar_wait_w(sb + MB_W2, 0);
            bar_arrive(BAR_PDONE, 384);
        }
        const uint32_t xbox = mlo + WIN + page_off(pair & 31, cls ^ XFLIP);
        const uint32_t ybox = mlo + page_off(2 * g + 32 * nh, kh ^ yflip) + h * 128;
#pragma unroll 1
        for (uint32_t it = 0; it < NSEG + 3; it++) {
            const int s = (int)it - 3;
            const uint32_t ui = uniform(it), slot = ((ui + 1) & 3) << 14, kvo = (~ui & 1) * KV_BYTES, xtlo = XTLO();
            {
                PHASE(5);
                const uint32_t first = L | (g << 9);
                if (s >= 0) mbar_expect_tx_if0(first, sb + MB_R2, 1024);
                if (s + 3 < NSEG) {
                    mbar_expect_tx_if0(first, sb + MB_RT1, 4096);
                    mbar_wait_w(sb + MB_XT + (ui & 1) * 8, (it >> 1) & 1);
                }
            }
            if (s >= 0) {
                PHASE(0);
                const uint32_t fo = FRAG() + sb, l4 = L >> 2;
                {
                    const uint32_t mb = L + (sb + SM_Z), aw = fo + SM_WQK, ra = L + (sb + g * 512), r2 = (L >> 1) + (rsb + SM_R2 + g * 256), r2b = rsb + MB_R2;
                    uint32_t a[NA][4], b[4][4];
#pragma unroll
                    for (int i = 0; i < NA; i++) ldsm4t(a[i], aw + i * 2048);
                    sched_fence(L);
                    TL(24);
                    bar_sync(BAR_MEM, 384);
#pragma unroll
                    for (int p = 0; p < 4; p++) ldsm4t(b[p], mb + (12 + p) * 512);
                    sched_fence(L);
                    float c[2][4] = {{0.f, 0.f, 0.f, 0.f}, {0.f, 0.f, 0.f, 0.f}};
#pragma unroll
                    for (int i = 0; i < 16; i++) {
                        mma16816v(c[i & 1], a[i % NA], b[i >> 2][i & 2], b[i >> 2][(i & 2) + 1]);
                        ldsm4t(a[i % NA], aw + (i + NA) * 2048);
                    }
                    sts128(ra + SM_R3, make_uint4(__float_as_uint(c[0][0]), __float_as_uint(c[0][1]), __float_as_uint(c[0][2]), __float_as_uint(c[0][3])));
                    sts128(ra + SM_O, make_uint4(__float_as_uint(c[1][0]), __float_as_uint(c[1][1]), __float_as_uint(c[1][2]), __float_as_uint(c[1][3])));
                    bar_arrive(BAR_Q3, 256);
                    TL(29);
                    float acc[4][4];
#pragma unroll
                    for (int t = 0; t < 4; t++) { acc[t][0] = acc[t][1] = acc[t][2] = acc[t][3] = 0.f; }
#pragma unroll
                    for (int i = 16; i < 24; i++) {
                        mma16816v(acc[i & 1], a[i % NA], b[(i - 16) >> 1][2 * (i & 1)], b[(i - 16) >> 1][2 * (i & 1) + 1]);
                        if (i + NA < 24) ldsm4t(a[i % NA], aw + (i + NA) * 2048);
                        else ldsm4t(a[i % NA], mb + (i + NA - 24) * 512);
                    }
#pragma unroll
                    for (int p = 0; p < 12; p++) {
                        mma16816v(acc[(2 * p) & 3], wv[2 * p], a[(24 + p) % NA][0], a[(24 + p) % NA][1]);
                        mma16816v(acc[(2 * p + 1) & 3], wv[2 * p + 1], a[(24 + p) % NA][2], a[(24 + p) % NA][3]);
                        if (p + NA < 12) ldsm4t(a[(24 + p) % NA], mb + (p + NA) * 512);
                    }
                    if (s + 3 < NSEG) bar_arrive(BAR_VP, 256);
                    float o[4];
#pragma unroll
                    for (int i = 0; i < 4; i++) o[i] = (acc[0][i] + acc[1][i]) + (acc[2][i] + acc[3][i]);
                    st_async2(r2, kh ? o[0] : o[2], kh ? o[1] : o[3], r2b);
                    TL(10);
                    const float o0 = kh ? o[2] : o[0], o1 = kh ? o[3] : o[1];
                    const uint32_t qo = SM_QKV + 4096 + nh * 1024 + (2 * g + kh) * 128, qr = l4 + (rsb + qo), ql = l4 + (sb + qo), vb = rsb + MB_V, rl = (L >> 1) + (sb + SM_R2 + g * 256);
                    char* xd = make_ptr(l4 + (xbox + 2048 + (2 * g + kh) * 128 + slot), mhi);
                    asm volatile("" ::"l"(xd), "r"(qr), "r"(vb), "f"(o0), "f"(o1));
                    mbar_wait_w(sb + MB_R2, s & 1);
                    uint32_t vx, vy;
                    asm volatile("ld.shared.v2.u32 {%0,%1}, [%2];" : "=r"(vx), "=r"(vy) : "r"(rl) : "memory");
                    const uint32_t w0 = pack_bf16(o0 + __uint_as_float(vx), o1 + __uint_as_float(vy));
                    st_relaxed_u32(xd, w0);
                    bar_arrive(BAR_PUBV, 160);
                    st_async1(qr, w0, vb);
                    sts32(ql, w0);
                    __syncwarp();
                    mbar_expect_tx_if0(L, sb + MB_V, 128);
                    TL(11);
                }
                const uint32_t vma = L + (sb + SM_QKV + 4096 + g * 512), yo = l4 + (ybox + slot);
                uint32_t va[2][2][4];
                {
                    const uint32_t qa = QFRAG(), vf = VFRAG(), va0 = vf + VBASE(), va1 = (vf ^ 32) + VBASE();
                    const uint32_t kf = ((L << 3) & 0x380) | ((L ^ (L >> 3)) & 0x30) | (L & 0x40), kb0 = sb + SM_KV + kvo + g * 1024;
                    const int d = (int)(L >> 6) - (int)((L >> 3) & 6) + 8 * (j - (int)g);
                    const uint32_t keep = (d < 0 ? 0u : 0xFFFFu) | (d < 1 ? 0u : 0xFFFF0000u), sa = l4 + (sb + SM_S + g * 128);
                    const uint32_t q0 = qa + (sb + nh * 1024), q1 = qa + (sb + (nh ^ 1) * 1024);
                    float sc[4] = {0.f, 0.f, 0.f, 0.f}, sd[4] = {0.f, 0.f, 0.f, 0.f};
                    uint32_t a[4][4], kb[2][4];
                    mbar_wait_w(sb + MB_KV + (~ui & 1) * 8, (s >> 1) & 1);
                    ldsm4(kb[0], kf + (kb0 + nh * 4096)); ldsm4(kb[1], (kf ^ 64) + (kb0 + nh * 4096));
                    mbar_wait_w(sb + MB_P, s & 1);
                    TL(12);
#pragma unroll
                    for (int k = 0; k < 4; k++) ldsm4t(a[k], q0 + k * 256);
#pragma unroll
                    for (int k = 0; k < 4; k++) mma16816v((k & 1) ? sd : sc, a[k], kb[k >> 1][2 * (k & 1)], kb[k >> 1][2 * (k & 1) + 1]);
                    ldsm4(kb[0], kf + (kb0 + (nh ^ 1) * 4096)); ldsm4(kb[1], (kf ^ 64) + (kb0 + (nh ^ 1) * 4096));
                    sched_fence(vf | yo);
                    bar_sync(BAR_QK, 224);
                    TLB(3);
#pragma unroll
                    for (int k = 0; k < 4; k++) ldsm4t(a[k], q1 + k * 256);
                    sched_fence(L);
#pragma unroll
                    for (int k = 0; k < 4; k++) mma16816v((k & 1) ? sd : sc, a[k], kb[k >> 1][2 * (k & 1)], kb[k >> 1][2 * (k & 1) + 1]);
                    ldsm4t(va[0][0], va0); ldsm4t(va[0][1], va0 + 2048);
                    sts32(sa, scale_scores(sc[0] + sd[0], sc[1] + sd[1]));
                    sts32(sa + 768, (scale_scores(sc[2] + sd[2], sc[3] + sd[3]) & keep) | (0xFF80FF80u & ~keep));
                    bar_arrive(BAR_SV, 352);
                    ldsm4t(va[1][0], va1); ldsm4t(va[1][1], va1 + 2048);
                }
                bar_sync(BAR_S, 160);
                TLB(4);
                uint32_t pw[6], vm[4];
                if (s + 1 < NSEG) {
                softmax40(pw, l4 + (sb + SM_S), [&]() {
                    bar_sync(BAR_V, 160);
                    ldsm4(vm, vma);
                });
                uint32_t a1[NP2][4];
                float inv[2];
                {
                    uint32_t w[4];
                    pv32<false>(w, inv, va, vm, pw, [&]() {
                        sched_fence(L);
#pragma unroll
                        for (int k = 0; k < NP2; k++) ldsm4t(a1[k], fo + SM_WO2 + k * 2048);
                    });
#pragma unroll
                    for (int i = 0; i < 4; i++) sts32(l4 + (sb + SM_O + g * 512) + i * 128, w[i]);
                }
                const uint32_t lo = L + (sb + SM_O);
                bar_arrive(BAR_O2, 256);
                bar_sync(BAR_O, 128);
                TLB(5);
                {
                    float y0[4] = {0.f, 0.f, 0.f, 0.f}, y1[4] = {0.f, 0.f, 0.f, 0.f}, y2[4] = {0.f, 0.f, 0.f, 0.f};
                    uint32_t b[4][4];
#pragma unroll
                    for (int p = 0; p < 4; p++) ldsm4t(b[p], lo + p * 512);
                    inv[0] = rcp_approx(inv[0]); inv[1] = rcp_approx(inv[1]);
                    asm volatile("st.shared.v2.f32 [%0], {%1, %2};" ::"r"(((L >> 1) & 0x18) + (sb + SM_INV + g * 32)), "f"(inv[0]), "f"(inv[1]) : "memory");
                    bar_arrive(BAR_INV, 256);
                    sched_fence(L);
#pragma unroll
                    for (int k = 0; k < 8; k++) {
                        const int p = k >> 1, u = k & 1;
                        mma16816v(y2, a1[k % NP2], b[p][2 * u], b[p][2 * u + 1]);
                        if (k + NP2 < 8) ldsm4t(a1[k % NP2], fo + SM_WO2 + (k + NP2) * 2048);
                        else if (k + NP2 < 16 - WO_RF1) ldsm4t(a1[k % NP2], fo + SM_WO1 + (k + NP2 - 8 + WO_RF1) * 2048);
                        mma16816v(y0, wo[k], b[p][2 * u], b[p][2 * u + 1]);
                        if (k < WO_RF1) mma16816v(y1, wo[8 + (k < WO_RF1 ? k : 0)], b[p][2 * u], b[p][2 * u + 1]);
                        else mma16816v(y1, a1[(k + 8 - WO_RF1) % NP2], b[p][2 * u], b[p][2 * u + 1]);
                        if (k < P2_FENCE) sched_fence(L);
                    }
                    char* yd = make_ptr(yo, mhi);
                    char* yd1 = make_ptr(yo ^ 4096, mhi);
                    st_relaxed_u32(yd1 + 0x80000, pack_bf16(y2[0] * inv[0], y2[1] * inv[1]));
                    st_relaxed_u32(yd + 0x82000, pack_bf16(y2[2] * inv[0], y2[3] * inv[1]));
                    st_relaxed_u32(yd, pack_bf16(y0[0] * inv[0], y0[1] * inv[1]));
                    st_relaxed_u32(yd1 + 0x2000, pack_bf16(y0[2] * inv[0], y0[3] * inv[1]));
                    st_relaxed_u32(yd + 0x40000, pack_bf16(y1[0] * inv[0], y1[1] * inv[1]));
                    st_relaxed_u32(yd1 + 0x42000, pack_bf16(y1[2] * inv[0], y1[3] * inv[1]));
                }
                bar_arrive(BAR_SENTC, 384);
                TL(13);
                bar_sync(BAR_SENT, 256);
                } else {
                    bar_sync(BAR_V, 160);
                }
            } else {
                bar_sync(BAR_PRO, 288);
            }
            float o[8];
            {
                PHASE(1);
                float d[16];
                const uint64_t da = make_desc(SB0 + SM_WV, 16, 1024);
                auto batch = [&](auto k0c, auto k1c) {
                    static_for<decltype(k0c)::value, decltype(k1c)::value>([&](auto kc) {
                        constexpr int k = decltype(kc)::value, off = (k >> 2) * 256 + (k & 3) * 2;
                        if constexpr (k >= 24) wgmma_ss32u<off>(d, da + (k - 24) * 128, xtlo);
                        else wgmma_rs32u<off, k != 0>(d, wv[k], xtlo);
                    });
                };
                const uint32_t vf = VFRAG(), va0 = vf + VBASE(), va1 = (vf ^ 32) + VBASE(), vma = L + (sb + SM_QKV + 4096 + g * 512), sa = (L >> 2) + (sb + SM_S + 768);
                const uint32_t rt = L + (rsb + SM_RT + 8192 + g * 1024);
                uint32_t va[2][2][4], vm[4], pw[6], w[4];
                wg_fence();
                batch(std::integral_constant<int, 0>(), std::integral_constant<int, TA0>());
                wg_commit();
                batch(std::integral_constant<int, TA0>(), std::integral_constant<int, 32>());
                wg_commit();
                wg_wait<1>();
                softmax40(pw, sa, [&]() {});
                ldsm4t(va[0][0], va0); ldsm4t(va[0][1], va0 + 2048);
                ldsm4t(va[1][0], va1); ldsm4t(va[1][1], va1 + 2048);
                ldsm4(vm, vma);
                wg_wait<0>();
                TL(27);
                float inv[2];
                pv32<true>(w, inv, va, vm, pw, [&]() {
                    if (s + 3 < NSEG) {
#pragma unroll
                        for (int i = 0; i < 2; i++)
                            st_async4(rt + i * 512, kh ? d[4 * i] : d[8 + 4 * i], kh ? d[4 * i + 1] : d[9 + 4 * i], kh ? d[4 * i + 2] : d[10 + 4 * i], kh ? d[4 * i + 3] : d[11 + 4 * i], rsb + MB_RT1);
                    }
#pragma unroll
                    for (int i = 0; i < 8; i++) o[i] = kh ? d[8 + i] : d[i];
                });
                stsm4t((L & 0x70) * 5 + ((L >> 3) & 0x30) + (sb + SM_TO + g * 640), w[0], w[1], w[2], w[3]);
                __syncwarp();
                const uint4 r = lds128(((L >> 2) & 0x70) * 5 + (L & 0x30) + (sb + SM_TO + g * 640));
                if (s >= 0) stg128(reinterpret_cast<char*>(g_ox) + (((L & 0x1C0) << 7) + (L & 0x30) + (((ui - 3) * SEG + 8 * j) * HD + h * DH + 32 * g) * 2), r);
                TL(26);
            }
            if (s + 3 < NSEG) {
                PHASE(3);
                const uint32_t rt = L + (sb + SM_RT + 8192 + g * 1024), so = FRAG() + (sb + SM_STG + 4096);
                mbar_wait_w(sb + MB_RT1, it & 1);
                TL(28);
                uint32_t w[4];
#pragma unroll
                for (int i = 0; i < 2; i++) {
                    const uint4 v = lds128(rt + i * 512);
                    w[2 * i] = pack_bf16(o[4 * i] + __uint_as_float(v.x), o[4 * i + 1] + __uint_as_float(v.y));
                    w[2 * i + 1] = pack_bf16(o[4 * i + 2] + __uint_as_float(v.z), o[4 * i + 3] + __uint_as_float(v.w));
                }
                stsm4t(so, w[0], w[1], w[2], w[3]);
                __syncwarp();
                mbar_arrive_if0(L, sb + MB_STG);
                TL(15);
            }
        }
    }
    KT_END(2);
    asm volatile("barrier.cluster.arrive.relaxed; barrier.cluster.wait;" ::: "memory");
}
constexpr int B_UCH = 73 * 64;
constexpr int B_SCH = 33 * 64;
constexpr int B_KLEN = 2128;
constexpr int B_KCH = 2 * B_KLEN * 2 + 64;
constexpr int B_KBOX = 136 * 32;
constexpr int B_SM_U = 0;
constexpr int B_SM_S = 8 * B_UCH;
constexpr int B_SM_K = B_SM_S + 8 * B_SCH;
constexpr int B_SM_KT = B_SM_K + 8 * B_KCH;
constexpr int B_SM_VT = B_SM_KT + 8 * B_KBOX;
constexpr int B_SM_QT = B_SM_VT + 32768;
constexpr int B_SM_BAR = B_SM_QT + 32768;
constexpr int B_SMEM = B_SM_BAR + 128 + 512;
static_assert(B_SM_KT % 256 == 0 && B_SM_S % 512 == 0 && B_SMEM <= 232448, "tiles");
constexpr int PROBE_N = 4;
#define PROBE_R 2
constexpr int B_C = 2056;

__device__ __forceinline__ uint32_t atomic_round_trip(char* p) {
    uint32_t t0, t1, v;
    asm volatile("{.reg .pred p;\n"
                 "mov.u32 %0, %%clock;\n"
                 "atom.relaxed.gpu.global.add.u32 %2, [%3], 1;\n"
                 "setp.ne.u32 p, %2, 0x7FFFFFFF;\n"
                 "mov.u32 %1, 0;\n"
                 "@p mov.u32 %1, %%clock;}" : "=&r"(t0), "=&r"(t1), "=&r"(v) : "l"(p) : "memory");
    return t1 - t0;
}
__device__ __forceinline__ uint32_t round_trips(char* a, char* b, uint32_t stride, int lane) {
    for (int i = lane >> 3; i < 2 * PROBE_N; i += 4) stg128(((i & 1) ? b : a) + (i >> 1) * stride + (lane & 7) * 16, make_uint4(0, 0, 0, 0));
    __syncwarp();
    uint32_t ta = 0xFFFF, tb = 0xFFFF;
    if (lane == 0) {
        __threadfence();
#pragma unroll 1
        for (int i = 0; i < PROBE_N; i++) { ta = min(ta, atomic_round_trip(a + i * stride)); tb = min(tb, atomic_round_trip(b + i * stride)); }
    }
    __syncwarp();
    return ta | (tb << 16);
}
__device__ __forceinline__ void measure_distance(char* mbox, int lane) {
    const uint32_t b = blockIdx.x;
    unsigned smid;
    asm volatile("mov.u32 %0, %%smid;" : "=r"(smid));
    char* w1 = mbox + WIN + (b & 31) * 128;
    uint32_t r = 0xFFFFFFFF;
#pragma unroll 1
    for (int i = 0; i < PROBE_R; i++) r = __vminu2(r, round_trips(w1 + page_off(50 + 5 * i + (b >> 5), 0), w1 + page_off(50 + 5 * i + (b >> 5), 1), 16384, lane));
    if (lane == 0) g_cls[smid] = r;
    if (b == 128) {
        char *p = mbox + page_off(0, 0), *q = mbox + page_off(0, 1);
        uint32_t r0 = 0xFFFFFFFF;
#pragma unroll 1
        for (int i = 0; i < PROBE_R; i++) r0 = __vminu2(r0, round_trips(p, q, 128, lane));
        if (lane == 0) { g_reg[1] = ((r0 & 0xFFFF) > (r0 >> 16)) != ((r & 0xFFFF) > (r >> 16)); g_reg[0] = 0; g_reg[2] = 0; }
        const uint4 sent = make_uint4(SENT, SENT, SENT, SENT);
        stg128(p + lane * 16, sent); stg128(q + lane * 16, sent);
    }
    if (b == 129) for (int i = lane; i < 128; i += 32) g_xflag[i] = 0;
}

#define SP(i)
#define SP2(i)
#define PF_STOP 1
#define SENT_AT 3
#define Q_LATE 1
#define PF_DEPTH 4
#define PF_STRIDE 256
struct ChainInputs { const char* w[4]; const char *x, *mem0; };
#define EF_MASK 15
#define EF(i) (((EF_MASK >> (i)) & 1) ? policy_evict_first() : policy_evict_normal())
__device__ __forceinline__ void l2_prefetch(const char* p, uint32_t bytes) {
    asm volatile("cp.async.bulk.prefetch.L2.global [%0], %1;" ::"l"(p), "r"(bytes) : "memory");
}
#define WG_CONV(N, LIST, A0, A1, A2, A3, LO, OF, ...) \
    if constexpr (NN == N) asm volatile("{.reg .b32 l; .reg .b64 e; add.u32 l, %" #LO ", %" #OF "; mov.b64 e, {l, 0x80000020};\n" \
        "wgmma.mma_async.sync.aligned.m64n" #N "k16.f32.bf16.bf16 {" LIST "}, {%" #A0 ",%" #A1 ",%" #A2 ",%" #A3 "}, e, 1, 1, 1, 0;}" \
        : __VA_ARGS__ : "r"(a[0]), "r"(a[1]), "r"(a[2]), "r"(a[3]), "r"(lo), "n"(OFF));
#define WL4 "%0,%1,%2,%3"
#define WL8 WL4 ",%4,%5,%6,%7"
#define WL12 WL8 ",%8,%9,%10,%11"
#define WL16 WL12 ",%12,%13,%14,%15"
#define WL20 WL16 ",%16,%17,%18,%19"
#define WL24 WL20 ",%20,%21,%22,%23"
#define WL28 WL24 ",%24,%25,%26,%27"
#define WL32 WL28 ",%28,%29,%30,%31"
template <int NN, int OFF> __device__ __forceinline__ void wgmma_conv(float (&d)[32], const uint32_t (&a)[4], uint32_t lo) {
    WG_CONV(8, WL4, 4, 5, 6, 7, 8, 9, R4(0))
    WG_CONV(16, WL8, 8, 9, 10, 11, 12, 13, R4(0), R4(4))
    WG_CONV(24, WL12, 12, 13, 14, 15, 16, 17, R4(0), R4(4), R4(8))
    WG_CONV(32, WL16, 16, 17, 18, 19, 20, 21, R16(0))
    WG_CONV(40, WL20, 20, 21, 22, 23, 24, 25, R16(0), R4(16))
    WG_CONV(48, WL24, 24, 25, 26, 27, 28, 29, R16(0), R4(16), R4(20))
    WG_CONV(56, WL28, 28, 29, 30, 31, 32, 33, R16(0), R4(16), R4(20), R4(24))
    WG_CONV(64, WL32, 32, 33, 34, 35, 36, 37, R16(0), R16(16))
}
__device__ __forceinline__ void copy_to_peer(uint32_t dst, uint32_t src, uint32_t bytes, uint32_t bar) {
    asm volatile("cp.async.bulk.shared::cluster.shared::cta.mbarrier::complete_tx::bytes [%0], [%1], %2, [%3];" ::"r"(dst), "r"(src), "r"(bytes), "r"(bar) : "memory");
}
__device__ __forceinline__ uint32_t lds_volatile(uint32_t a) {
    uint32_t v;
    asm volatile("ld.volatile.shared.u32 %0, [%1];" : "=r"(v) : "r"(a) : "memory");
    return v;
}
__device__ __forceinline__ uint32_t swz64(uint32_t a) { return a ^ ((a >> 3) & 0x30); }
__device__ __forceinline__ void fence_async() { asm volatile("fence.proxy.async.shared::cta;" ::: "memory"); }

__global__ void __cluster_dims__(2, 1, 1) __launch_bounds__(576, 1)
ssm_kernel(const __grid_constant__ CUtensorMap mapK, const __grid_constant__ CUtensorMap mapV, const __grid_constant__ CUtensorMap mapQ,
           const __grid_constant__ CUtensorMap mapO, const bf16* __restrict__ shiftk, const bf16* __restrict__ ssmk, const bf16* __restrict__ Dv,
           char* __restrict__ mbox, const __grid_constant__ ChainInputs ci) {
    extern __shared__ __align__(128) uint8_t smem_raw[];
    const uint32_t sb = (smem_u32(smem_raw) + 511) & ~511u;
    const int rank = blockIdx.x & 1, ch0 = blockIdx.x * 8, c16 = ch0 & ~15, t0 = rank * 1024;
    const int t = threadIdx.x, warp = t >> 5, lane = t & 31;
    const uint32_t bar = sb + B_SM_BAR, barQ = bar + 64, barU = bar + 72, barY = bar + 80, flag = bar + 88;
    SP(0);
    if (lane == 0 && warp < 16 && blockIdx.x < 128) {
        const int i = warp >> 1;
        if (warp & 1) {
            if (i < 3) { mbar_init(barQ + i * 8, 1); mbar_expect_tx(barQ + i * 8, i ? 16384 : 32768); }
            if (i == 3) sts32(flag, 0);
        } else {
            mbar_init(bar + i * 8, 1);
            asm volatile("fence.mbarrier_init.release.cluster;" ::: "memory");
            mbar_expect_tx(bar + i * 8, B_KBOX + 4096);
            tma_load_2d(sb + B_SM_KT + i * B_KBOX, &mapK, c16, t0 + i * 128 - 8, bar + i * 8, EF(0));
            tma_load_2d(sb + B_SM_VT + i * 4096, &mapV, c16, t0 + i * 128, bar + i * 8, EF(0));
        }
        asm volatile("fence.mbarrier_init.release.cluster;" ::: "memory");
    }
    __syncwarp();
    if (warp == 14) SP2(14);
    KT_START(1);
    if (warp == 17) {
        launch_dependents();
        asm volatile("barrier.cluster.arrive.relaxed.aligned;" ::: "memory");
        measure_distance(mbox, lane);
        asm volatile("barrier.cluster.wait.aligned;" ::: "memory");
        KT_MARK(14);
        return;
    }
    if (blockIdx.x >= 128) return;
    if (warp == 16) {
        asm volatile("barrier.cluster.arrive.relaxed.aligned; barrier.cluster.wait.aligned;" ::: "memory");
        SP2(8);
        if (Q_LATE) for (int i = 0; i < 8; i++) { mbar_wait_w(bar + i * 8, 0); SP2(i); }
        if (lane < 8) tma_load_2d(sb + B_SM_QT + lane * 4096, &mapQ, c16, t0 + lane * 128, barQ, EF(3));
        if (!Q_LATE) for (int i = 0; i < 8; i++) mbar_wait_w(bar + i * 8, 0);
        if (lane == 0) {
            l2_prefetch(ci.x + blockIdx.x * 2048, 2048);
            if (blockIdx.x < 8) l2_prefetch(ci.mem0 + blockIdx.x * 2048, 2048);
        }
        uint32_t v[PF_DEPTH], acc = 0;
#pragma unroll
        for (int u = 0; u < PF_DEPTH; u++) v[u] = 0;
        constexpr int PER = 32 * PF_STRIDE, NW = 65536 / PER;
#pragma unroll 1
        for (int i = 0; i < 4 * NW && lds_volatile(flag) == 0; i += PF_DEPTH) {
#pragma unroll
            for (int u = 0; u < PF_DEPTH; u++) {
                const char* a = ci.w[(i + u) / NW] + blockIdx.x * 65536 + ((i + u) % NW) * PER + lane * PF_STRIDE;
                acc |= v[u];
                asm volatile("ld.global.cg.L2::256B.u32 %0, [%1];" : "=r"(v[u]) : "l"(a) : "memory");
            }
        }
#pragma unroll
        for (int u = 0; u < PF_DEPTH; u++) acc |= v[u];
        if (acc == 0x7FFF7FFFu && v[0] == 0x7FFEu) g_err = 1;
        SP2(12);
        KT_MARK(15);
        return;
    }
    asm volatile("barrier.cluster.arrive.relaxed.aligned;" ::: "memory");
    const int far = warp & 1, unit = rank ^ far;
    uint32_t w[4];
    uint32_t d2;
    asm volatile("ld.global.nc.u32 %0, [%1];" : "=r"(d2) : "l"(Dv + ch0 + (warp >> 2) * 2));
    {
        const int ch = warp & 7, half = warp >> 3;
        const uint32_t kb = sb + B_SM_K + ch * B_KCH;
        const uint4* src = reinterpret_cast<const uint4*>(ssmk + (size_t)(ch0 + ch) * S_LEN);
        uint4 kr[4];
#pragma unroll
        for (int i = 0; i < 4; i++) kr[i] = ldg128(src + half * 128 + i * 32 + lane, EF(1));
        const uint32_t edge = half ? 0u : __ldg(reinterpret_cast<const uint32_t*>(src + 128));
        const uint2 sw = __ldg(reinterpret_cast<const uint2*>(shiftk + (size_t)(c16 + unit * 8 + (lane >> 2)) * 4));
        w[0] = __byte_perm(sw.x, 0, 0x1010); w[1] = __byte_perm(sw.x, 0, 0x3232); w[2] = __byte_perm(sw.y, 0, 0x1010); w[3] = __byte_perm(sw.y, 0, 0x3232);
        if (half) sts128(sb + B_SM_U + ch * B_UCH + 4096 + lane * 16, make_uint4(0, 0, 0, 0));
#pragma unroll
        for (int i = 0; i < 4; i++) {
            const uint4 lo = kr[i];
            const uint32_t nx = __shfl_down_sync(~0u, lo.x, 1), n0 = (i < 3) ? __shfl_sync(~0u, kr[i < 3 ? i + 1 : 3].x, 0) : edge;
            const uint32_t hix = (lane < 31) ? nx : n0;
            const int c = 256 - (half * 128 + 32 * i + lane);
            sts128(kb + c * 16, make_uint4(__byte_perm(hix, lo.w, 0x7610), __byte_perm(lo.w, lo.z, 0x7610), __byte_perm(lo.z, lo.y, 0x7610), __byte_perm(lo.y, lo.x, 0x7610)));
            sts128(kb + B_KLEN * 2 + 64 + c * 16, make_uint4(__byte_perm(lo.w, lo.w, 0x1032), __byte_perm(lo.z, lo.z, 0x1032), __byte_perm(lo.y, lo.y, 0x1032), __byte_perm(lo.x, lo.x, 0x1032)));
        }
        const uint32_t k0w = __shfl_sync(~0u, kr[0].x, 0);
        if (half == 0 && lane < 8) {
            sts128(kb + (257 + lane) * 16, make_uint4(lane == 0 ? (k0w & 0xFFFFu) : 0u, 0u, 0u, 0u));
            sts128(kb + B_KLEN * 2 + 64 + (257 + lane) * 16, make_uint4(0u, 0u, 0u, 0u));
        }
    }
    auto sentinels = [&]() {
        const uint4 sent = make_uint4(SENT, SENT, SENT, SENT);
        char* p0 = mbox + blockIdx.x * 16384 + t * 16;
        if (blockIdx.x != 0 || (t & 255) >= 32) stg128(p0, sent);
        stg128(p0 + 8192, sent);
        char* p1 = mbox + WIN + blockIdx.x * 12800 + t * 16;
        stg128(p1, sent);
        if (t < 288) stg128(p1 + 8192, sent);
    };
    if (SENT_AT == 1) sentinels();
    asm volatile("barrier.cluster.wait.acquire.aligned;" ::: "memory");
    SP(1);
    {
        const int box = warp >> 1, row0 = 63 - 32 * rank - 4 * box;
        const uint32_t kt = sb + B_SM_KT + box * B_KBOX + 256 + lane * 32, s0 = (unit ^ ((lane >> 2) & 1)) * 16;
        const uint32_t a0 = kt + s0, a2 = kt - 64 + (unit ^ (((lane + 6) >> 2) & 1)) * 16, a4 = kt - 128 + (s0 ^ 16), av = sb + B_SM_VT + box * 4096 + lane * 32 + s0;
        const uint32_t ul = (lane & 7) * B_UCH + row0 * 64 + (lane >> 3) * 16;
        const uint32_t ud = sb + (far ? B_SM_S + (lane & 7) * (B_SCH - B_UCH) - (1 - rank) * 2048 : B_SM_U);
        mbar_wait_w(bar + box * 8, 0);
        SP(2);
#pragma unroll
        for (int i = 0; i < 4; i++) {
            uint32_t k0[4], k2[4], k4[4], vv[4], o[4];
            ldsm4t(k0, a0 + i * 1024); ldsm4t(k2, a2 + i * 1024); ldsm4t(k4, a4 + i * 1024); ldsm4t(vv, av + i * 1024);
#pragma unroll
            for (int j = 0; j < 4; j++) {
                uint32_t a = bf16_mul(__byte_perm(k4[j], k2[j], 0x5432), w[3]);
                a = bf16_add(a, bf16_mul(k2[j], w[2]));
                a = bf16_add(a, bf16_mul(__byte_perm(k2[j], k0[j], 0x5432), w[1]));
                a = bf16_add(a, bf16_mul(k0[j], w[0]));
                o[j] = bf16_mul(a, vv[j]);
            }
            stsm4(ud + swz64(ul - i * 64), o[0], o[1], o[2], o[3]);
        }
        fence_async();
        __syncwarp();
        if (far && lane < 8) {
            const uint32_t o = lane * B_UCH + (row0 - 3) * 64;
            copy_to_peer(peer_addr(sb + B_SM_U + o, rank ^ 1), ud + o, 256, peer_addr(barU, rank ^ 1));
        }
    }
    bar_sync(1, 512);
    mbar_wait_w(barU, 0);
    if (SENT_AT == 2) sentinels();
    SP(3);
    const int wg = warp >> 2, wq = warp & 3, hi = wq >> 1, g = lane >> 2, tq = lane & 3;
    const uint32_t zero = lds32(sb + B_SM_U + 4096);
#pragma unroll 1
    for (int cc = 0; cc < 2; cc++) {
        const int ch = 2 * wg + cc;
        const uint32_t kb = sb + B_SM_K + ch * B_KCH, ub = sb + B_SM_U + ch * B_UCH;
        const uint32_t dw = __byte_perm(d2, 0, cc ? 0x3232 : 0x1010);
        const int e0 = B_C - g + 2 * tq;
        const uint32_t f0 = ((e0 & 1) ? (kb + B_KLEN * 2 + 64 + (e0 - 1) * 2) : (kb + e0 * 2)) - 32 * wq;
        const uint32_t lo = uniform((ub >> 4) | 0x10000);
        float d[32];
#pragma unroll
        for (int i = 0; i < 32; i++) d[i] = 0.f;
        uint32_t A[2][2][4];
        static_for<0, 32>([&](auto jc) {
            constexpr int j = decltype(jc)::value, N = 64 - 8 * (j / 4);
            if (j >= 2) wg_wait<1>();
            uint32_t(&a)[4] = A[j & 1][0];
            uint32_t(&b)[4] = A[j & 1][1];
            a[0] = lds32(f0 - 128 * j); a[1] = lds32(f0 - 128 * j - 16); a[2] = lds32(f0 - 128 * j + 16);
            b[0] = lds32(f0 - 128 * j + 32); b[2] = lds32(f0 - 128 * j + 48);
            a[3] = a[0] ^ zero; b[1] = a[2] ^ zero; b[3] = b[0] ^ zero;
            wg_fence();
            wgmma_conv<N, 8 * j>(d, a, lo);
            wgmma_conv<N, 8 * j + 2>(d, b, lo);
            wg_commit();
        });
        wg_wait<0>();
        if (cc) SP(4);
        if (PF_STOP == 1 && cc && t == 0) sts32(flag, 1);
        bar_sync(2 + wg, 128);
        if (!hi && tq == 3) { float x = d[13]; d[13] = d[29]; d[29] = x; x = d[15]; d[15] = d[31]; d[31] = x; }
        if (hi && tq == 0) { d[0] = 0.f; d[2] = 0.f; }
        {
            const uint32_t xs = kb + (wq ^ 2) * 2048 + lane * 4;
            const uint32_t xn = hi ? xs + (tq ? 124 : 140) : xs + (tq < 3 ? 4 : -12), wrap = hi ? (tq ? 0 : -1) : (tq < 3 ? 0 : 1);
#pragma unroll
            for (int nb = 0; nb < 4; nb++) {
                const uint32_t xw = xn + ((nb + wrap) & 3) * 512;
#pragma unroll
                for (int i = 0; i < 2; i++) {
                    const float e0v = hi ? d[4 * nb + 2 * i] : d[16 + 4 * nb + 2 * i], e1v = hi ? d[4 * nb + 2 * i + 1] : d[16 + 4 * nb + 2 * i + 1];
                    sts32(hi ? xw + i * 256 : xs + nb * 512 + i * 256 + 128, __float_as_uint(e0v));
                    sts32(hi ? xs + nb * 512 + i * 256 : xw + i * 256, __float_as_uint(e1v));
                }
            }
        }
        bar_sync(2 + wg, 128);
#pragma unroll
        for (int p = 0; p < 2; p++) {
            int row = 16 * p + (lane >> 4) * 8 + (lane & 7);
            row = hi ? row + 31 : row == 31 ? 63 : row;
            const uint32_t a = sb + B_SM_U + swz64(ch * B_UCH + row * 64 + ((wq & 1) * 2 + ((lane >> 3) & 1)) * 16);
            uint32_t u[4];
            ldsm4t(u, a);
#pragma unroll
            for (int b = 0; b < 4; b++) {
                const int r = 8 * p + 2 * b;
                const float y0 = (hi ? d[16 + r] : d[r]) + __uint_as_float(lds32(kb + wq * 2048 + r * 128 + lane * 4));
                const float y1 = (hi ? d[17 + r] : d[r + 1]) + __uint_as_float(lds32(kb + wq * 2048 + r * 128 + 128 + lane * 4));
                u[b] = bf16_add(pack_bf16(y0, y1), bf16_mul(u[b], dw));
            }
            stsm4t(a, u[0], u[1], u[2], u[3]);
        }
        fence_async();
        bar_sync(2 + wg, 128);
        if (SENT_AT == 3 && cc == 0) sentinels();
        if (wq == 0 && lane == 0) copy_to_peer(peer_addr(sb + B_SM_S + ch * B_SCH, rank ^ 1), ub + rank * 2048, 2048, peer_addr(barY, rank ^ 1));
    }
    if (PF_STOP == 2 && t == 0) sts32(flag, 1);
    SP(5);
    mbar_wait_w(barQ, 0);
    bar_sync(1, 512);
    mbar_wait_w(barY, 0);
    asm volatile("barrier.cluster.arrive.relaxed.aligned;" ::: "memory");
    SP(6);
#pragma unroll
    for (int i = 0; i < 4; i++) {
        const int fr = i & 1, row = 63 - 32 * rank - 2 * warp - (i >> 1);
        const uint32_t qa = sb + B_SM_QT + warp * 2048 + (i >> 1) * 1024 + lane * 32 + ((rank ^ fr ^ (lane >> 2)) & 1) * 16;
        uint32_t y[4], q[4];
        ldsm4t(y, sb + (fr ? B_SM_S + (lane & 7) * (B_SCH - B_UCH) - (1 - rank) * 2048 : B_SM_U) + swz64((lane & 7) * B_UCH + row * 64 + (lane >> 3) * 16));
        ldsm4(q, qa);
        stsm4(qa, bf16_mul(q[0], y[0]), bf16_mul(q[1], y[1]), bf16_mul(q[2], y[2]), bf16_mul(q[3], y[3]));
    }
    fence_async();
    __syncwarp();
    if (lane == 0) {
        asm volatile("cp.async.bulk.tensor.2d.global.shared::cta.bulk_group.L2::cache_hint [%0, {%2, %3}], [%1], %4;"
                     ::"l"(&mapO), "r"(sb + B_SM_QT + warp * 2048), "r"(DM + c16), "r"(t0 + warp * 64), "l"(EF(4)) : "memory");
        asm volatile("cp.async.bulk.commit_group;" ::: "memory");
    }
    if (SENT_AT == 0) sentinels();
    if (warp == 0) SP2(10);
    if (lane == 0) asm volatile("cp.async.bulk.wait_group.read 0;" ::: "memory");
    __syncwarp();
    if (warp == 0) SP2(11);
    asm volatile("barrier.cluster.wait.aligned;" ::: "memory");
    SP(7);
    KT_END(1);
}

typedef CUresult (*EncodeFn)(CUtensorMap*, CUtensorMapDataType, cuuint32_t, void*, const cuuint64_t*, const cuuint64_t*, const cuuint32_t*,
                             const cuuint32_t*, CUtensorMapInterleave, CUtensorMapSwizzle, CUtensorMapL2promotion, CUtensorMapFloatOOBfill);

static void make_map(EncodeFn fn, CUtensorMap* m, const void* ptr, uint64_t inner, uint64_t outer, uint32_t box_in, uint32_t box_out,
                     CUtensorMapL2promotion promo = CU_TENSOR_MAP_L2_PROMOTION_L2_256B) {
    cuuint64_t dims[2] = {inner, outer};
    cuuint64_t strides[1] = {inner * 2};
    cuuint32_t box[2] = {box_in, box_out};
    cuuint32_t es[2] = {1, 1};
    fn(m, CU_TENSOR_MAP_DATA_TYPE_BFLOAT16, 2, const_cast<void*>(ptr), dims, strides, box, es, CU_TENSOR_MAP_INTERLEAVE_NONE,
       CU_TENSOR_MAP_SWIZZLE_128B, promo, CU_TENSOR_MAP_FLOAT_OOB_FILL_NONE);
}

#define G2_ST 7
#define PROMO_W CU_TENSOR_MAP_L2_PROMOTION_L2_256B
#define PROMO_O CU_TENSOR_MAP_L2_PROMOTION_L2_256B
#define SSM_PROMO CU_TENSOR_MAP_L2_PROMOTION_NONE
extern "C" void kernel_launch(void* const* d_in, const int* in_sizes, int n_in, void* d_out, int out_size) {
    const bf16* x = (const bf16*)d_in[0];
    const bf16* mem0 = (const bf16*)d_in[1];
    const bf16* Wq = (const bf16*)d_in[2];
    const bf16* Wk = (const bf16*)d_in[3];
    const bf16* Wv = (const bf16*)d_in[4];
    const bf16* Wo = (const bf16*)d_in[5];
    const bf16* Bq = (const bf16*)d_in[7];
    const bf16* Bk = (const bf16*)d_in[8];
    const bf16* Bv = (const bf16*)d_in[9];
    const bf16* Bsh = (const bf16*)d_in[10];
    const bf16* Bssm = (const bf16*)d_in[11];
    const bf16* BD = (const bf16*)d_in[12];
    bf16* out = (bf16*)d_out;

    static bool init = false;
    static EncodeFn enc = nullptr;
    static void *p_tok, *p_ox, *p_mbox;
    static int nclusters = 64;
    if (!init) {
        cudaDriverEntryPointQueryResult qr;
        cudaGetDriverEntryPoint("cuTensorMapEncodeTiled", (void**)&enc, cudaEnableDefault, &qr);
        cudaGetSymbolAddress(&p_tok, g_tok);
        cudaGetSymbolAddress(&p_ox, g_ox);
        cudaGetSymbolAddress(&p_mbox, g_mbox);
        cudaFuncSetAttribute(proj_kernel<96, G2_ST>, cudaFuncAttributeMaxDynamicSharedMemorySize, PROJ_SMEM);
        cudaFuncSetAttribute(proj_kernel<128, 7>, cudaFuncAttributeMaxDynamicSharedMemorySize, PROJ_SMEM);
        cudaFuncSetAttribute(chain_kernel, cudaFuncAttributeMaxDynamicSharedMemorySize, CHAIN_SMEM);
        cudaFuncSetAttribute(ssm_kernel, cudaFuncAttributeMaxDynamicSharedMemorySize, B_SMEM);
        cudaLaunchConfig_t cfg = {};
        cfg.gridDim = dim3(132); cfg.blockDim = dim3(384); cfg.dynamicSmemBytes = CHAIN_SMEM;
        cudaLaunchAttribute at[1];
        at[0].id = cudaLaunchAttributeClusterDimension; at[0].val.clusterDim.x = 2; at[0].val.clusterDim.y = 1; at[0].val.clusterDim.z = 1;
        cfg.attrs = at; cfg.numAttrs = 1;
        int n = 0;
        if (cudaOccupancyMaxActiveClusters(&n, chain_kernel, &cfg) == cudaSuccess && n > 64) nclusters = n < 66 ? n : 66;
        (void)cudaGetLastError();
        init = true;
    }
    char* mbox = (char*)(((uintptr_t)p_mbox + 2 * WIN - 1) & ~(uintptr_t)(2 * WIN - 1));
    CUtensorMap mX, mT32, mT16, mTQ, mKV, mWq, mWk, mWv, mWoC, mWo, mOxE, mOutE, mOx, mOut;
    {
        cuuint64_t dims[3] = {64, S_LEN, DM / 64};
        cuuint64_t strides[2] = {DM * 2, 128};
        cuuint32_t box[3] = {64, 32, 4};
        cuuint32_t es[3] = {1, 1, 1};
        enc(&mX, CU_TENSOR_MAP_DATA_TYPE_BFLOAT16, 3, const_cast<bf16*>(x), dims, strides, box, es, CU_TENSOR_MAP_INTERLEAVE_NONE,
            CU_TENSOR_MAP_SWIZZLE_128B, CU_TENSOR_MAP_L2_PROMOTION_L2_256B, CU_TENSOR_MAP_FLOAT_OOB_FILL_NONE);
    }
    make_map(enc, &mT32, p_tok, DH, 4 * NH * 3 * SEG, 64, 32, CU_TENSOR_MAP_L2_PROMOTION_L2_128B);
    make_map(enc, &mT16, p_tok, DH, 4 * NH * 3 * SEG, 64, 16, CU_TENSOR_MAP_L2_PROMOTION_L2_128B);
    {
        cuuint64_t dims[2] = {512, 4 * NH * 12};
        cuuint64_t strides[1] = {2048};
        cuuint32_t box[2] = {256, 4};
        cuuint32_t es[2] = {1, 1};
        enc(&mTQ, CU_TENSOR_MAP_DATA_TYPE_UINT32, 2, p_tok, dims, strides, box, es, CU_TENSOR_MAP_INTERLEAVE_NONE,
            CU_TENSOR_MAP_SWIZZLE_NONE, CU_TENSOR_MAP_L2_PROMOTION_L2_128B, CU_TENSOR_MAP_FLOAT_OOB_FILL_NONE);
    }
    {
        cuuint64_t dims[3] = {64, 4 * NH * 3 * SEG, 2};
        cuuint64_t strides[2] = {DH * 2, 128};
        cuuint32_t box[3] = {64, 32, 2};
        cuuint32_t es[3] = {1, 1, 1};
        enc(&mKV, CU_TENSOR_MAP_DATA_TYPE_BFLOAT16, 3, p_tok, dims, strides, box, es, CU_TENSOR_MAP_INTERLEAVE_NONE,
            CU_TENSOR_MAP_SWIZZLE_128B, CU_TENSOR_MAP_L2_PROMOTION_L2_128B, CU_TENSOR_MAP_FLOAT_OOB_FILL_NONE);
    }
    make_map(enc, &mWq, Wq, HD, DM, 64, 16, CU_TENSOR_MAP_L2_PROMOTION_L2_128B);
    make_map(enc, &mWk, Wk, HD, DM, 64, 16, CU_TENSOR_MAP_L2_PROMOTION_L2_128B);
    make_map(enc, &mWv, Wv, HD, DM, 64, 16, CU_TENSOR_MAP_L2_PROMOTION_L2_128B);
    make_map(enc, &mWoC, Wo, DM, HD, 64, 128, CU_TENSOR_MAP_L2_PROMOTION_L2_128B);
    const bool early = nclusters >= 66;
    make_map(enc, &mWo, Wo, DM, HD, 64, 64, PROMO_W);
    make_map(enc, &mOxE, p_ox, HD, S_LEN, 64, EARLY_NT / 2);
    make_map(enc, &mOutE, out, OUT_LD, S_LEN, 64, EARLY_NT);
    make_map(enc, &mOx, p_ox, HD, S_LEN, 64, (early ? 96 : 128) >> FIN_SO, PROMO_O);
    make_map(enc, &mOut, out, OUT_LD, S_LEN, 64, early ? 96 : 128);

    CUtensorMap mB[4];
    for (int i = 0; i < 4; i++) {
        cuuint64_t dims[2] = {(cuuint64_t)(i < 3 ? DM : OUT_LD), S_LEN};
        cuuint64_t strides[1] = {dims[0] * 2};
        cuuint32_t box[2] = {16, i == 0 ? 136u : i < 3 ? 128u : 64u};
        cuuint32_t es[2] = {1, 1};
        enc(&mB[i], CU_TENSOR_MAP_DATA_TYPE_BFLOAT16, 2, const_cast<bf16*>(i == 0 ? Bk : i == 1 ? Bv : i == 2 ? Bq : out), dims, strides, box, es,
            CU_TENSOR_MAP_INTERLEAVE_NONE, CU_TENSOR_MAP_SWIZZLE_32B, SSM_PROMO, CU_TENSOR_MAP_FLOAT_OOB_FILL_NONE);
    }
    cudaStream_t st = cudaStreamPerThread;
    const ChainInputs ci = {{(const char*)Wv, (const char*)Wk, (const char*)Wq, (const char*)Wo}, (const char*)x, (const char*)mem0};
    ssm_kernel<<<132, 576, B_SMEM, st>>>(mB[0], mB[1], mB[2], mB[3], Bsh, Bssm, BD, mbox, ci);
    cudaLaunchAttribute pdl[1];
    pdl[0].id = cudaLaunchAttributeProgrammaticStreamSerialization; pdl[0].val.programmaticStreamSerializationAllowed = 1;
    cudaLaunchConfig_t lc = {};
    lc.stream = st; lc.attrs = pdl;
    lc.gridDim = dim3(2 * nclusters); lc.blockDim = dim3(384); lc.dynamicSmemBytes = CHAIN_SMEM; lc.numAttrs = PDL & 1;
    cudaLaunchKernelEx(&lc, chain_kernel, mX, mT32, mT16, mTQ, mKV, mWq, mWk, mWv, mWoC, mem0, mbox);
    lc.gridDim = dim3(2 * nclusters); lc.blockDim = dim3(288); lc.dynamicSmemBytes = PROJ_SMEM; lc.numAttrs = (PDL >> 1) & 1;
    cudaLaunchKernelEx(&lc, early ? proj_kernel<96, G2_ST> : proj_kernel<128, 7>, mWo, mOx, mOut, mOxE, mOutE);
}
```

```cpp
#include <cuda_runtime.h>
#include <cuda_bf16.h>
#include <cuda.h>
#include <stdint.h>
#include <type_traits>

typedef __nv_bfloat16 bf16;

constexpr int S_LEN = 2048, DM = 1024, NH = 32, DH = 128, NSEG = 64, SEG = 32;
constexpr int HD = NH * DH;
constexpr int OUT_LD = 2048;
constexpr unsigned SENT = 0xFFFFFFFFu;

__device__ bf16 g_tok[4 * NH * 3 * SEG * DH];
__device__ bf16 g_ox[(size_t)S_LEN * HD];
__device__ uint4 g_mbox[4 * 131072];
__device__ unsigned g_xflag[128];
__device__ unsigned g_reg[4];
__device__ __align__(16) unsigned g_cls[256];
__device__ unsigned g_err;
constexpr uint32_t WIN = 2u << 20;
__host__ __device__ constexpr uint32_t page_off(uint32_t idx, uint32_t c) {
    return ((idx & 1) << 13) | ((idx >> 1) << 16) | (((c ^ idx ^ (idx >> 1) ^ (idx >> 2) ^ (idx >> 4)) & 1) << 12);
}
#define STAT(i, c) (void)(c)
#define EARLY_ROLE 1
#define PDL 3

__device__ __forceinline__ void launch_dependents() { asm volatile("griddepcontrol.launch_dependents;" ::: "memory"); }
__device__ __forceinline__ void wait_prerequisites() { asm volatile("griddepcontrol.wait;" ::: "memory"); }
__device__ __forceinline__ void prefetch_map(const CUtensorMap* m) { asm volatile("prefetch.tensormap [%0];" ::"l"(m) : "memory"); }
#define KT_MARK(k)
#define KT_START(k)
#define KT_END(k)

__device__ __forceinline__ uint32_t smem_u32(const void* p) { return (uint32_t)__cvta_generic_to_shared(p); }
__device__ __forceinline__ void ldsm4(uint32_t& r0, uint32_t& r1, uint32_t& r2, uint32_t& r3, uint32_t a) {
    asm volatile("ldmatrix.sync.aligned.m8n8.x4.shared.b16 {%0,%1,%2,%3}, [%4];" : "=r"(r0), "=r"(r1), "=r"(r2), "=r"(r3) : "r"(a) : "memory");
}
__device__ __forceinline__ void ldsm4t(uint32_t& r0, uint32_t& r1, uint32_t& r2, uint32_t& r3, uint32_t a) {
    asm volatile("ldmatrix.sync.aligned.m8n8.x4.trans.shared.b16 {%0,%1,%2,%3}, [%4];" : "=r"(r0), "=r"(r1), "=r"(r2), "=r"(r3) : "r"(a) : "memory");
}
__device__ __forceinline__ void ldsm2(uint32_t& r0, uint32_t& r1, uint32_t a) {
    asm volatile("ldmatrix.sync.aligned.m8n8.x2.shared.b16 {%0,%1}, [%2];" : "=r"(r0), "=r"(r1) : "r"(a) : "memory");
}
__device__ __forceinline__ void stg128(void* p, uint4 v) {
    asm volatile("st.global.v4.u32 [%0], {%1,%2,%3,%4};" ::"l"(p), "r"(v.x), "r"(v.y), "r"(v.z), "r"(v.w) : "memory");
}
__device__ __forceinline__ void stsm4(uint32_t a, uint32_t r0, uint32_t r1, uint32_t r2, uint32_t r3) {
    asm volatile("stmatrix.sync.aligned.m8n8.x4.shared.b16 [%0], {%1,%2,%3,%4};" ::"r"(a), "r"(r0), "r"(r1), "r"(r2), "r"(r3) : "memory");
}
__device__ __forceinline__ void mma16816(float (&d)[4], uint32_t a0, uint32_t a1, uint32_t a2, uint32_t a3, uint32_t b0, uint32_t b1) {
    asm("mma.sync.aligned.m16n8k16.row.col.f32.bf16.bf16.f32 {%0,%1,%2,%3},{%4,%5,%6,%7},{%8,%9},{%0,%1,%2,%3};"
                 : "+f"(d[0]), "+f"(d[1]), "+f"(d[2]), "+f"(d[3])
                 : "r"(a0), "r"(a1), "r"(a2), "r"(a3), "r"(b0), "r"(b1));
}
__device__ __forceinline__ void mma1688(float (&d)[4], uint32_t a0, uint32_t a1, uint32_t b0) {
    asm("mma.sync.aligned.m16n8k8.row.col.f32.bf16.bf16.f32 {%0,%1,%2,%3},{%4,%5},{%6},{%0,%1,%2,%3};"
        : "+f"(d[0]), "+f"(d[1]), "+f"(d[2]), "+f"(d[3]) : "r"(a0), "r"(a1), "r"(b0));
}
__device__ __forceinline__ uint32_t movmat(uint32_t a) {
    uint32_t d;
    asm volatile("movmatrix.sync.aligned.m8n8.trans.b16 %0, %1;" : "=r"(d) : "r"(a));
    return d;
}
__device__ __forceinline__ uint32_t pack_bf16(float lo, float hi) {
    uint32_t r;
    asm("cvt.rn.bf16x2.f32 %0, %1, %2;" : "=r"(r) : "f"(hi), "f"(lo));
    return r;
}
__device__ __forceinline__ uint32_t bf16_mul(uint32_t a, uint32_t b) {
    uint32_t d;
    asm("mul.rn.bf16x2 %0, %1, %2;" : "=r"(d) : "r"(a), "r"(b));
    return d;
}
__device__ __forceinline__ uint32_t bf16_add(uint32_t a, uint32_t b) {
    uint32_t d;
    asm("add.rn.bf16x2 %0, %1, %2;" : "=r"(d) : "r"(a), "r"(b));
    return d;
}

__device__ __forceinline__ float bf16_round(float x) { return __bfloat162float(__float2bfloat16_rn(x)); }
__device__ __forceinline__ float bf_lo(uint32_t w) { return __uint_as_float(w << 16); }
__device__ __forceinline__ float bf_hi(uint32_t w) { return __uint_as_float(w & 0xFFFF0000u); }
__device__ __forceinline__ void bar_sync(int id, int n) { asm volatile("bar.sync %0, %1;" ::"r"(id), "r"(n) : "memory"); }
__device__ __forceinline__ void bar_sync_keep(int id, int n, uint32_t a, uint32_t b) {
    asm volatile("bar.sync %0, %1; // %2 %3" ::"r"(id), "r"(n), "r"(a), "r"(b) : "memory");
}
__device__ __forceinline__ bool bar_red_or(int id, int n, bool p) {
    uint32_t r;
    asm volatile("{.reg .pred p, q; setp.ne.u32 p, %3, 0; bar.red.or.pred q, %1, %2, p; selp.u32 %0, 1, 0, q;}" : "=r"(r) : "r"(id), "r"(n), "r"((uint32_t)p) : "memory");
    return r != 0;
}
__device__ __forceinline__ void bar_arrive(int id, int n) { asm volatile("bar.arrive %0, %1;" ::"r"(id), "r"(n) : "memory"); }
__device__ __forceinline__ void cp_async16(uint32_t dst, const void* src) {
    asm volatile("cp.async.cg.shared.global [%0], [%1], 16;" ::"r"(dst), "l"(src) : "memory");
}
__device__ __forceinline__ void cp_commit() { asm volatile("cp.async.commit_group;" ::: "memory"); }
template <int N> __device__ __forceinline__ void cp_wait() { asm volatile("cp.async.wait_group %0;" ::"n"(N) : "memory"); }
__device__ __forceinline__ uint4 ld_relaxed_v4(const void* p) {
    uint4 v;
    asm volatile("ld.relaxed.gpu.global.v4.u32 {%0,%1,%2,%3}, [%4];" : "=r"(v.x), "=r"(v.y), "=r"(v.z), "=r"(v.w) : "l"(p) : "memory");
    return v;
}
__device__ __forceinline__ void st_relaxed_u32(void* p, uint32_t v) { asm volatile("st.relaxed.gpu.global.u32 [%0], %1;" ::"l"(p), "r"(v) : "memory"); }
__device__ __forceinline__ void st_relaxed_v2(void* p, uint32_t a, uint32_t b) {
    asm volatile("st.relaxed.gpu.global.v2.u32 [%0], {%1,%2};" ::"l"(p), "r"(a), "r"(b) : "memory");
}
__device__ __forceinline__ void sts128(uint32_t a, uint4 v) {
    asm volatile("st.shared.v4.u32 [%0], {%1,%2,%3,%4};" ::"r"(a), "r"(v.x), "r"(v.y), "r"(v.z), "r"(v.w) : "memory");
}
__device__ __forceinline__ uint4 lds128(uint32_t a) {
    uint4 v;
    asm volatile("ld.shared.v4.u32 {%0,%1,%2,%3}, [%4];" : "=r"(v.x), "=r"(v.y), "=r"(v.z), "=r"(v.w) : "r"(a) : "memory");
    return v;
}
__device__ __forceinline__ void sts32(uint32_t a, uint32_t v) { asm volatile("st.shared.u32 [%0], %1;" ::"r"(a), "r"(v) : "memory"); }
__device__ __forceinline__ uint32_t lds32(uint32_t a) {
    uint32_t v;
    asm volatile("ld.shared.u32 %0, [%1];" : "=r"(v) : "r"(a) : "memory");
    return v;
}
__device__ __forceinline__ void mbar_init(uint32_t a, uint32_t c) { asm volatile("mbarrier.init.shared::cta.b64 [%0], %1;" ::"r"(a), "r"(c) : "memory"); }
__device__ __forceinline__ void mbar_expect_tx(uint32_t a, uint32_t bytes) {
    asm volatile("mbarrier.arrive.expect_tx.shared::cta.b64 _, [%0], %1;" ::"r"(a), "r"(bytes) : "memory");
}
__device__ __forceinline__ void mbar_arrive(uint32_t a) { asm volatile("mbarrier.arrive.shared::cta.b64 _, [%0];" ::"r"(a) : "memory"); }
__device__ __forceinline__ void mbar_wait(uint32_t a, uint32_t parity) {
    asm volatile("{.reg .pred p; .reg .u32 c;\n"
                 "mov.u32 c, 0;\n"
                 "MBW_LOOP:\n"
                 "add.u32 c, c, 1;\n"
                 "setp.gt.u32 p, c, 0x10000;\n"
                 "@!p mbarrier.try_wait.parity.shared::cta.b64 p, [%0], %1;\n"
                 "@!p bra.uni MBW_LOOP;}" ::"r"(a), "r"(parity) : "memory");
}
__device__ __forceinline__ void mbar_wait_w(uint32_t a, uint32_t parity) {
    asm volatile("{.reg .pred p; .reg .u32 c;\n"
                 "mov.u32 c, 0;\n"
                 "MBW_LOOP:\n"
                 "add.u32 c, c, 1;\n"
                 "setp.gt.u32 p, c, 0x10000;\n"
                 "@!p mbarrier.try_wait.parity.shared::cta.b64 p, [%0], %1;\n"
                 "vote.sync.all.pred p, p, 0xFFFFFFFF;\n"
                 "@!p bra.uni MBW_LOOP;}" ::"r"(a), "r"(parity) : "memory");
}
__device__ __forceinline__ void mbar_expect_tx_if0(uint32_t sel, uint32_t a, uint32_t bytes) {
    asm volatile("{.reg .pred p; setp.eq.u32 p, %2, 0; @p mbarrier.arrive.expect_tx.shared::cta.b64 _, [%0], %1;}" ::"r"(a), "r"(bytes), "r"(sel) : "memory");
}
__device__ __forceinline__ void mbar_arrive_if0(uint32_t sel, uint32_t a) {
    asm volatile("{.reg .pred p; setp.eq.u32 p, %1, 0; @p mbarrier.arrive.shared::cta.b64 _, [%0];}" ::"r"(a), "r"(sel) : "memory");
}
__device__ __forceinline__ void bulk_load(uint32_t dst, const void* src, uint32_t bytes, uint32_t bar) {
    asm volatile("cp.async.bulk.shared::cluster.global.mbarrier::complete_tx::bytes [%0], [%1], %2, [%3];" ::"r"(dst), "l"(src), "r"(bytes), "r"(bar) : "memory");
}
__device__ __forceinline__ void tma_load_2d(uint32_t dst, const CUtensorMap* map, int c0, int c1, uint32_t bar) {
    asm volatile("cp.async.bulk.tensor.2d.shared::cluster.global.mbarrier::complete_tx::bytes [%0], [%1, {%3, %4}], [%2];"
                 ::"r"(dst), "l"(map), "r"(bar), "r"(c0), "r"(c1) : "memory");
}
__device__ __forceinline__ void tma_load_2d_both(uint32_t dst, const CUtensorMap* map, int c0, int c1, uint32_t bar) {
    asm volatile("cp.async.bulk.tensor.2d.shared::cluster.global.mbarrier::complete_tx::bytes.multicast::cluster [%0], [%1, {%3, %4}], [%2], %5;"
                 ::"r"(dst), "l"(map), "r"(bar), "r"(c0), "r"(c1), "h"((uint16_t)3) : "memory");
}
__device__ __forceinline__ uint64_t policy_evict_first() {
    uint64_t p;
    asm("createpolicy.fractional.L2::evict_first.b64 %0, 1.0;" : "=l"(p));
    return p;
}
__device__ __forceinline__ uint64_t policy_evict_normal() {
    uint64_t p;
    asm("createpolicy.fractional.L2::evict_normal.b64 %0, 1.0;" : "=l"(p));
    return p;
}
__device__ __forceinline__ void tma_load_2d(uint32_t dst, const CUtensorMap* map, int c0, int c1, uint32_t bar, uint64_t pol) {
    asm volatile("cp.async.bulk.tensor.2d.shared::cluster.global.mbarrier::complete_tx::bytes.L2::cache_hint [%0], [%1, {%3, %4}], [%2], %5;"
                 ::"r"(dst), "l"(map), "r"(bar), "r"(c0), "r"(c1), "l"(pol) : "memory");
}
__device__ __forceinline__ uint4 ldg128(const void* p, uint64_t pol) {
    uint4 v;
    asm("ld.global.nc.L2::cache_hint.v4.u32 {%0,%1,%2,%3}, [%4], %5;" : "=r"(v.x), "=r"(v.y), "=r"(v.z), "=r"(v.w) : "l"(p), "l"(pol));
    return v;
}
__device__ __forceinline__ void stg128(void* p, uint4 v, uint64_t pol) {
    asm volatile("st.global.L2::cache_hint.v4.u32 [%0], {%1,%2,%3,%4}, %5;" ::"l"(p), "r"(v.x), "r"(v.y), "r"(v.z), "r"(v.w), "l"(pol) : "memory");
}
__device__ __forceinline__ void tma_store_2d(const CUtensorMap* map, uint32_t src, int c0, int c1) {
    asm volatile("cp.async.bulk.tensor.2d.global.shared::cta.bulk_group [%0, {%2, %3}], [%1];" ::"l"(map), "r"(src), "r"(c0), "r"(c1) : "memory");
}
__device__ __forceinline__ char* make_ptr(uint32_t lo, uint32_t hi) {
    uint64_t p;
    asm("mov.b64 %0, {%1, %2};" : "=l"(p) : "r"(lo), "r"(hi));
    return reinterpret_cast<char*>(p);
}
__device__ __forceinline__ uint64_t make_desc(uint32_t saddr, uint32_t lbo, uint32_t sbo) {
    return (uint64_t)((saddr & 0x3FFFF) >> 4) | ((uint64_t)((lbo >> 4) & 0x3FFF) << 16) | ((uint64_t)((sbo >> 4) & 0x3FFF) << 32) | ((uint64_t)1 << 62);
}
__device__ __forceinline__ void wg_fence() { asm volatile("wgmma.fence.sync.aligned;" ::: "memory"); }
__device__ __forceinline__ void wg_commit() { asm volatile("wgmma.commit_group.sync.aligned;" ::: "memory"); }
template <int N> __device__ __forceinline__ void wg_wait() { asm volatile("wgmma.wait_group.sync.aligned %0;" ::"n"(N) : "memory"); }

#define R4(b) "+f"(d[b + 0]), "+f"(d[b + 1]), "+f"(d[b + 2]), "+f"(d[b + 3])
#define R16(b) R4(b), R4(b + 4), R4(b + 8), R4(b + 12)
template <int N> __device__ __forceinline__ void wgmma_proj(float (&d)[N / 2], uint64_t da, uint64_t db) {
    if constexpr (N == 96)
        asm volatile("wgmma.mma_async.sync.aligned.m64n96k16.f32.bf16.bf16 {"
            "%0,%1,%2,%3,%4,%5,%6,%7,%8,%9,%10,%11,%12,%13,%14,%15,%16,%17,%18,%19,%20,%21,%22,%23,%24,%25,%26,%27,%28,%29,%30,%31,%32,%33,%34,%35,%36,%37,%38,%39,"
            "%40,%41,%42,%43,%44,%45,%46,%47"
            "}, %48, %49, 1, 1, 1, 1, 0;" : R16(0), R16(16), R16(32) : "l"(da), "l"(db));
    if constexpr (N == 128)
        asm volatile("wgmma.mma_async.sync.aligned.m64n128k16.f32.bf16.bf16 {"
            "%0,%1,%2,%3,%4,%5,%6,%7,%8,%9,%10,%11,%12,%13,%14,%15,%16,%17,%18,%19,%20,%21,%22,%23,%24,%25,%26,%27,%28,%29,%30,%31,%32,%33,%34,%35,%36,%37,%38,%39,"
            "%40,%41,%42,%43,%44,%45,%46,%47,%48,%49,%50,%51,%52,%53,%54,%55,%56,%57,%58,%59,%60,%61,%62,%63"
            "}, %64, %65, 1, 1, 1, 1, 0;" : R16(0), R16(16), R16(32), R16(48) : "l"(da), "l"(db));
    if constexpr (N == 256)
        asm volatile("wgmma.mma_async.sync.aligned.m64n256k16.f32.bf16.bf16 {"
            "%0,%1,%2,%3,%4,%5,%6,%7,%8,%9,%10,%11,%12,%13,%14,%15,%16,%17,%18,%19,%20,%21,%22,%23,%24,%25,%26,%27,%28,%29,%30,%31,%32,%33,%34,%35,%36,%37,%38,%39,"
            "%40,%41,%42,%43,%44,%45,%46,%47,%48,%49,%50,%51,%52,%53,%54,%55,%56,%57,%58,%59,%60,%61,%62,%63,%64,%65,%66,%67,%68,%69,%70,%71,%72,%73,%74,%75,%76,%7"
            "7,%78,%79,%80,%81,%82,%83,%84,%85,%86,%87,%88,%89,%90,%91,%92,%93,%94,%95,%96,%97,%98,%99,%100,%101,%102,%103,%104,%105,%106,%107,%108,%109,%110,%111,"
            "%112,%113,%114,%115,%116,%117,%118,%119,%120,%121,%122,%123,%124,%125,%126,%127"
            "}, %128, %129, 1, 1, 1, 1, 0;" : R16(0), R16(16), R16(32), R16(48), R16(64), R16(80), R16(96), R16(112) : "l"(da), "l"(db));
}

__device__ __forceinline__ void wgmma_rs32(float (&d)[16], const uint32_t (&a)[4], uint64_t db, bool acc) {
    asm volatile(
        "{.reg .pred p; setp.ne.b32 p, %21, 0;\n"
        "wgmma.mma_async.sync.aligned.m64n32k16.f32.bf16.bf16 {%0,%1,%2,%3,%4,%5,%6,%7,%8,%9,%10,%11,%12,%13,%14,%15}, {%16,%17,%18,%19}, %20, p, 1, 1, 0;}"
        : R16(0) : "r"(a[0]), "r"(a[1]), "r"(a[2]), "r"(a[3]), "l"(db), "n"(1) );
}
__device__ __forceinline__ void wgmma_rs32_first(float (&d)[16], const uint32_t (&a)[4], uint64_t db) {
    asm volatile(
        "{.reg .pred p; setp.ne.b32 p, %21, 0;\n"
        "wgmma.mma_async.sync.aligned.m64n32k16.f32.bf16.bf16 {%0,%1,%2,%3,%4,%5,%6,%7,%8,%9,%10,%11,%12,%13,%14,%15}, {%16,%17,%18,%19}, %20, p, 1, 1, 0;}"
        : R16(0) : "r"(a[0]), "r"(a[1]), "r"(a[2]), "r"(a[3]), "l"(db), "n"(0) );
}
__device__ __forceinline__ void wgmma_ss32(float (&d)[16], uint64_t da, uint64_t db) {
    asm volatile(
        "wgmma.mma_async.sync.aligned.m64n32k16.f32.bf16.bf16 {%0,%1,%2,%3,%4,%5,%6,%7,%8,%9,%10,%11,%12,%13,%14,%15}, %16, %17, 1, 1, 1, 1, 0;"
        : R16(0) : "l"(da), "l"(db));
}
template <int OFF, int ACC> __device__ __forceinline__ void wgmma_rs32u(float (&d)[16], const uint32_t (&a)[4], uint32_t lo) {
    asm volatile(
        "{.reg .pred p; .reg .b32 l; .reg .b64 e; setp.ne.b32 p, %22, 0; add.u32 l, %20, %21; mov.b64 e, {l, 0x40000040};\n"
        "wgmma.mma_async.sync.aligned.m64n32k16.f32.bf16.bf16 {%0,%1,%2,%3,%4,%5,%6,%7,%8,%9,%10,%11,%12,%13,%14,%15}, {%16,%17,%18,%19}, e, p, 1, 1, 0;}"
        : R16(0) : "r"(a[0]), "r"(a[1]), "r"(a[2]), "r"(a[3]), "r"(lo), "n"(OFF), "n"(ACC));
}
template <int OFF> __device__ __forceinline__ void wgmma_ss32u(float (&d)[16], uint64_t da, uint32_t lo) {
    asm volatile(
        "{.reg .b32 l; .reg .b64 e; add.u32 l, %17, %18; mov.b64 e, {l, 0x40000040};\n"
        "wgmma.mma_async.sync.aligned.m64n32k16.f32.bf16.bf16 {%0,%1,%2,%3,%4,%5,%6,%7,%8,%9,%10,%11,%12,%13,%14,%15}, %16, e, 1, 1, 1, 1, 0;}"
        : R16(0) : "l"(da), "r"(lo), "n"(OFF));
}
template <int K0, int K1, class F> __device__ __forceinline__ void static_for(F f) {
    if constexpr (K0 < K1) { f(std::integral_constant<int, K0>()); static_for<K0 + 1, K1>(f); }
}
__device__ __forceinline__ void st_async4(uint32_t a, float x, float y, float z, float w, uint32_t bar) {
    asm volatile("st.async.weak.shared::cluster.mbarrier::complete_tx::bytes.v4.f32 [%0], {%1,%2,%3,%4}, [%5];" ::"r"(a), "f"(x), "f"(y), "f"(z), "f"(w), "r"(bar) : "memory");
}
__device__ __forceinline__ void st_async2(uint32_t a, float x, float y, uint32_t bar) {
    asm volatile("st.async.weak.shared::cluster.mbarrier::complete_tx::bytes.v2.f32 [%0], {%1,%2}, [%3];" ::"r"(a), "f"(x), "f"(y), "r"(bar) : "memory");
}
__device__ __forceinline__ void st_async1(uint32_t a, uint32_t x, uint32_t bar) {
    asm volatile("st.async.weak.shared::cluster.mbarrier::complete_tx::bytes.b32 [%0], %1, [%2];" ::"r"(a), "r"(x), "r"(bar) : "memory");
}
__device__ __forceinline__ void stsm4t(uint32_t a, uint32_t r0, uint32_t r1, uint32_t r2, uint32_t r3) {
    asm volatile("stmatrix.sync.aligned.m8n8.x4.trans.shared.b16 [%0], {%1,%2,%3,%4};" ::"r"(a), "r"(r0), "r"(r1), "r"(r2), "r"(r3) : "memory");
}
__device__ __forceinline__ void ldsm4t(uint32_t (&r)[4], uint32_t a) { ldsm4t(r[0], r[1], r[2], r[3], a); }
__device__ __forceinline__ void ldsm4(uint32_t (&r)[4], uint32_t a) { ldsm4(r[0], r[1], r[2], r[3], a); }
__device__ __forceinline__ void mma16816(float (&d)[4], const uint32_t (&a)[4], uint32_t b0, uint32_t b1) { mma16816(d, a[0], a[1], a[2], a[3], b0, b1); }
__device__ __forceinline__ void sched_fence(uint32_t v) {
    asm volatile("{.reg .pred p; setp.ne.u32 p, %0, 0xFFFFFFFF; vote.sync.all.pred p, p, 0xFFFFFFFF; @p bra.uni SF_OK; exit; SF_OK:}" ::"r"(v) : "memory");
}
__device__ __forceinline__ void mma16816v(float (&d)[4], const uint32_t (&a)[4], uint32_t b0, uint32_t b1) {
    asm volatile("mma.sync.aligned.m16n8k16.row.col.f32.bf16.bf16.f32 {%0,%1,%2,%3},{%4,%5,%6,%7},{%8,%9},{%0,%1,%2,%3};"
                 : "+f"(d[0]), "+f"(d[1]), "+f"(d[2]), "+f"(d[3]) : "r"(a[0]), "r"(a[1]), "r"(a[2]), "r"(a[3]), "r"(b0), "r"(b1));
}
__device__ __forceinline__ uint32_t uniform(uint32_t v) { return __reduce_max_sync(~0u, v); }

#define WPRE 0
#define G2_X 0
#define G2_K 4
#define FIN_SO 0
#define KROT 0
#define WFIRST 0
template <int NT, int STAGES> struct ProjCfg {
    static constexpr int STAGE_BYTES = 16384 + NT * 128;
    static constexpr int EPI = NT == 256 ? STAGES * STAGE_BYTES : 0;
    static constexpr int BARS = 229376 + (NT == 256 ? 192 : 0);
    static_assert(STAGES * STAGE_BYTES <= 229376 && EPI + NT * 256 <= 229376 && STAGES <= 12, "smem");
};
constexpr int PROJ_ROLE = 229376 + 384, PROJ_SMEM = PROJ_ROLE + 16;
__device__ __forceinline__ unsigned claim_pair(unsigned* reg) {
    unsigned smid, ncl = gridDim.x >> 1;
    asm volatile("mov.u32 %0, %%smid;" : "=r"(smid));
    uint2 m;
    for (int guard = 0; guard < 1024; guard++) {
        asm volatile("ld.relaxed.gpu.global.v2.u32 {%0, %1}, [%2];" : "=r"(m.x), "=r"(m.y) : "l"(g_cls + (smid & ~1u)) : "memory");
        if (m.x && m.y) break;
    }
    const unsigned r = __vminu2(m.x, m.y), c = (r & 0xFFFF) > (r >> 16);
    unsigned n = atomicAdd(reg, c ? 0x10000u : 1u);
    const unsigned i = c ? n >> 16 : n & 0xFFFF, order = ((n >> 16) + (n & 0xFFFF)) << 8;
    if (i < 32) return c * 32 + i + order;
    for (int guard = 0; guard < (1 << 20); guard++) {
        asm volatile("ld.relaxed.gpu.global.u32 %0, [%1];" : "=r"(n) : "l"(reg) : "memory");
        if ((n >> 16) + (n & 0xFFFF) >= ncl) break;
    }
    const unsigned k = (c ? n & 0xFFFF : n >> 16) + i - 32;
    return (k < 32 ? (c ^ 1) * 32 + k : 64) + order;
}
template <int NT, int STAGES> __device__ __forceinline__ void proj_init(uint32_t sb) {
    for (int i = 0; i < STAGES; i++) { mbar_init(sb + ProjCfg<NT, STAGES>::BARS + 8 * i, 1); mbar_init(sb + ProjCfg<NT, STAGES>::BARS + 8 * (STAGES + i), 16); }
    asm volatile("fence.mbarrier_init.release.cluster;" ::: "memory");
}
template <int NT, int STAGES, bool SHARE_O, class T, class R>
__device__ __forceinline__ void proj_tiles(uint32_t sb, int warp, uint32_t rank, int ntiles, const CUtensorMap* mapW, const CUtensorMap* mapO,
                                           const CUtensorMap* mapOut, T tile, R ready, int rot = 0) {
    using Cfg = ProjCfg<NT, STAGES>;
    const uint32_t bars = sb + Cfg::BARS;
    const int lane = threadIdx.x & 31;
    if (warp == 8) {
        int st = 0; uint32_t ph = 1;
        for (int i = 0; i < ntiles; i++) {
            int col, tok;
            tile(i, col, tok);
            constexpr bool PRE = WPRE && !SHARE_O;
            if (PRE && lane == 0)
                for (int kb = 0; kb < STAGES; kb++) {
                    mbar_expect_tx(bars + 8 * kb, Cfg::STAGE_BYTES);
                    tma_load_2d_both(sb + kb * Cfg::STAGE_BYTES + rank * 8192, mapW, col + rank * 64, kb * 64, bars + 8 * kb);
                }
            ready(i);
            if (lane == 0) {
                if (PRE) {
                    for (int kb = 0; kb < STAGES; kb++) tma_load_2d(sb + kb * Cfg::STAGE_BYTES + 16384, mapO, kb * 64, tok, bars + 8 * kb);
                    ph = 0;
                }
                for (int kb = PRE ? STAGES : 0; kb < HD / 64; kb++) {
                    mbar_wait(bars + 8 * (STAGES + st), ph);
                    const uint32_t full = bars + 8 * st, sa = sb + st * Cfg::STAGE_BYTES;
                    mbar_expect_tx(full, SHARE_O ? Cfg::STAGE_BYTES : G2_X == 1 ? 16384 : G2_X == 2 ? NT * 128 : Cfg::STAGE_BYTES);
                    if (SHARE_O) {
                        tma_load_2d(sa, mapW, col, kb * 64, full);
                        tma_load_2d(sa + 8192, mapW, col + 64, kb * 64, full);
                        tma_load_2d_both(sa + 16384 + rank * (NT * 64), mapO, kb * 64, tok + rank * (NT / 2), full);
                    } else {
                        const int k0 = ((kb + rot) & 63) * 64;
                        if (WFIRST) tma_load_2d_both(sa + rank * 8192, mapW, col + rank * 64, k0, full);
                        if (G2_X != 1) tma_load_2d(sa + 16384, mapO, k0, G2_X == 3 ? tok & 511 : tok, full);
                        if (!WFIRST && G2_X != 2) tma_load_2d_both(sa + rank * 8192, mapW, col + rank * 64, k0, full);
                    }
                    if (++st == STAGES) { st = 0; ph ^= 1; }
                }
            }
            __syncwarp();
        }
    } else if (warp < 8) {
        const int wg = warp >> 2;
        uint32_t peer_empty;
        asm volatile("mapa.shared::cluster.u32 %0, %1, %2;" : "=r"(peer_empty) : "r"(bars + 8 * STAGES), "r"(rank ^ 1));
        auto release = [&](int stg) {
            if (lane == 0) {
                mbar_arrive(bars + 8 * (STAGES + stg));
                asm volatile("mbarrier.arrive.shared::cluster.b64 _, [%0];" ::"r"(peer_empty + 8 * stg) : "memory");
            }
        };
        const uint32_t ew = sb + Cfg::EPI + wg * (NT * 128);
        int st = 0; uint32_t ph = 0;
        for (int i = 0; i < ntiles; i++) {
            int col, tok;
            tile(i, col, tok);
            float d[NT / 2];
#pragma unroll
            for (int r = 0; r < NT / 2; r++) d[r] = 0.f;
            int prev = -1;
            for (int kb = 0; kb < HD / 64; kb++) {
                mbar_wait(bars + 8 * st, ph);
                const uint32_t sa = sb + st * Cfg::STAGE_BYTES;
                const uint64_t da = make_desc(sa + wg * 8192, 16, 1024), db = make_desc(sa + 16384, 16, 1024);
                wg_fence();
#pragma unroll
                for (int k = 0; k < (NT == 256 ? 4 : G2_K); k++) wgmma_proj<NT>(d, da + k * 128, db + k * 2);
                wg_commit();
                if (prev >= 0) { wg_wait<1>(); release(prev); }
                prev = st;
                if (++st == STAGES) { st = 0; ph ^= 1; }
            }
            wg_wait<0>();
            release(prev);
            if ((warp & 3) == 0 && lane == 0) asm volatile("cp.async.bulk.wait_group.read 0;" ::: "memory");
            if (Cfg::EPI) bar_sync(1 + wg, 128); else bar_sync(3, 256);
            const uint32_t ea = ew + ((lane >> 4) * 8 + (lane & 7)) * 128 + ((((warp & 3) * 2 + ((lane >> 3) & 1)) ^ (lane & 7)) * 16);
#pragma unroll
            for (int r = 0; r < NT / 16; r++)
                stsm4t(ea + r * 2048, pack_bf16(d[8 * r], d[8 * r + 1]), pack_bf16(d[8 * r + 2], d[8 * r + 3]), pack_bf16(d[8 * r + 4], d[8 * r + 5]), pack_bf16(d[8 * r + 6], d[8 * r + 7]));
            asm volatile("fence.proxy.async.shared::cta;" ::: "memory");
            bar_sync(1 + wg, 128);
            if ((warp & 3) == 0 && lane == 0) {
                tma_store_2d(mapOut, ew, col + wg * 64, tok);
                asm volatile("cp.async.bulk.commit_group;" ::: "memory");
            }
        }
        if ((warp & 3) == 0 && lane == 0) asm volatile("cp.async.bulk.wait_group 0;" ::: "memory");
    }
    __syncwarp();
}
constexpr int EARLY_NT = 256, EARLY_STAGES = 3;
constexpr int PROJ_THREADS = 288;

template <int NT, int STAGES>
__global__ void __cluster_dims__(2, 1, 1) __launch_bounds__(PROJ_THREADS, 1)
proj_kernel(const __grid_constant__ CUtensorMap mapW, const __grid_constant__ CUtensorMap mapO, const __grid_constant__ CUtensorMap mapOut,
            const __grid_constant__ CUtensorMap mapOE, const __grid_constant__ CUtensorMap mapOutE) {
    KT_START(3);
    extern __shared__ __align__(1024) uint8_t smem_proj[];
    const uint32_t sb = smem_u32(smem_proj), role = sb + PROJ_ROLE;
    if (sb & 1023) __trap();
    const uint32_t rank = blockIdx.x & 1;
    const int warp = threadIdx.x >> 5;
    if (threadIdx.x == 0) {
        proj_init<NT, STAGES>(sb);
        proj_init<EARLY_NT, EARLY_STAGES>(sb);
        if (rank == 0) {
            const unsigned p = claim_pair(g_reg + 2);
            if ((p >> 8) + 1 == gridDim.x >> 1) {
                g_reg[0] = 0;
                for (int i = 0; i < 64; i++) reinterpret_cast<uint4*>(g_cls)[i] = make_uint4(0, 0, 0, 0);
            }
            uint32_t ra;
            asm volatile("mapa.shared::cluster.u32 %0, %1, 1;" : "=r"(ra) : "r"(role));
            asm volatile("st.shared::cluster.u32 [%0], %1;" ::"r"(ra), "r"(p) : "memory");
            sts32(role, p);
        }
    }
    __syncthreads();
    asm volatile("barrier.cluster.arrive.release.aligned; barrier.cluster.wait.acquire.aligned;" ::: "memory");
    const int p = lds32(role) & 255, order = lds32(role) >> 8;
    if (NT == 96 && order < 2) {
        proj_tiles<EARLY_NT, EARLY_STAGES, true>(sb, warp, rank, 4, &mapW, &mapOE, &mapOutE,
            [&](int i, int& col, int& tok) { col = ((i & 1) * 4 + order * 2 + rank) * 128; tok = (i >> 1) * EARLY_NT; },
            [&](int i) {
                const unsigned need = 8 * (i >> 1) + 8 + 3;
                for (int guard = 0; guard < (1 << 16); guard++) {
                    const uint4 f = ld_relaxed_v4(g_xflag + (threadIdx.x & 31) * 4);
                    if (__all_sync(~0u, min(min(f.x, f.y), min(f.z, f.w)) >= need)) break;
                    __nanosleep(1000);
                }
                asm volatile("fence.acq_rel.gpu; fence.proxy.async.global;" ::: "memory");
            });
        __syncthreads();
        asm volatile("barrier.cluster.arrive.relaxed.aligned; barrier.cluster.wait.aligned;" ::: "memory");
    }
    if (p >= 64) return;
    proj_tiles<NT, STAGES, false>(sb, warp, rank, 1, &mapW, &mapO, &mapOut,
                                  [&](int, int& col, int& tok) { col = (p & 7) * 128; tok = S_LEN - 16 * NT + ((p >> 3) * 2 + rank) * NT; },
                                  [&](int) { wait_prerequisites();
                                  }, KROT == 0 ? 0 : KROT == 1 ? (p & 7) * 8 : KROT == 2 ? (p >> 3) * 8 : KROT == 3 ? ((p & 7) + (p >> 3)) * 8 : (p >> 5) * 32);
    KT_END(3);
    asm volatile("barrier.cluster.arrive.relaxed; barrier.cluster.wait;" ::: "memory");
}

#define WO_RF1 6
constexpr int SM_KV = 0, KV_BYTES = 18432;
constexpr int SM_XT = 2 * KV_BYTES;
constexpr int SM_STG = SM_XT + 65536;
constexpr int SM_Z = SM_STG + 6144;
constexpr int SM_RT = SM_Z + 8192;
constexpr int SM_QKV = SM_RT + 12288;
constexpr int SM_R1 = SM_QKV + 6144;
constexpr int SM_R2 = SM_R1 + 2048;
constexpr int SM_R3 = SM_R2 + 1024;
constexpr int SM_O = SM_R3 + 2048;
constexpr int SM_S = SM_O + 2048;
constexpr int SM_INV = SM_S + 1536;
constexpr int SM_TO = SM_R3;
constexpr int SM_WORK_END = SM_S + 2048;
constexpr int STG_QK = 0, STG_V = 98304;
#define PRO2 1
#define PRO3 1
#define WO_IT 2
__host__ __device__ constexpr int stg_wo(int r) { return r < 9 ? KV_BYTES + r * 2048 : r < 13 ? SM_QKV + (r - 9) * 2048 : SM_S; }
static_assert(WO_RF1 == 6 && SM_QKV % 1024 == 0 && SM_S % 1024 == 0 && SM_QKV + 8192 <= SM_TO, "staging of Wo");
__host__ __device__ constexpr int stg_qk(int t, int r) { return !PRO2 ? STG_QK + (t * 24 + r) * 2048 : t == 0 ? SM_XT + r * 2048 : r < SM_XT / 2048 ? r * 2048 : (r + 24) * 2048; }
constexpr int SM_WO1 = SM_WORK_END - WO_RF1 * 2048;
constexpr int STG_WO = SM_WO1 - 16384;
constexpr int SM_WQK = (SM_WO1 + 16384 > STG_V + 49152) ? SM_WO1 + 16384 : STG_V + 49152;
constexpr int SM_WV = SM_WQK + 32768;
constexpr int SM_WO2 = SM_WV + 16384;
constexpr int SM_BARS = SM_WO2 + 32768;
enum { MB_W0 = SM_BARS, MB_W1 = SM_BARS + 8, MB_W2 = SM_BARS + 16, MB_W3 = SM_BARS + 24, MB_XT = SM_BARS + 32  , MB_KV = SM_BARS + 48  ,
       MB_R3 = SM_BARS + 64, MB_R1 = SM_BARS + 72, MB_R2 = SM_BARS + 80, MB_RT0 = SM_BARS + 88, MB_RT1 = SM_BARS + 96, MB_FREE = SM_BARS + 104,
       MB_P = SM_BARS + 112, MB_V = SM_BARS + 120, MB_STG = SM_BARS + 128, MB_ROLE = SM_BARS + 136, MB_W4 = SM_BARS + 144, MB_W5 = SM_BARS + 152, SM_ROLE = SM_BARS + 160   };
constexpr int CHAIN_SMEM = SM_ROLE + 8;
static_assert(SM_WORK_END % 1024 == 0 && STG_WO >= STG_V, "work area");
static_assert(CHAIN_SMEM <= 232448 && WO_RF1 >= 6, "smem");

#define DLY_X 300
#define DLY_V 0
#define DLY_Y 250
#define DLY_Z 300
#define DLY_T 0
#define DLY_K 0
#define DLY_S 0
#define LATE_RD 1
#define TS_AT 5
#define XT_FIRST 0
#define GV 1
#define NSV (GV ? 320 : 352)
#define Q3_AT 9
#define NA 7
#define NP2 6
#define P2_FENCE 0
#define SPLIT 10
#define TA0 16
#define SENT_EARLY 1
#define Y_CHAIN 1
#define EF_W 1
#define XFLIP 0
#define YFLIP 0
#define ZFLIP 1
#define OFENCE 2
#define REG_A 240
#define REG_B 216
#define REG_C (3 * 168 - REG_A - REG_B)

enum { BAR_Y, BAR_MEM, BAR_PUB, BAR_QK, BAR_S, BAR_O, BAR_SENT, BAR_COMM, BAR_PUBV, BAR_PV, BAR_PDONE, BAR_VP, BAR_ZP, BAR_PRO, BAR_O2, BAR_SV,
       BAR_V = BAR_PV, BAR_SENTC = BAR_PDONE, BAR_Q3 = BAR_PRO, BAR_INV = BAR_PRO, BAR_XT0 = BAR_Y };

__device__ __forceinline__ uint32_t umax4(const uint4& v) { return max(max(v.x, v.y), max(v.z, v.w)); }
__device__ __forceinline__ unsigned gtime() { unsigned t; asm volatile("mov.u32 %0, %%globaltimer_lo;" : "=r"(t)::"memory"); return t; }
__device__ __forceinline__ unsigned clock32() { unsigned t; asm volatile("mov.u32 %0, %%clock;" : "=r"(t)::"memory"); return t; }
__device__ __forceinline__ void spin_cycles(int d) {
    if (d > 0) { const unsigned c0 = clock32(); while (clock32() - c0 < (unsigned)d) {} }
}
__device__ __forceinline__ float ex2_approx(float x) { float y; asm("ex2.approx.ftz.f32 %0, %1;" : "=f"(y) : "f"(x)); return y; }
__device__ __forceinline__ float rcp_approx(float x) { float y; asm("rcp.approx.ftz.f32 %0, %1;" : "=f"(y) : "f"(x)); return y; }
__device__ __forceinline__ void st_sent(const void* p) { asm volatile("st.relaxed.gpu.global.v4.u32 [%0], {%1,%1,%1,%1};" ::"l"(p), "r"(SENT) : "memory"); }
#define POLL_LD(p, a, b, c, d, addr) "@" p " ld.relaxed.gpu.global.v4.u32 {" a "," b "," c "," d "}, [" addr "];\n"
#define POLL_CK(p, a, b, c, d) "max.u32 m, " a "," b "; max.u32 n, " c "," d "; max.u32 m, m, n; setp.eq.u32 " p ", m, 0xFFFFFFFF;\n"
#define POLL_IO(v) "+r"(v.x), "+r"(v.y), "+r"(v.z), "+r"(v.w)
__device__ __forceinline__ void poll_init(uint4& v) { v = make_uint4(SENT, SENT, SENT, SENT); asm volatile("" : POLL_IO(v)); }
__device__ __forceinline__ int poll2(uint4 (&v)[2], const char* a) {
    int c = 0;
    asm volatile("{.reg .pred p0, p1, p; .reg .u32 m, n;\n"
                 "setp.eq.u32 p0, %8, 0; setp.eq.u32 p1, %8, 0;\n"
                 "POLL_LOOP:\n"
                 POLL_LD("p0", "%0", "%1", "%2", "%3", "%9") POLL_LD("p1", "%4", "%5", "%6", "%7", "%9+512")
                 "add.u32 %8, %8, 1;\n"
                 POLL_CK("p0", "%0", "%1", "%2", "%3") POLL_CK("p1", "%4", "%5", "%6", "%7")
                 "or.pred p, p0, p1; setp.lt.and.u32 p, %8, 0x10000, p; vote.sync.any.pred p, p, 0xFFFFFFFF;\n"
                 "@p bra.uni POLL_LOOP;}" : POLL_IO(v[0]), POLL_IO(v[1]), "+r"(c) : "l"(a) : "memory");
    return c;
}
__device__ __forceinline__ int poll4(uint4 (&v)[4], const char* a) {
    int c = 0;
    asm volatile("{.reg .pred p0, p1, p2, p3, p; .reg .u32 m, n;\n"
                 "setp.eq.u32 p0, %16, 0; setp.eq.u32 p1, %16, 0; setp.eq.u32 p2, %16, 0; setp.eq.u32 p3, %16, 0;\n"
                 "POLL_LOOP:\n"
                 POLL_LD("p0", "%0", "%1", "%2", "%3", "%17") POLL_LD("p1", "%4", "%5", "%6", "%7", "%17+2048")
                 POLL_LD("p2", "%8", "%9", "%10", "%11", "%17+4096") POLL_LD("p3", "%12", "%13", "%14", "%15", "%17+6144")
                 "add.u32 %16, %16, 1;\n"
                 POLL_CK("p0", "%0", "%1", "%2", "%3") POLL_CK("p1", "%4", "%5", "%6", "%7") POLL_CK("p2", "%8", "%9", "%10", "%11") POLL_CK("p3", "%12", "%13", "%14", "%15")
                 "or.pred p, p0, p1; or.pred p, p, p2; or.pred p, p, p3; setp.lt.and.u32 p, %16, 0x10000, p; vote.sync.any.pred p, p, 0xFFFFFFFF;\n"
                 "@p bra.uni POLL_LOOP;}" : POLL_IO(v[0]), POLL_IO(v[1]), POLL_IO(v[2]), POLL_IO(v[3]), "+r"(c) : "l"(a) : "memory");
    return c;
}
__device__ __forceinline__ uint32_t max_bf16x2(uint32_t a, uint32_t b) { uint32_t r; asm("max.bf16x2 %0, %1, %2;" : "=r"(r) : "r"(a), "r"(b)); return r; }
template <class F> __device__ __forceinline__ void softmax40(uint32_t (&pw)[6], uint32_t sa, F mid) {
    const float LOG2E = 1.4426950408889634f;
    uint32_t w[5];
    float e[10];
#pragma unroll
    for (int i = 0; i < 5; i++) w[i] = lds32(sa + i * 128);
    uint32_t m = max_bf16x2(max_bf16x2(max_bf16x2(w[0], w[1]), max_bf16x2(w[2], w[3])), w[4]);
    m = max_bf16x2(m, __shfl_xor_sync(~0u, m, 1));
    m = max_bf16x2(m, __shfl_xor_sync(~0u, m, 2));
    const float mb2 = fmaxf(bf_lo(m), bf_hi(m)) * LOG2E;
#pragma unroll
    for (int i = 0; i < 5; i++) {
        e[2 * i] = ex2_approx(fmaf(bf_lo(w[i]), LOG2E, -mb2));
        e[2 * i + 1] = ex2_approx(fmaf(bf_hi(w[i]), LOG2E, -mb2));
    }
    mid();
#pragma unroll
    for (int i = 0; i < 5; i++) pw[i] = pack_bf16(e[2 * i], e[2 * i + 1]);
    const float sum = (((e[0] + e[1]) + (e[2] + e[3])) + ((e[4] + e[5]) + (e[6] + e[7]))) + (e[8] + e[9]);
    const float hi = bf_hi(__float_as_uint(sum));
    pw[5] = pack_bf16(sum - hi, hi);
}
template <bool NORM, class F> __device__ __forceinline__ void pv32(uint32_t (&w)[4], float (&inv)[2], const uint32_t (&va)[2][2][4], const uint32_t (&vm)[4], const uint32_t (&pw)[6], F mid) {
    float o[2][3][4], t[4] = {0.f, 0.f, 0.f, 0.f};
#pragma unroll
    for (int i = 0; i < 3; i++)
#pragma unroll
        for (int m = 0; m < 2; m++) {
            o[m][i][0] = o[m][i][1] = o[m][i][2] = o[m][i][3] = 0.f;
            if (i < 2) mma16816(o[m][i], va[m][i & 1], pw[2 * i], pw[2 * i + 1]);
            else mma1688(o[m][i], vm[2 * m], vm[2 * m + 1], pw[4]);
        }
    mma1688(t, 0x3F803F80u, 0x3F803F80u, pw[5]);
    mid();
    if (NORM) { inv[0] = rcp_approx(t[0]); inv[1] = rcp_approx(t[1]); }
#pragma unroll
    for (int i = 0; i < 4; i++) {
        const float a = (o[i >> 1][0][2 * (i & 1)] + o[i >> 1][1][2 * (i & 1)]) + o[i >> 1][2][2 * (i & 1)];
        const float b = (o[i >> 1][0][2 * (i & 1) + 1] + o[i >> 1][1][2 * (i & 1) + 1]) + o[i >> 1][2][2 * (i & 1) + 1];
        w[i] = NORM ? pack_bf16(a * inv[0], b * inv[1]) : pack_bf16(a, b);
    }
    if (!NORM) { inv[0] = t[0]; inv[1] = t[1]; }
}
__device__ __forceinline__ uint32_t scale_scores(float a, float b) {
    const float scale = 0.08838834764831845f;
    const uint32_t w = pack_bf16(a, b);
    return pack_bf16(bf_lo(w) * scale, bf_hi(w) * scale);
}

__device__ __forceinline__ uint32_t peer_addr(uint32_t a, uint32_t rank) {
    uint32_t r;
    asm("mapa.shared::cluster.u32 %0, %1, %2;" : "=r"(r) : "r"(a), "r"(rank));
    return r;
}

#define TL(i) do {} while (0)
#define TLB(i) do {} while (0)
#define TLC(i) do {} while (0)

#define OPQ_LANE 1
#define PAD_A 0
#define PAD_B 0
#define PAD_C 0
template <int N> __device__ __forceinline__ void code_pad() {
#pragma unroll
    for (int i = 0; i < N; i++) asm volatile("pmevent 0;");
}
__global__ void __cluster_dims__(2, 1, 1) __launch_bounds__(384, 1)
chain_kernel(const __grid_constant__ CUtensorMap mapX, const __grid_constant__ CUtensorMap mapT32, const __grid_constant__ CUtensorMap mapT16,
             const __grid_constant__ CUtensorMap mapTQ, const __grid_constant__ CUtensorMap mapKV,
             const __grid_constant__ CUtensorMap mapWq, const __grid_constant__ CUtensorMap mapWk, const __grid_constant__ CUtensorMap mapWv,
             const __grid_constant__ CUtensorMap mapWo, const bf16* __restrict__ mem0, char* __restrict__ mbox) {
    KT_START(2);
    extern __shared__ __align__(1024) uint8_t smem_chain[];
    constexpr uint32_t SB0 = 1024;
    if (smem_u32(smem_chain) != (SB0 | ((blockIdx.x & 1) << 24))) __trap();
    const int kh = blockIdx.x & 1;
    if (threadIdx.x == 0) {
        const uint32_t sb = smem_u32(smem_chain);
        for (int i = 0; i < 14; i++) mbar_init(sb + SM_BARS + 8 * i, 1);
        mbar_init(sb + MB_P, 4); mbar_init(sb + MB_V, 4); mbar_init(sb + MB_STG, 8); mbar_init(sb + MB_ROLE, 1); mbar_init(sb + MB_W4, 1); mbar_init(sb + MB_W5, 1);
        mbar_expect_tx(sb + MB_ROLE, 4);
        asm volatile("fence.mbarrier_init.release.cluster;" ::: "memory");
    }
    if (threadIdx.x == 32) { prefetch_map(&mapWv); prefetch_map(&mapWq); prefetch_map(&mapWk); prefetch_map(&mapWo); prefetch_map(&mapX); }
    __syncwarp();
    asm volatile("barrier.cluster.arrive.relaxed.aligned;" ::: "memory");
    unsigned claimed = 0;
    if (threadIdx.x == 0 && kh == 0) claimed = claim_pair(g_reg) & 255;
    __syncwarp();
    asm volatile("barrier.cluster.wait.acquire.aligned;" ::: "memory");
    if (threadIdx.x == 0 && kh == 0) {
        st_async1((SB0 | (1u << 24)) + SM_ROLE, claimed, (SB0 | (1u << 24)) + MB_ROLE);
        st_async1(SB0 + SM_ROLE, claimed, SB0 + MB_ROLE);
    }
    __syncwarp();
    mbar_wait_w(smem_u32(smem_chain) + MB_ROLE, 0);
    const int pair = uniform(lds32(smem_u32(smem_chain) + SM_ROLE));
#define YFLIP_() (uniform(lds32(sb + SM_ROLE + 4)) ^ YFLIP)
    if (pair >= 64) return;
    if (threadIdx.x == 0) KT_MARK(5);
    const int h = pair >> 1, nh = pair & 1, j = 2 * nh + kh, role = 2 * pair + kh;
#define WG_ORDER 0x210
    const int warp = uniform(((WG_ORDER >> (4 * (threadIdx.x >> 7))) & 3) * 4 + ((threadIdx.x >> 5) & 3));
    const uint32_t g = warp & 3, sb = SB0 | (kh << 24), rsb = sb ^ (1u << 24), cls = pair >> 5, kflip = ZFLIP ^ kh;
    const uint32_t mlo = (uint32_t)(uintptr_t)mbox, mhi = (uint32_t)((uintptr_t)mbox >> 32);
    auto lane16 = [&]() {
        uint32_t t;
        asm volatile("{.reg .u32 l, x; mov.u32 l, %%laneid; xor.b32 x, l, 1; shl.b32 x, x, 4; shfl.sync.bfly.b32 %0, x, 1, 0x1f, 0xffffffff;}" : "=r"(t));
        return t;
    };
#define PHASE(k) uint32_t L; asm volatile("{.reg .u32 t; shr.u32 t, %1, %3; add.u32 %0, %2, t;}" : "=r"(L) : "r"(it), "r"(l16), "n"(8 + (k)))
#define ROWPAT() ((((L << 3) & 0x380) | ((L << 2) & 0x400)) | ((L ^ (L >> 3)) & 0x10) | (L & 0x60))
#define FRAG() (ROWPAT() ^ (g << 5))
#define QFRAG() ((((L >> 1) & 0x80) | (L & 0x70)) + ((L & 0x80) ? SM_KV + 16384 + kvo : SM_QKV))
#define VFRAG() (ROWPAT() ^ ((g & 1) << 6))
#define VBASE() (sb + SM_KV + 8192 + (g >> 1) * 4096 + kvo)
#define XTLO() ((uint32_t)make_desc(SB0 + SM_XT, 16, 1024) + (ui & 1) * 2048)
    if (warp >= 8) {
        asm volatile("setmaxnreg.dec.sync.aligned.u32 %0;" ::"n"(REG_C));
        code_pad<PAD_C>();
        const uint32_t l16 = lane16(), lane = l16 >> 4;
        auto load_xt = [&](int seg, int half) {
            const uint32_t bar = sb + MB_XT + (seg & 1) * 8;
            if (half == 0) mbar_expect_tx(bar, 32768);
            asm volatile("cp.async.bulk.tensor.3d.shared::cluster.global.mbarrier::complete_tx::bytes [%0], [%1, {%3, %4, %5}], [%2];"
                         ::"r"(sb + SM_XT + (seg & 1) * 32768 + half * 16384), "l"(&mapX), "r"(bar), "r"(0), "r"(seg * SEG), "r"(8 * kh + 4 * (half ^ kflip)) : "memory");
        };
        if (warp == 8) {
            const CUtensorMap* ws = kh ? &mapWq : &mapWk;
            const CUtensorMap* wn = kh ? &mapWk : &mapWq;
            const uint64_t pol = EF_W ? policy_evict_first() : policy_evict_normal();
            const int col = h * DH + 64 * nh, row = 512 * kh;
            if (lane == 0) { mbar_expect_tx(sb + MB_W0, 49152); mbar_expect_tx(sb + MB_W1, 49152); mbar_expect_tx(sb + MB_W4, 49152); mbar_expect_tx(sb + MB_W2, 49152); mbar_expect_tx(sb + MB_W3, PRO3 ? 65536 : 32768); }
            __syncwarp();
            if (lane < 24) {
                const int k = lane ^ (16 * kflip);
                tma_load_2d(sb + STG_V + lane * 2048, &mapWv, col, row + 16 * k, sb + MB_W0, pol);
                tma_load_2d(sb + stg_qk(0, lane), ws, col, row + 16 * k, sb + MB_W1, pol);
                tma_load_2d(sb + stg_qk(1, lane), wn, col, row + 16 * k, sb + MB_W4, pol);
            }
            if (lane < 8) {
                const int k = (24 + lane) ^ (16 * kflip);
                tma_load_2d(sb + SM_WQK + lane * 4096, ws, col, row + 16 * k, sb + MB_W2, pol);
                tma_load_2d(sb + SM_WQK + lane * 4096 + 2048, wn, col, row + 16 * k, sb + MB_W2, pol);
                tma_load_2d(sb + SM_WV + lane * 2048, &mapWv, col, row + 16 * k, sb + MB_W2, pol);
            }
            __syncwarp();
        }
        if (warp == 9) {
            bar_sync(BAR_XT0, 160);
            if (lane == 0) { load_xt(0, 0); load_xt(0, 1); }
            __syncwarp();
        }
        if (warp == 10 && lane == 0) {
            wait_prerequisites();
            launch_dependents();
            sts32(sb + SM_ROLE + 4, g_reg[1]);
        }
        __syncwarp();
        bar_sync(BAR_PDONE, 384);
        KT_MARK(9);
        if (warp == 8) {
            const uint32_t dst = lane < 14 ? stg_wo(lane) : lane < 16 ? SM_WO1 + (lane - 8) * 2048 : SM_WO2 + (lane - 16) * 2048;
            tma_load_2d(sb + dst, &mapWo, 256 * j + 64 * (lane >> 3), h * DH + 16 * (lane & 7), sb + MB_W3, EF_W ? policy_evict_first() : policy_evict_normal());
        }
        if ((warp & 1) == 0) for (int c = (warp - 8) * 16 + lane; c < 512; c += 64) {
            uint32_t w[4];
#pragma unroll
            for (int r = 0; r < 4; r++) {
                const uint32_t lo = reinterpret_cast<const uint16_t*>(mem0)[(2 * r) * DM + 512 * kh + c], hi = reinterpret_cast<const uint16_t*>(mem0)[(2 * r + 1) * DM + 512 * kh + c];
                w[r] = lo | (hi << 16);
            }
            sts128(sb + SM_Z + (c ^ (256 * kflip)) * 16, make_uint4(w[0], w[1], w[2], w[3]));
        }
        if (!PRO3 && warp == 8) mbar_wait_w(sb + MB_W5, 0);
        auto tok_start = [&](int s) {
            if (lane == 0) {
                if (TS_AT == 0) TL(21);
                if (s > -3 && s + 2 < NSEG) {
                    mbar_wait(sb + MB_STG, (s + 2) & 1);
                    if (TS_AT == 1) TL(21);
                    if (XT_FIRST && s + 4 < NSEG) load_xt(s + 4, 0);
                    if (TS_AT == 2) TL(21);
                    asm volatile("fence.proxy.async.shared::cta;" ::: "memory");
                    if (TS_AT == 3) TL(21);
                    const int r = ((s + 2) & 3) * NH + h;
                    tma_store_2d(kh ? &mapT32 : &mapTQ, sb + SM_STG, kh ? 64 * nh : 256 * nh, kh ? r * 96 + 32 : r * 12);
                    tma_store_2d(&mapT16, sb + SM_STG + 4096, 64 * nh, r * 96 + 64 + 16 * kh);
                    asm volatile("cp.async.bulk.commit_group;" ::: "memory");
                    if (TS_AT == 4) TL(21);
                }
                if ((!XT_FIRST || s == -3) && s + 4 < NSEG) load_xt(s + 4, 0);
                if (!LATE_RD || s < 0) asm volatile("cp.async.bulk.wait_group.read 0;" ::: "memory");
                if (s < 0) {
                    asm volatile("mbarrier.arrive.shared::cluster.b64 _, [%0];" ::"r"(rsb + MB_FREE) : "memory");
                    mbar_wait(sb + MB_FREE, (s + 3) & 1);
                }
            }
            __syncwarp();
        };
        auto tok_mid = [&](int s) {
            if (lane == 0) {
                if (s + 4 < NSEG) load_xt(s + 4, 1);
                if (s > -3 && s + 2 < NSEG) {
                    asm volatile("cp.async.bulk.wait_group 0;" ::: "memory");
                    if (s == 8 || s == 16) asm volatile("fence.acq_rel.gpu;" ::: "memory");
                    st_relaxed_u32(g_xflag + role, s + 3);
                }
            }
            __syncwarp();
        };
        auto kv_check = [&](int s) {
            if (s + 1 < NSEG) {
                if (lane < 4) {
                    unsigned f; int guard = 0;
                    do {
                        asm volatile("ld.acquire.gpu.global.u32 %0, [%1];" : "=r"(f) : "l"(g_xflag + h * 4 + lane) : "memory");
                        if (++guard > (1 << 20)) __trap();
                    } while (f <= (unsigned)(s + 1));
                }
                __syncwarp();
                asm volatile("fence.proxy.async.global;" ::: "memory");
            }
        };
        auto kv_load = [&](int s) {
            if (lane == 0 && s + 1 < NSEG) {
                const uint32_t bar = sb + MB_KV + ((s + 1) & 1) * 8, dst = sb + SM_KV + ((s + 1) & 1) * KV_BYTES;
                const int row = (((s + 1) & 3) * NH + h) * 96;
                mbar_expect_tx(bar, KV_BYTES);
                asm volatile("cp.async.bulk.tensor.3d.shared::cluster.global.mbarrier::complete_tx::bytes.multicast::cluster [%0], [%1, {%3, %4, %3}], [%2], %5;"
                             ::"r"(dst + kh * 8192), "l"(&mapKV), "r"(bar), "r"(0), "r"(row + 32 + 32 * kh), "h"((uint16_t)3) : "memory");
                bulk_load(dst + 16384, g_tok + row * DH + j * 1024, 2048, bar);
            }
            __syncwarp();
        };
        if (warp == 9) {
            if (!PRO2 && lane == 0) { load_xt(0, 0); load_xt(0, 1); }
#pragma unroll 1
            for (int s = -3; s < 0; s++) { tok_start(s); KT_MARK(13 + s); bar_arrive(BAR_PRO, 288); tok_mid(s); }
        }
        if (warp == 11) { kv_check(-1); kv_load(-1); }
        bar_arrive(BAR_MEM, 384);
        const uint32_t ybox = mlo + page_off(role & 63, cls ^ YFLIP_()), xoth = mlo + WIN + page_off((pair & 31) ^ 1, cls ^ XFLIP);
        const uint32_t zline = mlo + WIN + page_off(32 + ((role >> 5) & 1), cls ^ ZFLIP) + (role & 31) * 128, zbox = mlo + WIN + (page_off(32 + kh, 0) & ~4096u);
        const uint32_t xtype = g == GV ? 2 : g == 2 ? 0 : 1;
        const uint32_t ydst = (lane >> 3) * 128 + ((lane & 7) ^ (lane >> 3)) * 16, ysrc = lane * 128 + ((2 * g) ^ (lane & 7)) * 16;
#pragma unroll 1
        for (int s = 0; s < NSEG; s++) {
            const uint32_t slot = (s & 3) << 14;
            spin_cycles(DLY_T);
            if (g == 3) {
                spin_cycles(DLY_K);
                kv_check(s);
                const uint32_t L = l16, kvo = (s & 1) * KV_BYTES, qa = QFRAG(), sa = sb + SM_S + 512 + (L >> 2);
                float sc[4] = {0.f, 0.f, 0.f, 0.f}, sd[4] = {0.f, 0.f, 0.f, 0.f};
                uint32_t a[4][4], kb[2][4];
                mbar_wait_w(sb + MB_KV + (s & 1) * 8, (s >> 1) & 1);
                mbar_wait_w(sb + MB_P, s & 1);
#pragma unroll
                for (int c = 0; c < 2; c++) {
                    const uint32_t qc = qa + (sb + (nh ^ c) * 1024), kc = L + (sb + SM_QKV + 2048 + (nh ^ c) * 1024);
                    if (c) bar_sync(BAR_QK, 224);
                    ldsm4t(kb[0], kc); ldsm4t(a[0], qc); ldsm4t(a[1], qc + 256);
                    ldsm4t(kb[1], kc + 512); ldsm4t(a[2], qc + 512); ldsm4t(a[3], qc + 768);
                    mma16816v(sc, a[0], kb[0][0], kb[0][1]);
                    mma16816v(sd, a[1], kb[0][2], kb[0][3]);
                    mma16816v(sc, a[2], kb[1][0], kb[1][1]);
                    mma16816v(sd, a[3], kb[1][2], kb[1][3]);
                }
                sts32(sa, scale_scores(sc[0] + sd[0], sc[1] + sd[1]));
                sts32(sa + 768, scale_scores(sc[2] + sd[2], sc[3] + sd[3]));
                bar_arrive(BAR_S, 160);
                TL(25);
                bar_sync(BAR_SV, NSV);
                kv_load(s);
            } else {
                if (g == 1) { spin_cycles(DLY_S); tok_start(s); if (TS_AT == 5) TL(21); if (s == 0) KT_MARK(13); }
                const char* p = make_ptr(l16 + (xoth + xtype * 1024 + slot), mhi);
                const uint32_t dst = l16 + (sb + SM_QKV + xtype * 2048 + (nh ^ 1) * 1024);
                asm volatile("" ::"l"(p));
                uint4 v[2];
                poll_init(v[0]); poll_init(v[1]);
                if (g == GV) {
                    bar_sync(BAR_PUBV, 160);
                    mbar_wait_w(sb + MB_V, s & 1);
                    spin_cycles(DLY_V);
                } else {
                    bar_sync(BAR_PUB, 192);
                    spin_cycles(DLY_X);
                }
                const int r = poll2(v, p);
                STAT(1, r > 1 && warp == 10);
                sts128(dst, v[0]); sts128(dst + 512, v[1]);
                if (g != GV) bar_arrive(BAR_QK, 224);
                if (g == GV) { bar_arrive(BAR_V, 160); if (GV == 0) bar_arrive(BAR_SV, NSV); TL(17); }
                if (g == 1) {
                    TL(31);
                    if (LATE_RD) asm volatile("cp.async.bulk.wait_group.read 0;" ::: "memory");
                    bar_sync(BAR_SV, NSV);
                    tok_mid(s);
                    TL(22);
                }
                if (g == 2 && s >= 1) {
                    TL(16);
                    const uint32_t prev = (slot - 0x4000) & 0xC000;
                    const char* y = make_ptr(l16 + (ybox + prev), mhi);
                    const char* x = make_ptr(l16 + (xoth + prev + kh * 1536), mhi);
#pragma unroll
                    for (int i = 0; i < 8; i++) st_sent(y + i * 512);
#pragma unroll
                    for (int i = 0; i < 3; i++) st_sent(x + i * 512);
                    st_relaxed_u32(make_ptr(lane * 4 + (zline + (slot ^ 0x8000)), mhi), SENT);
                    TL(23);
                }
            }
            if (s + 1 == NSEG) break;
            {
                const char* p = make_ptr(l16 + (ybox + g * 1024 + slot), mhi);
                char* zdst = make_ptr(lane * 4 + (zline + g * 32 + slot), mhi);
                const uint32_t dst = ydst + (sb + SM_Z + g * 1024), dst1 = (ydst ^ 64) + (sb + SM_Z + g * 1024 + 512), src = ysrc + (sb + SM_Z), src1 = (ysrc ^ 16) + (sb + SM_Z);
                asm volatile("" ::"l"(p), "l"(zdst));
                uint4 v[2];
                poll_init(v[0]); poll_init(v[1]);
                bar_sync(BAR_SENTC, 384);
                spin_cycles(DLY_Y);
                const int r = poll2(v, p);
                STAT(2, r > 1 && warp == 8);
                sts128(dst, v[0]); sts128(dst1, v[1]);
                bar_sync(BAR_Y, 128);
                TL(18);
                uint32_t b[2][4];
                ldsm4t(b[0], src); ldsm4t(b[1], src1);
                const uint32_t one = 0x3F803F80u;
                float d0[4] = {0.f, 0.f, 0.f, 0.f}, d1[4] = {0.f, 0.f, 0.f, 0.f};
                mma16816(d0, one, one, one, one, b[0][0], b[0][1]);
                mma16816(d1, one, one, one, one, b[1][0], b[1][1]);
                mma16816(d0, one, one, one, one, b[0][2], b[0][3]);
                mma16816(d1, one, one, one, one, b[1][2], b[1][3]);
                const uint32_t w = (lane & 4) ? pack_bf16(d1[0], d1[1]) : pack_bf16(d0[0], d0[1]);
                asm volatile("{.reg .pred p; setp.lt.u32 p, %2, 128; @p st.relaxed.gpu.global.u32 [%0], %1;}" ::"l"(zdst), "r"(w), "r"(l16) : "memory");
                if (s + 3 < NSEG) bar_arrive(BAR_ZP, 256);
                TL(19);
            }
            {
                const char* p = make_ptr(l16 + (zbox + g * 512 + slot), mhi);
                const uint32_t dst = l16 + (sb + SM_Z + g * 512);
                asm volatile("" ::"l"(p));
                uint4 v[4];
                poll_init(v[0]); poll_init(v[1]); poll_init(v[2]); poll_init(v[3]);
                bar_sync(BAR_COMM, 128);
                spin_cycles(DLY_Z);
                const int r = poll4(v, p);
                STAT(0, r > 1 && warp == 8);
#pragma unroll
                for (int i = 0; i < 4; i++) sts128(dst + i * 2048, v[i]);
                bar_arrive(BAR_MEM, 384);
                TL(20);
            }
        }
    } else if (warp < 4) {
        asm volatile("setmaxnreg.inc.sync.aligned.u32 %0;" ::"n"(REG_A));
        code_pad<PAD_A>();
        const uint32_t l16 = lane16();
        uint32_t wa[2][24][4];
        {
            const uint32_t L = l16, fa = sb + FRAG();
            mbar_wait_w(sb + MB_W1, 0);
            KT_MARK(7);
#pragma unroll
            for (int t = 0; t < 2; t++) {
#pragma unroll
                for (int r = 0; r < 24; r++) ldsm4t(wa[t][r], fa + stg_qk(t, r));
                if (PRO2 && t == 0) { bar_arrive(BAR_XT0, 160); mbar_wait_w(sb + MB_W4, 0); }
            }
            mbar_wait_w(sb + MB_W2, 0);
            if (EARLY_ROLE) bar_sync(BAR_PDONE, 384); else bar_arrive(BAR_PDONE, 384);
        }
        auto batch1 = [&](float (&d)[16], uint32_t lo, auto tc, auto k0c, auto k1c) {
            constexpr int t = decltype(tc)::value;
            const uint64_t da = make_desc(SB0 + SM_WQK, 16, 1024);
            wg_fence();
            static_for<decltype(k0c)::value, decltype(k1c)::value>([&](auto kc) {
                constexpr int k = decltype(kc)::value, off = (k >> 2) * 256 + (k & 3) * 2;
                if constexpr (k >= 24) wgmma_ss32u<off>(d, da + ((k - 24) * 2 + t) * 128, lo);
                else wgmma_rs32u<off, k != 0 || t != 0>(d, wa[t][k], lo);
            });
            wg_commit();
        };
        const uint32_t xbox = mlo + WIN + page_off(pair & 31, cls ^ XFLIP);
        const uint32_t ybox = mlo + page_off(24 + 2 * g + 32 * nh, kh ^ YFLIP_()) + h * 128;
#pragma unroll 1
        for (uint32_t it = 0; it < NSEG + 3; it++) {
            const int s = (int)it - 3;
            const uint32_t ui = uniform(it), slot = ((ui + 1) & 3) << 14, kvo = (~ui & 1) * KV_BYTES, xtlo = XTLO();
            {
                PHASE(5);
                const uint32_t first = L | (g << 9);
                if (s >= 0) mbar_expect_tx_if0(first, sb + MB_R1, 2048);
                if (s + 3 < NSEG) {
                    mbar_expect_tx_if0(first, sb + MB_RT0, 8192);
                    mbar_wait_w(sb + MB_XT + (ui & 1) * 8, (it >> 1) & 1);
                }
            }
            if (s >= 0) {
                PHASE(0);
                const uint32_t mb = L + (sb + SM_Z), ra = L + (sb + g * 512), r1 = L + (rsb + SM_R1 + g * 512), r1b = rsb + MB_R1;
                sched_fence(r1);
                bar_sync(BAR_MEM, 384);
                TLB(0);
                float acc[2][2][4];
#pragma unroll
                for (int t = 0; t < 4; t++) { acc[t >> 1][t & 1][0] = acc[t >> 1][t & 1][1] = acc[t >> 1][t & 1][2] = acc[t >> 1][t & 1][3] = 0.f; }
                uint32_t b[4][4];
                uint4 u0, u1;
#pragma unroll
                for (int p = 0; p < 4; p++) ldsm4t(b[p], mb + p * 512);
#pragma unroll
                for (int p = 0; p < 12; p++) {
#pragma unroll
                    for (int u = 0; u < 2; u++) {
                        mma16816v(acc[0][u], wa[0][2 * p + u], b[p & 3][2 * u], b[p & 3][2 * u + 1]);
                        mma16816v(acc[1][u], wa[1][2 * p + u], b[p & 3][2 * u], b[p & 3][2 * u + 1]);
                    }
                    if (p + 4 < 12) ldsm4t(b[p & 3], mb + (p + 4) * 512);
                    if (p == Q3_AT) {
                        bar_sync(BAR_Q3, 256);
                        u0 = lds128(ra + SM_R3); u1 = lds128(ra + SM_O);
                    }
                }
                st_async4(r1, (acc[0][0][0] + __uint_as_float(u0.x)) + acc[0][1][0], (acc[0][0][1] + __uint_as_float(u0.y)) + acc[0][1][1],
                          (acc[0][0][2] + __uint_as_float(u0.z)) + acc[0][1][2], (acc[0][0][3] + __uint_as_float(u0.w)) + acc[0][1][3], r1b);
                TL(1);
                const float o0 = (acc[1][0][0] + __uint_as_float(u1.x)) + acc[1][1][0], o1 = (acc[1][0][1] + __uint_as_float(u1.y)) + acc[1][1][1];
                const float o2 = (acc[1][0][2] + __uint_as_float(u1.z)) + acc[1][1][2], o3 = (acc[1][0][3] + __uint_as_float(u1.w)) + acc[1][1][3];
                const uint32_t l4 = L >> 2, qo = SM_QKV + kh * 2048 + nh * 1024 + g * 256, qr = l4 + (rsb + qo), ql = l4 + (sb + qo), pb = rsb + MB_P;
                char* xd = make_ptr(l4 + (xbox + kh * 1024 + g * 256 + slot), mhi);
                asm volatile("" ::"l"(xd), "r"(qr), "r"(pb), "r"(qr + 128), "f"(o0), "f"(o1), "f"(o2), "f"(o3));
                mbar_wait_w(sb + MB_R1, s & 1);
                const uint4 v = lds128(ra + SM_R1);
                const uint32_t w0 = pack_bf16(o0 + __uint_as_float(v.x), o1 + __uint_as_float(v.y)), w1 = pack_bf16(o2 + __uint_as_float(v.z), o3 + __uint_as_float(v.w));
                st_relaxed_u32(xd, w0);
                st_relaxed_u32(xd + 128, w1);
                bar_arrive(BAR_PUB, 192);
                st_async1(qr, w0, pb);
                st_async1(qr + 128, w1, pb);
                sts32(ql, w0);
                sts32(ql + 128, w1);
                __syncwarp();
                mbar_expect_tx_if0(L, sb + MB_P, 256);
                TL(2);
                if (s + 3 < NSEG) bar_sync(BAR_VP, 256);
            } else {
                bar_sync(BAR_PRO, 288);
            }
            if (s + 3 < NSEG) {
                float d[16];
                batch1(d, xtlo, std::integral_constant<int, 0>(), std::integral_constant<int, 0>(), std::integral_constant<int, 32>());
                PHASE(1);
                const uint32_t rt = L + (rsb + SM_RT + g * 2048);
                wg_wait<0>();
                TL(7);
#pragma unroll
                for (int i = 0; i < 4; i++) st_async4(rt + i * 512, d[4 * i], d[4 * i + 1], d[4 * i + 2], d[4 * i + 3], rsb + MB_RT0);
            }
            if (s + 1 == NSEG) { bar_arrive(BAR_SV, NSV); break; }
            if (s >= 0) {
                PHASE(2);
                const uint32_t fo = FRAG() + (sb + SM_WO2 + 16384), lo = L + (sb + SM_O), yo = (L >> 2) + (ybox + slot);
                uint32_t a1[8][4];
                bar_sync(BAR_SV, NSV);
#pragma unroll
                for (int k = 0; k < 8; k++) ldsm4t(a1[k], fo + k * 2048);
                sched_fence(yo);
                bar_sync(BAR_O2, 256);
                TLB(14);
                float y0[4] = {0.f, 0.f, 0.f, 0.f}, y1[4] = {0.f, 0.f, 0.f, 0.f};
                uint32_t b[2][4];
                ldsm4t(b[0], lo); ldsm4t(b[1], lo + 512);
                sched_fence(L);
#pragma unroll
                for (int p = 0; p < 4; p++) {
                    mma16816v(y0, a1[2 * p], b[p & 1][0], b[p & 1][1]);
                    mma16816v(y1, a1[2 * p + 1], b[p & 1][2], b[p & 1][3]);
                    if (p < 2) ldsm4t(b[p & 1], lo + (p + 2) * 512);
                }
                bar_sync(BAR_INV, 256);
                float i0, i1;
                asm volatile("ld.shared.v2.f32 {%0, %1}, [%2];" : "=f"(i0), "=f"(i1) : "r"(((L >> 1) & 0x18) + (sb + SM_INV + g * 32)) : "memory");
                st_relaxed_u32(make_ptr(yo, mhi), pack_bf16((y0[0] + y1[0]) * i0, (y0[1] + y1[1]) * i1));
                st_relaxed_u32(make_ptr(yo ^ 4096, mhi) + 0x2000, pack_bf16((y0[2] + y1[2]) * i0, (y0[3] + y1[3]) * i1));
                bar_arrive(BAR_SENTC, 384);
                TL(6);
            }
            if (s + 3 < NSEG) {
                PHASE(4);
                float d[16];
                const uint32_t rt = L + (sb + SM_RT + g * 2048);
                if (SENT_EARLY && s >= 0) bar_sync(BAR_SENT, 256);
                mbar_wait_w(sb + MB_RT0, it & 1);
#pragma unroll
                for (int i = 0; i < 4; i++) {
                    const uint4 v = lds128(rt + i * 512);
                    d[4 * i] = __uint_as_float(v.x); d[4 * i + 1] = __uint_as_float(v.y); d[4 * i + 2] = __uint_as_float(v.z); d[4 * i + 3] = __uint_as_float(v.w);
                }
                if (!SENT_EARLY && s >= 0) bar_sync(BAR_SENT, 256);
                if (SPLIT > 0) batch1(d, xtlo, std::integral_constant<int, 1>(), std::integral_constant<int, 0>(), std::integral_constant<int, SPLIT>());
                if (s >= 0) bar_sync(BAR_ZP, 256);
                TLB(30);
                batch1(d, xtlo, std::integral_constant<int, 1>(), std::integral_constant<int, SPLIT>(), std::integral_constant<int, 32>());
                const uint32_t so = (kh ? FRAG() : ((L & 0x100) << 2) + (L & 0xF0) + g * 256) + (sb + SM_STG);
                wg_wait<0>();
                TL(8);
                uint32_t w[8];
#pragma unroll
                for (int i = 0; i < 8; i++) w[i] = pack_bf16(d[2 * i], d[2 * i + 1]);
                if (kh) {
                    stsm4t(so, w[0], w[1], w[2], w[3]);
                    stsm4t(so + 2048, w[4], w[5], w[6], w[7]);
                } else {
                    stsm4(so, w[0], w[1], w[2], w[3]);
                    stsm4(so + 2048, w[4], w[5], w[6], w[7]);
                }
                __syncwarp();
                mbar_arrive_if0(L, sb + MB_STG);
                TL(9);
            } else {
                bar_arrive(BAR_SENT, 256);
            }
        }
    } else {
        asm volatile("setmaxnreg.inc.sync.aligned.u32 %0;" ::"n"(REG_B));
        code_pad<PAD_B>();
        const uint32_t l16 = lane16();
        uint32_t wv[24][4], wo[8 + WO_RF1][4];
        {
            const uint32_t L = l16, fa = sb + FRAG();
            mbar_wait_w(sb + MB_W0, 0);
            KT_MARK(6);
#pragma unroll
            for (int r = 0; r < 24; r++) ldsm4t(wv[r], fa + STG_V + r * 2048);
#pragma unroll
            for (int r = 0; r < 8 + WO_RF1; r++) asm volatile("" : "=r"(wo[r][0]), "=r"(wo[r][1]), "=r"(wo[r][2]), "=r"(wo[r][3]));
            mbar_wait_w(sb + MB_W2, 0);
            if (EARLY_ROLE) bar_sync(BAR_PDONE, 384); else bar_arrive(BAR_PDONE, 384);
        }
        const uint32_t xbox = mlo + WIN + page_off(pair & 31, cls ^ XFLIP);
        const uint32_t ybox = mlo + page_off(2 * g + 32 * nh, kh ^ YFLIP_()) + h * 128;
#pragma unroll 1
        for (uint32_t it = 0; it < NSEG + 3; it++) {
            const int s = (int)it - 3;
            const uint32_t ui = uniform(it), slot = ((ui + 1) & 3) << 14, kvo = (~ui & 1) * KV_BYTES, xtlo = XTLO();
            {
                PHASE(5);
                const uint32_t first = L | (g << 9);
                if (s >= 0) mbar_expect_tx_if0(first, sb + MB_R2, 1024);
                if (s + 3 < NSEG) {
                    mbar_expect_tx_if0(first, sb + MB_RT1, 4096);
                    mbar_wait_w(sb + MB_XT + (ui & 1) * 8, (it >> 1) & 1);
                }
            }
            if (s >= 0) {
                PHASE(0);
                const uint32_t fo = FRAG() + sb, l4 = L >> 2;
                {
                    const uint32_t mb = L + (sb + SM_Z), aw = fo + SM_WQK, ra = L + (sb + g * 512), r2 = (L >> 1) + (rsb + SM_R2 + g * 256), r2b = rsb + MB_R2;
                    uint32_t a[NA][4], b[4][4];
#pragma unroll
                    for (int i = 0; i < NA; i++) ldsm4t(a[i], aw + i * 2048);
                    sched_fence(L);
                    TL(24);
                    bar_sync(BAR_MEM, 384);
#pragma unroll
                    for (int p = 0; p < 4; p++) ldsm4t(b[p], mb + (12 + p) * 512);
                    sched_fence(L);
                    float c[2][4] = {{0.f, 0.f, 0.f, 0.f}, {0.f, 0.f, 0.f, 0.f}};
#pragma unroll
                    for (int i = 0; i < 16; i++) {
                        mma16816v(c[i & 1], a[i % NA], b[i >> 2][i & 2], b[i >> 2][(i & 2) + 1]);
                        ldsm4t(a[i % NA], aw + (i + NA) * 2048);
                    }
                    sts128(ra + SM_R3, make_uint4(__float_as_uint(c[0][0]), __float_as_uint(c[0][1]), __float_as_uint(c[0][2]), __float_as_uint(c[0][3])));
                    sts128(ra + SM_O, make_uint4(__float_as_uint(c[1][0]), __float_as_uint(c[1][1]), __float_as_uint(c[1][2]), __float_as_uint(c[1][3])));
                    bar_arrive(BAR_Q3, 256);
                    TL(29);
                    float acc[4][4];
#pragma unroll
                    for (int t = 0; t < 4; t++) { acc[t][0] = acc[t][1] = acc[t][2] = acc[t][3] = 0.f; }
#pragma unroll
                    for (int i = 16; i < 24; i++) {
                        mma16816v(acc[i & 1], a[i % NA], b[(i - 16) >> 1][2 * (i & 1)], b[(i - 16) >> 1][2 * (i & 1) + 1]);
                        if (i + NA < 24) ldsm4t(a[i % NA], aw + (i + NA) * 2048);
                        else ldsm4t(a[i % NA], mb + (i + NA - 24) * 512);
                    }
#pragma unroll
                    for (int p = 0; p < 12; p++) {
                        mma16816v(acc[(2 * p) & 3], wv[2 * p], a[(24 + p) % NA][0], a[(24 + p) % NA][1]);
                        mma16816v(acc[(2 * p + 1) & 3], wv[2 * p + 1], a[(24 + p) % NA][2], a[(24 + p) % NA][3]);
                        if (p + NA < 12) ldsm4t(a[(24 + p) % NA], mb + (p + NA) * 512);
                    }
                    if (s + 3 < NSEG) bar_arrive(BAR_VP, 256);
                    float o[4];
#pragma unroll
                    for (int i = 0; i < 4; i++) o[i] = (acc[0][i] + acc[1][i]) + (acc[2][i] + acc[3][i]);
                    st_async2(r2, kh ? o[0] : o[2], kh ? o[1] : o[3], r2b);
                    TL(10);
                    const float o0 = kh ? o[2] : o[0], o1 = kh ? o[3] : o[1];
                    const uint32_t qo = SM_QKV + 4096 + nh * 1024 + (2 * g + kh) * 128, qr = l4 + (rsb + qo), ql = l4 + (sb + qo), vb = rsb + MB_V, rl = (L >> 1) + (sb + SM_R2 + g * 256);
                    char* xd = make_ptr(l4 + (xbox + 2048 + (2 * g + kh) * 128 + slot), mhi);
                    asm volatile("" ::"l"(xd), "r"(qr), "r"(vb), "f"(o0), "f"(o1));
                    mbar_wait_w(sb + MB_R2, s & 1);
                    uint32_t vx, vy;
                    asm volatile("ld.shared.v2.u32 {%0,%1}, [%2];" : "=r"(vx), "=r"(vy) : "r"(rl) : "memory");
                    const uint32_t w0 = pack_bf16(o0 + __uint_as_float(vx), o1 + __uint_as_float(vy));
                    st_relaxed_u32(xd, w0);
                    bar_arrive(BAR_PUBV, 160);
                    st_async1(qr, w0, vb);
                    sts32(ql, w0);
                    __syncwarp();
                    mbar_expect_tx_if0(L, sb + MB_V, 128);
                    TL(11);
                }
                const uint32_t vma = L + (sb + SM_QKV + 4096 + g * 512), yo = l4 + (ybox + slot);
                uint32_t va[2][2][4];
                {
                    const uint32_t qa = QFRAG(), vf = VFRAG(), va0 = vf + VBASE(), va1 = (vf ^ 32) + VBASE();
                    const uint32_t kf = ((L << 3) & 0x380) | ((L ^ (L >> 3)) & 0x30) | (L & 0x40), kb0 = sb + SM_KV + kvo + g * 1024;
                    const int d = (int)(L >> 6) - (int)((L >> 3) & 6) + 8 * (j - (int)g);
                    const uint32_t keep = (d < 0 ? 0u : 0xFFFFu) | (d < 1 ? 0u : 0xFFFF0000u), sa = l4 + (sb + SM_S + g * 128);
                    const uint32_t q0 = qa + (sb + nh * 1024), q1 = qa + (sb + (nh ^ 1) * 1024);
                    float sc[4] = {0.f, 0.f, 0.f, 0.f}, sd[4] = {0.f, 0.f, 0.f, 0.f};
                    uint32_t a[4][4], kb[2][4];
                    mbar_wait_w(sb + MB_KV + (~ui & 1) * 8, (s >> 1) & 1);
                    ldsm4(kb[0], kf + (kb0 + nh * 4096)); ldsm4(kb[1], (kf ^ 64) + (kb0 + nh * 4096));
                    mbar_wait_w(sb + MB_P, s & 1);
                    TL(12);
#pragma unroll
                    for (int k = 0; k < 4; k++) ldsm4t(a[k], q0 + k * 256);
#pragma unroll
                    for (int k = 0; k < 4; k++) mma16816v((k & 1) ? sd : sc, a[k], kb[k >> 1][2 * (k & 1)], kb[k >> 1][2 * (k & 1) + 1]);
                    ldsm4(kb[0], kf + (kb0 + (nh ^ 1) * 4096)); ldsm4(kb[1], (kf ^ 64) + (kb0 + (nh ^ 1) * 4096));
                    sched_fence(vf | yo);
                    bar_sync(BAR_QK, 224);
                    TLB(3);
#pragma unroll
                    for (int k = 0; k < 4; k++) ldsm4t(a[k], q1 + k * 256);
                    sched_fence(L);
#pragma unroll
                    for (int k = 0; k < 4; k++) mma16816v((k & 1) ? sd : sc, a[k], kb[k >> 1][2 * (k & 1)], kb[k >> 1][2 * (k & 1) + 1]);
                    ldsm4t(va[0][0], va0); ldsm4t(va[0][1], va0 + 2048);
                    sts32(sa, scale_scores(sc[0] + sd[0], sc[1] + sd[1]));
                    sts32(sa + 768, (scale_scores(sc[2] + sd[2], sc[3] + sd[3]) & keep) | (0xFF80FF80u & ~keep));
                    bar_arrive(BAR_SV, NSV);
                    ldsm4t(va[1][0], va1); ldsm4t(va[1][1], va1 + 2048);
                }
                bar_sync(BAR_S, 160);
                TLB(4);
                uint32_t pw[6], vm[4];
                if (s + 1 < NSEG) {
                softmax40(pw, l4 + (sb + SM_S), [&]() {
                    bar_sync(BAR_V, 160);
                    ldsm4(vm, vma);
                });
                uint32_t a1[NP2][4];
                float inv[2];
                {
                    uint32_t w[4];
                    pv32<false>(w, inv, va, vm, pw, [&]() {
                        sched_fence(L);
#pragma unroll
                        for (int k = 0; k < NP2; k++) ldsm4t(a1[k], fo + SM_WO2 + k * 2048);
                    });
#pragma unroll
                    for (int i = 0; i < 4; i++) sts32(l4 + (sb + SM_O + g * 512) + i * 128, w[i]);
                }
                const uint32_t lo = L + (sb + SM_O);
                bar_arrive(BAR_O2, 256);
                bar_sync(BAR_O, 128);
                TLB(5);
                {
                    float y0[4] = {0.f, 0.f, 0.f, 0.f}, y1[4] = {0.f, 0.f, 0.f, 0.f}, y2[4] = {0.f, 0.f, 0.f, 0.f};
                    uint32_t b[4][4];
#pragma unroll
                    for (int p = 0; p < 4; p++) ldsm4t(b[p], lo + p * 512);
                    inv[0] = rcp_approx(inv[0]); inv[1] = rcp_approx(inv[1]);
                    asm volatile("st.shared.v2.f32 [%0], {%1, %2};" ::"r"(((L >> 1) & 0x18) + (sb + SM_INV + g * 32)), "f"(inv[0]), "f"(inv[1]) : "memory");
                    bar_arrive(BAR_INV, 256);
                    sched_fence(L);
#pragma unroll
                    for (int k = 0; k < 8; k++) {
                        const int p = k >> 1, u = k & 1;
                        mma16816v(y2, a1[k % NP2], b[p][2 * u], b[p][2 * u + 1]);
                        if (k + NP2 < 8) ldsm4t(a1[k % NP2], fo + SM_WO2 + (k + NP2) * 2048);
                        else if (k + NP2 < 16 - WO_RF1) ldsm4t(a1[k % NP2], fo + SM_WO1 + (k + NP2 - 8 + WO_RF1) * 2048);
                        mma16816v(y0, wo[k], b[p][2 * u], b[p][2 * u + 1]);
                        if (k < WO_RF1) mma16816v(y1, wo[8 + (k < WO_RF1 ? k : 0)], b[p][2 * u], b[p][2 * u + 1]);
                        else mma16816v(y1, a1[(k + 8 - WO_RF1) % NP2], b[p][2 * u], b[p][2 * u + 1]);
                        if (k < P2_FENCE) sched_fence(L);
                    }
                    char* yd = make_ptr(yo, mhi);
                    char* yd1 = make_ptr(yo ^ 4096, mhi);
                    st_relaxed_u32(yd1 + 0x80000, pack_bf16(y2[0] * inv[0], y2[1] * inv[1]));
                    st_relaxed_u32(yd + 0x82000, pack_bf16(y2[2] * inv[0], y2[3] * inv[1]));
                    st_relaxed_u32(yd, pack_bf16(y0[0] * inv[0], y0[1] * inv[1]));
                    st_relaxed_u32(yd1 + 0x2000, pack_bf16(y0[2] * inv[0], y0[3] * inv[1]));
                    st_relaxed_u32(yd + 0x40000, pack_bf16(y1[0] * inv[0], y1[1] * inv[1]));
                    st_relaxed_u32(yd1 + 0x42000, pack_bf16(y1[2] * inv[0], y1[3] * inv[1]));
                }
                bar_arrive(BAR_SENTC, 384);
                TL(13);
                bar_sync(BAR_SENT, 256);
                } else {
                    bar_sync(BAR_V, 160);
                }
            } else {
                if (it == WO_IT) {
                    PHASE(2);
                    const uint32_t fa = sb + FRAG();
                    mbar_wait_w(sb + MB_W3, 0);
                    KT_MARK(8);
#pragma unroll
                    for (int r = 0; r < 8 + WO_RF1; r++) ldsm4t(wo[r], fa + stg_wo(r));
                }
                bar_sync(BAR_PRO, 288);
            }
            float o[8];
            {
                PHASE(1);
                float d[16];
                const uint64_t da = make_desc(SB0 + SM_WV, 16, 1024);
                auto batch = [&](auto k0c, auto k1c) {
                    static_for<decltype(k0c)::value, decltype(k1c)::value>([&](auto kc) {
                        constexpr int k = decltype(kc)::value, off = (k >> 2) * 256 + (k & 3) * 2;
                        if constexpr (k >= 24) wgmma_ss32u<off>(d, da + (k - 24) * 128, xtlo);
                        else wgmma_rs32u<off, k != 0>(d, wv[k], xtlo);
                    });
                };
                const uint32_t vf = VFRAG(), va0 = vf + VBASE(), va1 = (vf ^ 32) + VBASE(), vma = L + (sb + SM_QKV + 4096 + g * 512), sa = (L >> 2) + (sb + SM_S + 768);
                const uint32_t rt = L + (rsb + SM_RT + 8192 + g * 1024);
                uint32_t va[2][2][4], vm[4], pw[6], w[4];
                wg_fence();
                batch(std::integral_constant<int, 0>(), std::integral_constant<int, TA0>());
                wg_commit();
                batch(std::integral_constant<int, TA0>(), std::integral_constant<int, 32>());
                wg_commit();
                wg_wait<1>();
                softmax40(pw, sa, [&]() {});
                ldsm4t(va[0][0], va0); ldsm4t(va[0][1], va0 + 2048);
                ldsm4t(va[1][0], va1); ldsm4t(va[1][1], va1 + 2048);
                ldsm4(vm, vma);
                wg_wait<0>();
                TL(27);
                float inv[2];
                pv32<true>(w, inv, va, vm, pw, [&]() {
                    if (s + 3 < NSEG) {
#pragma unroll
                        for (int i = 0; i < 2; i++)
                            st_async4(rt + i * 512, kh ? d[4 * i] : d[8 + 4 * i], kh ? d[4 * i + 1] : d[9 + 4 * i], kh ? d[4 * i + 2] : d[10 + 4 * i], kh ? d[4 * i + 3] : d[11 + 4 * i], rsb + MB_RT1);
                    }
#pragma unroll
                    for (int i = 0; i < 8; i++) o[i] = kh ? d[8 + i] : d[i];
                });
                stsm4t((L & 0x70) * 5 + ((L >> 3) & 0x30) + (sb + SM_TO + g * 640), w[0], w[1], w[2], w[3]);
                __syncwarp();
                const uint4 r = lds128(((L >> 2) & 0x70) * 5 + (L & 0x30) + (sb + SM_TO + g * 640));
                if (s >= 0) stg128(reinterpret_cast<char*>(g_ox) + (((L & 0x1C0) << 7) + (L & 0x30) + (((ui - 3) * SEG + 8 * j) * HD + h * DH + 32 * g) * 2), r);
                TL(26);
            }
            if (s + 3 < NSEG) {
                PHASE(3);
                const uint32_t rt = L + (sb + SM_RT + 8192 + g * 1024), so = FRAG() + (sb + SM_STG + 4096);
                mbar_wait_w(sb + MB_RT1, it & 1);
                TL(28);
                uint32_t w[4];
#pragma unroll
                for (int i = 0; i < 2; i++) {
                    const uint4 v = lds128(rt + i * 512);
                    w[2 * i] = pack_bf16(o[4 * i] + __uint_as_float(v.x), o[4 * i + 1] + __uint_as_float(v.y));
                    w[2 * i + 1] = pack_bf16(o[4 * i + 2] + __uint_as_float(v.z), o[4 * i + 3] + __uint_as_float(v.w));
                }
                stsm4t(so, w[0], w[1], w[2], w[3]);
                __syncwarp();
                mbar_arrive_if0(L, sb + MB_STG);
                TL(15);
            }
        }
    }
    KT_END(2);
    asm volatile("barrier.cluster.arrive.relaxed; barrier.cluster.wait;" ::: "memory");
}
constexpr int B_UCH = 73 * 64;
constexpr int B_SCH = 33 * 64;
constexpr int B_KLEN = 2128;
constexpr int B_KCH = 2 * B_KLEN * 2 + 64;
constexpr int B_KBOX = 136 * 32;
constexpr int B_SM_U = 0;
constexpr int B_SM_S = 8 * B_UCH;
constexpr int B_SM_K = B_SM_S + 8 * B_SCH;
constexpr int B_SM_KT = B_SM_K + 8 * B_KCH;
constexpr int B_SM_VT = B_SM_KT + 8 * B_KBOX;
constexpr int B_SM_QT = B_SM_VT + 32768;
constexpr int B_SM_BAR = B_SM_QT + 32768;
constexpr int B_SMEM = B_SM_BAR + 128 + 512;
static_assert(B_SM_KT % 256 == 0 && B_SM_S % 512 == 0 && B_SMEM <= 232448, "tiles");
constexpr int PROBE_N = 4;
#define PROBE_R 2
constexpr int B_C = 2056;

__device__ __forceinline__ uint32_t atomic_round_trip(char* p) {
    uint32_t t0, t1, v;
    asm volatile("{.reg .pred p;\n"
                 "mov.u32 %0, %%clock;\n"
                 "atom.relaxed.gpu.global.add.u32 %2, [%3], 1;\n"
                 "setp.ne.u32 p, %2, 0x7FFFFFFF;\n"
                 "mov.u32 %1, 0;\n"
                 "@p mov.u32 %1, %%clock;}" : "=&r"(t0), "=&r"(t1), "=&r"(v) : "l"(p) : "memory");
    return t1 - t0;
}
__device__ __forceinline__ uint32_t round_trips(char* a, char* b, uint32_t stride, int lane) {
    for (int i = lane >> 3; i < 2 * PROBE_N; i += 4) stg128(((i & 1) ? b : a) + (i >> 1) * stride + (lane & 7) * 16, make_uint4(0, 0, 0, 0));
    __syncwarp();
    uint32_t ta = 0xFFFF, tb = 0xFFFF;
    if (lane == 0) {
        __threadfence();
#pragma unroll 1
        for (int i = 0; i < PROBE_N; i++) { ta = min(ta, atomic_round_trip(a + i * stride)); tb = min(tb, atomic_round_trip(b + i * stride)); }
    }
    __syncwarp();
    return ta | (tb << 16);
}
__device__ __forceinline__ void measure_distance(char* mbox, int lane) {
    const uint32_t b = blockIdx.x;
    unsigned smid;
    asm volatile("mov.u32 %0, %%smid;" : "=r"(smid));
    char* w1 = mbox + WIN + (b & 31) * 128;
    uint32_t r = 0xFFFFFFFF;
#pragma unroll 1
    for (int i = 0; i < PROBE_R; i++) r = __vminu2(r, round_trips(w1 + page_off(50 + 5 * i + (b >> 5), 0), w1 + page_off(50 + 5 * i + (b >> 5), 1), 16384, lane));
    if (lane == 0) g_cls[smid] = r;
    if (b == 128) {
        char *p = mbox + page_off(0, 0), *q = mbox + page_off(0, 1);
        uint32_t r0 = 0xFFFFFFFF;
#pragma unroll 1
        for (int i = 0; i < PROBE_R; i++) r0 = __vminu2(r0, round_trips(p, q, 128, lane));
        if (lane == 0) { g_reg[1] = ((r0 & 0xFFFF) > (r0 >> 16)) != ((r & 0xFFFF) > (r >> 16)); if (!EARLY_ROLE) g_reg[0] = 0; g_reg[2] = 0; }
        const uint4 sent = make_uint4(SENT, SENT, SENT, SENT);
        stg128(p + lane * 16, sent); stg128(q + lane * 16, sent);
    }
    if (b == 129) for (int i = lane; i < 128; i += 32) g_xflag[i] = 0;
}

#define SP(i)
#define SP2(i)
#define OUT_STG 0
#define PF_STOP 1
#define SENT_AT 3
#define Q_LATE 1
#define PF_DEPTH 4
#define PF_STRIDE 256
struct ChainInputs { const char* w[4]; const char *x, *mem0; };
#define EF_MASK 15
#define EF(i) (((EF_MASK >> (i)) & 1) ? policy_evict_first() : policy_evict_normal())
__device__ __forceinline__ void l2_prefetch(const char* p, uint32_t bytes) {
    asm volatile("cp.async.bulk.prefetch.L2.global [%0], %1;" ::"l"(p), "r"(bytes) : "memory");
}
#define WG_CONV(N, LIST, A0, A1, A2, A3, LO, OF, ...) \
    if constexpr (NN == N) asm volatile("{.reg .b32 l; .reg .b64 e; add.u32 l, %" #LO ", %" #OF "; mov.b64 e, {l, 0x80000020};\n" \
        "wgmma.mma_async.sync.aligned.m64n" #N "k16.f32.bf16.bf16 {" LIST "}, {%" #A0 ",%" #A1 ",%" #A2 ",%" #A3 "}, e, 1, 1, 1, 0;}" \
        : __VA_ARGS__ : "r"(a[0]), "r"(a[1]), "r"(a[2]), "r"(a[3]), "r"(lo), "n"(OFF));
#define WL4 "%0,%1,%2,%3"
#define WL8 WL4 ",%4,%5,%6,%7"
#define WL12 WL8 ",%8,%9,%10,%11"
#define WL16 WL12 ",%12,%13,%14,%15"
#define WL20 WL16 ",%16,%17,%18,%19"
#define WL24 WL20 ",%20,%21,%22,%23"
#define WL28 WL24 ",%24,%25,%26,%27"
#define WL32 WL28 ",%28,%29,%30,%31"
template <int NN, int OFF> __device__ __forceinline__ void wgmma_conv(float (&d)[32], const uint32_t (&a)[4], uint32_t lo) {
    WG_CONV(8, WL4, 4, 5, 6, 7, 8, 9, R4(0))
    WG_CONV(16, WL8, 8, 9, 10, 11, 12, 13, R4(0), R4(4))
    WG_CONV(24, WL12, 12, 13, 14, 15, 16, 17, R4(0), R4(4), R4(8))
    WG_CONV(32, WL16, 16, 17, 18, 19, 20, 21, R16(0))
    WG_CONV(40, WL20, 20, 21, 22, 23, 24, 25, R16(0), R4(16))
    WG_CONV(48, WL24, 24, 25, 26, 27, 28, 29, R16(0), R4(16), R4(20))
    WG_CONV(56, WL28, 28, 29, 30, 31, 32, 33, R16(0), R4(16), R4(20), R4(24))
    WG_CONV(64, WL32, 32, 33, 34, 35, 36, 37, R16(0), R16(16))
}
__device__ __forceinline__ void copy_to_peer(uint32_t dst, uint32_t src, uint32_t bytes, uint32_t bar) {
    asm volatile("cp.async.bulk.shared::cluster.shared::cta.mbarrier::complete_tx::bytes [%0], [%1], %2, [%3];" ::"r"(dst), "r"(src), "r"(bytes), "r"(bar) : "memory");
}
__device__ __forceinline__ uint32_t lds_volatile(uint32_t a) {
    uint32_t v;
    asm volatile("ld.volatile.shared.u32 %0, [%1];" : "=r"(v) : "r"(a) : "memory");
    return v;
}
__device__ __forceinline__ uint32_t swz64(uint32_t a) { return a ^ ((a >> 3) & 0x30); }
__device__ __forceinline__ void fence_async() { asm volatile("fence.proxy.async.shared::cta;" ::: "memory"); }

__global__ void __cluster_dims__(2, 1, 1) __launch_bounds__(576, 1)
ssm_kernel(const __grid_constant__ CUtensorMap mapK, const __grid_constant__ CUtensorMap mapV, const __grid_constant__ CUtensorMap mapQ,
           const __grid_constant__ CUtensorMap mapO, const bf16* __restrict__ shiftk, const bf16* __restrict__ ssmk, const bf16* __restrict__ Dv,
           char* __restrict__ mbox, const __grid_constant__ ChainInputs ci, bf16* __restrict__ outp) {
    extern __shared__ __align__(128) uint8_t smem_raw[];
    const uint32_t sb = (smem_u32(smem_raw) + 511) & ~511u;
    const int rank = blockIdx.x & 1, ch0 = blockIdx.x * 8, c16 = ch0 & ~15, t0 = rank * 1024;
    const int t = threadIdx.x, warp = t >> 5, lane = t & 31;
    const uint32_t bar = sb + B_SM_BAR, barQ = bar + 64, barU = bar + 72, barY = bar + 80, flag = bar + 88;
    SP(0);
    if (lane == 0 && warp < 16 && blockIdx.x < 128) {
        const int i = warp >> 1;
        if (warp & 1) {
            if (i < 3) { mbar_init(barQ + i * 8, 1); mbar_expect_tx(barQ + i * 8, i ? 16384 : 32768); }
            if (i == 3) sts32(flag, 0);
        } else {
            mbar_init(bar + i * 8, 1);
            asm volatile("fence.mbarrier_init.release.cluster;" ::: "memory");
            mbar_expect_tx(bar + i * 8, B_KBOX + 4096);
            tma_load_2d(sb + B_SM_KT + i * B_KBOX, &mapK, c16, t0 + i * 128 - 8, bar + i * 8, EF(0));
            tma_load_2d(sb + B_SM_VT + i * 4096, &mapV, c16, t0 + i * 128, bar + i * 8, EF(0));
        }
        asm volatile("fence.mbarrier_init.release.cluster;" ::: "memory");
    }
    __syncwarp();
    if (warp == 14) SP2(14);
    KT_START(1);
    if (warp == 17) {
        launch_dependents();
        asm volatile("barrier.cluster.arrive.relaxed.aligned;" ::: "memory");
        measure_distance(mbox, lane);
        asm volatile("barrier.cluster.wait.aligned;" ::: "memory");
        KT_MARK(14);
        return;
    }
    if (blockIdx.x >= 128) return;
    if (warp == 16) {
        asm volatile("barrier.cluster.arrive.relaxed.aligned; barrier.cluster.wait.aligned;" ::: "memory");
        SP2(8);
        if (Q_LATE) for (int i = 0; i < 8; i++) { mbar_wait_w(bar + i * 8, 0); SP2(i); }
        if (lane < 8) tma_load_2d(sb + B_SM_QT + lane * 4096, &mapQ, c16, t0 + lane * 128, barQ, EF(3));
        if (!Q_LATE) for (int i = 0; i < 8; i++) mbar_wait_w(bar + i * 8, 0);
        if (lane == 0) {
            l2_prefetch(ci.x + blockIdx.x * 2048, 2048);
            if (blockIdx.x < 8) l2_prefetch(ci.mem0 + blockIdx.x * 2048, 2048);
        }
        uint32_t v[PF_DEPTH], acc = 0;
#pragma unroll
        for (int u = 0; u < PF_DEPTH; u++) v[u] = 0;
        constexpr int PER = 32 * PF_STRIDE, NW = 65536 / PER;
#define PF_N (4 * NW)
        int i = 0;
#pragma unroll 1
        for (; i < PF_N && lds_volatile(flag) == 0; i += PF_DEPTH) {
#pragma unroll
            for (int u = 0; u < PF_DEPTH; u++) {
                const char* a = ci.w[(i + u) / NW] + blockIdx.x * 65536 + ((i + u) % NW) * PER + lane * PF_STRIDE;
                acc |= v[u];
                asm volatile("ld.global.cg.L2::256B.u32 %0, [%1];" : "=r"(v[u]) : "l"(a) : "memory");
            }
        }
#pragma unroll
        for (int u = 0; u < PF_DEPTH; u++) acc |= v[u];
        if (acc == 0x7FFF7FFFu && v[0] == 0x7FFEu) g_err = 1;
        SP2(12);
        KT_MARK(15);
        return;
    }
    asm volatile("barrier.cluster.arrive.relaxed.aligned;" ::: "memory");
    const int far = warp & 1, unit = rank ^ far;
    uint32_t w[4];
    uint32_t d2;
    asm volatile("ld.global.nc.u32 %0, [%1];" : "=r"(d2) : "l"(Dv + ch0 + (warp >> 2) * 2));
    {
        const int ch = warp & 7, half = warp >> 3;
        const uint32_t kb = sb + B_SM_K + ch * B_KCH;
        const uint4* src = reinterpret_cast<const uint4*>(ssmk + (size_t)(ch0 + ch) * S_LEN);
        uint4 kr[4];
#pragma unroll
        for (int i = 0; i < 4; i++) kr[i] = ldg128(src + half * 128 + i * 32 + lane, EF(1));
        const uint32_t edge = half ? 0u : __ldg(reinterpret_cast<const uint32_t*>(src + 128));
        const uint2 sw = __ldg(reinterpret_cast<const uint2*>(shiftk + (size_t)(c16 + unit * 8 + (lane >> 2)) * 4));
        w[0] = __byte_perm(sw.x, 0, 0x1010); w[1] = __byte_perm(sw.x, 0, 0x3232); w[2] = __byte_perm(sw.y, 0, 0x1010); w[3] = __byte_perm(sw.y, 0, 0x3232);
        if (half) sts128(sb + B_SM_U + ch * B_UCH + 4096 + lane * 16, make_uint4(0, 0, 0, 0));
#pragma unroll
        for (int i = 0; i < 4; i++) {
            const uint4 lo = kr[i];
            const uint32_t nx = __shfl_down_sync(~0u, lo.x, 1), n0 = (i < 3) ? __shfl_sync(~0u, kr[i < 3 ? i + 1 : 3].x, 0) : edge;
            const uint32_t hix = (lane < 31) ? nx : n0;
            const int c = 256 - (half * 128 + 32 * i + lane);
            sts128(kb + c * 16, make_uint4(__byte_perm(hix, lo.w, 0x7610), __byte_perm(lo.w, lo.z, 0x7610), __byte_perm(lo.z, lo.y, 0x7610), __byte_perm(lo.y, lo.x, 0x7610)));
            sts128(kb + B_KLEN * 2 + 64 + c * 16, make_uint4(__byte_perm(lo.w, lo.w, 0x1032), __byte_perm(lo.z, lo.z, 0x1032), __byte_perm(lo.y, lo.y, 0x1032), __byte_perm(lo.x, lo.x, 0x1032)));
        }
        const uint32_t k0w = __shfl_sync(~0u, kr[0].x, 0);
        if (half == 0 && lane < 8) {
            sts128(kb + (257 + lane) * 16, make_uint4(lane == 0 ? (k0w & 0xFFFFu) : 0u, 0u, 0u, 0u));
            sts128(kb + B_KLEN * 2 + 64 + (257 + lane) * 16, make_uint4(0u, 0u, 0u, 0u));
        }
    }
    auto sentinels = [&]() {
        const uint4 sent = make_uint4(SENT, SENT, SENT, SENT);
        char* p0 = mbox + blockIdx.x * 16384 + t * 16;
        if (blockIdx.x != 0 || (t & 255) >= 32) stg128(p0, sent);
        stg128(p0 + 8192, sent);
        char* p1 = mbox + WIN + blockIdx.x * 12800 + t * 16;
        stg128(p1, sent);
        if (t < 288) stg128(p1 + 8192, sent);
    };
    if (SENT_AT == 1) sentinels();
    asm volatile("barrier.cluster.wait.acquire.aligned;" ::: "memory");
    SP(1);
    {
        const int box = warp >> 1, row0 = 63 - 32 * rank - 4 * box;
        const uint32_t kt = sb + B_SM_KT + box * B_KBOX + 256 + lane * 32, s0 = (unit ^ ((lane >> 2) & 1)) * 16;
        const uint32_t a0 = kt + s0, a2 = kt - 64 + (unit ^ (((lane + 6) >> 2) & 1)) * 16, a4 = kt - 128 + (s0 ^ 16), av = sb + B_SM_VT + box * 4096 + lane * 32 + s0;
        const uint32_t ul = (lane & 7) * B_UCH + row0 * 64 + (lane >> 3) * 16;
        const uint32_t ud = sb + (far ? B_SM_S + (lane & 7) * (B_SCH - B_UCH) - (1 - rank) * 2048 : B_SM_U);
        mbar_wait_w(bar + box * 8, 0);
        SP(2);
#pragma unroll
        for (int i = 0; i < 4; i++) {
            uint32_t k0[4], k2[4], k4[4], vv[4], o[4];
            ldsm4t(k0, a0 + i * 1024); ldsm4t(k2, a2 + i * 1024); ldsm4t(k4, a4 + i * 1024); ldsm4t(vv, av + i * 1024);
#pragma unroll
            for (int j = 0; j < 4; j++) {
                uint32_t a = bf16_mul(__byte_perm(k4[j], k2[j], 0x5432), w[3]);
                a = bf16_add(a, bf16_mul(k2[j], w[2]));
                a = bf16_add(a, bf16_mul(__byte_perm(k2[j], k0[j], 0x5432), w[1]));
                a = bf16_add(a, bf16_mul(k0[j], w[0]));
                o[j] = bf16_mul(a, vv[j]);
            }
            stsm4(ud + swz64(ul - i * 64), o[0], o[1], o[2], o[3]);
        }
        fence_async();
        __syncwarp();
        if (far && lane < 8) {
            const uint32_t o = lane * B_UCH + (row0 - 3) * 64;
            copy_to_peer(peer_addr(sb + B_SM_U + o, rank ^ 1), ud + o, 256, peer_addr(barU, rank ^ 1));
        }
    }
    bar_sync(1, 512);
    mbar_wait_w(barU, 0);
    if (SENT_AT == 2) sentinels();
    SP(3);
    const int wg = warp >> 2, wq = warp & 3, hi = wq >> 1, g = lane >> 2, tq = lane & 3;
    const uint32_t zero = lds32(sb + B_SM_U + 4096);
#pragma unroll 1
    for (int cc = 0; cc < 2; cc++) {
        const int ch = 2 * wg + cc;
        const uint32_t kb = sb + B_SM_K + ch * B_KCH, ub = sb + B_SM_U + ch * B_UCH;
        const uint32_t dw = __byte_perm(d2, 0, cc ? 0x3232 : 0x1010);
        const int e0 = B_C - g + 2 * tq;
        const uint32_t f0 = ((e0 & 1) ? (kb + B_KLEN * 2 + 64 + (e0 - 1) * 2) : (kb + e0 * 2)) - 32 * wq;
        const uint32_t lo = uniform((ub >> 4) | 0x10000);
        float d[32];
#pragma unroll
        for (int i = 0; i < 32; i++) d[i] = 0.f;
        uint32_t A[2][2][4];
        static_for<0, 32>([&](auto jc) {
            constexpr int j = decltype(jc)::value, N = 64 - 8 * (j / 4);
            if (j >= 2) wg_wait<1>();
            uint32_t(&a)[4] = A[j & 1][0];
            uint32_t(&b)[4] = A[j & 1][1];
            a[0] = lds32(f0 - 128 * j); a[1] = lds32(f0 - 128 * j - 16); a[2] = lds32(f0 - 128 * j + 16);
            b[0] = lds32(f0 - 128 * j + 32); b[2] = lds32(f0 - 128 * j + 48);
            a[3] = a[0] ^ zero; b[1] = a[2] ^ zero; b[3] = b[0] ^ zero;
            wg_fence();
            wgmma_conv<N, 8 * j>(d, a, lo);
            wgmma_conv<N, 8 * j + 2>(d, b, lo);
            wg_commit();
        });
        wg_wait<0>();
        if (cc) SP(4);
        if (PF_STOP == 1 && cc && t == 0) sts32(flag, 1);
        bar_sync(2 + wg, 128);
        if (!hi && tq == 3) { float x = d[13]; d[13] = d[29]; d[29] = x; x = d[15]; d[15] = d[31]; d[31] = x; }
        if (hi && tq == 0) { d[0] = 0.f; d[2] = 0.f; }
        {
            const uint32_t xs = kb + (wq ^ 2) * 2048 + lane * 4;
            const uint32_t xn = hi ? xs + (tq ? 124 : 140) : xs + (tq < 3 ? 4 : -12), wrap = hi ? (tq ? 0 : -1) : (tq < 3 ? 0 : 1);
#pragma unroll
            for (int nb = 0; nb < 4; nb++) {
                const uint32_t xw = xn + ((nb + wrap) & 3) * 512;
#pragma unroll
                for (int i = 0; i < 2; i++) {
                    const float e0v = hi ? d[4 * nb + 2 * i] : d[16 + 4 * nb + 2 * i], e1v = hi ? d[4 * nb + 2 * i + 1] : d[16 + 4 * nb + 2 * i + 1];
                    sts32(hi ? xw + i * 256 : xs + nb * 512 + i * 256 + 128, __float_as_uint(e0v));
                    sts32(hi ? xs + nb * 512 + i * 256 : xw + i * 256, __float_as_uint(e1v));
                }
            }
        }
        bar_sync(2 + wg, 128);
#pragma unroll
        for (int p = 0; p < 2; p++) {
            int row = 16 * p + (lane >> 4) * 8 + (lane & 7);
            row = hi ? row + 31 : row == 31 ? 63 : row;
            const uint32_t a = sb + B_SM_U + swz64(ch * B_UCH + row * 64 + ((wq & 1) * 2 + ((lane >> 3) & 1)) * 16);
            uint32_t u[4];
            ldsm4t(u, a);
#pragma unroll
            for (int b = 0; b < 4; b++) {
                const int r = 8 * p + 2 * b;
                const float y0 = (hi ? d[16 + r] : d[r]) + __uint_as_float(lds32(kb + wq * 2048 + r * 128 + lane * 4));
                const float y1 = (hi ? d[17 + r] : d[r + 1]) + __uint_as_float(lds32(kb + wq * 2048 + r * 128 + 128 + lane * 4));
                u[b] = bf16_add(pack_bf16(y0, y1), bf16_mul(u[b], dw));
            }
            stsm4t(a, u[0], u[1], u[2], u[3]);
        }
        fence_async();
        bar_sync(2 + wg, 128);
        if (SENT_AT == 3 && cc == 0) sentinels();
        if (wq == 0 && lane == 0) copy_to_peer(peer_addr(sb + B_SM_S + ch * B_SCH, rank ^ 1), ub + rank * 2048, 2048, peer_addr(barY, rank ^ 1));
    }
    if (PF_STOP == 2 && t == 0) sts32(flag, 1);
    SP(5);
    mbar_wait_w(barQ, 0);
    bar_sync(1, 512);
    mbar_wait_w(barY, 0);
    asm volatile("barrier.cluster.arrive.relaxed.aligned;" ::: "memory");
    SP(6);
#pragma unroll
    for (int i = 0; i < 4; i++) {
        const int fr = i & 1, row = 63 - 32 * rank - 2 * warp - (i >> 1);
        const uint32_t qa = sb + B_SM_QT + warp * 2048 + (i >> 1) * 1024 + lane * 32 + ((rank ^ fr ^ (lane >> 2)) & 1) * 16;
        uint32_t y[4], q[4];
        ldsm4t(y, sb + (fr ? B_SM_S + (lane & 7) * (B_SCH - B_UCH) - (1 - rank) * 2048 : B_SM_U) + swz64((lane & 7) * B_UCH + row * 64 + (lane >> 3) * 16));
        ldsm4(q, qa);
        stsm4(qa, bf16_mul(q[0], y[0]), bf16_mul(q[1], y[1]), bf16_mul(q[2], y[2]), bf16_mul(q[3], y[3]));
    }
    fence_async();
    __syncwarp();
    if (lane == 0) {
        asm volatile("cp.async.bulk.tensor.2d.global.shared::cta.bulk_group.L2::cache_hint [%0, {%2, %3}], [%1], %4;"
                     ::"l"(&mapO), "r"(sb + B_SM_QT + warp * 2048), "r"(DM + c16), "r"(t0 + warp * 64), "l"(EF(4)) : "memory");
        asm volatile("cp.async.bulk.commit_group;" ::: "memory");
    }
    if (SENT_AT == 0) sentinels();
    if (warp == 0) SP2(10);
    if (lane == 0) asm volatile("cp.async.bulk.wait_group.read 0;" ::: "memory");
    __syncwarp();
    if (warp == 0) SP2(11);
    asm volatile("barrier.cluster.wait.aligned;" ::: "memory");
    SP(7);
    KT_END(1);
}

typedef CUresult (*EncodeFn)(CUtensorMap*, CUtensorMapDataType, cuuint32_t, void*, const cuuint64_t*, const cuuint64_t*, const cuuint32_t*,
                             const cuuint32_t*, CUtensorMapInterleave, CUtensorMapSwizzle, CUtensorMapL2promotion, CUtensorMapFloatOOBfill);

static void make_map(EncodeFn fn, CUtensorMap* m, const void* ptr, uint64_t inner, uint64_t outer, uint32_t box_in, uint32_t box_out,
                     CUtensorMapL2promotion promo = CU_TENSOR_MAP_L2_PROMOTION_L2_256B) {
    cuuint64_t dims[2] = {inner, outer};
    cuuint64_t strides[1] = {inner * 2};
    cuuint32_t box[2] = {box_in, box_out};
    cuuint32_t es[2] = {1, 1};
    fn(m, CU_TENSOR_MAP_DATA_TYPE_BFLOAT16, 2, const_cast<void*>(ptr), dims, strides, box, es, CU_TENSOR_MAP_INTERLEAVE_NONE,
       CU_TENSOR_MAP_SWIZZLE_128B, promo, CU_TENSOR_MAP_FLOAT_OOB_FILL_NONE);
}

#define G2_ST 7
#define PROMO_W CU_TENSOR_MAP_L2_PROMOTION_L2_256B
#define PROMO_O CU_TENSOR_MAP_L2_PROMOTION_L2_256B
#define SSM_PROMO CU_TENSOR_MAP_L2_PROMOTION_NONE
extern "C" void kernel_launch(void* const* d_in, const int* in_sizes, int n_in, void* d_out, int out_size) {
    const bf16* x = (const bf16*)d_in[0];
    const bf16* mem0 = (const bf16*)d_in[1];
    const bf16* Wq = (const bf16*)d_in[2];
    const bf16* Wk = (const bf16*)d_in[3];
    const bf16* Wv = (const bf16*)d_in[4];
    const bf16* Wo = (const bf16*)d_in[5];
    const bf16* Bq = (const bf16*)d_in[7];
    const bf16* Bk = (const bf16*)d_in[8];
    const bf16* Bv = (const bf16*)d_in[9];
    const bf16* Bsh = (const bf16*)d_in[10];
    const bf16* Bssm = (const bf16*)d_in[11];
    const bf16* BD = (const bf16*)d_in[12];
    bf16* out = (bf16*)d_out;

    static bool init = false;
    static EncodeFn enc = nullptr;
    static void *p_tok, *p_ox, *p_mbox;
    static int nclusters = 64;
    if (!init) {
        cudaDriverEntryPointQueryResult qr;
        cudaGetDriverEntryPoint("cuTensorMapEncodeTiled", (void**)&enc, cudaEnableDefault, &qr);
        cudaGetSymbolAddress(&p_tok, g_tok);
        cudaGetSymbolAddress(&p_ox, g_ox);
        cudaGetSymbolAddress(&p_mbox, g_mbox);
        cudaFuncSetAttribute(proj_kernel<96, G2_ST>, cudaFuncAttributeMaxDynamicSharedMemorySize, PROJ_SMEM);
        cudaFuncSetAttribute(proj_kernel<128, 7>, cudaFuncAttributeMaxDynamicSharedMemorySize, PROJ_SMEM);
        cudaFuncSetAttribute(chain_kernel, cudaFuncAttributeMaxDynamicSharedMemorySize, CHAIN_SMEM);
        cudaFuncSetAttribute(ssm_kernel, cudaFuncAttributeMaxDynamicSharedMemorySize, B_SMEM);
        cudaLaunchConfig_t cfg = {};
        cfg.gridDim = dim3(132); cfg.blockDim = dim3(384); cfg.dynamicSmemBytes = CHAIN_SMEM;
        cudaLaunchAttribute at[1];
        at[0].id = cudaLaunchAttributeClusterDimension; at[0].val.clusterDim.x = 2; at[0].val.clusterDim.y = 1; at[0].val.clusterDim.z = 1;
        cfg.attrs = at; cfg.numAttrs = 1;
        int n = 0;
        if (cudaOccupancyMaxActiveClusters(&n, chain_kernel, &cfg) == cudaSuccess && n > 64) nclusters = n < 66 ? n : 66;
        (void)cudaGetLastError();
        init = true;
    }
    char* mbox = (char*)(((uintptr_t)p_mbox + 2 * WIN - 1) & ~(uintptr_t)(2 * WIN - 1));
    CUtensorMap mX, mT32, mT16, mTQ, mKV, mWq, mWk, mWv, mWoC, mWo, mOxE, mOutE, mOx, mOut;
    {
        cuuint64_t dims[3] = {64, S_LEN, DM / 64};
        cuuint64_t strides[2] = {DM * 2, 128};
        cuuint32_t box[3] = {64, 32, 4};
        cuuint32_t es[3] = {1, 1, 1};
        enc(&mX, CU_TENSOR_MAP_DATA_TYPE_BFLOAT16, 3, const_cast<bf16*>(x), dims, strides, box, es, CU_TENSOR_MAP_INTERLEAVE_NONE,
            CU_TENSOR_MAP_SWIZZLE_128B, CU_TENSOR_MAP_L2_PROMOTION_L2_256B, CU_TENSOR_MAP_FLOAT_OOB_FILL_NONE);
    }
    make_map(enc, &mT32, p_tok, DH, 4 * NH * 3 * SEG, 64, 32, CU_TENSOR_MAP_L2_PROMOTION_L2_128B);
    make_map(enc, &mT16, p_tok, DH, 4 * NH * 3 * SEG, 64, 16, CU_TENSOR_MAP_L2_PROMOTION_L2_128B);
    {
        cuuint64_t dims[2] = {512, 4 * NH * 12};
        cuuint64_t strides[1] = {2048};
        cuuint32_t box[2] = {256, 4};
        cuuint32_t es[2] = {1, 1};
        enc(&mTQ, CU_TENSOR_MAP_DATA_TYPE_UINT32, 2, p_tok, dims, strides, box, es, CU_TENSOR_MAP_INTERLEAVE_NONE,
            CU_TENSOR_MAP_SWIZZLE_NONE, CU_TENSOR_MAP_L2_PROMOTION_L2_128B, CU_TENSOR_MAP_FLOAT_OOB_FILL_NONE);
    }
    {
        cuuint64_t dims[3] = {64, 4 * NH * 3 * SEG, 2};
        cuuint64_t strides[2] = {DH * 2, 128};
        cuuint32_t box[3] = {64, 32, 2};
        cuuint32_t es[3] = {1, 1, 1};
        enc(&mKV, CU_TENSOR_MAP_DATA_TYPE_BFLOAT16, 3, p_tok, dims, strides, box, es, CU_TENSOR_MAP_INTERLEAVE_NONE,
            CU_TENSOR_MAP_SWIZZLE_128B, CU_TENSOR_MAP_L2_PROMOTION_L2_128B, CU_TENSOR_MAP_FLOAT_OOB_FILL_NONE);
    }
    make_map(enc, &mWq, Wq, HD, DM, 64, 16, CU_TENSOR_MAP_L2_PROMOTION_L2_128B);
    make_map(enc, &mWk, Wk, HD, DM, 64, 16, CU_TENSOR_MAP_L2_PROMOTION_L2_128B);
    make_map(enc, &mWv, Wv, HD, DM, 64, 16, CU_TENSOR_MAP_L2_PROMOTION_L2_128B);
    make_map(enc, &mWoC, Wo, DM, HD, 64, PRO3 ? 16 : 128, CU_TENSOR_MAP_L2_PROMOTION_L2_128B);
    const bool early = nclusters >= 66;
    make_map(enc, &mWo, Wo, DM, HD, 64, 64, PROMO_W);
    make_map(enc, &mOxE, p_ox, HD, S_LEN, 64, EARLY_NT / 2);
    make_map(enc, &mOutE, out, OUT_LD, S_LEN, 64, EARLY_NT);
    make_map(enc, &mOx, p_ox, HD, S_LEN, 64, (early ? 96 : 128) >> FIN_SO, PROMO_O);
    make_map(enc, &mOut, out, OUT_LD, S_LEN, 64, early ? 96 : 128);

    CUtensorMap mB[4];
    for (int i = 0; i < 4; i++) {
        cuuint64_t dims[2] = {(cuuint64_t)(i < 3 ? DM : OUT_LD), S_LEN};
        cuuint64_t strides[1] = {dims[0] * 2};
        cuuint32_t box[2] = {16, i == 0 ? 136u : i < 3 ? 128u : 64u};
        cuuint32_t es[2] = {1, 1};
        enc(&mB[i], CU_TENSOR_MAP_DATA_TYPE_BFLOAT16, 2, const_cast<bf16*>(i == 0 ? Bk : i == 1 ? Bv : i == 2 ? Bq : out), dims, strides, box, es,
            CU_TENSOR_MAP_INTERLEAVE_NONE, CU_TENSOR_MAP_SWIZZLE_32B, SSM_PROMO, CU_TENSOR_MAP_FLOAT_OOB_FILL_NONE);
    }
    cudaStream_t st = cudaStreamPerThread;
    const ChainInputs ci = {{(const char*)Wv, (const char*)Wk, (const char*)Wq, (const char*)Wo}, (const char*)x, (const char*)mem0};
    ssm_kernel<<<132, 576, B_SMEM, st>>>(mB[0], mB[1], mB[2], mB[3], Bsh, Bssm, BD, mbox, ci, out);
    cudaLaunchAttribute pdl[1];
    pdl[0].id = cudaLaunchAttributeProgrammaticStreamSerialization; pdl[0].val.programmaticStreamSerializationAllowed = 1;
    cudaLaunchConfig_t lc = {};
    lc.stream = st; lc.attrs = pdl;
    lc.gridDim = dim3(2 * nclusters); lc.blockDim = dim3(384); lc.dynamicSmemBytes = CHAIN_SMEM; lc.numAttrs = PDL & 1;
    cudaLaunchKernelEx(&lc, chain_kernel, mX, mT32, mT16, mTQ, mKV, mWq, mWk, mWv, mWoC, mem0, mbox);
    lc.gridDim = dim3(2 * nclusters); lc.blockDim = dim3(PROJ_THREADS); lc.dynamicSmemBytes = PROJ_SMEM; lc.numAttrs = (PDL >> 1) & 1;
    cudaLaunchKernelEx(&lc, early ? proj_kernel<96, G2_ST> : proj_kernel<128, 7>, mWo, mOx, mOut, mOxE, mOutE);
}
```

```cpp
#include <cuda_runtime.h>
#include <cuda_bf16.h>
#include <cuda.h>
#include <stdint.h>
#include <type_traits>

typedef __nv_bfloat16 bf16;

constexpr int S_LEN = 2048, DM = 1024, NH = 32, DH = 128, NSEG = 64, SEG = 32;
constexpr int HD = NH * DH;
constexpr int OUT_LD = 2048;
constexpr unsigned SENT = 0xFFFFFFFFu;

__device__ bf16 g_tok[4 * NH * 3 * SEG * DH];
__device__ bf16 g_ox[(size_t)S_LEN * HD];
__device__ uint4 g_mbox[4 * 131072];
__device__ unsigned g_xflag[128];
__device__ unsigned g_reg[4];
__device__ __align__(16) unsigned g_cls[256];
__device__ unsigned g_err;
constexpr uint32_t WIN = 2u << 20;
__host__ __device__ constexpr uint32_t page_off(uint32_t idx, uint32_t c) {
    return ((idx & 1) << 13) | ((idx >> 1) << 16) | (((c ^ idx ^ (idx >> 1) ^ (idx >> 2) ^ (idx >> 4)) & 1) << 12);
}
#define STAT(i, c) (void)(c)
#define EARLY_ROLE 1
#define PDL 3

__device__ __forceinline__ void launch_dependents() { asm volatile("griddepcontrol.launch_dependents;" ::: "memory"); }
__device__ __forceinline__ void wait_prerequisites() { asm volatile("griddepcontrol.wait;" ::: "memory"); }
__device__ __forceinline__ void prefetch_map(const CUtensorMap* m) { asm volatile("prefetch.tensormap [%0];" ::"l"(m) : "memory"); }
#define KT_MARK(k)
#define KT_START(k)
#define KT_END(k)

__device__ __forceinline__ uint32_t smem_u32(const void* p) { return (uint32_t)__cvta_generic_to_shared(p); }
__device__ __forceinline__ void ldsm4(uint32_t& r0, uint32_t& r1, uint32_t& r2, uint32_t& r3, uint32_t a) {
    asm volatile("ldmatrix.sync.aligned.m8n8.x4.shared.b16 {%0,%1,%2,%3}, [%4];" : "=r"(r0), "=r"(r1), "=r"(r2), "=r"(r3) : "r"(a) : "memory");
}
__device__ __forceinline__ void ldsm4t(uint32_t& r0, uint32_t& r1, uint32_t& r2, uint32_t& r3, uint32_t a) {
    asm volatile("ldmatrix.sync.aligned.m8n8.x4.trans.shared.b16 {%0,%1,%2,%3}, [%4];" : "=r"(r0), "=r"(r1), "=r"(r2), "=r"(r3) : "r"(a) : "memory");
}
__device__ __forceinline__ void ldsm2(uint32_t& r0, uint32_t& r1, uint32_t a) {
    asm volatile("ldmatrix.sync.aligned.m8n8.x2.shared.b16 {%0,%1}, [%2];" : "=r"(r0), "=r"(r1) : "r"(a) : "memory");
}
__device__ __forceinline__ void stg128(void* p, uint4 v) {
    asm volatile("st.global.v4.u32 [%0], {%1,%2,%3,%4};" ::"l"(p), "r"(v.x), "r"(v.y), "r"(v.z), "r"(v.w) : "memory");
}
__device__ __forceinline__ void stsm4(uint32_t a, uint32_t r0, uint32_t r1, uint32_t r2, uint32_t r3) {
    asm volatile("stmatrix.sync.aligned.m8n8.x4.shared.b16 [%0], {%1,%2,%3,%4};" ::"r"(a), "r"(r0), "r"(r1), "r"(r2), "r"(r3) : "memory");
}
__device__ __forceinline__ void mma16816(float (&d)[4], uint32_t a0, uint32_t a1, uint32_t a2, uint32_t a3, uint32_t b0, uint32_t b1) {
    asm("mma.sync.aligned.m16n8k16.row.col.f32.bf16.bf16.f32 {%0,%1,%2,%3},{%4,%5,%6,%7},{%8,%9},{%0,%1,%2,%3};"
                 : "+f"(d[0]), "+f"(d[1]), "+f"(d[2]), "+f"(d[3])
                 : "r"(a0), "r"(a1), "r"(a2), "r"(a3), "r"(b0), "r"(b1));
}
__device__ __forceinline__ void mma1688(float (&d)[4], uint32_t a0, uint32_t a1, uint32_t b0) {
    asm("mma.sync.aligned.m16n8k8.row.col.f32.bf16.bf16.f32 {%0,%1,%2,%3},{%4,%5},{%6},{%0,%1,%2,%3};"
        : "+f"(d[0]), "+f"(d[1]), "+f"(d[2]), "+f"(d[3]) : "r"(a0), "r"(a1), "r"(b0));
}
__device__ __forceinline__ uint32_t movmat(uint32_t a) {
    uint32_t d;
    asm volatile("movmatrix.sync.aligned.m8n8.trans.b16 %0, %1;" : "=r"(d) : "r"(a));
    return d;
}
__device__ __forceinline__ uint32_t pack_bf16(float lo, float hi) {
    uint32_t r;
    asm("cvt.rn.bf16x2.f32 %0, %1, %2;" : "=r"(r) : "f"(hi), "f"(lo));
    return r;
}
__device__ __forceinline__ uint32_t bf16_mul(uint32_t a, uint32_t b) {
    uint32_t d;
    asm("mul.rn.bf16x2 %0, %1, %2;" : "=r"(d) : "r"(a), "r"(b));
    return d;
}
__device__ __forceinline__ uint32_t bf16_add(uint32_t a, uint32_t b) {
    uint32_t d;
    asm("add.rn.bf16x2 %0, %1, %2;" : "=r"(d) : "r"(a), "r"(b));
    return d;
}

__device__ __forceinline__ float bf16_round(float x) { return __bfloat162float(__float2bfloat16_rn(x)); }
__device__ __forceinline__ float bf_lo(uint32_t w) { return __uint_as_float(w << 16); }
__device__ __forceinline__ float bf_hi(uint32_t w) { return __uint_as_float(w & 0xFFFF0000u); }
__device__ __forceinline__ void bar_sync(int id, int n) { asm volatile("bar.sync %0, %1;" ::"r"(id), "r"(n) : "memory"); }
__device__ __forceinline__ void bar_sync_keep(int id, int n, uint32_t a, uint32_t b) {
    asm volatile("bar.sync %0, %1; // %2 %3" ::"r"(id), "r"(n), "r"(a), "r"(b) : "memory");
}
__device__ __forceinline__ bool bar_red_or(int id, int n, bool p) {
    uint32_t r;
    asm volatile("{.reg .pred p, q; setp.ne.u32 p, %3, 0; bar.red.or.pred q, %1, %2, p; selp.u32 %0, 1, 0, q;}" : "=r"(r) : "r"(id), "r"(n), "r"((uint32_t)p) : "memory");
    return r != 0;
}
__device__ __forceinline__ void bar_arrive(int id, int n) { asm volatile("bar.arrive %0, %1;" ::"r"(id), "r"(n) : "memory"); }
__device__ __forceinline__ void cp_async16(uint32_t dst, const void* src) {
    asm volatile("cp.async.cg.shared.global [%0], [%1], 16;" ::"r"(dst), "l"(src) : "memory");
}
__device__ __forceinline__ void cp_commit() { asm volatile("cp.async.commit_group;" ::: "memory"); }
template <int N> __device__ __forceinline__ void cp_wait() { asm volatile("cp.async.wait_group %0;" ::"n"(N) : "memory"); }
__device__ __forceinline__ uint4 ld_relaxed_v4(const void* p) {
    uint4 v;
    asm volatile("ld.relaxed.gpu.global.v4.u32 {%0,%1,%2,%3}, [%4];" : "=r"(v.x), "=r"(v.y), "=r"(v.z), "=r"(v.w) : "l"(p) : "memory");
    return v;
}
__device__ __forceinline__ void st_relaxed_u32(void* p, uint32_t v) { asm volatile("st.relaxed.gpu.global.u32 [%0], %1;" ::"l"(p), "r"(v) : "memory"); }
__device__ __forceinline__ void st_relaxed_v2(void* p, uint32_t a, uint32_t b) {
    asm volatile("st.relaxed.gpu.global.v2.u32 [%0], {%1,%2};" ::"l"(p), "r"(a), "r"(b) : "memory");
}
__device__ __forceinline__ void sts128(uint32_t a, uint4 v) {
    asm volatile("st.shared.v4.u32 [%0], {%1,%2,%3,%4};" ::"r"(a), "r"(v.x), "r"(v.y), "r"(v.z), "r"(v.w) : "memory");
}
__device__ __forceinline__ uint4 lds128(uint32_t a) {
    uint4 v;
    asm volatile("ld.shared.v4.u32 {%0,%1,%2,%3}, [%4];" : "=r"(v.x), "=r"(v.y), "=r"(v.z), "=r"(v.w) : "r"(a) : "memory");
    return v;
}
__device__ __forceinline__ void sts32(uint32_t a, uint32_t v) { asm volatile("st.shared.u32 [%0], %1;" ::"r"(a), "r"(v) : "memory"); }
__device__ __forceinline__ uint32_t lds32(uint32_t a) {
    uint32_t v;
    asm volatile("ld.shared.u32 %0, [%1];" : "=r"(v) : "r"(a) : "memory");
    return v;
}
__device__ __forceinline__ void mbar_init(uint32_t a, uint32_t c) { asm volatile("mbarrier.init.shared::cta.b64 [%0], %1;" ::"r"(a), "r"(c) : "memory"); }
__device__ __forceinline__ void mbar_expect_tx(uint32_t a, uint32_t bytes) {
    asm volatile("mbarrier.arrive.expect_tx.shared::cta.b64 _, [%0], %1;" ::"r"(a), "r"(bytes) : "memory");
}
__device__ __forceinline__ void mbar_arrive(uint32_t a) { asm volatile("mbarrier.arrive.shared::cta.b64 _, [%0];" ::"r"(a) : "memory"); }
__device__ __forceinline__ void mbar_wait(uint32_t a, uint32_t parity) {
    asm volatile("{.reg .pred p; .reg .u32 c;\n"
                 "mov.u32 c, 0;\n"
                 "MBW_LOOP:\n"
                 "add.u32 c, c, 1;\n"
                 "setp.gt.u32 p, c, 0x10000;\n"
                 "@!p mbarrier.try_wait.parity.shared::cta.b64 p, [%0], %1;\n"
                 "@!p bra.uni MBW_LOOP;}" ::"r"(a), "r"(parity) : "memory");
}
__device__ __forceinline__ void mbar_wait_w(uint32_t a, uint32_t parity) {
    asm volatile("{.reg .pred p; .reg .u32 c;\n"
                 "mov.u32 c, 0;\n"
                 "MBW_LOOP:\n"
                 "add.u32 c, c, 1;\n"
                 "setp.gt.u32 p, c, 0x10000;\n"
                 "@!p mbarrier.try_wait.parity.shared::cta.b64 p, [%0], %1;\n"
                 "vote.sync.all.pred p, p, 0xFFFFFFFF;\n"
                 "@!p bra.uni MBW_LOOP;}" ::"r"(a), "r"(parity) : "memory");
}
__device__ __forceinline__ void mbar_expect_tx_if0(uint32_t sel, uint32_t a, uint32_t bytes) {
    asm volatile("{.reg .pred p; setp.eq.u32 p, %2, 0; @p mbarrier.arrive.expect_tx.shared::cta.b64 _, [%0], %1;}" ::"r"(a), "r"(bytes), "r"(sel) : "memory");
}
__device__ __forceinline__ void mbar_arrive_if0(uint32_t sel, uint32_t a) {
    asm volatile("{.reg .pred p; setp.eq.u32 p, %1, 0; @p mbarrier.arrive.shared::cta.b64 _, [%0];}" ::"r"(a), "r"(sel) : "memory");
}
__device__ __forceinline__ void bulk_load(uint32_t dst, const void* src, uint32_t bytes, uint32_t bar) {
    asm volatile("cp.async.bulk.shared::cluster.global.mbarrier::complete_tx::bytes [%0], [%1], %2, [%3];" ::"r"(dst), "l"(src), "r"(bytes), "r"(bar) : "memory");
}
__device__ __forceinline__ void tma_load_2d(uint32_t dst, const CUtensorMap* map, int c0, int c1, uint32_t bar) {
    asm volatile("cp.async.bulk.tensor.2d.shared::cluster.global.mbarrier::complete_tx::bytes [%0], [%1, {%3, %4}], [%2];"
                 ::"r"(dst), "l"(map), "r"(bar), "r"(c0), "r"(c1) : "memory");
}
__device__ __forceinline__ void tma_load_2d_both(uint32_t dst, const CUtensorMap* map, int c0, int c1, uint32_t bar) {
    asm volatile("cp.async.bulk.tensor.2d.shared::cluster.global.mbarrier::complete_tx::bytes.multicast::cluster [%0], [%1, {%3, %4}], [%2], %5;"
                 ::"r"(dst), "l"(map), "r"(bar), "r"(c0), "r"(c1), "h"((uint16_t)3) : "memory");
}
__device__ __forceinline__ uint64_t policy_evict_first() {
    uint64_t p;
    asm("createpolicy.fractional.L2::evict_first.b64 %0, 1.0;" : "=l"(p));
    return p;
}
__device__ __forceinline__ uint64_t policy_evict_normal() {
    uint64_t p;
    asm("createpolicy.fractional.L2::evict_normal.b64 %0, 1.0;" : "=l"(p));
    return p;
}
__device__ __forceinline__ void tma_load_2d(uint32_t dst, const CUtensorMap* map, int c0, int c1, uint32_t bar, uint64_t pol) {
    asm volatile("cp.async.bulk.tensor.2d.shared::cluster.global.mbarrier::complete_tx::bytes.L2::cache_hint [%0], [%1, {%3, %4}], [%2], %5;"
                 ::"r"(dst), "l"(map), "r"(bar), "r"(c0), "r"(c1), "l"(pol) : "memory");
}
__device__ __forceinline__ uint4 ldg128(const void* p, uint64_t pol) {
    uint4 v;
    asm("ld.global.nc.L2::cache_hint.v4.u32 {%0,%1,%2,%3}, [%4], %5;" : "=r"(v.x), "=r"(v.y), "=r"(v.z), "=r"(v.w) : "l"(p), "l"(pol));
    return v;
}
__device__ __forceinline__ void stg128(void* p, uint4 v, uint64_t pol) {
    asm volatile("st.global.L2::cache_hint.v4.u32 [%0], {%1,%2,%3,%4}, %5;" ::"l"(p), "r"(v.x), "r"(v.y), "r"(v.z), "r"(v.w), "l"(pol) : "memory");
}
__device__ __forceinline__ void tma_store_2d(const CUtensorMap* map, uint32_t src, int c0, int c1) {
    asm volatile("cp.async.bulk.tensor.2d.global.shared::cta.bulk_group [%0, {%2, %3}], [%1];" ::"l"(map), "r"(src), "r"(c0), "r"(c1) : "memory");
}
__device__ __forceinline__ char* make_ptr(uint32_t lo, uint32_t hi) {
    uint64_t p;
    asm("mov.b64 %0, {%1, %2};" : "=l"(p) : "r"(lo), "r"(hi));
    return reinterpret_cast<char*>(p);
}
__device__ __forceinline__ uint64_t make_desc(uint32_t saddr, uint32_t lbo, uint32_t sbo) {
    return (uint64_t)((saddr & 0x3FFFF) >> 4) | ((uint64_t)((lbo >> 4) & 0x3FFF) << 16) | ((uint64_t)((sbo >> 4) & 0x3FFF) << 32) | ((uint64_t)1 << 62);
}
__device__ __forceinline__ void wg_fence() { asm volatile("wgmma.fence.sync.aligned;" ::: "memory"); }
__device__ __forceinline__ void wg_commit() { asm volatile("wgmma.commit_group.sync.aligned;" ::: "memory"); }
template <int N> __device__ __forceinline__ void wg_wait() { asm volatile("wgmma.wait_group.sync.aligned %0;" ::"n"(N) : "memory"); }

#define R4(b) "+f"(d[b + 0]), "+f"(d[b + 1]), "+f"(d[b + 2]), "+f"(d[b + 3])
#define R16(b) R4(b), R4(b + 4), R4(b + 8), R4(b + 12)
template <int N> __device__ __forceinline__ void wgmma_proj(float (&d)[N / 2], uint64_t da, uint64_t db) {
    if constexpr (N == 96)
        asm volatile("wgmma.mma_async.sync.aligned.m64n96k16.f32.bf16.bf16 {"
            "%0,%1,%2,%3,%4,%5,%6,%7,%8,%9,%10,%11,%12,%13,%14,%15,%16,%17,%18,%19,%20,%21,%22,%23,%24,%25,%26,%27,%28,%29,%30,%31,%32,%33,%34,%35,%36,%37,%38,%39,"
            "%40,%41,%42,%43,%44,%45,%46,%47"
            "}, %48, %49, 1, 1, 1, 1, 0;" : R16(0), R16(16), R16(32) : "l"(da), "l"(db));
    if constexpr (N == 128)
        asm volatile("wgmma.mma_async.sync.aligned.m64n128k16.f32.bf16.bf16 {"
            "%0,%1,%2,%3,%4,%5,%6,%7,%8,%9,%10,%11,%12,%13,%14,%15,%16,%17,%18,%19,%20,%21,%22,%23,%24,%25,%26,%27,%28,%29,%30,%31,%32,%33,%34,%35,%36,%37,%38,%39,"
            "%40,%41,%42,%43,%44,%45,%46,%47,%48,%49,%50,%51,%52,%53,%54,%55,%56,%57,%58,%59,%60,%61,%62,%63"
            "}, %64, %65, 1, 1, 1, 1, 0;" : R16(0), R16(16), R16(32), R16(48) : "l"(da), "l"(db));
    if constexpr (N == 256)
        asm volatile("wgmma.mma_async.sync.aligned.m64n256k16.f32.bf16.bf16 {"
            "%0,%1,%2,%3,%4,%5,%6,%7,%8,%9,%10,%11,%12,%13,%14,%15,%16,%17,%18,%19,%20,%21,%22,%23,%24,%25,%26,%27,%28,%29,%30,%31,%32,%33,%34,%35,%36,%37,%38,%39,"
            "%40,%41,%42,%43,%44,%45,%46,%47,%48,%49,%50,%51,%52,%53,%54,%55,%56,%57,%58,%59,%60,%61,%62,%63,%64,%65,%66,%67,%68,%69,%70,%71,%72,%73,%74,%75,%76,%7"
            "7,%78,%79,%80,%81,%82,%83,%84,%85,%86,%87,%88,%89,%90,%91,%92,%93,%94,%95,%96,%97,%98,%99,%100,%101,%102,%103,%104,%105,%106,%107,%108,%109,%110,%111,"
            "%112,%113,%114,%115,%116,%117,%118,%119,%120,%121,%122,%123,%124,%125,%126,%127"
            "}, %128, %129, 1, 1, 1, 1, 0;" : R16(0), R16(16), R16(32), R16(48), R16(64), R16(80), R16(96), R16(112) : "l"(da), "l"(db));
}

__device__ __forceinline__ void wgmma_rs32(float (&d)[16], const uint32_t (&a)[4], uint64_t db, bool acc) {
    asm volatile(
        "{.reg .pred p; setp.ne.b32 p, %21, 0;\n"
        "wgmma.mma_async.sync.aligned.m64n32k16.f32.bf16.bf16 {%0,%1,%2,%3,%4,%5,%6,%7,%8,%9,%10,%11,%12,%13,%14,%15}, {%16,%17,%18,%19}, %20, p, 1, 1, 0;}"
        : R16(0) : "r"(a[0]), "r"(a[1]), "r"(a[2]), "r"(a[3]), "l"(db), "n"(1) );
}
__device__ __forceinline__ void wgmma_rs32_first(float (&d)[16], const uint32_t (&a)[4], uint64_t db) {
    asm volatile(
        "{.reg .pred p; setp.ne.b32 p, %21, 0;\n"
        "wgmma.mma_async.sync.aligned.m64n32k16.f32.bf16.bf16 {%0,%1,%2,%3,%4,%5,%6,%7,%8,%9,%10,%11,%12,%13,%14,%15}, {%16,%17,%18,%19}, %20, p, 1, 1, 0;}"
        : R16(0) : "r"(a[0]), "r"(a[1]), "r"(a[2]), "r"(a[3]), "l"(db), "n"(0) );
}
__device__ __forceinline__ void wgmma_ss32(float (&d)[16], uint64_t da, uint64_t db) {
    asm volatile(
        "wgmma.mma_async.sync.aligned.m64n32k16.f32.bf16.bf16 {%0,%1,%2,%3,%4,%5,%6,%7,%8,%9,%10,%11,%12,%13,%14,%15}, %16, %17, 1, 1, 1, 1, 0;"
        : R16(0) : "l"(da), "l"(db));
}
template <int OFF, int ACC> __device__ __forceinline__ void wgmma_rs32u(float (&d)[16], const uint32_t (&a)[4], uint32_t lo) {
    asm volatile(
        "{.reg .pred p; .reg .b32 l; .reg .b64 e; setp.ne.b32 p, %22, 0; add.u32 l, %20, %21; mov.b64 e, {l, 0x40000040};\n"
        "wgmma.mma_async.sync.aligned.m64n32k16.f32.bf16.bf16 {%0,%1,%2,%3,%4,%5,%6,%7,%8,%9,%10,%11,%12,%13,%14,%15}, {%16,%17,%18,%19}, e, p, 1, 1, 0;}"
        : R16(0) : "r"(a[0]), "r"(a[1]), "r"(a[2]), "r"(a[3]), "r"(lo), "n"(OFF), "n"(ACC));
}
template <int OFF> __device__ __forceinline__ void wgmma_ss32u(float (&d)[16], uint64_t da, uint32_t lo) {
    asm volatile(
        "{.reg .b32 l; .reg .b64 e; add.u32 l, %17, %18; mov.b64 e, {l, 0x40000040};\n"
        "wgmma.mma_async.sync.aligned.m64n32k16.f32.bf16.bf16 {%0,%1,%2,%3,%4,%5,%6,%7,%8,%9,%10,%11,%12,%13,%14,%15}, %16, e, 1, 1, 1, 1, 0;}"
        : R16(0) : "l"(da), "r"(lo), "n"(OFF));
}
template <int K0, int K1, class F> __device__ __forceinline__ void static_for(F f) {
    if constexpr (K0 < K1) { f(std::integral_constant<int, K0>()); static_for<K0 + 1, K1>(f); }
}
__device__ __forceinline__ void st_async4(uint32_t a, float x, float y, float z, float w, uint32_t bar) {
    asm volatile("st.async.weak.shared::cluster.mbarrier::complete_tx::bytes.v4.f32 [%0], {%1,%2,%3,%4}, [%5];" ::"r"(a), "f"(x), "f"(y), "f"(z), "f"(w), "r"(bar) : "memory");
}
__device__ __forceinline__ void st_async2(uint32_t a, float x, float y, uint32_t bar) {
    asm volatile("st.async.weak.shared::cluster.mbarrier::complete_tx::bytes.v2.f32 [%0], {%1,%2}, [%3];" ::"r"(a), "f"(x), "f"(y), "r"(bar) : "memory");
}
__device__ __forceinline__ void st_async1(uint32_t a, uint32_t x, uint32_t bar) {
    asm volatile("st.async.weak.shared::cluster.mbarrier::complete_tx::bytes.b32 [%0], %1, [%2];" ::"r"(a), "r"(x), "r"(bar) : "memory");
}
__device__ __forceinline__ uint32_t peer_addr(uint32_t a, uint32_t rank) {
    uint32_t r;
    asm("mapa.shared::cluster.u32 %0, %1, %2;" : "=r"(r) : "r"(a), "r"(rank));
    return r;
}
__device__ __forceinline__ void stsm4t(uint32_t a, uint32_t r0, uint32_t r1, uint32_t r2, uint32_t r3) {
    asm volatile("stmatrix.sync.aligned.m8n8.x4.trans.shared.b16 [%0], {%1,%2,%3,%4};" ::"r"(a), "r"(r0), "r"(r1), "r"(r2), "r"(r3) : "memory");
}
__device__ __forceinline__ void ldsm4t(uint32_t (&r)[4], uint32_t a) { ldsm4t(r[0], r[1], r[2], r[3], a); }
__device__ __forceinline__ void ldsm4(uint32_t (&r)[4], uint32_t a) { ldsm4(r[0], r[1], r[2], r[3], a); }
__device__ __forceinline__ void mma16816(float (&d)[4], const uint32_t (&a)[4], uint32_t b0, uint32_t b1) { mma16816(d, a[0], a[1], a[2], a[3], b0, b1); }
__device__ __forceinline__ void sched_fence(uint32_t v) {
    asm volatile("{.reg .pred p; setp.ne.u32 p, %0, 0xFFFFFFFF; vote.sync.all.pred p, p, 0xFFFFFFFF; @p bra.uni SF_OK; exit; SF_OK:}" ::"r"(v) : "memory");
}
__device__ __forceinline__ void mma16816v(float (&d)[4], const uint32_t (&a)[4], uint32_t b0, uint32_t b1) {
    asm volatile("mma.sync.aligned.m16n8k16.row.col.f32.bf16.bf16.f32 {%0,%1,%2,%3},{%4,%5,%6,%7},{%8,%9},{%0,%1,%2,%3};"
                 : "+f"(d[0]), "+f"(d[1]), "+f"(d[2]), "+f"(d[3]) : "r"(a[0]), "r"(a[1]), "r"(a[2]), "r"(a[3]), "r"(b0), "r"(b1));
}
__device__ __forceinline__ uint32_t uniform(uint32_t v) { return __reduce_max_sync(~0u, v); }

#define WPRE 0
#define G2_X 0
#define G2_K 4
#define FIN_SO 0
#define PROJ_FAST 1
#define KROT 0
#define WFIRST 0
template <int NT, int STAGES> struct ProjCfg {
    static constexpr int STAGE_BYTES = 16384 + NT * 128;
    static constexpr int EPI = NT == 256 ? STAGES * STAGE_BYTES : 0;
    static constexpr int BARS = 229376 + (NT == 256 ? 192 : 0);
    static_assert(STAGES * STAGE_BYTES <= 229376 && EPI + NT * 256 <= 229376 && STAGES <= 12, "smem");
};
constexpr int PROJ_ROLE = 229376 + 384, PROJ_SMEM = PROJ_ROLE + 16;
__device__ __forceinline__ unsigned claim_pair(unsigned* reg) {
    unsigned smid, ncl = gridDim.x >> 1;
    asm volatile("mov.u32 %0, %%smid;" : "=r"(smid));
    uint2 m;
    for (int guard = 0; guard < 1024; guard++) {
        asm volatile("ld.relaxed.gpu.global.v2.u32 {%0, %1}, [%2];" : "=r"(m.x), "=r"(m.y) : "l"(g_cls + (smid & ~1u)) : "memory");
        if (m.x && m.y) break;
    }
    const unsigned r = __vminu2(m.x, m.y), c = (r & 0xFFFF) > (r >> 16);
    unsigned n = atomicAdd(reg, c ? 0x10000u : 1u);
    const unsigned i = c ? n >> 16 : n & 0xFFFF, order = ((n >> 16) + (n & 0xFFFF)) << 8;
    if (i < 32) return c * 32 + i + order;
    for (int guard = 0; guard < (1 << 20); guard++) {
        asm volatile("ld.relaxed.gpu.global.u32 %0, [%1];" : "=r"(n) : "l"(reg) : "memory");
        if ((n >> 16) + (n & 0xFFFF) >= ncl) break;
    }
    const unsigned k = (c ? n & 0xFFFF : n >> 16) + i - 32;
    return (k < 32 ? (c ^ 1) * 32 + k : 64) + order;
}
template <int NT, int STAGES> __device__ __forceinline__ void proj_init(uint32_t sb) {
    for (int i = 0; i < STAGES; i++) { mbar_init(sb + ProjCfg<NT, STAGES>::BARS + 8 * i, 1); mbar_init(sb + ProjCfg<NT, STAGES>::BARS + 8 * (STAGES + i), 16); }
    asm volatile("fence.mbarrier_init.release.cluster;" ::: "memory");
}
template <int NT, int STAGES, bool SHARE_O, class T, class R>
__device__ __forceinline__ void proj_tiles(uint32_t sb, int warp, uint32_t rank, int ntiles, const CUtensorMap* mapW, const CUtensorMap* mapO,
                                           const CUtensorMap* mapOut, T tile, R ready, int rot = 0) {
    using Cfg = ProjCfg<NT, STAGES>;
    const uint32_t bars = sb + Cfg::BARS;
    const int lane = threadIdx.x & 31;
    if (warp == 8) {
        int st = 0; uint32_t ph = 1;
        for (int i = 0; i < ntiles; i++) {
            int col, tok;
            tile(i, col, tok);
            constexpr bool PRE = WPRE && !SHARE_O;
            if (PRE && lane == 0)
                for (int kb = 0; kb < STAGES; kb++) {
                    mbar_expect_tx(bars + 8 * kb, Cfg::STAGE_BYTES);
                    tma_load_2d_both(sb + kb * Cfg::STAGE_BYTES + rank * 8192, mapW, col + rank * 64, kb * 64, bars + 8 * kb);
                }
            ready(i);
            if (lane == 0) {
                if (PRE) {
                    for (int kb = 0; kb < STAGES; kb++) tma_load_2d(sb + kb * Cfg::STAGE_BYTES + 16384, mapO, kb * 64, tok, bars + 8 * kb);
                    ph = 0;
                }
                for (int kb = PRE ? STAGES : 0; kb < HD / 64; kb++) {
                    mbar_wait(bars + 8 * (STAGES + st), ph);
                    const uint32_t full = bars + 8 * st, sa = sb + st * Cfg::STAGE_BYTES;
                    mbar_expect_tx(full, SHARE_O ? Cfg::STAGE_BYTES : G2_X == 1 ? 16384 : G2_X == 2 ? NT * 128 : Cfg::STAGE_BYTES);
                    if (SHARE_O) {
                        tma_load_2d(sa, mapW, col, kb * 64, full);
                        tma_load_2d(sa + 8192, mapW, col + 64, kb * 64, full);
                        tma_load_2d_both(sa + 16384 + rank * (NT * 64), mapO, kb * 64, tok + rank * (NT / 2), full);
                    } else {
                        const int k0 = ((kb + rot) & 63) * 64;
                        if (WFIRST) tma_load_2d_both(sa + rank * 8192, mapW, col + rank * 64, k0, full);
                        if (G2_X != 1) tma_load_2d(sa + 16384, mapO, k0, G2_X == 3 ? tok & 511 : tok, full);
                        if (!WFIRST && G2_X != 2) tma_load_2d_both(sa + rank * 8192, mapW, col + rank * 64, k0, full);
                    }
                    if (++st == STAGES) { st = 0; ph ^= 1; }
                }
            }
            __syncwarp();
        }
    } else if (warp < 8) {
        const int wg = warp >> 2;
        uint32_t peer_empty;
        asm volatile("mapa.shared::cluster.u32 %0, %1, %2;" : "=r"(peer_empty) : "r"(bars + 8 * STAGES), "r"(rank ^ 1));
        auto release = [&](int stg) {
            if (lane == 0) {
                mbar_arrive(bars + 8 * (STAGES + stg));
                asm volatile("mbarrier.arrive.shared::cluster.b64 _, [%0];" ::"r"(peer_empty + 8 * stg) : "memory");
            }
        };
        const uint32_t ew = sb + Cfg::EPI + wg * (NT * 128);
        int st = 0; uint32_t ph = 0;
        for (int i = 0; i < ntiles; i++) {
            int col, tok;
            tile(i, col, tok);
            float d[NT / 2];
#pragma unroll
            for (int r = 0; r < NT / 2; r++) d[r] = 0.f;
            int prev = -1;
            for (int kb = 0; kb < HD / 64; kb++) {
                mbar_wait(bars + 8 * st, ph);
                const uint32_t sa = sb + st * Cfg::STAGE_BYTES;
                const uint64_t da = make_desc(sa + wg * 8192, 16, 1024), db = make_desc(sa + 16384, 16, 1024);
                wg_fence();
#pragma unroll
                for (int k = 0; k < (NT == 256 ? 4 : G2_K); k++) wgmma_proj<NT>(d, da + k * 128, db + k * 2);
                wg_commit();
                if (prev >= 0) { wg_wait<1>(); release(prev); }
                prev = st;
                if (++st == STAGES) { st = 0; ph ^= 1; }
            }
            wg_wait<0>();
            release(prev);
            if ((warp & 3) == 0 && lane == 0) asm volatile("cp.async.bulk.wait_group.read 0;" ::: "memory");
            if (Cfg::EPI) bar_sync(1 + wg, 128); else bar_sync(3, 256);
            const uint32_t ea = ew + ((lane >> 4) * 8 + (lane & 7)) * 128 + ((((warp & 3) * 2 + ((lane >> 3) & 1)) ^ (lane & 7)) * 16);
#pragma unroll
            for (int r = 0; r < NT / 16; r++)
                stsm4t(ea + r * 2048, pack_bf16(d[8 * r], d[8 * r + 1]), pack_bf16(d[8 * r + 2], d[8 * r + 3]), pack_bf16(d[8 * r + 4], d[8 * r + 5]), pack_bf16(d[8 * r + 6], d[8 * r + 7]));
            asm volatile("fence.proxy.async.shared::cta;" ::: "memory");
            bar_sync(1 + wg, 128);
            if ((warp & 3) == 0 && lane == 0) {
                tma_store_2d(mapOut, ew, col + wg * 64, tok);
                asm volatile("cp.async.bulk.commit_group;" ::: "memory");
            }
        }
        if ((warp & 3) == 0 && lane == 0) asm volatile("cp.async.bulk.wait_group 0;" ::: "memory");
    }
    __syncwarp();
}
constexpr int EARLY_NT = 256, EARLY_STAGES = 3;
constexpr int PROJ_THREADS = 288;

template <int NT, int STAGES>
__global__ void __cluster_dims__(2, 1, 1) __launch_bounds__(PROJ_THREADS, 1)
proj_kernel(const __grid_constant__ CUtensorMap mapW, const __grid_constant__ CUtensorMap mapO, const __grid_constant__ CUtensorMap mapOut,
            const __grid_constant__ CUtensorMap mapOE, const __grid_constant__ CUtensorMap mapOutE) {
    KT_START(3);
    extern __shared__ __align__(1024) uint8_t smem_proj[];
    const uint32_t sb = smem_u32(smem_proj), role = sb + PROJ_ROLE;
    if (sb & 1023) __trap();
    const uint32_t rank = blockIdx.x & 1;
    const int warp = threadIdx.x >> 5;
    if (threadIdx.x == 0) {
        mbar_init(role + 8, 1);
        mbar_expect_tx(role + 8, 4);
        proj_init<NT, STAGES>(sb);
        proj_init<EARLY_NT, EARLY_STAGES>(sb);
    }
    if (threadIdx.x == 32) { prefetch_map(&mapO); prefetch_map(&mapW); prefetch_map(&mapOut); }
    __syncwarp();
    asm volatile("barrier.cluster.arrive.relaxed.aligned;" ::: "memory");
    unsigned claimed = 0;
    if (threadIdx.x == 256 && rank == 0) claimed = claim_pair(g_reg + 2);
    __syncwarp();
    asm volatile("barrier.cluster.wait.acquire.aligned;" ::: "memory");
    if (threadIdx.x == 256 && rank == 0) {
        st_async1(peer_addr(role, 1), claimed, peer_addr(role + 8, 1));
        st_async1(peer_addr(role, 0), claimed, peer_addr(role + 8, 0));
        if ((claimed >> 8) + 1 == gridDim.x >> 1) {
            g_reg[0] = 0;
            for (int i = 0; i < 64; i++) reinterpret_cast<uint4*>(g_cls)[i] = make_uint4(0, 0, 0, 0);
        }
    }
    __syncwarp();
    mbar_wait_w(role + 8, 0);
    const int p = lds32(role) & 255, order = lds32(role) >> 8;
    if (NT == 96 && order < 2) {
        proj_tiles<EARLY_NT, EARLY_STAGES, true>(sb, warp, rank, 4, &mapW, &mapOE, &mapOutE,
            [&](int i, int& col, int& tok) { col = ((i & 1) * 4 + order * 2 + rank) * 128; tok = (i >> 1) * EARLY_NT; },
            [&](int i) {
                const unsigned need = 8 * (i >> 1) + 8 + 3;
                for (int guard = 0; guard < (1 << 16); guard++) {
                    const uint4 f = ld_relaxed_v4(g_xflag + (threadIdx.x & 31) * 4);
                    if (__all_sync(~0u, min(min(f.x, f.y), min(f.z, f.w)) >= need)) break;
                    __nanosleep(1000);
                }
                asm volatile("fence.acq_rel.gpu; fence.proxy.async.global;" ::: "memory");
            });
        __syncthreads();
        asm volatile("barrier.cluster.arrive.relaxed.aligned; barrier.cluster.wait.aligned;" ::: "memory");
    }
    if (p >= 64) return;
    proj_tiles<NT, STAGES, false>(sb, warp, rank, 1, &mapW, &mapO, &mapOut,
                                  [&](int, int& col, int& tok) { col = (p & 7) * 128; tok = S_LEN - 16 * NT + ((p >> 3) * 2 + rank) * NT; },
                                  [&](int) { wait_prerequisites();
                                  }, KROT == 0 ? 0 : KROT == 1 ? (p & 7) * 8 : KROT == 2 ? (p >> 3) * 8 : KROT == 3 ? ((p & 7) + (p >> 3)) * 8 : (p >> 5) * 32);
    KT_END(3);
    asm volatile("barrier.cluster.arrive.relaxed; barrier.cluster.wait;" ::: "memory");
}

#define WO_RF1 6
constexpr int SM_KV = 0, KV_BYTES = 18432;
constexpr int SM_XT = 2 * KV_BYTES;
constexpr int SM_STG = SM_XT + 65536;
constexpr int SM_Z = SM_STG + 6144;
constexpr int SM_RT = SM_Z + 8192;
constexpr int SM_QKV = SM_RT + 12288;
constexpr int SM_R1 = SM_QKV + 6144;
constexpr int SM_R2 = SM_R1 + 2048;
constexpr int SM_R3 = SM_R2 + 1024;
constexpr int SM_O = SM_R3 + 2048;
constexpr int SM_S = SM_O + 2048;
constexpr int SM_INV = SM_S + 1536;
constexpr int SM_TO = SM_R3;
constexpr int SM_WORK_END = SM_S + 2048;
constexpr int STG_QK = 0, STG_V = 98304;
#define PRO2 1
#define PRO3 1
#define WO_IT 2
__host__ __device__ constexpr int stg_wo(int r) { return r < 9 ? KV_BYTES + r * 2048 : r < 13 ? SM_QKV + (r - 9) * 2048 : SM_S; }
static_assert(WO_RF1 == 6 && SM_QKV % 1024 == 0 && SM_S % 1024 == 0 && SM_QKV + 8192 <= SM_TO, "staging of Wo");
__host__ __device__ constexpr int stg_qk(int t, int r) { return !PRO2 ? STG_QK + (t * 24 + r) * 2048 : t == 0 ? SM_XT + r * 2048 : r < SM_XT / 2048 ? r * 2048 : (r + 24) * 2048; }
constexpr int SM_WO1 = SM_WORK_END - WO_RF1 * 2048;
constexpr int STG_WO = SM_WO1 - 16384;
constexpr int SM_WQK = (SM_WO1 + 16384 > STG_V + 49152) ? SM_WO1 + 16384 : STG_V + 49152;
constexpr int SM_WV = SM_WQK + 32768;
constexpr int SM_WO2 = SM_WV + 16384;
constexpr int SM_BARS = SM_WO2 + 32768;
enum { MB_W0 = SM_BARS, MB_W1 = SM_BARS + 8, MB_W2 = SM_BARS + 16, MB_W3 = SM_BARS + 24, MB_XT = SM_BARS + 32  , MB_KV = SM_BARS + 48  ,
       MB_R3 = SM_BARS + 64, MB_R1 = SM_BARS + 72, MB_R2 = SM_BARS + 80, MB_RT0 = SM_BARS + 88, MB_RT1 = SM_BARS + 96, MB_FREE = SM_BARS + 104,
       MB_P = SM_BARS + 112, MB_V = SM_BARS + 120, MB_STG = SM_BARS + 128, MB_ROLE = SM_BARS + 136, MB_W4 = SM_BARS + 144, MB_W5 = SM_BARS + 152, SM_ROLE = SM_BARS + 160   };
constexpr int CHAIN_SMEM = SM_ROLE + 8;
static_assert(SM_WORK_END % 1024 == 0 && STG_WO >= STG_V, "work area");
static_assert(CHAIN_SMEM <= 232448 && WO_RF1 >= 6, "smem");

#define DLY_X 300
#define DLY_V 0
#define DLY_Y 250
#define DLY_Z 300
#define DLY_T 0
#define DLY_K 0
#define DLY_S 0
#define LATE_RD 1
#define TS_AT 5
#define XT_FIRST 0
#define GV 1
#define NSV (GV ? 320 : 352)
#define Q3_AT 9
#define NA 7
#define NP2 6
#define P2_FENCE 0
#define SPLIT 10
#define TA0 16
#define SENT_EARLY 1
#define Y_CHAIN 1
#define EF_W 1
#define XFLIP 0
#define YFLIP 0
#define ZFLIP 1
#define OFENCE 2
#define REG_A 240
#define REG_B 216
#define REG_C (3 * 168 - REG_A - REG_B)

enum { BAR_Y, BAR_MEM, BAR_PUB, BAR_QK, BAR_S, BAR_O, BAR_SENT, BAR_COMM, BAR_PUBV, BAR_PV, BAR_PDONE, BAR_VP, BAR_ZP, BAR_PRO, BAR_O2, BAR_SV,
       BAR_V = BAR_PV, BAR_SENTC = BAR_PDONE, BAR_Q3 = BAR_PRO, BAR_INV = BAR_PRO, BAR_XT0 = BAR_Y };

__device__ __forceinline__ uint32_t umax4(const uint4& v) { return max(max(v.x, v.y), max(v.z, v.w)); }
__device__ __forceinline__ unsigned gtime() { unsigned t; asm volatile("mov.u32 %0, %%globaltimer_lo;" : "=r"(t)::"memory"); return t; }
__device__ __forceinline__ unsigned clock32() { unsigned t; asm volatile("mov.u32 %0, %%clock;" : "=r"(t)::"memory"); return t; }
__device__ __forceinline__ void spin_cycles(int d) {
    if (d > 0) { const unsigned c0 = clock32(); while (clock32() - c0 < (unsigned)d) {} }
}
__device__ __forceinline__ float ex2_approx(float x) { float y; asm("ex2.approx.ftz.f32 %0, %1;" : "=f"(y) : "f"(x)); return y; }
__device__ __forceinline__ float rcp_approx(float x) { float y; asm("rcp.approx.ftz.f32 %0, %1;" : "=f"(y) : "f"(x)); return y; }
__device__ __forceinline__ void st_sent(const void* p) { asm volatile("st.relaxed.gpu.global.v4.u32 [%0], {%1,%1,%1,%1};" ::"l"(p), "r"(SENT) : "memory"); }
#define POLL_LD(p, a, b, c, d, addr) "@" p " ld.relaxed.gpu.global.v4.u32 {" a "," b "," c "," d "}, [" addr "];\n"
#define POLL_CK(p, a, b, c, d) "max.u32 m, " a "," b "; max.u32 n, " c "," d "; max.u32 m, m, n; setp.eq.u32 " p ", m, 0xFFFFFFFF;\n"
#define POLL_IO(v) "+r"(v.x), "+r"(v.y), "+r"(v.z), "+r"(v.w)
__device__ __forceinline__ void poll_init(uint4& v) { v = make_uint4(SENT, SENT, SENT, SENT); asm volatile("" : POLL_IO(v)); }
__device__ __forceinline__ int poll2(uint4 (&v)[2], const char* a) {
    int c = 0;
    asm volatile("{.reg .pred p0, p1, p; .reg .u32 m, n;\n"
                 "setp.eq.u32 p0, %8, 0; setp.eq.u32 p1, %8, 0;\n"
                 "POLL_LOOP:\n"
                 POLL_LD("p0", "%0", "%1", "%2", "%3", "%9") POLL_LD("p1", "%4", "%5", "%6", "%7", "%9+512")
                 "add.u32 %8, %8, 1;\n"
                 POLL_CK("p0", "%0", "%1", "%2", "%3") POLL_CK("p1", "%4", "%5", "%6", "%7")
                 "or.pred p, p0, p1; setp.lt.and.u32 p, %8, 0x10000, p; vote.sync.any.pred p, p, 0xFFFFFFFF;\n"
                 "@p bra.uni POLL_LOOP;}" : POLL_IO(v[0]), POLL_IO(v[1]), "+r"(c) : "l"(a) : "memory");
    return c;
}
__device__ __forceinline__ int poll4(uint4 (&v)[4], const char* a) {
    int c = 0;
    asm volatile("{.reg .pred p0, p1, p2, p3, p; .reg .u32 m, n;\n"
                 "setp.eq.u32 p0, %16, 0; setp.eq.u32 p1, %16, 0; setp.eq.u32 p2, %16, 0; setp.eq.u32 p3, %16, 0;\n"
                 "POLL_LOOP:\n"
                 POLL_LD("p0", "%0", "%1", "%2", "%3", "%17") POLL_LD("p1", "%4", "%5", "%6", "%7", "%17+2048")
                 POLL_LD("p2", "%8", "%9", "%10", "%11", "%17+4096") POLL_LD("p3", "%12", "%13", "%14", "%15", "%17+6144")
                 "add.u32 %16, %16, 1;\n"
                 POLL_CK("p0", "%0", "%1", "%2", "%3") POLL_CK("p1", "%4", "%5", "%6", "%7") POLL_CK("p2", "%8", "%9", "%10", "%11") POLL_CK("p3", "%12", "%13", "%14", "%15")
                 "or.pred p, p0, p1; or.pred p, p, p2; or.pred p, p, p3; setp.lt.and.u32 p, %16, 0x10000, p; vote.sync.any.pred p, p, 0xFFFFFFFF;\n"
                 "@p bra.uni POLL_LOOP;}" : POLL_IO(v[0]), POLL_IO(v[1]), POLL_IO(v[2]), POLL_IO(v[3]), "+r"(c) : "l"(a) : "memory");
    return c;
}
__device__ __forceinline__ uint32_t max_bf16x2(uint32_t a, uint32_t b) { uint32_t r; asm("max.bf16x2 %0, %1, %2;" : "=r"(r) : "r"(a), "r"(b)); return r; }
template <class F> __device__ __forceinline__ void softmax40(uint32_t (&pw)[6], uint32_t sa, F mid) {
    const float LOG2E = 1.4426950408889634f;
    uint32_t w[5];
    float e[10];
#pragma unroll
    for (int i = 0; i < 5; i++) w[i] = lds32(sa + i * 128);
    uint32_t m = max_bf16x2(max_bf16x2(max_bf16x2(w[0], w[1]), max_bf16x2(w[2], w[3])), w[4]);
    m = max_bf16x2(m, __shfl_xor_sync(~0u, m, 1));
    m = max_bf16x2(m, __shfl_xor_sync(~0u, m, 2));
    const float mb2 = fmaxf(bf_lo(m), bf_hi(m)) * LOG2E;
#pragma unroll
    for (int i = 0; i < 5; i++) {
        e[2 * i] = ex2_approx(fmaf(bf_lo(w[i]), LOG2E, -mb2));
        e[2 * i + 1] = ex2_approx(fmaf(bf_hi(w[i]), LOG2E, -mb2));
    }
    mid();
#pragma unroll
    for (int i = 0; i < 5; i++) pw[i] = pack_bf16(e[2 * i], e[2 * i + 1]);
    const float sum = (((e[0] + e[1]) + (e[2] + e[3])) + ((e[4] + e[5]) + (e[6] + e[7]))) + (e[8] + e[9]);
    const float hi = bf_hi(__float_as_uint(sum));
    pw[5] = pack_bf16(sum - hi, hi);
}
template <bool NORM, class F> __device__ __forceinline__ void pv32(uint32_t (&w)[4], float (&inv)[2], const uint32_t (&va)[2][2][4], const uint32_t (&vm)[4], const uint32_t (&pw)[6], F mid) {
    float o[2][3][4], t[4] = {0.f, 0.f, 0.f, 0.f};
#pragma unroll
    for (int i = 0; i < 3; i++)
#pragma unroll
        for (int m = 0; m < 2; m++) {
            o[m][i][0] = o[m][i][1] = o[m][i][2] = o[m][i][3] = 0.f;
            if (i < 2) mma16816(o[m][i], va[m][i & 1], pw[2 * i], pw[2 * i + 1]);
            else mma1688(o[m][i], vm[2 * m], vm[2 * m + 1], pw[4]);
        }
    mma1688(t, 0x3F803F80u, 0x3F803F80u, pw[5]);
    mid();
    if (NORM) { inv[0] = rcp_approx(t[0]); inv[1] = rcp_approx(t[1]); }
#pragma unroll
    for (int i = 0; i < 4; i++) {
        const float a = (o[i >> 1][0][2 * (i & 1)] + o[i >> 1][1][2 * (i & 1)]) + o[i >> 1][2][2 * (i & 1)];
        const float b = (o[i >> 1][0][2 * (i & 1) + 1] + o[i >> 1][1][2 * (i & 1) + 1]) + o[i >> 1][2][2 * (i & 1) + 1];
        w[i] = NORM ? pack_bf16(a * inv[0], b * inv[1]) : pack_bf16(a, b);
    }
    if (!NORM) { inv[0] = t[0]; inv[1] = t[1]; }
}
__device__ __forceinline__ uint32_t scale_scores(float a, float b) {
    const float scale = 0.08838834764831845f;
    const uint32_t w = pack_bf16(a, b);
    return pack_bf16(bf_lo(w) * scale, bf_hi(w) * scale);
}

#define TL(i) do {} while (0)
#define TLB(i) do {} while (0)
#define TLC(i) do {} while (0)

#define OPQ_LANE 1
#define CLAIM_T 64
#define PAD_A 0
#define PAD_B 0
#define PAD_C 0
template <int N> __device__ __forceinline__ void code_pad() {
#pragma unroll
    for (int i = 0; i < N; i++) asm volatile("pmevent 0;");
}
__global__ void __cluster_dims__(2, 1, 1) __launch_bounds__(384, 1)
chain_kernel(const __grid_constant__ CUtensorMap mapX, const __grid_constant__ CUtensorMap mapT32, const __grid_constant__ CUtensorMap mapT16,
             const __grid_constant__ CUtensorMap mapTQ, const __grid_constant__ CUtensorMap mapKV,
             const __grid_constant__ CUtensorMap mapWq, const __grid_constant__ CUtensorMap mapWk, const __grid_constant__ CUtensorMap mapWv,
             const __grid_constant__ CUtensorMap mapWo, const bf16* __restrict__ mem0, char* __restrict__ mbox) {
    KT_START(2);
    extern __shared__ __align__(1024) uint8_t smem_chain[];
    constexpr uint32_t SB0 = 1024;
    if (smem_u32(smem_chain) != (SB0 | ((blockIdx.x & 1) << 24))) __trap();
    const int kh = blockIdx.x & 1;
    if (threadIdx.x == 0) {
        const uint32_t sb = smem_u32(smem_chain);
        for (int i = 0; i < 14; i++) mbar_init(sb + SM_BARS + 8 * i, 1);
        mbar_init(sb + MB_P, 4); mbar_init(sb + MB_V, 4); mbar_init(sb + MB_STG, 8); mbar_init(sb + MB_ROLE, 1); mbar_init(sb + MB_W4, 1); mbar_init(sb + MB_W5, 1);
        mbar_expect_tx(sb + MB_ROLE, 4);
        asm volatile("fence.mbarrier_init.release.cluster;" ::: "memory");
    }
    if (threadIdx.x == 32) { prefetch_map(&mapWv); prefetch_map(&mapWq); prefetch_map(&mapWk); prefetch_map(&mapWo); prefetch_map(&mapX); }
    __syncwarp();
    asm volatile("barrier.cluster.arrive.relaxed.aligned;" ::: "memory");
    unsigned claimed = 0;
    if (threadIdx.x == CLAIM_T && kh == 0) claimed = claim_pair(g_reg) & 255;
    __syncwarp();
    asm volatile("barrier.cluster.wait.acquire.aligned;" ::: "memory");
    if (threadIdx.x == CLAIM_T && kh == 0) {
        st_async1((SB0 | (1u << 24)) + SM_ROLE, claimed, (SB0 | (1u << 24)) + MB_ROLE);
        st_async1(SB0 + SM_ROLE, claimed, SB0 + MB_ROLE);
    }
    __syncwarp();
    mbar_wait_w(smem_u32(smem_chain) + MB_ROLE, 0);
    const int pair = uniform(lds32(smem_u32(smem_chain) + SM_ROLE));
#define YFLIP_() (uniform(lds32(sb + SM_ROLE + 4)) ^ YFLIP)
    if (pair >= 64) return;
    if (threadIdx.x == 0) KT_MARK(5);
    const int h = pair >> 1, nh = pair & 1, j = 2 * nh + kh, role = 2 * pair + kh;
#define WG_ORDER 0x210
    const int warp = uniform(((WG_ORDER >> (4 * (threadIdx.x >> 7))) & 3) * 4 + ((threadIdx.x >> 5) & 3));
    const uint32_t g = warp & 3, sb = SB0 | (kh << 24), rsb = sb ^ (1u << 24), cls = pair >> 5, kflip = ZFLIP ^ kh;
    const uint32_t mlo = (uint32_t)(uintptr_t)mbox, mhi = (uint32_t)((uintptr_t)mbox >> 32);
    auto lane16 = [&]() {
        uint32_t t;
        asm volatile("{.reg .u32 l, x; mov.u32 l, %%laneid; xor.b32 x, l, 1; shl.b32 x, x, 4; shfl.sync.bfly.b32 %0, x, 1, 0x1f, 0xffffffff;}" : "=r"(t));
        return t;
    };
#define PHASE(k) uint32_t L; asm volatile("{.reg .u32 t; shr.u32 t, %1, %3; add.u32 %0, %2, t;}" : "=r"(L) : "r"(it), "r"(l16), "n"(8 + (k)))
#define ROWPAT() ((((L << 3) & 0x380) | ((L << 2) & 0x400)) | ((L ^ (L >> 3)) & 0x10) | (L & 0x60))
#define FRAG() (ROWPAT() ^ (g << 5))
#define QFRAG() ((((L >> 1) & 0x80) | (L & 0x70)) + ((L & 0x80) ? SM_KV + 16384 + kvo : SM_QKV))
#define VFRAG() (ROWPAT() ^ ((g & 1) << 6))
#define VBASE() (sb + SM_KV + 8192 + (g >> 1) * 4096 + kvo)
#define XTLO() ((uint32_t)make_desc(SB0 + SM_XT, 16, 1024) + (ui & 1) * 2048)
    if (warp >= 8) {
        asm volatile("setmaxnreg.dec.sync.aligned.u32 %0;" ::"n"(REG_C));
        code_pad<PAD_C>();
        const uint32_t l16 = lane16(), lane = l16 >> 4;
        auto load_xt = [&](int seg, int half) {
            const uint32_t bar = sb + MB_XT + (seg & 1) * 8;
            if (half == 0) mbar_expect_tx(bar, 32768);
            asm volatile("cp.async.bulk.tensor.3d.shared::cluster.global.mbarrier::complete_tx::bytes [%0], [%1, {%3, %4, %5}], [%2];"
                         ::"r"(sb + SM_XT + (seg & 1) * 32768 + half * 16384), "l"(&mapX), "r"(bar), "r"(0), "r"(seg * SEG), "r"(8 * kh + 4 * (half ^ kflip)) : "memory");
        };
        if (warp == 8) {
            const CUtensorMap* ws = kh ? &mapWq : &mapWk;
            const CUtensorMap* wn = kh ? &mapWk : &mapWq;
            const uint64_t pol = EF_W ? policy_evict_first() : policy_evict_normal();
            const int col = h * DH + 64 * nh, row = 512 * kh;
            if (lane == 0) { mbar_expect_tx(sb + MB_W0, 49152); mbar_expect_tx(sb + MB_W1, 49152); mbar_expect_tx(sb + MB_W4, 49152); mbar_expect_tx(sb + MB_W2, 49152); mbar_expect_tx(sb + MB_W3, PRO3 ? 65536 : 32768); }
            __syncwarp();
            if (lane < 24) {
                const int k = lane ^ (16 * kflip);
                tma_load_2d(sb + STG_V + lane * 2048, &mapWv, col, row + 16 * k, sb + MB_W0, pol);
                tma_load_2d(sb + stg_qk(0, lane), ws, col, row + 16 * k, sb + MB_W1, pol);
                tma_load_2d(sb + stg_qk(1, lane), wn, col, row + 16 * k, sb + MB_W4, pol);
            }
            if (lane < 8) {
                const int k = (24 + lane) ^ (16 * kflip);
                tma_load_2d(sb + SM_WQK + lane * 4096, ws, col, row + 16 * k, sb + MB_W2, pol);
                tma_load_2d(sb + SM_WQK + lane * 4096 + 2048, wn, col, row + 16 * k, sb + MB_W2, pol);
                tma_load_2d(sb + SM_WV + lane * 2048, &mapWv, col, row + 16 * k, sb + MB_W2, pol);
            }
            __syncwarp();
        }
        if (warp == 9) {
            bar_sync(BAR_XT0, 160);
            if (lane == 0) { load_xt(0, 0); load_xt(0, 1); }
            __syncwarp();
        }
        if (warp == 10 && lane == 0) {
            wait_prerequisites();
            launch_dependents();
            sts32(sb + SM_ROLE + 4, g_reg[1]);
        }
        __syncwarp();
        bar_sync(BAR_PDONE, 384);
        KT_MARK(9);
        if (warp == 8) {
            const uint32_t dst = lane < 14 ? stg_wo(lane) : lane < 16 ? SM_WO1 + (lane - 8) * 2048 : SM_WO2 + (lane - 16) * 2048;
            tma_load_2d(sb + dst, &mapWo, 256 * j + 64 * (lane >> 3), h * DH + 16 * (lane & 7), sb + MB_W3, EF_W ? policy_evict_first() : policy_evict_normal());
        }
        if ((warp & 1) == 0) for (int c = (warp - 8) * 16 + lane; c < 512; c += 64) {
            uint32_t w[4];
#pragma unroll
            for (int r = 0; r < 4; r++) {
                const uint32_t lo = reinterpret_cast<const uint16_t*>(mem0)[(2 * r) * DM + 512 * kh + c], hi = reinterpret_cast<const uint16_t*>(mem0)[(2 * r + 1) * DM + 512 * kh + c];
                w[r] = lo | (hi << 16);
            }
            sts128(sb + SM_Z + (c ^ (256 * kflip)) * 16, make_uint4(w[0], w[1], w[2], w[3]));
        }
        if (!PRO3 && warp == 8) mbar_wait_w(sb + MB_W5, 0);
        auto tok_start = [&](int s) {
            if (lane == 0) {
                if (TS_AT == 0) TL(21);
                if (s > -3 && s + 2 < NSEG) {
                    mbar_wait(sb + MB_STG, (s + 2) & 1);
                    if (TS_AT == 1) TL(21);
                    if (XT_FIRST && s + 4 < NSEG) load_xt(s + 4, 0);
                    if (TS_AT == 2) TL(21);
                    asm volatile("fence.proxy.async.shared::cta;" ::: "memory");
                    if (TS_AT == 3) TL(21);
                    const int r = ((s + 2) & 3) * NH + h;
                    tma_store_2d(kh ? &mapT32 : &mapTQ, sb + SM_STG, kh ? 64 * nh : 256 * nh, kh ? r * 96 + 32 : r * 12);
                    tma_store_2d(&mapT16, sb + SM_STG + 4096, 64 * nh, r * 96 + 64 + 16 * kh);
                    asm volatile("cp.async.bulk.commit_group;" ::: "memory");
                    if (TS_AT == 4) TL(21);
                }
                if ((!XT_FIRST || s == -3) && s + 4 < NSEG) load_xt(s + 4, 0);
                if (!LATE_RD || s < 0) asm volatile("cp.async.bulk.wait_group.read 0;" ::: "memory");
                if (s < 0) {
                    asm volatile("mbarrier.arrive.shared::cluster.b64 _, [%0];" ::"r"(rsb + MB_FREE) : "memory");
                    mbar_wait(sb + MB_FREE, (s + 3) & 1);
                }
            }
            __syncwarp();
        };
        auto tok_mid = [&](int s) {
            if (lane == 0) {
                if (s + 4 < NSEG) load_xt(s + 4, 1);
                if (s > -3 && s + 2 < NSEG) {
                    asm volatile("cp.async.bulk.wait_group 0;" ::: "memory");
                    if (s == 8 || s == 16) asm volatile("fence.acq_rel.gpu;" ::: "memory");
                    st_relaxed_u32(g_xflag + role, s + 3);
                }
            }
            __syncwarp();
        };
        auto kv_check = [&](int s) {
            if (s + 1 < NSEG) {
                if (lane < 4) {
                    unsigned f; int guard = 0;
                    do {
                        asm volatile("ld.acquire.gpu.global.u32 %0, [%1];" : "=r"(f) : "l"(g_xflag + h * 4 + lane) : "memory");
                        if (++guard > (1 << 20)) __trap();
                    } while (f <= (unsigned)(s + 1));
                }
                __syncwarp();
                asm volatile("fence.proxy.async.global;" ::: "memory");
            }
        };
        auto kv_load = [&](int s) {
            if (lane == 0 && s + 1 < NSEG) {
                const uint32_t bar = sb + MB_KV + ((s + 1) & 1) * 8, dst = sb + SM_KV + ((s + 1) & 1) * KV_BYTES;
                const int row = (((s + 1) & 3) * NH + h) * 96;
                mbar_expect_tx(bar, KV_BYTES);
                asm volatile("cp.async.bulk.tensor.3d.shared::cluster.global.mbarrier::complete_tx::bytes.multicast::cluster [%0], [%1, {%3, %4, %3}], [%2], %5;"
                             ::"r"(dst + kh * 8192), "l"(&mapKV), "r"(bar), "r"(0), "r"(row + 32 + 32 * kh), "h"((uint16_t)3) : "memory");
                bulk_load(dst + 16384, g_tok + row * DH + j * 1024, 2048, bar);
            }
            __syncwarp();
        };
        if (warp == 9) {
            if (!PRO2 && lane == 0) { load_xt(0, 0); load_xt(0, 1); }
#pragma unroll 1
            for (int s = -3; s < 0; s++) { tok_start(s); KT_MARK(13 + s); bar_arrive(BAR_PRO, 288); tok_mid(s); }
        }
        if (warp == 11) { kv_check(-1); kv_load(-1); }
        bar_arrive(BAR_MEM, 384);
        const uint32_t ybox = mlo + page_off(role & 63, cls ^ YFLIP_()), xoth = mlo + WIN + page_off((pair & 31) ^ 1, cls ^ XFLIP);
        const uint32_t zline = mlo + WIN + page_off(32 + ((role >> 5) & 1), cls ^ ZFLIP) + (role & 31) * 128, zbox = mlo + WIN + (page_off(32 + kh, 0) & ~4096u);
        const uint32_t xtype = g == GV ? 2 : g == 2 ? 0 : 1;
        const uint32_t ydst = (lane >> 3) * 128 + ((lane & 7) ^ (lane >> 3)) * 16, ysrc = lane * 128 + ((2 * g) ^ (lane & 7)) * 16;
#pragma unroll 1
        for (int s = 0; s < NSEG; s++) {
            const uint32_t slot = (s & 3) << 14;
            spin_cycles(DLY_T);
            if (g == 3) {
                spin_cycles(DLY_K);
                kv_check(s);
                const uint32_t L = l16, kvo = (s & 1) * KV_BYTES, qa = QFRAG(), sa = sb + SM_S + 512 + (L >> 2);
                float sc[4] = {0.f, 0.f, 0.f, 0.f}, sd[4] = {0.f, 0.f, 0.f, 0.f};
                uint32_t a[4][4], kb[2][4];
                mbar_wait_w(sb + MB_KV + (s & 1) * 8, (s >> 1) & 1);
                mbar_wait_w(sb + MB_P, s & 1);
#pragma unroll
                for (int c = 0; c < 2; c++) {
                    const uint32_t qc = qa + (sb + (nh ^ c) * 1024), kc = L + (sb + SM_QKV + 2048 + (nh ^ c) * 1024);
                    if (c) bar_sync(BAR_QK, 224);
                    ldsm4t(kb[0], kc); ldsm4t(a[0], qc); ldsm4t(a[1], qc + 256);
                    ldsm4t(kb[1], kc + 512); ldsm4t(a[2], qc + 512); ldsm4t(a[3], qc + 768);
                    mma16816v(sc, a[0], kb[0][0], kb[0][1]);
                    mma16816v(sd, a[1], kb[0][2], kb[0][3]);
                    mma16816v(sc, a[2], kb[1][0], kb[1][1]);
                    mma16816v(sd, a[3], kb[1][2], kb[1][3]);
                }
                sts32(sa, scale_scores(sc[0] + sd[0], sc[1] + sd[1]));
                sts32(sa + 768, scale_scores(sc[2] + sd[2], sc[3] + sd[3]));
                bar_arrive(BAR_S, 160);
                TL(25);
                bar_sync(BAR_SV, NSV);
                kv_load(s);
            } else {
                if (g == 1) { spin_cycles(DLY_S); tok_start(s); if (TS_AT == 5) TL(21); if (s == 0) KT_MARK(13); }
                const char* p = make_ptr(l16 + (xoth + xtype * 1024 + slot), mhi);
                const uint32_t dst = l16 + (sb + SM_QKV + xtype * 2048 + (nh ^ 1) * 1024);
                asm volatile("" ::"l"(p));
                uint4 v[2];
                poll_init(v[0]); poll_init(v[1]);
                if (g == GV) {
                    bar_sync(BAR_PUBV, 160);
                    mbar_wait_w(sb + MB_V, s & 1);
                    spin_cycles(DLY_V);
                } else {
                    bar_sync(BAR_PUB, 192);
                    spin_cycles(DLY_X);
                }
                const int r = poll2(v, p);
                STAT(1, r > 1 && warp == 10);
                sts128(dst, v[0]); sts128(dst + 512, v[1]);
                if (g != GV) bar_arrive(BAR_QK, 224);
                if (g == GV) { bar_arrive(BAR_V, 160); if (GV == 0) bar_arrive(BAR_SV, NSV); TL(17); }
                if (g == 1) {
                    TL(31);
                    if (LATE_RD) asm volatile("cp.async.bulk.wait_group.read 0;" ::: "memory");
                    bar_sync(BAR_SV, NSV);
                    tok_mid(s);
                    TL(22);
                }
                if (g == 2 && s >= 1) {
                    TL(16);
                    const uint32_t prev = (slot - 0x4000) & 0xC000;
                    const char* y = make_ptr(l16 + (ybox + prev), mhi);
                    const char* x = make_ptr(l16 + (xoth + prev + kh * 1536), mhi);
#pragma unroll
                    for (int i = 0; i < 8; i++) st_sent(y + i * 512);
#pragma unroll
                    for (int i = 0; i < 3; i++) st_sent(x + i * 512);
                    st_relaxed_u32(make_ptr(lane * 4 + (zline + (slot ^ 0x8000)), mhi), SENT);
                    TL(23);
                }
            }
            if (s + 1 == NSEG) break;
            {
                const char* p = make_ptr(l16 + (ybox + g * 1024 + slot), mhi);
                char* zdst = make_ptr(lane * 4 + (zline + g * 32 + slot), mhi);
                const uint32_t dst = ydst + (sb + SM_Z + g * 1024), dst1 = (ydst ^ 64) + (sb + SM_Z + g * 1024 + 512), src = ysrc + (sb + SM_Z), src1 = (ysrc ^ 16) + (sb + SM_Z);
                asm volatile("" ::"l"(p), "l"(zdst));
                uint4 v[2];
                poll_init(v[0]); poll_init(v[1]);
                bar_sync(BAR_SENTC, 384);
                spin_cycles(DLY_Y);
                const int r = poll2(v, p);
                STAT(2, r > 1 && warp == 8);
                sts128(dst, v[0]); sts128(dst1, v[1]);
                bar_sync(BAR_Y, 128);
                TL(18);
                uint32_t b[2][4];
                ldsm4t(b[0], src); ldsm4t(b[1], src1);
                const uint32_t one = 0x3F803F80u;
                float d0[4] = {0.f, 0.f, 0.f, 0.f}, d1[4] = {0.f, 0.f, 0.f, 0.f};
                mma16816(d0, one, one, one, one, b[0][0], b[0][1]);
                mma16816(d1, one, one, one, one, b[1][0], b[1][1]);
                mma16816(d0, one, one, one, one, b[0][2], b[0][3]);
                mma16816(d1, one, one, one, one, b[1][2], b[1][3]);
                const uint32_t w = (lane & 4) ? pack_bf16(d1[0], d1[1]) : pack_bf16(d0[0], d0[1]);
                asm volatile("{.reg .pred p; setp.lt.u32 p, %2, 128; @p st.relaxed.gpu.global.u32 [%0], %1;}" ::"l"(zdst), "r"(w), "r"(l16) : "memory");
                if (s + 3 < NSEG) bar_arrive(BAR_ZP, 256);
                TL(19);
            }
            {
                const char* p = make_ptr(l16 + (zbox + g * 512 + slot), mhi);
                const uint32_t dst = l16 + (sb + SM_Z + g * 512);
                asm volatile("" ::"l"(p));
                uint4 v[4];
                poll_init(v[0]); poll_init(v[1]); poll_init(v[2]); poll_init(v[3]);
                bar_sync(BAR_COMM, 128);
                spin_cycles(DLY_Z);
                const int r = poll4(v, p);
                STAT(0, r > 1 && warp == 8);
#pragma unroll
                for (int i = 0; i < 4; i++) sts128(dst + i * 2048, v[i]);
                bar_arrive(BAR_MEM, 384);
                TL(20);
            }
        }
    } else if (warp < 4) {
        asm volatile("setmaxnreg.inc.sync.aligned.u32 %0;" ::"n"(REG_A));
        code_pad<PAD_A>();
        const uint32_t l16 = lane16();
        uint32_t wa[2][24][4];
        {
            const uint32_t L = l16, fa = sb + FRAG();
            mbar_wait_w(sb + MB_W1, 0);
            KT_MARK(7);
#pragma unroll
            for (int t = 0; t < 2; t++) {
#pragma unroll
                for (int r = 0; r < 24; r++) ldsm4t(wa[t][r], fa + stg_qk(t, r));
                if (PRO2 && t == 0) { bar_arrive(BAR_XT0, 160); mbar_wait_w(sb + MB_W4, 0); }
            }
            mbar_wait_w(sb + MB_W2, 0);
            if (EARLY_ROLE) bar_sync(BAR_PDONE, 384); else bar_arrive(BAR_PDONE, 384);
        }
        auto batch1 = [&](float (&d)[16], uint32_t lo, auto tc, auto k0c, auto k1c) {
            constexpr int t = decltype(tc)::value;
            const uint64_t da = make_desc(SB0 + SM_WQK, 16, 1024);
            wg_fence();
            static_for<decltype(k0c)::value, decltype(k1c)::value>([&](auto kc) {
                constexpr int k = decltype(kc)::value, off = (k >> 2) * 256 + (k & 3) * 2;
                if constexpr (k >= 24) wgmma_ss32u<off>(d, da + ((k - 24) * 2 + t) * 128, lo);
                else wgmma_rs32u<off, k != 0 || t != 0>(d, wa[t][k], lo);
            });
            wg_commit();
        };
        const uint32_t xbox = mlo + WIN + page_off(pair & 31, cls ^ XFLIP);
        const uint32_t ybox = mlo + page_off(24 + 2 * g + 32 * nh, kh ^ YFLIP_()) + h * 128;
#pragma unroll 1
        for (uint32_t it = 0; it < NSEG + 3; it++) {
            const int s = (int)it - 3;
            const uint32_t ui = uniform(it), slot = ((ui + 1) & 3) << 14, kvo = (~ui & 1) * KV_BYTES, xtlo = XTLO();
            {
                PHASE(5);
                const uint32_t first = L | (g << 9);
                if (s >= 0) mbar_expect_tx_if0(first, sb + MB_R1, 2048);
                if (s + 3 < NSEG) {
                    mbar_expect_tx_if0(first, sb + MB_RT0, 8192);
                    mbar_wait_w(sb + MB_XT + (ui & 1) * 8, (it >> 1) & 1);
                }
            }
            if (s >= 0) {
                PHASE(0);
                const uint32_t mb = L + (sb + SM_Z), ra = L + (sb + g * 512), r1 = L + (rsb + SM_R1 + g * 512), r1b = rsb + MB_R1;
                sched_fence(r1);
                bar_sync(BAR_MEM, 384);
                TLB(0);
                float acc[2][2][4];
#pragma unroll
                for (int t = 0; t < 4; t++) { acc[t >> 1][t & 1][0] = acc[t >> 1][t & 1][1] = acc[t >> 1][t & 1][2] = acc[t >> 1][t & 1][3] = 0.f; }
                uint32_t b[4][4];
                uint4 u0, u1;
#pragma unroll
                for (int p = 0; p < 4; p++) ldsm4t(b[p], mb + p * 512);
#pragma unroll
                for (int p = 0; p < 12; p++) {
#pragma unroll
                    for (int u = 0; u < 2; u++) {
                        mma16816v(acc[0][u], wa[0][2 * p + u], b[p & 3][2 * u], b[p & 3][2 * u + 1]);
                        mma16816v(acc[1][u], wa[1][2 * p + u], b[p & 3][2 * u], b[p & 3][2 * u + 1]);
                    }
                    if (p + 4 < 12) ldsm4t(b[p & 3], mb + (p + 4) * 512);
                    if (p == Q3_AT) {
                        bar_sync(BAR_Q3, 256);
                        u0 = lds128(ra + SM_R3); u1 = lds128(ra + SM_O);
                    }
                }
                st_async4(r1, (acc[0][0][0] + __uint_as_float(u0.x)) + acc[0][1][0], (acc[0][0][1] + __uint_as_float(u0.y)) + acc[0][1][1],
                          (acc[0][0][2] + __uint_as_float(u0.z)) + acc[0][1][2], (acc[0][0][3] + __uint_as_float(u0.w)) + acc[0][1][3], r1b);
                TL(1);
                const float o0 = (acc[1][0][0] + __uint_as_float(u1.x)) + acc[1][1][0], o1 = (acc[1][0][1] + __uint_as_float(u1.y)) + acc[1][1][1];
                const float o2 = (acc[1][0][2] + __uint_as_float(u1.z)) + acc[1][1][2], o3 = (acc[1][0][3] + __uint_as_float(u1.w)) + acc[1][1][3];
                const uint32_t l4 = L >> 2, qo = SM_QKV + kh * 2048 + nh * 1024 + g * 256, qr = l4 + (rsb + qo), ql = l4 + (sb + qo), pb = rsb + MB_P;
                char* xd = make_ptr(l4 + (xbox + kh * 1024 + g * 256 + slot), mhi);
                asm volatile("" ::"l"(xd), "r"(qr), "r"(pb), "r"(qr + 128), "f"(o0), "f"(o1), "f"(o2), "f"(o3));
                mbar_wait_w(sb + MB_R1, s & 1);
                const uint4 v = lds128(ra + SM_R1);
                const uint32_t w0 = pack_bf16(o0 + __uint_as_float(v.x), o1 + __uint_as_float(v.y)), w1 = pack_bf16(o2 + __uint_as_float(v.z), o3 + __uint_as_float(v.w));
                st_relaxed_u32(xd, w0);
                st_relaxed_u32(xd + 128, w1);
                bar_arrive(BAR_PUB, 192);
                st_async1(qr, w0, pb);
                st_async1(qr + 128, w1, pb);
                sts32(ql, w0);
                sts32(ql + 128, w1);
                __syncwarp();
                mbar_expect_tx_if0(L, sb + MB_P, 256);
                TL(2);
                if (s + 3 < NSEG) bar_sync(BAR_VP, 256);
            } else {
                bar_sync(BAR_PRO, 288);
            }
            if (s + 3 < NSEG) {
                float d[16];
                batch1(d, xtlo, std::integral_constant<int, 0>(), std::integral_constant<int, 0>(), std::integral_constant<int, 32>());
                PHASE(1);
                const uint32_t rt = L + (rsb + SM_RT + g * 2048);
                wg_wait<0>();
                TL(7);
#pragma unroll
                for (int i = 0; i < 4; i++) st_async4(rt + i * 512, d[4 * i], d[4 * i + 1], d[4 * i + 2], d[4 * i + 3], rsb + MB_RT0);
            }
            if (s + 1 == NSEG) { bar_arrive(BAR_SV, NSV); break; }
            if (s >= 0) {
                PHASE(2);
                const uint32_t fo = FRAG() + (sb + SM_WO2 + 16384), lo = L + (sb + SM_O), yo = (L >> 2) + (ybox + slot);
                uint32_t a1[8][4];
                bar_sync(BAR_SV, NSV);
#pragma unroll
                for (int k = 0; k < 8; k++) ldsm4t(a1[k], fo + k * 2048);
                sched_fence(yo);
                bar_sync(BAR_O2, 256);
                TLB(14);
                float y0[4] = {0.f, 0.f, 0.f, 0.f}, y1[4] = {0.f, 0.f, 0.f, 0.f};
                uint32_t b[2][4];
                ldsm4t(b[0], lo); ldsm4t(b[1], lo + 512);
                sched_fence(L);
#pragma unroll
                for (int p = 0; p < 4; p++) {
                    mma16816v(y0, a1[2 * p], b[p & 1][0], b[p & 1][1]);
                    mma16816v(y1, a1[2 * p + 1], b[p & 1][2], b[p & 1][3]);
                    if (p < 2) ldsm4t(b[p & 1], lo + (p + 2) * 512);
                }
                bar_sync(BAR_INV, 256);
                float i0, i1;
                asm volatile("ld.shared.v2.f32 {%0, %1}, [%2];" : "=f"(i0), "=f"(i1) : "r"(((L >> 1) & 0x18) + (sb + SM_INV + g * 32)) : "memory");
                st_relaxed_u32(make_ptr(yo, mhi), pack_bf16((y0[0] + y1[0]) * i0, (y0[1] + y1[1]) * i1));
                st_relaxed_u32(make_ptr(yo ^ 4096, mhi) + 0x2000, pack_bf16((y0[2] + y1[2]) * i0, (y0[3] + y1[3]) * i1));
                bar_arrive(BAR_SENTC, 384);
                TL(6);
            }
            if (s + 3 < NSEG) {
                PHASE(4);
                float d[16];
                const uint32_t rt = L + (sb + SM_RT + g * 2048);
                if (SENT_EARLY && s >= 0) bar_sync(BAR_SENT, 256);
                mbar_wait_w(sb + MB_RT0, it & 1);
#pragma unroll
                for (int i = 0; i < 4; i++) {
                    const uint4 v = lds128(rt + i * 512);
                    d[4 * i] = __uint_as_float(v.x); d[4 * i + 1] = __uint_as_float(v.y); d[4 * i + 2] = __uint_as_float(v.z); d[4 * i + 3] = __uint_as_float(v.w);
                }
                if (!SENT_EARLY && s >= 0) bar_sync(BAR_SENT, 256);
                if (SPLIT > 0) batch1(d, xtlo, std::integral_constant<int, 1>(), std::integral_constant<int, 0>(), std::integral_constant<int, SPLIT>());
                if (s >= 0) bar_sync(BAR_ZP, 256);
                TLB(30);
                batch1(d, xtlo, std::integral_constant<int, 1>(), std::integral_constant<int, SPLIT>(), std::integral_constant<int, 32>());
                const uint32_t so = (kh ? FRAG() : ((L & 0x100) << 2) + (L & 0xF0) + g * 256) + (sb + SM_STG);
                wg_wait<0>();
                TL(8);
                uint32_t w[8];
#pragma unroll
                for (int i = 0; i < 8; i++) w[i] = pack_bf16(d[2 * i], d[2 * i + 1]);
                if (kh) {
                    stsm4t(so, w[0], w[1], w[2], w[3]);
                    stsm4t(so + 2048, w[4], w[5], w[6], w[7]);
                } else {
                    stsm4(so, w[0], w[1], w[2], w[3]);
                    stsm4(so + 2048, w[4], w[5], w[6], w[7]);
                }
                __syncwarp();
                mbar_arrive_if0(L, sb + MB_STG);
                TL(9);
            } else {
                bar_arrive(BAR_SENT, 256);
            }
        }
    } else {
        asm volatile("setmaxnreg.inc.sync.aligned.u32 %0;" ::"n"(REG_B));
        code_pad<PAD_B>();
        const uint32_t l16 = lane16();
        uint32_t wv[24][4], wo[8 + WO_RF1][4];
        {
            const uint32_t L = l16, fa = sb + FRAG();
            mbar_wait_w(sb + MB_W0, 0);
            KT_MARK(6);
#pragma unroll
            for (int r = 0; r < 24; r++) ldsm4t(wv[r], fa + STG_V + r * 2048);
#pragma unroll
            for (int r = 0; r < 8 + WO_RF1; r++) asm volatile("" : "=r"(wo[r][0]), "=r"(wo[r][1]), "=r"(wo[r][2]), "=r"(wo[r][3]));
            mbar_wait_w(sb + MB_W2, 0);
            if (EARLY_ROLE) bar_sync(BAR_PDONE, 384); else bar_arrive(BAR_PDONE, 384);
        }
        const uint32_t xbox = mlo + WIN + page_off(pair & 31, cls ^ XFLIP);
        const uint32_t ybox = mlo + page_off(2 * g + 32 * nh, kh ^ YFLIP_()) + h * 128;
#pragma unroll 1
        for (uint32_t it = 0; it < NSEG + 3; it++) {
            const int s = (int)it - 3;
            const uint32_t ui = uniform(it), slot = ((ui + 1) & 3) << 14, kvo = (~ui & 1) * KV_BYTES, xtlo = XTLO();
            {
                PHASE(5);
                const uint32_t first = L | (g << 9);
                if (s >= 0) mbar_expect_tx_if0(first, sb + MB_R2, 1024);
                if (s + 3 < NSEG) {
                    mbar_expect_tx_if0(first, sb + MB_RT1, 4096);
                    mbar_wait_w(sb + MB_XT + (ui & 1) * 8, (it >> 1) & 1);
                }
            }
            if (s >= 0) {
                PHASE(0);
                const uint32_t fo = FRAG() + sb, l4 = L >> 2;
                {
                    const uint32_t mb = L + (sb + SM_Z), aw = fo + SM_WQK, ra = L + (sb + g * 512), r2 = (L >> 1) + (rsb + SM_R2 + g * 256), r2b = rsb + MB_R2;
                    uint32_t a[NA][4], b[4][4];
#pragma unroll
                    for (int i = 0; i < NA; i++) ldsm4t(a[i], aw + i * 2048);
                    sched_fence(L);
                    TL(24);
                    bar_sync(BAR_MEM, 384);
#pragma unroll
                    for (int p = 0; p < 4; p++) ldsm4t(b[p], mb + (12 + p) * 512);
                    sched_fence(L);
                    float c[2][4] = {{0.f, 0.f, 0.f, 0.f}, {0.f, 0.f, 0.f, 0.f}};
#pragma unroll
                    for (int i = 0; i < 16; i++) {
                        mma16816v(c[i & 1], a[i % NA], b[i >> 2][i & 2], b[i >> 2][(i & 2) + 1]);
                        ldsm4t(a[i % NA], aw + (i + NA) * 2048);
                    }
                    sts128(ra + SM_R3, make_uint4(__float_as_uint(c[0][0]), __float_as_uint(c[0][1]), __float_as_uint(c[0][2]), __float_as_uint(c[0][3])));
                    sts128(ra + SM_O, make_uint4(__float_as_uint(c[1][0]), __float_as_uint(c[1][1]), __float_as_uint(c[1][2]), __float_as_uint(c[1][3])));
                    bar_arrive(BAR_Q3, 256);
                    TL(29);
                    float acc[4][4];
#pragma unroll
                    for (int t = 0; t < 4; t++) { acc[t][0] = acc[t][1] = acc[t][2] = acc[t][3] = 0.f; }
#pragma unroll
                    for (int i = 16; i < 24; i++) {
                        mma16816v(acc[i & 1], a[i % NA], b[(i - 16) >> 1][2 * (i & 1)], b[(i - 16) >> 1][2 * (i & 1) + 1]);
                        if (i + NA < 24) ldsm4t(a[i % NA], aw + (i + NA) * 2048);
                        else ldsm4t(a[i % NA], mb + (i + NA - 24) * 512);
                    }
#pragma unroll
                    for (int p = 0; p < 12; p++) {
                        mma16816v(acc[(2 * p) & 3], wv[2 * p], a[(24 + p) % NA][0], a[(24 + p) % NA][1]);
                        mma16816v(acc[(2 * p + 1) & 3], wv[2 * p + 1], a[(24 + p) % NA][2], a[(24 + p) % NA][3]);
                        if (p + NA < 12) ldsm4t(a[(24 + p) % NA], mb + (p + NA) * 512);
                    }
                    if (s + 3 < NSEG) bar_arrive(BAR_VP, 256);
                    float o[4];
#pragma unroll
                    for (int i = 0; i < 4; i++) o[i] = (acc[0][i] + acc[1][i]) + (acc[2][i] + acc[3][i]);
                    st_async2(r2, kh ? o[0] : o[2], kh ? o[1] : o[3], r2b);
                    TL(10);
                    const float o0 = kh ? o[2] : o[0], o1 = kh ? o[3] : o[1];
                    const uint32_t qo = SM_QKV + 4096 + nh * 1024 + (2 * g + kh) * 128, qr = l4 + (rsb + qo), ql = l4 + (sb + qo), vb = rsb + MB_V, rl = (L >> 1) + (sb + SM_R2 + g * 256);
                    char* xd = make_ptr(l4 + (xbox + 2048 + (2 * g + kh) * 128 + slot), mhi);
                    asm volatile("" ::"l"(xd), "r"(qr), "r"(vb), "f"(o0), "f"(o1));
                    mbar_wait_w(sb + MB_R2, s & 1);
                    uint32_t vx, vy;
                    asm volatile("ld.shared.v2.u32 {%0,%1}, [%2];" : "=r"(vx), "=r"(vy) : "r"(rl) : "memory");
                    const uint32_t w0 = pack_bf16(o0 + __uint_as_float(vx), o1 + __uint_as_float(vy));
                    st_relaxed_u32(xd, w0);
                    bar_arrive(BAR_PUBV, 160);
                    st_async1(qr, w0, vb);
                    sts32(ql, w0);
                    __syncwarp();
                    mbar_expect_tx_if0(L, sb + MB_V, 128);
                    TL(11);
                }
                const uint32_t vma = L + (sb + SM_QKV + 4096 + g * 512), yo = l4 + (ybox + slot);
                uint32_t va[2][2][4];
                {
                    const uint32_t qa = QFRAG(), vf = VFRAG(), va0 = vf + VBASE(), va1 = (vf ^ 32) + VBASE();
                    const uint32_t kf = ((L << 3) & 0x380) | ((L ^ (L >> 3)) & 0x30) | (L & 0x40), kb0 = sb + SM_KV + kvo + g * 1024;
                    const int d = (int)(L >> 6) - (int)((L >> 3) & 6) + 8 * (j - (int)g);
                    const uint32_t keep = (d < 0 ? 0u : 0xFFFFu) | (d < 1 ? 0u : 0xFFFF0000u), sa = l4 + (sb + SM_S + g * 128);
                    const uint32_t q0 = qa + (sb + nh * 1024), q1 = qa + (sb + (nh ^ 1) * 1024);
                    float sc[4] = {0.f, 0.f, 0.f, 0.f}, sd[4] = {0.f, 0.f, 0.f, 0.f};
                    uint32_t a[4][4], kb[2][4];
                    mbar_wait_w(sb + MB_KV + (~ui & 1) * 8, (s >> 1) & 1);
                    ldsm4(kb[0], kf + (kb0 + nh * 4096)); ldsm4(kb[1], (kf ^ 64) + (kb0 + nh * 4096));
                    mbar_wait_w(sb + MB_P, s & 1);
                    TL(12);
#pragma unroll
                    for (int k = 0; k < 4; k++) ldsm4t(a[k], q0 + k * 256);
#pragma unroll
                    for (int k = 0; k < 4; k++) mma16816v((k & 1) ? sd : sc, a[k], kb[k >> 1][2 * (k & 1)], kb[k >> 1][2 * (k & 1) + 1]);
                    ldsm4(kb[0], kf + (kb0 + (nh ^ 1) * 4096)); ldsm4(kb[1], (kf ^ 64) + (kb0 + (nh ^ 1) * 4096));
                    sched_fence(vf | yo);
                    bar_sync(BAR_QK, 224);
                    TLB(3);
#pragma unroll
                    for (int k = 0; k < 4; k++) ldsm4t(a[k], q1 + k * 256);
                    sched_fence(L);
#pragma unroll
                    for (int k = 0; k < 4; k++) mma16816v((k & 1) ? sd : sc, a[k], kb[k >> 1][2 * (k & 1)], kb[k >> 1][2 * (k & 1) + 1]);
                    ldsm4t(va[0][0], va0); ldsm4t(va[0][1], va0 + 2048);
                    sts32(sa, scale_scores(sc[0] + sd[0], sc[1] + sd[1]));
                    sts32(sa + 768, (scale_scores(sc[2] + sd[2], sc[3] + sd[3]) & keep) | (0xFF80FF80u & ~keep));
                    bar_arrive(BAR_SV, NSV);
                    ldsm4t(va[1][0], va1); ldsm4t(va[1][1], va1 + 2048);
                }
                bar_sync(BAR_S, 160);
                TLB(4);
                uint32_t pw[6], vm[4];
                if (s + 1 < NSEG) {
                softmax40(pw, l4 + (sb + SM_S), [&]() {
                    bar_sync(BAR_V, 160);
                    ldsm4(vm, vma);
                });
                uint32_t a1[NP2][4];
                float inv[2];
                {
                    uint32_t w[4];
                    pv32<false>(w, inv, va, vm, pw, [&]() {
                        sched_fence(L);
#pragma unroll
                        for (int k = 0; k < NP2; k++) ldsm4t(a1[k], fo + SM_WO2 + k * 2048);
                    });
#pragma unroll
                    for (int i = 0; i < 4; i++) sts32(l4 + (sb + SM_O + g * 512) + i * 128, w[i]);
                }
                const uint32_t lo = L + (sb + SM_O);
                bar_arrive(BAR_O2, 256);
                bar_sync(BAR_O, 128);
                TLB(5);
                {
                    float y0[4] = {0.f, 0.f, 0.f, 0.f}, y1[4] = {0.f, 0.f, 0.f, 0.f}, y2[4] = {0.f, 0.f, 0.f, 0.f};
                    uint32_t b[4][4];
#pragma unroll
                    for (int p = 0; p < 4; p++) ldsm4t(b[p], lo + p * 512);
                    inv[0] = rcp_approx(inv[0]); inv[1] = rcp_approx(inv[1]);
                    asm volatile("st.shared.v2.f32 [%0], {%1, %2};" ::"r"(((L >> 1) & 0x18) + (sb + SM_INV + g * 32)), "f"(inv[0]), "f"(inv[1]) : "memory");
                    bar_arrive(BAR_INV, 256);
                    sched_fence(L);
#pragma unroll
                    for (int k = 0; k < 8; k++) {
                        const int p = k >> 1, u = k & 1;
                        mma16816v(y2, a1[k % NP2], b[p][2 * u], b[p][2 * u + 1]);
                        if (k + NP2 < 8) ldsm4t(a1[k % NP2], fo + SM_WO2 + (k + NP2) * 2048);
                        else if (k + NP2 < 16 - WO_RF1) ldsm4t(a1[k % NP2], fo + SM_WO1 + (k + NP2 - 8 + WO_RF1) * 2048);
                        mma16816v(y0, wo[k], b[p][2 * u], b[p][2 * u + 1]);
                        if (k < WO_RF1) mma16816v(y1, wo[8 + (k < WO_RF1 ? k : 0)], b[p][2 * u], b[p][2 * u + 1]);
                        else mma16816v(y1, a1[(k + 8 - WO_RF1) % NP2], b[p][2 * u], b[p][2 * u + 1]);
                        if (k < P2_FENCE) sched_fence(L);
                    }
                    char* yd = make_ptr(yo, mhi);
                    char* yd1 = make_ptr(yo ^ 4096, mhi);
                    st_relaxed_u32(yd1 + 0x80000, pack_bf16(y2[0] * inv[0], y2[1] * inv[1]));
                    st_relaxed_u32(yd + 0x82000, pack_bf16(y2[2] * inv[0], y2[3] * inv[1]));
                    st_relaxed_u32(yd, pack_bf16(y0[0] * inv[0], y0[1] * inv[1]));
                    st_relaxed_u32(yd1 + 0x2000, pack_bf16(y0[2] * inv[0], y0[3] * inv[1]));
                    st_relaxed_u32(yd + 0x40000, pack_bf16(y1[0] * inv[0], y1[1] * inv[1]));
                    st_relaxed_u32(yd1 + 0x42000, pack_bf16(y1[2] * inv[0], y1[3] * inv[1]));
                }
                bar_arrive(BAR_SENTC, 384);
                TL(13);
                bar_sync(BAR_SENT, 256);
                } else {
                    bar_sync(BAR_V, 160);
                }
            } else {
                if (it == WO_IT) {
                    PHASE(2);
                    const uint32_t fa = sb + FRAG();
                    mbar_wait_w(sb + MB_W3, 0);
                    KT_MARK(8);
#pragma unroll
                    for (int r = 0; r < 8 + WO_RF1; r++) ldsm4t(wo[r], fa + stg_wo(r));
                }
                bar_sync(BAR_PRO, 288);
            }
            float o[8];
            {
                PHASE(1);
                float d[16];
                const uint64_t da = make_desc(SB0 + SM_WV, 16, 1024);
                auto batch = [&](auto k0c, auto k1c) {
                    static_for<decltype(k0c)::value, decltype(k1c)::value>([&](auto kc) {
                        constexpr int k = decltype(kc)::value, off = (k >> 2) * 256 + (k & 3) * 2;
                        if constexpr (k >= 24) wgmma_ss32u<off>(d, da + (k - 24) * 128, xtlo);
                        else wgmma_rs32u<off, k != 0>(d, wv[k], xtlo);
                    });
                };
                const uint32_t vf = VFRAG(), va0 = vf + VBASE(), va1 = (vf ^ 32) + VBASE(), vma = L + (sb + SM_QKV + 4096 + g * 512), sa = (L >> 2) + (sb + SM_S + 768);
                const uint32_t rt = L + (rsb + SM_RT + 8192 + g * 1024);
                uint32_t va[2][2][4], vm[4], pw[6], w[4];
                wg_fence();
                batch(std::integral_constant<int, 0>(), std::integral_constant<int, TA0>());
                wg_commit();
                batch(std::integral_constant<int, TA0>(), std::integral_constant<int, 32>());
                wg_commit();
                wg_wait<1>();
                softmax40(pw, sa, [&]() {});
                ldsm4t(va[0][0], va0); ldsm4t(va[0][1], va0 + 2048);
                ldsm4t(va[1][0], va1); ldsm4t(va[1][1], va1 + 2048);
                ldsm4(vm, vma);
                wg_wait<0>();
                TL(27);
                float inv[2];
                pv32<true>(w, inv, va, vm, pw, [&]() {
                    if (s + 3 < NSEG) {
#pragma unroll
                        for (int i = 0; i < 2; i++)
                            st_async4(rt + i * 512, kh ? d[4 * i] : d[8 + 4 * i], kh ? d[4 * i + 1] : d[9 + 4 * i], kh ? d[4 * i + 2] : d[10 + 4 * i], kh ? d[4 * i + 3] : d[11 + 4 * i], rsb + MB_RT1);
                    }
#pragma unroll
                    for (int i = 0; i < 8; i++) o[i] = kh ? d[8 + i] : d[i];
                });
                stsm4t((L & 0x70) * 5 + ((L >> 3) & 0x30) + (sb + SM_TO + g * 640), w[0], w[1], w[2], w[3]);
                __syncwarp();
                const uint4 r = lds128(((L >> 2) & 0x70) * 5 + (L & 0x30) + (sb + SM_TO + g * 640));
                if (s >= 0) stg128(reinterpret_cast<char*>(g_ox) + (((L & 0x1C0) << 7) + (L & 0x30) + (((ui - 3) * SEG + 8 * j) * HD + h * DH + 32 * g) * 2), r);
                TL(26);
            }
            if (s + 3 < NSEG) {
                PHASE(3);
                const uint32_t rt = L + (sb + SM_RT + 8192 + g * 1024), so = FRAG() + (sb + SM_STG + 4096);
                mbar_wait_w(sb + MB_RT1, it & 1);
                TL(28);
                uint32_t w[4];
#pragma unroll
                for (int i = 0; i < 2; i++) {
                    const uint4 v = lds128(rt + i * 512);
                    w[2 * i] = pack_bf16(o[4 * i] + __uint_as_float(v.x), o[4 * i + 1] + __uint_as_float(v.y));
                    w[2 * i + 1] = pack_bf16(o[4 * i + 2] + __uint_as_float(v.z), o[4 * i + 3] + __uint_as_float(v.w));
                }
                stsm4t(so, w[0], w[1], w[2], w[3]);
                __syncwarp();
                mbar_arrive_if0(L, sb + MB_STG);
                TL(15);
            }
        }
    }
    KT_END(2);
    asm volatile("barrier.cluster.arrive.relaxed; barrier.cluster.wait;" ::: "memory");
}
constexpr int B_UCH = 73 * 64;
constexpr int B_SCH = 33 * 64;
constexpr int B_KLEN = 2128;
constexpr int B_KCH = 2 * B_KLEN * 2 + 64;
constexpr int B_KBOX = 136 * 32;
constexpr int B_SM_U = 0;
constexpr int B_SM_S = 8 * B_UCH;
constexpr int B_SM_K = B_SM_S + 8 * B_SCH;
constexpr int B_SM_KT = B_SM_K + 8 * B_KCH;
constexpr int B_SM_VT = B_SM_KT + 8 * B_KBOX;
constexpr int B_SM_QT = B_SM_VT + 32768;
constexpr int B_SM_BAR = B_SM_QT + 32768;
constexpr int B_SMEM = B_SM_BAR + 128 + 512;
static_assert(B_SM_KT % 256 == 0 && B_SM_S % 512 == 0 && B_SMEM <= 232448, "tiles");
constexpr int PROBE_N = 4;
#define PROBE_R 2
constexpr int B_C = 2056;

__device__ __forceinline__ uint32_t atomic_round_trip(char* p) {
    uint32_t t0, t1, v;
    asm volatile("{.reg .pred p;\n"
                 "mov.u32 %0, %%clock;\n"
                 "atom.relaxed.gpu.global.add.u32 %2, [%3], 1;\n"
                 "setp.ne.u32 p, %2, 0x7FFFFFFF;\n"
                 "mov.u32 %1, 0;\n"
                 "@p mov.u32 %1, %%clock;}" : "=&r"(t0), "=&r"(t1), "=&r"(v) : "l"(p) : "memory");
    return t1 - t0;
}
__device__ __forceinline__ uint32_t round_trips(char* a, char* b, uint32_t stride, int lane) {
    for (int i = lane >> 3; i < 2 * PROBE_N; i += 4) stg128(((i & 1) ? b : a) + (i >> 1) * stride + (lane & 7) * 16, make_uint4(0, 0, 0, 0));
    __syncwarp();
    uint32_t ta = 0xFFFF, tb = 0xFFFF;
    if (lane == 0) {
        __threadfence();
#pragma unroll 1
        for (int i = 0; i < PROBE_N; i++) { ta = min(ta, atomic_round_trip(a + i * stride)); tb = min(tb, atomic_round_trip(b + i * stride)); }
    }
    __syncwarp();
    return ta | (tb << 16);
}
__device__ __forceinline__ void measure_distance(char* mbox, int lane) {
    const uint32_t b = blockIdx.x;
    unsigned smid;
    asm volatile("mov.u32 %0, %%smid;" : "=r"(smid));
    char* w1 = mbox + WIN + (b & 31) * 128;
    uint32_t r = 0xFFFFFFFF;
#pragma unroll 1
    for (int i = 0; i < PROBE_R; i++) r = __vminu2(r, round_trips(w1 + page_off(50 + 5 * i + (b >> 5), 0), w1 + page_off(50 + 5 * i + (b >> 5), 1), 16384, lane));
    if (lane == 0) g_cls[smid] = r;
    if (b == 128) {
        char *p = mbox + page_off(0, 0), *q = mbox + page_off(0, 1);
        uint32_t r0 = 0xFFFFFFFF;
#pragma unroll 1
        for (int i = 0; i < PROBE_R; i++) r0 = __vminu2(r0, round_trips(p, q, 128, lane));
        if (lane == 0) { g_reg[1] = ((r0 & 0xFFFF) > (r0 >> 16)) != ((r & 0xFFFF) > (r >> 16)); if (!EARLY_ROLE) g_reg[0] = 0; g_reg[2] = 0; }
        const uint4 sent = make_uint4(SENT, SENT, SENT, SENT);
        stg128(p + lane * 16, sent); stg128(q + lane * 16, sent);
    }
    if (b == 129) for (int i = lane; i < 128; i += 32) g_xflag[i] = 0;
}

#define SP(i)
#define SP2(i)
#define OUT_STG 0
#define PF_STOP 1
#define SENT_AT 3
#define Q_LATE 1
#define PF_DEPTH 4
#define PF_STRIDE 256
struct ChainInputs { const char* w[4]; const char *x, *mem0; };
#define EF_MASK 15
#define EF(i) (((EF_MASK >> (i)) & 1) ? policy_evict_first() : policy_evict_normal())
__device__ __forceinline__ void l2_prefetch(const char* p, uint32_t bytes) {
    asm volatile("cp.async.bulk.prefetch.L2.global [%0], %1;" ::"l"(p), "r"(bytes) : "memory");
}
#define WG_CONV(N, LIST, A0, A1, A2, A3, LO, OF, ...) \
    if constexpr (NN == N) asm volatile("{.reg .b32 l; .reg .b64 e; add.u32 l, %" #LO ", %" #OF "; mov.b64 e, {l, 0x80000020};\n" \
        "wgmma.mma_async.sync.aligned.m64n" #N "k16.f32.bf16.bf16 {" LIST "}, {%" #A0 ",%" #A1 ",%" #A2 ",%" #A3 "}, e, 1, 1, 1, 0;}" \
        : __VA_ARGS__ : "r"(a[0]), "r"(a[1]), "r"(a[2]), "r"(a[3]), "r"(lo), "n"(OFF));
#define WL4 "%0,%1,%2,%3"
#define WL8 WL4 ",%4,%5,%6,%7"
#define WL12 WL8 ",%8,%9,%10,%11"
#define WL16 WL12 ",%12,%13,%14,%15"
#define WL20 WL16 ",%16,%17,%18,%19"
#define WL24 WL20 ",%20,%21,%22,%23"
#define WL28 WL24 ",%24,%25,%26,%27"
#define WL32 WL28 ",%28,%29,%30,%31"
template <int NN, int OFF> __device__ __forceinline__ void wgmma_conv(float (&d)[32], const uint32_t (&a)[4], uint32_t lo) {
    WG_CONV(8, WL4, 4, 5, 6, 7, 8, 9, R4(0))
    WG_CONV(16, WL8, 8, 9, 10, 11, 12, 13, R4(0), R4(4))
    WG_CONV(24, WL12, 12, 13, 14, 15, 16, 17, R4(0), R4(4), R4(8))
    WG_CONV(32, WL16, 16, 17, 18, 19, 20, 21, R16(0))
    WG_CONV(40, WL20, 20, 21, 22, 23, 24, 25, R16(0), R4(16))
    WG_CONV(48, WL24, 24, 25, 26, 27, 28, 29, R16(0), R4(16), R4(20))
    WG_CONV(56, WL28, 28, 29, 30, 31, 32, 33, R16(0), R4(16), R4(20), R4(24))
    WG_CONV(64, WL32, 32, 33, 34, 35, 36, 37, R16(0), R16(16))
}
__device__ __forceinline__ void copy_to_peer(uint32_t dst, uint32_t src, uint32_t bytes, uint32_t bar) {
    asm volatile("cp.async.bulk.shared::cluster.shared::cta.mbarrier::complete_tx::bytes [%0], [%1], %2, [%3];" ::"r"(dst), "r"(src), "r"(bytes), "r"(bar) : "memory");
}
__device__ __forceinline__ uint32_t lds_volatile(uint32_t a) {
    uint32_t v;
    asm volatile("ld.volatile.shared.u32 %0, [%1];" : "=r"(v) : "r"(a) : "memory");
    return v;
}
__device__ __forceinline__ uint32_t swz64(uint32_t a) { return a ^ ((a >> 3) & 0x30); }
__device__ __forceinline__ void fence_async() { asm volatile("fence.proxy.async.shared::cta;" ::: "memory"); }

__global__ void __cluster_dims__(2, 1, 1) __launch_bounds__(576, 1)
ssm_kernel(const __grid_constant__ CUtensorMap mapK, const __grid_constant__ CUtensorMap mapV, const __grid_constant__ CUtensorMap mapQ,
           const __grid_constant__ CUtensorMap mapO, const bf16* __restrict__ shiftk, const bf16* __restrict__ ssmk, const bf16* __restrict__ Dv,
           char* __restrict__ mbox, const __grid_constant__ ChainInputs ci, bf16* __restrict__ outp) {
    extern __shared__ __align__(128) uint8_t smem_raw[];
    const uint32_t sb = (smem_u32(smem_raw) + 511) & ~511u;
    const int rank = blockIdx.x & 1, ch0 = blockIdx.x * 8, c16 = ch0 & ~15, t0 = rank * 1024;
    const int t = threadIdx.x, warp = t >> 5, lane = t & 31;
    const uint32_t bar = sb + B_SM_BAR, barQ = bar + 64, barU = bar + 72, barY = bar + 80, flag = bar + 88;
    SP(0);
    if (lane == 0 && warp < 16 && blockIdx.x < 128) {
        const int i = warp >> 1;
        if (warp & 1) {
            if (i < 3) { mbar_init(barQ + i * 8, 1); mbar_expect_tx(barQ + i * 8, i ? 16384 : 32768); }
            if (i == 3) sts32(flag, 0);
        } else {
            mbar_init(bar + i * 8, 1);
            asm volatile("fence.mbarrier_init.release.cluster;" ::: "memory");
            mbar_expect_tx(bar + i * 8, B_KBOX + 4096);
            tma_load_2d(sb + B_SM_KT + i * B_KBOX, &mapK, c16, t0 + i * 128 - 8, bar + i * 8, EF(0));
            tma_load_2d(sb + B_SM_VT + i * 4096, &mapV, c16, t0 + i * 128, bar + i * 8, EF(0));
        }
        asm volatile("fence.mbarrier_init.release.cluster;" ::: "memory");
    }
    __syncwarp();
    if (warp == 14) SP2(14);
    KT_START(1);
    if (warp == 17) {
        launch_dependents();
        asm volatile("barrier.cluster.arrive.relaxed.aligned;" ::: "memory");
        measure_distance(mbox, lane);
        asm volatile("barrier.cluster.wait.aligned;" ::: "memory");
        KT_MARK(14);
        return;
    }
    if (blockIdx.x >= 128) return;
    if (warp == 16) {
        asm volatile("barrier.cluster.arrive.relaxed.aligned; barrier.cluster.wait.aligned;" ::: "memory");
        SP2(8);
        if (Q_LATE) for (int i = 0; i < 8; i++) { mbar_wait_w(bar + i * 8, 0); SP2(i); }
        if (lane < 8) tma_load_2d(sb + B_SM_QT + lane * 4096, &mapQ, c16, t0 + lane * 128, barQ, EF(3));
        if (!Q_LATE) for (int i = 0; i < 8; i++) mbar_wait_w(bar + i * 8, 0);
        if (lane == 0) {
            l2_prefetch(ci.x + blockIdx.x * 2048, 2048);
            if (blockIdx.x < 8) l2_prefetch(ci.mem0 + blockIdx.x * 2048, 2048);
        }
        uint32_t v[PF_DEPTH], acc = 0;
#pragma unroll
        for (int u = 0; u < PF_DEPTH; u++) v[u] = 0;
        constexpr int PER = 32 * PF_STRIDE, NW = 65536 / PER;
#define PF_N (4 * NW)
        int i = 0;
#pragma unroll 1
        for (; i < PF_N && lds_volatile(flag) == 0; i += PF_DEPTH) {
#pragma unroll
            for (int u = 0; u < PF_DEPTH; u++) {
                const char* a = ci.w[(i + u) / NW] + blockIdx.x * 65536 + ((i + u) % NW) * PER + lane * PF_STRIDE;
                acc |= v[u];
                asm volatile("ld.global.cg.L2::256B.u32 %0, [%1];" : "=r"(v[u]) : "l"(a) : "memory");
            }
        }
#pragma unroll
        for (int u = 0; u < PF_DEPTH; u++) acc |= v[u];
        if (acc == 0x7FFF7FFFu && v[0] == 0x7FFEu) g_err = 1;
        SP2(12);
        KT_MARK(15);
        return;
    }
    asm volatile("barrier.cluster.arrive.relaxed.aligned;" ::: "memory");
    const int far = warp & 1, unit = rank ^ far;
    uint32_t w[4];
    uint32_t d2;
    asm volatile("ld.global.nc.u32 %0, [%1];" : "=r"(d2) : "l"(Dv + ch0 + (warp >> 2) * 2));
    {
        const int ch = warp & 7, half = warp >> 3;
        const uint32_t kb = sb + B_SM_K + ch * B_KCH;
        const uint4* src = reinterpret_cast<const uint4*>(ssmk + (size_t)(ch0 + ch) * S_LEN);
        uint4 kr[4];
#pragma unroll
        for (int i = 0; i < 4; i++) kr[i] = ldg128(src + half * 128 + i * 32 + lane, EF(1));
        const uint32_t edge = half ? 0u : __ldg(reinterpret_cast<const uint32_t*>(src + 128));
        const uint2 sw = __ldg(reinterpret_cast<const uint2*>(shiftk + (size_t)(c16 + unit * 8 + (lane >> 2)) * 4));
        w[0] = __byte_perm(sw.x, 0, 0x1010); w[1] = __byte_perm(sw.x, 0, 0x3232); w[2] = __byte_perm(sw.y, 0, 0x1010); w[3] = __byte_perm(sw.y, 0, 0x3232);
        if (half) sts128(sb + B_SM_U + ch * B_UCH + 4096 + lane * 16, make_uint4(0, 0, 0, 0));
#pragma unroll
        for (int i = 0; i < 4; i++) {
            const uint4 lo = kr[i];
            const uint32_t nx = __shfl_down_sync(~0u, lo.x, 1), n0 = (i < 3) ? __shfl_sync(~0u, kr[i < 3 ? i + 1 : 3].x, 0) : edge;
            const uint32_t hix = (lane < 31) ? nx : n0;
            const int c = 256 - (half * 128 + 32 * i + lane);
            sts128(kb + c * 16, make_uint4(__byte_perm(hix, lo.w, 0x7610), __byte_perm(lo.w, lo.z, 0x7610), __byte_perm(lo.z, lo.y, 0x7610), __byte_perm(lo.y, lo.x, 0x7610)));
            sts128(kb + B_KLEN * 2 + 64 + c * 16, make_uint4(__byte_perm(lo.w, lo.w, 0x1032), __byte_perm(lo.z, lo.z, 0x1032), __byte_perm(lo.y, lo.y, 0x1032), __byte_perm(lo.x, lo.x, 0x1032)));
        }
        const uint32_t k0w = __shfl_sync(~0u, kr[0].x, 0);
        if (half == 0 && lane < 8) {
            sts128(kb + (257 + lane) * 16, make_uint4(lane == 0 ? (k0w & 0xFFFFu) : 0u, 0u, 0u, 0u));
            sts128(kb + B_KLEN * 2 + 64 + (257 + lane) * 16, make_uint4(0u, 0u, 0u, 0u));
        }
    }
    auto sentinels = [&]() {
        const uint4 sent = make_uint4(SENT, SENT, SENT, SENT);
        char* p0 = mbox + blockIdx.x * 16384 + t * 16;
        if (blockIdx.x != 0 || (t & 255) >= 32) stg128(p0, sent);
        stg128(p0 + 8192, sent);
        char* p1 = mbox + WIN + blockIdx.x * 12800 + t * 16;
        stg128(p1, sent);
        if (t < 288) stg128(p1 + 8192, sent);
    };
    if (SENT_AT == 1) sentinels();
    asm volatile("barrier.cluster.wait.acquire.aligned;" ::: "memory");
    SP(1);
    {
        const int box = warp >> 1, row0 = 63 - 32 * rank - 4 * box;
        const uint32_t kt = sb + B_SM_KT + box * B_KBOX + 256 + lane * 32, s0 = (unit ^ ((lane >> 2) & 1)) * 16;
        const uint32_t a0 = kt + s0, a2 = kt - 64 + (unit ^ (((lane + 6) >> 2) & 1)) * 16, a4 = kt - 128 + (s0 ^ 16), av = sb + B_SM_VT + box * 4096 + lane * 32 + s0;
        const uint32_t ul = (lane & 7) * B_UCH + row0 * 64 + (lane >> 3) * 16;
        const uint32_t ud = sb + (far ? B_SM_S + (lane & 7) * (B_SCH - B_UCH) - (1 - rank) * 2048 : B_SM_U);
        mbar_wait_w(bar + box * 8, 0);
        SP(2);
#pragma unroll
        for (int i = 0; i < 4; i++) {
            uint32_t k0[4], k2[4], k4[4], vv[4], o[4];
            ldsm4t(k0, a0 + i * 1024); ldsm4t(k2, a2 + i * 1024); ldsm4t(k4, a4 + i * 1024); ldsm4t(vv, av + i * 1024);
#pragma unroll
            for (int j = 0; j < 4; j++) {
                uint32_t a = bf16_mul(__byte_perm(k4[j], k2[j], 0x5432), w[3]);
                a = bf16_add(a, bf16_mul(k2[j], w[2]));
                a = bf16_add(a, bf16_mul(__byte_perm(k2[j], k0[j], 0x5432), w[1]));
                a = bf16_add(a, bf16_mul(k0[j], w[0]));
                o[j] = bf16_mul(a, vv[j]);
            }
            stsm4(ud + swz64(ul - i * 64), o[0], o[1], o[2], o[3]);
        }
        fence_async();
        __syncwarp();
        if (far && lane < 8) {
            const uint32_t o = lane * B_UCH + (row0 - 3) * 64;
            copy_to_peer(peer_addr(sb + B_SM_U + o, rank ^ 1), ud + o, 256, peer_addr(barU, rank ^ 1));
        }
    }
    bar_sync(1, 512);
    mbar_wait_w(barU, 0);
    if (SENT_AT == 2) sentinels();
    SP(3);
    const int wg = warp >> 2, wq = warp & 3, hi = wq >> 1, g = lane >> 2, tq = lane & 3;
    const uint32_t zero = lds32(sb + B_SM_U + 4096);
#pragma unroll 1
    for (int cc = 0; cc < 2; cc++) {
        const int ch = 2 * wg + cc;
        const uint32_t kb = sb + B_SM_K + ch * B_KCH, ub = sb + B_SM_U + ch * B_UCH;
        const uint32_t dw = __byte_perm(d2, 0, cc ? 0x3232 : 0x1010);
        const int e0 = B_C - g + 2 * tq;
        const uint32_t f0 = ((e0 & 1) ? (kb + B_KLEN * 2 + 64 + (e0 - 1) * 2) : (kb + e0 * 2)) - 32 * wq;
        const uint32_t lo = uniform((ub >> 4) | 0x10000);
        float d[32];
#pragma unroll
        for (int i = 0; i < 32; i++) d[i] = 0.f;
        uint32_t A[2][2][4];
        static_for<0, 32>([&](auto jc) {
            constexpr int j = decltype(jc)::value, N = 64 - 8 * (j / 4);
            if (j >= 2) wg_wait<1>();
            uint32_t(&a)[4] = A[j & 1][0];
            uint32_t(&b)[4] = A[j & 1][1];
            a[0] = lds32(f0 - 128 * j); a[1] = lds32(f0 - 128 * j - 16); a[2] = lds32(f0 - 128 * j + 16);
            b[0] = lds32(f0 - 128 * j + 32); b[2] = lds32(f0 - 128 * j + 48);
            a[3] = a[0] ^ zero; b[1] = a[2] ^ zero; b[3] = b[0] ^ zero;
            wg_fence();
            wgmma_conv<N, 8 * j>(d, a, lo);
            wgmma_conv<N, 8 * j + 2>(d, b, lo);
            wg_commit();
        });
        wg_wait<0>();
        if (cc) SP(4);
        if (PF_STOP == 1 && cc && t == 0) sts32(flag, 1);
        bar_sync(2 + wg, 128);
        if (!hi && tq == 3) { float x = d[13]; d[13] = d[29]; d[29] = x; x = d[15]; d[15] = d[31]; d[31] = x; }
        if (hi && tq == 0) { d[0] = 0.f; d[2] = 0.f; }
        {
            const uint32_t xs = kb + (wq ^ 2) * 2048 + lane * 4;
            const uint32_t xn = hi ? xs + (tq ? 124 : 140) : xs + (tq < 3 ? 4 : -12), wrap = hi ? (tq ? 0 : -1) : (tq < 3 ? 0 : 1);
#pragma unroll
            for (int nb = 0; nb < 4; nb++) {
                const uint32_t xw = xn + ((nb + wrap) & 3) * 512;
#pragma unroll
                for (int i = 0; i < 2; i++) {
                    const float e0v = hi ? d[4 * nb + 2 * i] : d[16 + 4 * nb + 2 * i], e1v = hi ? d[4 * nb + 2 * i + 1] : d[16 + 4 * nb + 2 * i + 1];
                    sts32(hi ? xw + i * 256 : xs + nb * 512 + i * 256 + 128, __float_as_uint(e0v));
                    sts32(hi ? xs + nb * 512 + i * 256 : xw + i * 256, __float_as_uint(e1v));
                }
            }
        }
        bar_sync(2 + wg, 128);
#pragma unroll
        for (int p = 0; p < 2; p++) {
            int row = 16 * p + (lane >> 4) * 8 + (lane & 7);
            row = hi ? row + 31 : row == 31 ? 63 : row;
            const uint32_t a = sb + B_SM_U + swz64(ch * B_UCH + row * 64 + ((wq & 1) * 2 + ((lane >> 3) & 1)) * 16);
            uint32_t u[4];
            ldsm4t(u, a);
#pragma unroll
            for (int b = 0; b < 4; b++) {
                const int r = 8 * p + 2 * b;
                const float y0 = (hi ? d[16 + r] : d[r]) + __uint_as_float(lds32(kb + wq * 2048 + r * 128 + lane * 4));
                const float y1 = (hi ? d[17 + r] : d[r + 1]) + __uint_as_float(lds32(kb + wq * 2048 + r * 128 + 128 + lane * 4));
                u[b] = bf16_add(pack_bf16(y0, y1), bf16_mul(u[b], dw));
            }
            stsm4t(a, u[0], u[1], u[2], u[3]);
        }
        fence_async();
        bar_sync(2 + wg, 128);
        if (SENT_AT == 3 && cc == 0) sentinels();
        if (wq == 0 && lane == 0) copy_to_peer(peer_addr(sb + B_SM_S + ch * B_SCH, rank ^ 1), ub + rank * 2048, 2048, peer_addr(barY, rank ^ 1));
    }
    if (PF_STOP == 2 && t == 0) sts32(flag, 1);
    SP(5);
    mbar_wait_w(barQ, 0);
    bar_sync(1, 512);
    mbar_wait_w(barY, 0);
    asm volatile("barrier.cluster.arrive.relaxed.aligned;" ::: "memory");
    SP(6);
#pragma unroll
    for (int i = 0; i < 4; i++) {
        const int fr = i & 1, row = 63 - 32 * rank - 2 * warp - (i >> 1);
        const uint32_t qa = sb + B_SM_QT + warp * 2048 + (i >> 1) * 1024 + lane * 32 + ((rank ^ fr ^ (lane >> 2)) & 1) * 16;
        uint32_t y[4], q[4];
        ldsm4t(y, sb + (fr ? B_SM_S + (lane & 7) * (B_SCH - B_UCH) - (1 - rank) * 2048 : B_SM_U) + swz64((lane & 7) * B_UCH + row * 64 + (lane >> 3) * 16));
        ldsm4(q, qa);
        stsm4(qa, bf16_mul(q[0], y[0]), bf16_mul(q[1], y[1]), bf16_mul(q[2], y[2]), bf16_mul(q[3], y[3]));
    }
    fence_async();
    __syncwarp();
    if (lane == 0) {
        asm volatile("cp.async.bulk.tensor.2d.global.shared::cta.bulk_group.L2::cache_hint [%0, {%2, %3}], [%1], %4;"
                     ::"l"(&mapO), "r"(sb + B_SM_QT + warp * 2048), "r"(DM + c16), "r"(t0 + warp * 64), "l"(EF(4)) : "memory");
        asm volatile("cp.async.bulk.commit_group;" ::: "memory");
    }
    if (SENT_AT == 0) sentinels();
    if (warp == 0) SP2(10);
    if (lane == 0) asm volatile("cp.async.bulk.wait_group.read 0;" ::: "memory");
    __syncwarp();
    if (warp == 0) SP2(11);
    asm volatile("barrier.cluster.wait.aligned;" ::: "memory");
    SP(7);
    KT_END(1);
}

typedef CUresult (*EncodeFn)(CUtensorMap*, CUtensorMapDataType, cuuint32_t, void*, const cuuint64_t*, const cuuint64_t*, const cuuint32_t*,
                             const cuuint32_t*, CUtensorMapInterleave, CUtensorMapSwizzle, CUtensorMapL2promotion, CUtensorMapFloatOOBfill);

static void make_map(EncodeFn fn, CUtensorMap* m, const void* ptr, uint64_t inner, uint64_t outer, uint32_t box_in, uint32_t box_out,
                     CUtensorMapL2promotion promo = CU_TENSOR_MAP_L2_PROMOTION_L2_256B) {
    cuuint64_t dims[2] = {inner, outer};
    cuuint64_t strides[1] = {inner * 2};
    cuuint32_t box[2] = {box_in, box_out};
    cuuint32_t es[2] = {1, 1};
    fn(m, CU_TENSOR_MAP_DATA_TYPE_BFLOAT16, 2, const_cast<void*>(ptr), dims, strides, box, es, CU_TENSOR_MAP_INTERLEAVE_NONE,
       CU_TENSOR_MAP_SWIZZLE_128B, promo, CU_TENSOR_MAP_FLOAT_OOB_FILL_NONE);
}

#define G2_ST 7
#define PROMO_W CU_TENSOR_MAP_L2_PROMOTION_L2_256B
#define PROMO_O CU_TENSOR_MAP_L2_PROMOTION_L2_256B
#define SSM_PROMO CU_TENSOR_MAP_L2_PROMOTION_NONE
extern "C" void kernel_launch(void* const* d_in, const int* in_sizes, int n_in, void* d_out, int out_size) {
    const bf16* x = (const bf16*)d_in[0];
    const bf16* mem0 = (const bf16*)d_in[1];
    const bf16* Wq = (const bf16*)d_in[2];
    const bf16* Wk = (const bf16*)d_in[3];
    const bf16* Wv = (const bf16*)d_in[4];
    const bf16* Wo = (const bf16*)d_in[5];
    const bf16* Bq = (const bf16*)d_in[7];
    const bf16* Bk = (const bf16*)d_in[8];
    const bf16* Bv = (const bf16*)d_in[9];
    const bf16* Bsh = (const bf16*)d_in[10];
    const bf16* Bssm = (const bf16*)d_in[11];
    const bf16* BD = (const bf16*)d_in[12];
    bf16* out = (bf16*)d_out;

    static bool init = false;
    static EncodeFn enc = nullptr;
    static void *p_tok, *p_ox, *p_mbox;
    static int nclusters = 64;
    if (!init) {
        cudaDriverEntryPointQueryResult qr;
        cudaGetDriverEntryPoint("cuTensorMapEncodeTiled", (void**)&enc, cudaEnableDefault, &qr);
        cudaGetSymbolAddress(&p_tok, g_tok);
        cudaGetSymbolAddress(&p_ox, g_ox);
        cudaGetSymbolAddress(&p_mbox, g_mbox);
        cudaFuncSetAttribute(proj_kernel<96, G2_ST>, cudaFuncAttributeMaxDynamicSharedMemorySize, PROJ_SMEM);
        cudaFuncSetAttribute(proj_kernel<128, 7>, cudaFuncAttributeMaxDynamicSharedMemorySize, PROJ_SMEM);
        cudaFuncSetAttribute(chain_kernel, cudaFuncAttributeMaxDynamicSharedMemorySize, CHAIN_SMEM);
        cudaFuncSetAttribute(ssm_kernel, cudaFuncAttributeMaxDynamicSharedMemorySize, B_SMEM);
        cudaLaunchConfig_t cfg = {};
        cfg.gridDim = dim3(132); cfg.blockDim = dim3(384); cfg.dynamicSmemBytes = CHAIN_SMEM;
        cudaLaunchAttribute at[1];
        at[0].id = cudaLaunchAttributeClusterDimension; at[0].val.clusterDim.x = 2; at[0].val.clusterDim.y = 1; at[0].val.clusterDim.z = 1;
        cfg.attrs = at; cfg.numAttrs = 1;
        int n = 0;
        if (cudaOccupancyMaxActiveClusters(&n, chain_kernel, &cfg) == cudaSuccess && n > 64) nclusters = n < 66 ? n : 66;
        (void)cudaGetLastError();
        init = true;
    }
    char* mbox = (char*)(((uintptr_t)p_mbox + 2 * WIN - 1) & ~(uintptr_t)(2 * WIN - 1));
    CUtensorMap mX, mT32, mT16, mTQ, mKV, mWq, mWk, mWv, mWoC, mWo, mOxE, mOutE, mOx, mOut;
    {
        cuuint64_t dims[3] = {64, S_LEN, DM / 64};
        cuuint64_t strides[2] = {DM * 2, 128};
        cuuint32_t box[3] = {64, 32, 4};
        cuuint32_t es[3] = {1, 1, 1};
        enc(&mX, CU_TENSOR_MAP_DATA_TYPE_BFLOAT16, 3, const_cast<bf16*>(x), dims, strides, box, es, CU_TENSOR_MAP_INTERLEAVE_NONE,
            CU_TENSOR_MAP_SWIZZLE_128B, CU_TENSOR_MAP_L2_PROMOTION_L2_256B, CU_TENSOR_MAP_FLOAT_OOB_FILL_NONE);
    }
    make_map(enc, &mT32, p_tok, DH, 4 * NH * 3 * SEG, 64, 32, CU_TENSOR_MAP_L2_PROMOTION_L2_128B);
    make_map(enc, &mT16, p_tok, DH, 4 * NH * 3 * SEG, 64, 16, CU_TENSOR_MAP_L2_PROMOTION_L2_128B);
    {
        cuuint64_t dims[2] = {512, 4 * NH * 12};
        cuuint64_t strides[1] = {2048};
        cuuint32_t box[2] = {256, 4};
        cuuint32_t es[2] = {1, 1};
        enc(&mTQ, CU_TENSOR_MAP_DATA_TYPE_UINT32, 2, p_tok, dims, strides, box, es, CU_TENSOR_MAP_INTERLEAVE_NONE,
            CU_TENSOR_MAP_SWIZZLE_NONE, CU_TENSOR_MAP_L2_PROMOTION_L2_128B, CU_TENSOR_MAP_FLOAT_OOB_FILL_NONE);
    }
    {
        cuuint64_t dims[3] = {64, 4 * NH * 3 * SEG, 2};
        cuuint64_t strides[2] = {DH * 2, 128};
        cuuint32_t box[3] = {64, 32, 2};
        cuuint32_t es[3] = {1, 1, 1};
        enc(&mKV, CU_TENSOR_MAP_DATA_TYPE_BFLOAT16, 3, p_tok, dims, strides, box, es, CU_TENSOR_MAP_INTERLEAVE_NONE,
            CU_TENSOR_MAP_SWIZZLE_128B, CU_TENSOR_MAP_L2_PROMOTION_L2_128B, CU_TENSOR_MAP_FLOAT_OOB_FILL_NONE);
    }
    make_map(enc, &mWq, Wq, HD, DM, 64, 16, CU_TENSOR_MAP_L2_PROMOTION_L2_128B);
    make_map(enc, &mWk, Wk, HD, DM, 64, 16, CU_TENSOR_MAP_L2_PROMOTION_L2_128B);
    make_map(enc, &mWv, Wv, HD, DM, 64, 16, CU_TENSOR_MAP_L2_PROMOTION_L2_128B);
    make_map(enc, &mWoC, Wo, DM, HD, 64, PRO3 ? 16 : 128, CU_TENSOR_MAP_L2_PROMOTION_L2_128B);
    const bool early = nclusters >= 66;
    make_map(enc, &mWo, Wo, DM, HD, 64, 64, PROMO_W);
    make_map(enc, &mOxE, p_ox, HD, S_LEN, 64, EARLY_NT / 2);
    make_map(enc, &mOutE, out, OUT_LD, S_LEN, 64, EARLY_NT);
    make_map(enc, &mOx, p_ox, HD, S_LEN, 64, (early ? 96 : 128) >> FIN_SO, PROMO_O);
    make_map(enc, &mOut, out, OUT_LD, S_LEN, 64, early ? 96 : 128);

    CUtensorMap mB[4];
    for (int i = 0; i < 4; i++) {
        cuuint64_t dims[2] = {(cuuint64_t)(i < 3 ? DM : OUT_LD), S_LEN};
        cuuint64_t strides[1] = {dims[0] * 2};
        cuuint32_t box[2] = {16, i == 0 ? 136u : i < 3 ? 128u : 64u};
        cuuint32_t es[2] = {1, 1};
        enc(&mB[i], CU_TENSOR_MAP_DATA_TYPE_BFLOAT16, 2, const_cast<bf16*>(i == 0 ? Bk : i == 1 ? Bv : i == 2 ? Bq : out), dims, strides, box, es,
            CU_TENSOR_MAP_INTERLEAVE_NONE, CU_TENSOR_MAP_SWIZZLE_32B, SSM_PROMO, CU_TENSOR_MAP_FLOAT_OOB_FILL_NONE);
    }
    cudaStream_t st = cudaStreamPerThread;
    const ChainInputs ci = {{(const char*)Wv, (const char*)Wk, (const char*)Wq, (const char*)Wo}, (const char*)x, (const char*)mem0};
    ssm_kernel<<<132, 576, B_SMEM, st>>>(mB[0], mB[1], mB[2], mB[3], Bsh, Bssm, BD, mbox, ci, out);
    cudaLaunchAttribute pdl[1];
    pdl[0].id = cudaLaunchAttributeProgrammaticStreamSerialization; pdl[0].val.programmaticStreamSerializationAllowed = 1;
    cudaLaunchConfig_t lc = {};
    lc.stream = st; lc.attrs = pdl;
    lc.gridDim = dim3(2 * nclusters); lc.blockDim = dim3(384); lc.dynamicSmemBytes = CHAIN_SMEM; lc.numAttrs = PDL & 1;
    cudaLaunchKernelEx(&lc, chain_kernel, mX, mT32, mT16, mTQ, mKV, mWq, mWk, mWv, mWoC, mem0, mbox);
    lc.gridDim = dim3(2 * nclusters); lc.blockDim = dim3(PROJ_THREADS); lc.dynamicSmemBytes = PROJ_SMEM; lc.numAttrs = (PDL >> 1) & 1;
    cudaLaunchKernelEx(&lc, early ? proj_kernel<96, G2_ST> : proj_kernel<128, 7>, mWo, mOx, mOut, mOxE, mOutE);
}
```

```cpp
#include <cuda_runtime.h>
#include <cuda_bf16.h>
#include <cuda.h>
#include <stdint.h>
#include <type_traits>

typedef __nv_bfloat16 bf16;

constexpr int S_LEN = 2048, DM = 1024, NH = 32, DH = 128, NSEG = 64, SEG = 32;
constexpr int HD = NH * DH;
constexpr int OUT_LD = 2048;
constexpr unsigned SENT = 0xFFFFFFFFu;

__device__ bf16 g_tok[4 * NH * 3 * SEG * DH];
__device__ bf16 g_ox[(size_t)S_LEN * HD];
__device__ uint4 g_mbox[4 * 131072];
__device__ unsigned g_xflag[128];
__device__ unsigned g_reg[4];
__device__ __align__(16) unsigned g_cls[256];
__device__ unsigned g_err;
constexpr uint32_t WIN = 2u << 20;
__host__ __device__ constexpr uint32_t page_off(uint32_t idx, uint32_t c) {
    return ((idx & 1) << 13) | ((idx >> 1) << 16) | (((c ^ idx ^ (idx >> 1) ^ (idx >> 2) ^ (idx >> 4)) & 1) << 12);
}
#define STAT(i, c) (void)(c)
#define EARLY_ROLE 1
#define PDL 3

__device__ __forceinline__ void launch_dependents() { asm volatile("griddepcontrol.launch_dependents;" ::: "memory"); }
__device__ __forceinline__ void wait_prerequisites() { asm volatile("griddepcontrol.wait;" ::: "memory"); }
__device__ __forceinline__ void prefetch_map(const CUtensorMap* m) { asm volatile("prefetch.tensormap [%0];" ::"l"(m) : "memory"); }
#define KT_MARK(k)
#define KT_START(k)
#define KT_END(k)

__device__ __forceinline__ uint32_t smem_u32(const void* p) { return (uint32_t)__cvta_generic_to_shared(p); }
__device__ __forceinline__ void ldsm4(uint32_t& r0, uint32_t& r1, uint32_t& r2, uint32_t& r3, uint32_t a) {
    asm volatile("ldmatrix.sync.aligned.m8n8.x4.shared.b16 {%0,%1,%2,%3}, [%4];" : "=r"(r0), "=r"(r1), "=r"(r2), "=r"(r3) : "r"(a) : "memory");
}
__device__ __forceinline__ void ldsm4t(uint32_t& r0, uint32_t& r1, uint32_t& r2, uint32_t& r3, uint32_t a) {
    asm volatile("ldmatrix.sync.aligned.m8n8.x4.trans.shared.b16 {%0,%1,%2,%3}, [%4];" : "=r"(r0), "=r"(r1), "=r"(r2), "=r"(r3) : "r"(a) : "memory");
}
__device__ __forceinline__ void ldsm2(uint32_t& r0, uint32_t& r1, uint32_t a) {
    asm volatile("ldmatrix.sync.aligned.m8n8.x2.shared.b16 {%0,%1}, [%2];" : "=r"(r0), "=r"(r1) : "r"(a) : "memory");
}
__device__ __forceinline__ void stg128(void* p, uint4 v) {
    asm volatile("st.global.v4.u32 [%0], {%1,%2,%3,%4};" ::"l"(p), "r"(v.x), "r"(v.y), "r"(v.z), "r"(v.w) : "memory");
}
__device__ __forceinline__ void stsm4(uint32_t a, uint32_t r0, uint32_t r1, uint32_t r2, uint32_t r3) {
    asm volatile("stmatrix.sync.aligned.m8n8.x4.shared.b16 [%0], {%1,%2,%3,%4};" ::"r"(a), "r"(r0), "r"(r1), "r"(r2), "r"(r3) : "memory");
}
__device__ __forceinline__ void mma16816(float (&d)[4], uint32_t a0, uint32_t a1, uint32_t a2, uint32_t a3, uint32_t b0, uint32_t b1) {
    asm("mma.sync.aligned.m16n8k16.row.col.f32.bf16.bf16.f32 {%0,%1,%2,%3},{%4,%5,%6,%7},{%8,%9},{%0,%1,%2,%3};"
                 : "+f"(d[0]), "+f"(d[1]), "+f"(d[2]), "+f"(d[3])
                 : "r"(a0), "r"(a1), "r"(a2), "r"(a3), "r"(b0), "r"(b1));
}
__device__ __forceinline__ void mma1688(float (&d)[4], uint32_t a0, uint32_t a1, uint32_t b0) {
    asm("mma.sync.aligned.m16n8k8.row.col.f32.bf16.bf16.f32 {%0,%1,%2,%3},{%4,%5},{%6},{%0,%1,%2,%3};"
        : "+f"(d[0]), "+f"(d[1]), "+f"(d[2]), "+f"(d[3]) : "r"(a0), "r"(a1), "r"(b0));
}
__device__ __forceinline__ uint32_t movmat(uint32_t a) {
    uint32_t d;
    asm volatile("movmatrix.sync.aligned.m8n8.trans.b16 %0, %1;" : "=r"(d) : "r"(a));
    return d;
}
__device__ __forceinline__ uint32_t pack_bf16(float lo, float hi) {
    uint32_t r;
    asm("cvt.rn.bf16x2.f32 %0, %1, %2;" : "=r"(r) : "f"(hi), "f"(lo));
    return r;
}
__device__ __forceinline__ uint32_t bf16_mul(uint32_t a, uint32_t b) {
    uint32_t d;
    asm("mul.rn.bf16x2 %0, %1, %2;" : "=r"(d) : "r"(a), "r"(b));
    return d;
}
__device__ __forceinline__ uint32_t bf16_add(uint32_t a, uint32_t b) {
    uint32_t d;
    asm("add.rn.bf16x2 %0, %1, %2;" : "=r"(d) : "r"(a), "r"(b));
    return d;
}

__device__ __forceinline__ float bf16_round(float x) { return __bfloat162float(__float2bfloat16_rn(x)); }
__device__ __forceinline__ float bf_lo(uint32_t w) { return __uint_as_float(w << 16); }
__device__ __forceinline__ float bf_hi(uint32_t w) { return __uint_as_float(w & 0xFFFF0000u); }
__device__ __forceinline__ void bar_sync(int id, int n) { asm volatile("bar.sync %0, %1;" ::"r"(id), "r"(n) : "memory"); }
__device__ __forceinline__ void bar_sync_keep(int id, int n, uint32_t a, uint32_t b) {
    asm volatile("bar.sync %0, %1; // %2 %3" ::"r"(id), "r"(n), "r"(a), "r"(b) : "memory");
}
__device__ __forceinline__ bool bar_red_or(int id, int n, bool p) {
    uint32_t r;
    asm volatile("{.reg .pred p, q; setp.ne.u32 p, %3, 0; bar.red.or.pred q, %1, %2, p; selp.u32 %0, 1, 0, q;}" : "=r"(r) : "r"(id), "r"(n), "r"((uint32_t)p) : "memory");
    return r != 0;
}
__device__ __forceinline__ void bar_arrive(int id, int n) { asm volatile("bar.arrive %0, %1;" ::"r"(id), "r"(n) : "memory"); }
__device__ __forceinline__ void cp_async16(uint32_t dst, const void* src) {
    asm volatile("cp.async.cg.shared.global [%0], [%1], 16;" ::"r"(dst), "l"(src) : "memory");
}
__device__ __forceinline__ void cp_commit() { asm volatile("cp.async.commit_group;" ::: "memory"); }
template <int N> __device__ __forceinline__ void cp_wait() { asm volatile("cp.async.wait_group %0;" ::"n"(N) : "memory"); }
__device__ __forceinline__ uint4 ld_relaxed_v4(const void* p) {
    uint4 v;
    asm volatile("ld.relaxed.gpu.global.v4.u32 {%0,%1,%2,%3}, [%4];" : "=r"(v.x), "=r"(v.y), "=r"(v.z), "=r"(v.w) : "l"(p) : "memory");
    return v;
}
__device__ __forceinline__ void st_relaxed_u32(void* p, uint32_t v) { asm volatile("st.relaxed.gpu.global.u32 [%0], %1;" ::"l"(p), "r"(v) : "memory"); }
__device__ __forceinline__ void st_relaxed_v2(void* p, uint32_t a, uint32_t b) {
    asm volatile("st.relaxed.gpu.global.v2.u32 [%0], {%1,%2};" ::"l"(p), "r"(a), "r"(b) : "memory");
}
__device__ __forceinline__ void sts128(uint32_t a, uint4 v) {
    asm volatile("st.shared.v4.u32 [%0], {%1,%2,%3,%4};" ::"r"(a), "r"(v.x), "r"(v.y), "r"(v.z), "r"(v.w) : "memory");
}
__device__ __forceinline__ uint4 lds128(uint32_t a) {
    uint4 v;
    asm volatile("ld.shared.v4.u32 {%0,%1,%2,%3}, [%4];" : "=r"(v.x), "=r"(v.y), "=r"(v.z), "=r"(v.w) : "r"(a) : "memory");
    return v;
}
__device__ __forceinline__ void sts32(uint32_t a, uint32_t v) { asm volatile("st.shared.u32 [%0], %1;" ::"r"(a), "r"(v) : "memory"); }
__device__ __forceinline__ uint32_t lds32(uint32_t a) {
    uint32_t v;
    asm volatile("ld.shared.u32 %0, [%1];" : "=r"(v) : "r"(a) : "memory");
    return v;
}
__device__ __forceinline__ void mbar_init(uint32_t a, uint32_t c) { asm volatile("mbarrier.init.shared::cta.b64 [%0], %1;" ::"r"(a), "r"(c) : "memory"); }
__device__ __forceinline__ void mbar_expect_tx(uint32_t a, uint32_t bytes) {
    asm volatile("mbarrier.arrive.expect_tx.shared::cta.b64 _, [%0], %1;" ::"r"(a), "r"(bytes) : "memory");
}
__device__ __forceinline__ void mbar_arrive(uint32_t a) { asm volatile("mbarrier.arrive.shared::cta.b64 _, [%0];" ::"r"(a) : "memory"); }
__device__ __forceinline__ void mbar_wait(uint32_t a, uint32_t parity) {
    asm volatile("{.reg .pred p; .reg .u32 c;\n"
                 "mov.u32 c, 0;\n"
                 "MBW_LOOP:\n"
                 "add.u32 c, c, 1;\n"
                 "setp.gt.u32 p, c, 0x10000;\n"
                 "@!p mbarrier.try_wait.parity.shared::cta.b64 p, [%0], %1;\n"
                 "@!p bra.uni MBW_LOOP;}" ::"r"(a), "r"(parity) : "memory");
}
__device__ __forceinline__ void mbar_wait_w(uint32_t a, uint32_t parity) {
    asm volatile("{.reg .pred p; .reg .u32 c;\n"
                 "mov.u32 c, 0;\n"
                 "MBW_LOOP:\n"
                 "add.u32 c, c, 1;\n"
                 "setp.gt.u32 p, c, 0x10000;\n"
                 "@!p mbarrier.try_wait.parity.shared::cta.b64 p, [%0], %1;\n"
                 "vote.sync.all.pred p, p, 0xFFFFFFFF;\n"
                 "@!p bra.uni MBW_LOOP;}" ::"r"(a), "r"(parity) : "memory");
}
__device__ __forceinline__ void mbar_expect_tx_if0(uint32_t sel, uint32_t a, uint32_t bytes) {
    asm volatile("{.reg .pred p; setp.eq.u32 p, %2, 0; @p mbarrier.arrive.expect_tx.shared::cta.b64 _, [%0], %1;}" ::"r"(a), "r"(bytes), "r"(sel) : "memory");
}
__device__ __forceinline__ void mbar_arrive_if0(uint32_t sel, uint32_t a) {
    asm volatile("{.reg .pred p; setp.eq.u32 p, %1, 0; @p mbarrier.arrive.shared::cta.b64 _, [%0];}" ::"r"(a), "r"(sel) : "memory");
}
__device__ __forceinline__ void bulk_load(uint32_t dst, const void* src, uint32_t bytes, uint32_t bar) {
    asm volatile("cp.async.bulk.shared::cluster.global.mbarrier::complete_tx::bytes [%0], [%1], %2, [%3];" ::"r"(dst), "l"(src), "r"(bytes), "r"(bar) : "memory");
}
__device__ __forceinline__ void tma_load_2d(uint32_t dst, const CUtensorMap* map, int c0, int c1, uint32_t bar) {
    asm volatile("cp.async.bulk.tensor.2d.shared::cluster.global.mbarrier::complete_tx::bytes [%0], [%1, {%3, %4}], [%2];"
                 ::"r"(dst), "l"(map), "r"(bar), "r"(c0), "r"(c1) : "memory");
}
__device__ __forceinline__ void tma_load_2d_both(uint32_t dst, const CUtensorMap* map, int c0, int c1, uint32_t bar) {
    asm volatile("cp.async.bulk.tensor.2d.shared::cluster.global.mbarrier::complete_tx::bytes.multicast::cluster [%0], [%1, {%3, %4}], [%2], %5;"
                 ::"r"(dst), "l"(map), "r"(bar), "r"(c0), "r"(c1), "h"((uint16_t)3) : "memory");
}
__device__ __forceinline__ uint64_t policy_evict_first() {
    uint64_t p;
    asm("createpolicy.fractional.L2::evict_first.b64 %0, 1.0;" : "=l"(p));
    return p;
}
__device__ __forceinline__ uint64_t policy_evict_normal() {
    uint64_t p;
    asm("createpolicy.fractional.L2::evict_normal.b64 %0, 1.0;" : "=l"(p));
    return p;
}
__device__ __forceinline__ void tma_load_2d(uint32_t dst, const CUtensorMap* map, int c0, int c1, uint32_t bar, uint64_t pol) {
    asm volatile("cp.async.bulk.tensor.2d.shared::cluster.global.mbarrier::complete_tx::bytes.L2::cache_hint [%0], [%1, {%3, %4}], [%2], %5;"
                 ::"r"(dst), "l"(map), "r"(bar), "r"(c0), "r"(c1), "l"(pol) : "memory");
}
__device__ __forceinline__ uint4 ldg128(const void* p, uint64_t pol) {
    uint4 v;
    asm("ld.global.nc.L2::cache_hint.v4.u32 {%0,%1,%2,%3}, [%4], %5;" : "=r"(v.x), "=r"(v.y), "=r"(v.z), "=r"(v.w) : "l"(p), "l"(pol));
    return v;
}
__device__ __forceinline__ void stg128(void* p, uint4 v, uint64_t pol) {
    asm volatile("st.global.L2::cache_hint.v4.u32 [%0], {%1,%2,%3,%4}, %5;" ::"l"(p), "r"(v.x), "r"(v.y), "r"(v.z), "r"(v.w), "l"(pol) : "memory");
}
__device__ __forceinline__ void tma_store_2d(const CUtensorMap* map, uint32_t src, int c0, int c1) {
    asm volatile("cp.async.bulk.tensor.2d.global.shared::cta.bulk_group [%0, {%2, %3}], [%1];" ::"l"(map), "r"(src), "r"(c0), "r"(c1) : "memory");
}
__device__ __forceinline__ char* make_ptr(uint32_t lo, uint32_t hi) {
    uint64_t p;
    asm("mov.b64 %0, {%1, %2};" : "=l"(p) : "r"(lo), "r"(hi));
    return reinterpret_cast<char*>(p);
}
__device__ __forceinline__ uint64_t make_desc(uint32_t saddr, uint32_t lbo, uint32_t sbo) {
    return (uint64_t)((saddr & 0x3FFFF) >> 4) | ((uint64_t)((lbo >> 4) & 0x3FFF) << 16) | ((uint64_t)((sbo >> 4) & 0x3FFF) << 32) | ((uint64_t)1 << 62);
}
__device__ __forceinline__ void wg_fence() { asm volatile("wgmma.fence.sync.aligned;" ::: "memory"); }
__device__ __forceinline__ void wg_commit() { asm volatile("wgmma.commit_group.sync.aligned;" ::: "memory"); }
template <int N> __device__ __forceinline__ void wg_wait() { asm volatile("wgmma.wait_group.sync.aligned %0;" ::"n"(N) : "memory"); }

#define R4(b) "+f"(d[b + 0]), "+f"(d[b + 1]), "+f"(d[b + 2]), "+f"(d[b + 3])
#define R16(b) R4(b), R4(b + 4), R4(b + 8), R4(b + 12)
template <int N> __device__ __forceinline__ void wgmma_proj(float (&d)[N / 2], uint64_t da, uint64_t db) {
    if constexpr (N == 96)
        asm volatile("wgmma.mma_async.sync.aligned.m64n96k16.f32.bf16.bf16 {"
            "%0,%1,%2,%3,%4,%5,%6,%7,%8,%9,%10,%11,%12,%13,%14,%15,%16,%17,%18,%19,%20,%21,%22,%23,%24,%25,%26,%27,%28,%29,%30,%31,%32,%33,%34,%35,%36,%37,%38,%39,"
            "%40,%41,%42,%43,%44,%45,%46,%47"
            "}, %48, %49, 1, 1, 1, 1, 0;" : R16(0), R16(16), R16(32) : "l"(da), "l"(db));
    if constexpr (N == 128)
        asm volatile("wgmma.mma_async.sync.aligned.m64n128k16.f32.bf16.bf16 {"
            "%0,%1,%2,%3,%4,%5,%6,%7,%8,%9,%10,%11,%12,%13,%14,%15,%16,%17,%18,%19,%20,%21,%22,%23,%24,%25,%26,%27,%28,%29,%30,%31,%32,%33,%34,%35,%36,%37,%38,%39,"
            "%40,%41,%42,%43,%44,%45,%46,%47,%48,%49,%50,%51,%52,%53,%54,%55,%56,%57,%58,%59,%60,%61,%62,%63"
            "}, %64, %65, 1, 1, 1, 1, 0;" : R16(0), R16(16), R16(32), R16(48) : "l"(da), "l"(db));
    if constexpr (N == 256)
        asm volatile("wgmma.mma_async.sync.aligned.m64n256k16.f32.bf16.bf16 {"
            "%0,%1,%2,%3,%4,%5,%6,%7,%8,%9,%10,%11,%12,%13,%14,%15,%16,%17,%18,%19,%20,%21,%22,%23,%24,%25,%26,%27,%28,%29,%30,%31,%32,%33,%34,%35,%36,%37,%38,%39,"
            "%40,%41,%42,%43,%44,%45,%46,%47,%48,%49,%50,%51,%52,%53,%54,%55,%56,%57,%58,%59,%60,%61,%62,%63,%64,%65,%66,%67,%68,%69,%70,%71,%72,%73,%74,%75,%76,%7"
            "7,%78,%79,%80,%81,%82,%83,%84,%85,%86,%87,%88,%89,%90,%91,%92,%93,%94,%95,%96,%97,%98,%99,%100,%101,%102,%103,%104,%105,%106,%107,%108,%109,%110,%111,"
            "%112,%113,%114,%115,%116,%117,%118,%119,%120,%121,%122,%123,%124,%125,%126,%127"
            "}, %128, %129, 1, 1, 1, 1, 0;" : R16(0), R16(16), R16(32), R16(48), R16(64), R16(80), R16(96), R16(112) : "l"(da), "l"(db));
}

__device__ __forceinline__ void wgmma_rs32(float (&d)[16], const uint32_t (&a)[4], uint64_t db, bool acc) {
    asm volatile(
        "{.reg .pred p; setp.ne.b32 p, %21, 0;\n"
        "wgmma.mma_async.sync.aligned.m64n32k16.f32.bf16.bf16 {%0,%1,%2,%3,%4,%5,%6,%7,%8,%9,%10,%11,%12,%13,%14,%15}, {%16,%17,%18,%19}, %20, p, 1, 1, 0;}"
        : R16(0) : "r"(a[0]), "r"(a[1]), "r"(a[2]), "r"(a[3]), "l"(db), "n"(1) );
}
__device__ __forceinline__ void wgmma_rs32_first(float (&d)[16], const uint32_t (&a)[4], uint64_t db) {
    asm volatile(
        "{.reg .pred p; setp.ne.b32 p, %21, 0;\n"
        "wgmma.mma_async.sync.aligned.m64n32k16.f32.bf16.bf16 {%0,%1,%2,%3,%4,%5,%6,%7,%8,%9,%10,%11,%12,%13,%14,%15}, {%16,%17,%18,%19}, %20, p, 1, 1, 0;}"
        : R16(0) : "r"(a[0]), "r"(a[1]), "r"(a[2]), "r"(a[3]), "l"(db), "n"(0) );
}
__device__ __forceinline__ void wgmma_ss32(float (&d)[16], uint64_t da, uint64_t db) {
    asm volatile(
        "wgmma.mma_async.sync.aligned.m64n32k16.f32.bf16.bf16 {%0,%1,%2,%3,%4,%5,%6,%7,%8,%9,%10,%11,%12,%13,%14,%15}, %16, %17, 1, 1, 1, 1, 0;"
        : R16(0) : "l"(da), "l"(db));
}
template <int OFF, int ACC> __device__ __forceinline__ void wgmma_rs32u(float (&d)[16], const uint32_t (&a)[4], uint32_t lo) {
    asm volatile(
        "{.reg .pred p; .reg .b32 l; .reg .b64 e; setp.ne.b32 p, %22, 0; add.u32 l, %20, %21; mov.b64 e, {l, 0x40000040};\n"
        "wgmma.mma_async.sync.aligned.m64n32k16.f32.bf16.bf16 {%0,%1,%2,%3,%4,%5,%6,%7,%8,%9,%10,%11,%12,%13,%14,%15}, {%16,%17,%18,%19}, e, p, 1, 1, 0;}"
        : R16(0) : "r"(a[0]), "r"(a[1]), "r"(a[2]), "r"(a[3]), "r"(lo), "n"(OFF), "n"(ACC));
}
template <int OFF, int ACC> __device__ __forceinline__ void wgmma_ss32u(float (&d)[16], uint64_t da, uint32_t lo) {
    asm volatile(
        "{.reg .pred p; .reg .b32 l; .reg .b64 e; setp.ne.b32 p, %19, 0; add.u32 l, %17, %18; mov.b64 e, {l, 0x40000040};\n"
        "wgmma.mma_async.sync.aligned.m64n32k16.f32.bf16.bf16 {%0,%1,%2,%3,%4,%5,%6,%7,%8,%9,%10,%11,%12,%13,%14,%15}, %16, e, p, 1, 1, 1, 0;}"
        : R16(0) : "l"(da), "r"(lo), "n"(OFF), "n"(ACC));
}
template <int K0, int K1, class F> __device__ __forceinline__ void static_for(F f) {
    if constexpr (K0 < K1) { f(std::integral_constant<int, K0>()); static_for<K0 + 1, K1>(f); }
}
__device__ __forceinline__ void st_async4(uint32_t a, float x, float y, float z, float w, uint32_t bar) {
    asm volatile("st.async.weak.shared::cluster.mbarrier::complete_tx::bytes.v4.f32 [%0], {%1,%2,%3,%4}, [%5];" ::"r"(a), "f"(x), "f"(y), "f"(z), "f"(w), "r"(bar) : "memory");
}
__device__ __forceinline__ void st_async2(uint32_t a, float x, float y, uint32_t bar) {
    asm volatile("st.async.weak.shared::cluster.mbarrier::complete_tx::bytes.v2.f32 [%0], {%1,%2}, [%3];" ::"r"(a), "f"(x), "f"(y), "r"(bar) : "memory");
}
__device__ __forceinline__ void st_async1(uint32_t a, uint32_t x, uint32_t bar) {
    asm volatile("st.async.weak.shared::cluster.mbarrier::complete_tx::bytes.b32 [%0], %1, [%2];" ::"r"(a), "r"(x), "r"(bar) : "memory");
}
__device__ __forceinline__ uint32_t peer_addr(uint32_t a, uint32_t rank) {
    uint32_t r;
    asm("mapa.shared::cluster.u32 %0, %1, %2;" : "=r"(r) : "r"(a), "r"(rank));
    return r;
}
__device__ __forceinline__ void stsm4t(uint32_t a, uint32_t r0, uint32_t r1, uint32_t r2, uint32_t r3) {
    asm volatile("stmatrix.sync.aligned.m8n8.x4.trans.shared.b16 [%0], {%1,%2,%3,%4};" ::"r"(a), "r"(r0), "r"(r1), "r"(r2), "r"(r3) : "memory");
}
__device__ __forceinline__ void ldsm4t(uint32_t (&r)[4], uint32_t a) { ldsm4t(r[0], r[1], r[2], r[3], a); }
__device__ __forceinline__ void ldsm4(uint32_t (&r)[4], uint32_t a) { ldsm4(r[0], r[1], r[2], r[3], a); }
__device__ __forceinline__ void mma16816(float (&d)[4], const uint32_t (&a)[4], uint32_t b0, uint32_t b1) { mma16816(d, a[0], a[1], a[2], a[3], b0, b1); }
__device__ __forceinline__ void sched_fence(uint32_t v) {
    asm volatile("{.reg .pred p; setp.ne.u32 p, %0, 0xFFFFFFFF; vote.sync.all.pred p, p, 0xFFFFFFFF; @p bra.uni SF_OK; exit; SF_OK:}" ::"r"(v) : "memory");
}
__device__ __forceinline__ void mma16816v(float (&d)[4], const uint32_t (&a)[4], uint32_t b0, uint32_t b1) {
    asm volatile("mma.sync.aligned.m16n8k16.row.col.f32.bf16.bf16.f32 {%0,%1,%2,%3},{%4,%5,%6,%7},{%8,%9},{%0,%1,%2,%3};"
                 : "+f"(d[0]), "+f"(d[1]), "+f"(d[2]), "+f"(d[3]) : "r"(a[0]), "r"(a[1]), "r"(a[2]), "r"(a[3]), "r"(b0), "r"(b1));
}
__device__ __forceinline__ uint32_t uniform(uint32_t v) { return __reduce_max_sync(~0u, v); }

#define WPRE 0
#define G2_X 0
#define G2_K 4
#define FIN_SO 0
#define PROJ_FAST 1
#define KROT 0
#define WFIRST 0
template <int NT, int STAGES> struct ProjCfg {
    static constexpr int STAGE_BYTES = 16384 + NT * 128;
    static constexpr int EPI = NT == 256 ? STAGES * STAGE_BYTES : 0;
    static constexpr int BARS = 229376 + (NT == 256 ? 192 : 0);
    static_assert(STAGES * STAGE_BYTES <= 229376 && EPI + NT * 256 <= 229376 && STAGES <= 12, "smem");
};
constexpr int PROJ_ROLE = 229376 + 384, PROJ_SMEM = PROJ_ROLE + 16;
__device__ __forceinline__ unsigned claim_pair(unsigned* reg) {
    unsigned smid, ncl = gridDim.x >> 1;
    asm volatile("mov.u32 %0, %%smid;" : "=r"(smid));
    uint2 m;
    for (int guard = 0; guard < 1024; guard++) {
        asm volatile("ld.relaxed.gpu.global.v2.u32 {%0, %1}, [%2];" : "=r"(m.x), "=r"(m.y) : "l"(g_cls + (smid & ~1u)) : "memory");
        if (m.x && m.y) break;
    }
    const unsigned r = __vminu2(m.x, m.y), c = (r & 0xFFFF) > (r >> 16);
    unsigned n = atomicAdd(reg, c ? 0x10000u : 1u);
    const unsigned i = c ? n >> 16 : n & 0xFFFF, order = ((n >> 16) + (n & 0xFFFF)) << 8;
    if (i < 32) return c * 32 + i + order;
    for (int guard = 0; guard < (1 << 20); guard++) {
        asm volatile("ld.relaxed.gpu.global.u32 %0, [%1];" : "=r"(n) : "l"(reg) : "memory");
        if ((n >> 16) + (n & 0xFFFF) >= ncl) break;
    }
    const unsigned k = (c ? n & 0xFFFF : n >> 16) + i - 32;
    return (k < 32 ? (c ^ 1) * 32 + k : 64) + order;
}
template <int NT, int STAGES> __device__ __forceinline__ void proj_init(uint32_t sb) {
    for (int i = 0; i < STAGES; i++) { mbar_init(sb + ProjCfg<NT, STAGES>::BARS + 8 * i, 1); mbar_init(sb + ProjCfg<NT, STAGES>::BARS + 8 * (STAGES + i), 16); }
    asm volatile("fence.mbarrier_init.release.cluster;" ::: "memory");
}
template <int NT, int STAGES, bool SHARE_O, class T, class R>
__device__ __forceinline__ void proj_tiles(uint32_t sb, int warp, uint32_t rank, int ntiles, const CUtensorMap* mapW, const CUtensorMap* mapO,
                                           const CUtensorMap* mapOut, T tile, R ready, int rot = 0) {
    using Cfg = ProjCfg<NT, STAGES>;
    const uint32_t bars = sb + Cfg::BARS;
    const int lane = threadIdx.x & 31;
    if (warp == 8) {
        int st = 0; uint32_t ph = 1;
        for (int i = 0; i < ntiles; i++) {
            int col, tok;
            tile(i, col, tok);
            constexpr bool PRE = WPRE && !SHARE_O;
            if (PRE && lane == 0)
                for (int kb = 0; kb < STAGES; kb++) {
                    mbar_expect_tx(bars + 8 * kb, Cfg::STAGE_BYTES);
                    tma_load_2d_both(sb + kb * Cfg::STAGE_BYTES + rank * 8192, mapW, col + rank * 64, kb * 64, bars + 8 * kb);
                }
            ready(i);
            if (lane == 0) {
                if (PRE) {
                    for (int kb = 0; kb < STAGES; kb++) tma_load_2d(sb + kb * Cfg::STAGE_BYTES + 16384, mapO, kb * 64, tok, bars + 8 * kb);
                    ph = 0;
                }
                for (int kb = PRE ? STAGES : 0; kb < HD / 64; kb++) {
                    mbar_wait(bars + 8 * (STAGES + st), ph);
                    const uint32_t full = bars + 8 * st, sa = sb + st * Cfg::STAGE_BYTES;
                    mbar_expect_tx(full, SHARE_O ? Cfg::STAGE_BYTES : G2_X == 1 ? 16384 : G2_X == 2 ? NT * 128 : Cfg::STAGE_BYTES);
                    if (SHARE_O) {
                        tma_load_2d(sa, mapW, col, kb * 64, full);
                        tma_load_2d(sa + 8192, mapW, col + 64, kb * 64, full);
                        tma_load_2d_both(sa + 16384 + rank * (NT * 64), mapO, kb * 64, tok + rank * (NT / 2), full);
                    } else {
                        const int k0 = ((kb + rot) & 63) * 64;
                        if (WFIRST) tma_load_2d_both(sa + rank * 8192, mapW, col + rank * 64, k0, full);
                        if (G2_X != 1) tma_load_2d(sa + 16384, mapO, k0, G2_X == 3 ? tok & 511 : tok, full);
                        if (!WFIRST && G2_X != 2) tma_load_2d_both(sa + rank * 8192, mapW, col + rank * 64, k0, full);
                    }
                    if (++st == STAGES) { st = 0; ph ^= 1; }
                }
            }
            __syncwarp();
        }
    } else if (warp < 8) {
        const int wg = warp >> 2;
        uint32_t peer_empty;
        asm volatile("mapa.shared::cluster.u32 %0, %1, %2;" : "=r"(peer_empty) : "r"(bars + 8 * STAGES), "r"(rank ^ 1));
        auto release = [&](int stg) {
            if (lane == 0) {
                mbar_arrive(bars + 8 * (STAGES + stg));
                asm volatile("mbarrier.arrive.shared::cluster.b64 _, [%0];" ::"r"(peer_empty + 8 * stg) : "memory");
            }
        };
        const uint32_t ew = sb + Cfg::EPI + wg * (NT * 128);
        int st = 0; uint32_t ph = 0;
        for (int i = 0; i < ntiles; i++) {
            int col, tok;
            tile(i, col, tok);
            float d[NT / 2];
#pragma unroll
            for (int r = 0; r < NT / 2; r++) d[r] = 0.f;
            int prev = -1;
            for (int kb = 0; kb < HD / 64; kb++) {
                mbar_wait(bars + 8 * st, ph);
                const uint32_t sa = sb + st * Cfg::STAGE_BYTES;
                const uint64_t da = make_desc(sa + wg * 8192, 16, 1024), db = make_desc(sa + 16384, 16, 1024);
                wg_fence();
#pragma unroll
                for (int k = 0; k < (NT == 256 ? 4 : G2_K); k++) wgmma_proj<NT>(d, da + k * 128, db + k * 2);
                wg_commit();
                if (prev >= 0) { wg_wait<1>(); release(prev); }
                prev = st;
                if (++st == STAGES) { st = 0; ph ^= 1; }
            }
            wg_wait<0>();
            release(prev);
            if ((warp & 3) == 0 && lane == 0) asm volatile("cp.async.bulk.wait_group.read 0;" ::: "memory");
            if (Cfg::EPI) bar_sync(1 + wg, 128); else bar_sync(3, 256);
            const uint32_t ea = ew + ((lane >> 4) * 8 + (lane & 7)) * 128 + ((((warp & 3) * 2 + ((lane >> 3) & 1)) ^ (lane & 7)) * 16);
#pragma unroll
            for (int r = 0; r < NT / 16; r++)
                stsm4t(ea + r * 2048, pack_bf16(d[8 * r], d[8 * r + 1]), pack_bf16(d[8 * r + 2], d[8 * r + 3]), pack_bf16(d[8 * r + 4], d[8 * r + 5]), pack_bf16(d[8 * r + 6], d[8 * r + 7]));
            asm volatile("fence.proxy.async.shared::cta;" ::: "memory");
            bar_sync(1 + wg, 128);
            if ((warp & 3) == 0 && lane == 0) {
                tma_store_2d(mapOut, ew, col + wg * 64, tok);
                asm volatile("cp.async.bulk.commit_group;" ::: "memory");
            }
        }
        if ((warp & 3) == 0 && lane == 0) asm volatile("cp.async.bulk.wait_group 0;" ::: "memory");
    }
    __syncwarp();
}
constexpr int EARLY_NT = 256, EARLY_STAGES = 3;
constexpr int PROJ_THREADS = 288;

template <int NT, int STAGES>
__global__ void __cluster_dims__(2, 1, 1) __launch_bounds__(PROJ_THREADS, 1)
proj_kernel(const __grid_constant__ CUtensorMap mapW, const __grid_constant__ CUtensorMap mapO, const __grid_constant__ CUtensorMap mapOut,
            const __grid_constant__ CUtensorMap mapOE, const __grid_constant__ CUtensorMap mapOutE) {
    KT_START(3);
    extern __shared__ __align__(1024) uint8_t smem_proj[];
    const uint32_t sb = smem_u32(smem_proj), role = sb + PROJ_ROLE;
    if (sb & 1023) __trap();
    const uint32_t rank = blockIdx.x & 1;
    const int warp = threadIdx.x >> 5;
    if (threadIdx.x == 0) {
        mbar_init(role + 8, 1);
        mbar_expect_tx(role + 8, 4);
        proj_init<NT, STAGES>(sb);
        proj_init<EARLY_NT, EARLY_STAGES>(sb);
    }
    if (threadIdx.x == 32) { prefetch_map(&mapO); prefetch_map(&mapW); prefetch_map(&mapOut); }
    __syncwarp();
    asm volatile("barrier.cluster.arrive.relaxed.aligned;" ::: "memory");
    unsigned claimed = 0;
    if (threadIdx.x == 256 && rank == 0) claimed = claim_pair(g_reg + 2);
    __syncwarp();
    asm volatile("barrier.cluster.wait.acquire.aligned;" ::: "memory");
    if (threadIdx.x == 256 && rank == 0) {
        st_async1(peer_addr(role, 1), claimed, peer_addr(role + 8, 1));
        st_async1(peer_addr(role, 0), claimed, peer_addr(role + 8, 0));
        if ((claimed >> 8) + 1 == gridDim.x >> 1) {
            g_reg[0] = 0;
            for (int i = 0; i < 64; i++) reinterpret_cast<uint4*>(g_cls)[i] = make_uint4(0, 0, 0, 0);
        }
    }
    __syncwarp();
    mbar_wait_w(role + 8, 0);
    const int p = lds32(role) & 255, order = lds32(role) >> 8;
    if (NT == 96 && order < 2) {
        proj_tiles<EARLY_NT, EARLY_STAGES, true>(sb, warp, rank, 4, &mapW, &mapOE, &mapOutE,
            [&](int i, int& col, int& tok) { col = ((i & 1) * 4 + order * 2 + rank) * 128; tok = (i >> 1) * EARLY_NT; },
            [&](int i) {
                const unsigned need = 8 * (i >> 1) + 8 + 3;
                for (int guard = 0; guard < (1 << 16); guard++) {
                    const uint4 f = ld_relaxed_v4(g_xflag + (threadIdx.x & 31) * 4);
                    if (__all_sync(~0u, min(min(f.x, f.y), min(f.z, f.w)) >= need)) break;
                    __nanosleep(1000);
                }
                asm volatile("fence.acq_rel.gpu; fence.proxy.async.global;" ::: "memory");
            });
        __syncthreads();
        asm volatile("barrier.cluster.arrive.relaxed.aligned; barrier.cluster.wait.aligned;" ::: "memory");
    }
    if (p >= 64) return;
    proj_tiles<NT, STAGES, false>(sb, warp, rank, 1, &mapW, &mapO, &mapOut,
                                  [&](int, int& col, int& tok) { col = (p & 7) * 128; tok = S_LEN - 16 * NT + ((p >> 3) * 2 + rank) * NT; },
                                  [&](int) { wait_prerequisites();
                                  }, KROT == 0 ? 0 : KROT == 1 ? (p & 7) * 8 : KROT == 2 ? (p >> 3) * 8 : KROT == 3 ? ((p & 7) + (p >> 3)) * 8 : (p >> 5) * 32);
    KT_END(3);
    asm volatile("barrier.cluster.arrive.relaxed; barrier.cluster.wait;" ::: "memory");
}

#define WO_RF1 6
constexpr int SM_KV = 0, KV_BYTES = 18432;
constexpr int SM_XT = 2 * KV_BYTES;
constexpr int SM_STG = SM_XT + 65536;
constexpr int SM_Z = SM_STG + 6144;
constexpr int SM_RT = SM_Z + 8192;
constexpr int SM_QKV = SM_RT + 12288;
constexpr int SM_R1 = SM_QKV + 6144;
constexpr int SM_R2 = SM_R1 + 2048;
constexpr int SM_R3 = SM_R2 + 1024;
constexpr int SM_O = SM_R3 + 2048;
constexpr int SM_S = SM_O + 2048;
constexpr int SM_INV = SM_S + 1536;
constexpr int SM_TO = SM_R3;
constexpr int SM_WORK_END = SM_S + 2048;
constexpr int STG_QK = 0, STG_V = 98304;
#define PRO2 1
#define PRO3 1
#define WO_IT 2
#define XP 0
__host__ __device__ constexpr int stg_wo(int r) { return r < 9 ? KV_BYTES + r * 2048 : r < 13 ? SM_QKV + (r - 9) * 2048 : SM_S; }
static_assert(WO_RF1 == 6 && SM_QKV % 1024 == 0 && SM_S % 1024 == 0 && SM_QKV + 8192 <= SM_TO, "staging of Wo");
__host__ __device__ constexpr int stg_qk(int t, int r) { return !PRO2 ? STG_QK + (t * 24 + r) * 2048 : t == 0 ? SM_XT + r * 2048 : r < SM_XT / 2048 ? r * 2048 : (r + 24) * 2048; }
constexpr int SM_WO1 = SM_WORK_END - WO_RF1 * 2048;
constexpr int STG_WO = SM_WO1 - 16384;
constexpr int SM_WQK = (SM_WO1 + 16384 > STG_V + 49152) ? SM_WO1 + 16384 : STG_V + 49152;
constexpr int SM_WV = SM_WQK + 32768;
constexpr int SM_WO2 = SM_WV + 16384;
constexpr int SM_BARS = SM_WO2 + 32768;
enum { MB_W0 = SM_BARS, MB_W1 = SM_BARS + 8, MB_W2 = SM_BARS + 16, MB_W3 = SM_BARS + 24, MB_XT = SM_BARS + 32  , MB_KV = SM_BARS + 48  ,
       MB_R3 = SM_BARS + 64, MB_R1 = SM_BARS + 72, MB_R2 = SM_BARS + 80, MB_RT0 = SM_BARS + 88, MB_RT1 = SM_BARS + 96, MB_FREE = SM_BARS + 104,
       MB_P = SM_BARS + 112, MB_V = SM_BARS + 120, MB_STG = SM_BARS + 128, MB_ROLE = SM_BARS + 136, MB_W4 = SM_BARS + 144, MB_W5 = SM_BARS + 152, SM_ROLE = SM_BARS + 160   };
constexpr int CHAIN_SMEM = SM_ROLE + 8;
static_assert(SM_WORK_END % 1024 == 0 && STG_WO >= STG_V, "work area");
static_assert(CHAIN_SMEM <= 232448 && WO_RF1 >= 6, "smem");

#define DLY_X 300
#define DLY_V 0
#define DLY_Y 290
#define DLY_Z 300
#define DLY_T 0
#define DLY_K 0
#define DLY_S 0
#define LATE_RD 1
#define TS_AT 5
#define TS_LATE 0
#define XB_EARLY 0
#define RT0_N 4
#define ORD0 2
#define ORD1 0
#define ORDV 0
#define RT_BF 2
__host__ __device__ constexpr int kstep(int ord, int i) { return ord == 0 ? i : ord == 1 ? (i + 24) % 32 : ord == 2 ? (i % 4 == 3 ? 24 + i / 4 : i / 4 * 3 + i % 4) : ord == 3 ? (i < 16 ? (i % 2 ? 24 + i / 2 : i / 2) : i - 8) : (i < 8 ? i : i < 16 ? i + 16 : i - 8); }
#define XT_FIRST 0
#define GV 1
#define NSV (GV ? 320 : 352)
#define Q3_AT 9
#define NA 7
#define NP2 6
#define P2_FENCE 0
#define SPLIT 8
#define TA0 16
#define SENT_EARLY 1
#define Y_CHAIN 1
#define EF_W 1
#define XFLIP 0
#define YFLIP 0
#define ZFLIP 1
#define OFENCE 2
#define REG_A 240
#define REG_B 216
#define REG_C (3 * 168 - REG_A - REG_B)

enum { BAR_Y, BAR_MEM, BAR_PUB, BAR_QK, BAR_S, BAR_O, BAR_SENT, BAR_COMM, BAR_PUBV, BAR_PV, BAR_PDONE, BAR_VP, BAR_ZP, BAR_PRO, BAR_O2, BAR_SV,
       BAR_V = BAR_PV, BAR_SENTC = BAR_PDONE, BAR_Q3 = BAR_PRO, BAR_INV = BAR_PRO, BAR_XT0 = BAR_Y };

__device__ __forceinline__ uint32_t umax4(const uint4& v) { return max(max(v.x, v.y), max(v.z, v.w)); }
__device__ __forceinline__ unsigned gtime() { unsigned t; asm volatile("mov.u32 %0, %%globaltimer_lo;" : "=r"(t)::"memory"); return t; }
__device__ __forceinline__ unsigned clock32() { unsigned t; asm volatile("mov.u32 %0, %%clock;" : "=r"(t)::"memory"); return t; }
__device__ __forceinline__ void spin_cycles(int d) {
    if (d > 0) { const unsigned c0 = clock32(); while (clock32() - c0 < (unsigned)d) {} }
}
__device__ __forceinline__ float ex2_approx(float x) { float y; asm("ex2.approx.ftz.f32 %0, %1;" : "=f"(y) : "f"(x)); return y; }
__device__ __forceinline__ float rcp_approx(float x) { float y; asm("rcp.approx.ftz.f32 %0, %1;" : "=f"(y) : "f"(x)); return y; }
__device__ __forceinline__ void st_sent(const void* p) { asm volatile("st.relaxed.gpu.global.v4.u32 [%0], {%1,%1,%1,%1};" ::"l"(p), "r"(SENT) : "memory"); }
#define POLL_LD(p, a, b, c, d, addr) "@" p " ld.relaxed.gpu.global.v4.u32 {" a "," b "," c "," d "}, [" addr "];\n"
#define POLL_CK(p, a, b, c, d) "max.u32 m, " a "," b "; max.u32 n, " c "," d "; max.u32 m, m, n; setp.eq.u32 " p ", m, 0xFFFFFFFF;\n"
#define POLL_IO(v) "+r"(v.x), "+r"(v.y), "+r"(v.z), "+r"(v.w)
__device__ __forceinline__ void poll_init(uint4& v) { v = make_uint4(SENT, SENT, SENT, SENT); asm volatile("" : POLL_IO(v)); }
__device__ __forceinline__ int poll2(uint4 (&v)[2], const char* a) {
    int c = 0;
    asm volatile("{.reg .pred p0, p1, p; .reg .u32 m, n;\n"
                 "setp.eq.u32 p0, %8, 0; setp.eq.u32 p1, %8, 0;\n"
                 "POLL_LOOP:\n"
                 POLL_LD("p0", "%0", "%1", "%2", "%3", "%9") POLL_LD("p1", "%4", "%5", "%6", "%7", "%9+512")
                 "add.u32 %8, %8, 1;\n"
                 POLL_CK("p0", "%0", "%1", "%2", "%3") POLL_CK("p1", "%4", "%5", "%6", "%7")
                 "or.pred p, p0, p1; setp.lt.and.u32 p, %8, 0x10000, p; vote.sync.any.pred p, p, 0xFFFFFFFF;\n"
                 "@p bra.uni POLL_LOOP;}" : POLL_IO(v[0]), POLL_IO(v[1]), "+r"(c) : "l"(a) : "memory");
    return c;
}
template <int ST> __device__ __forceinline__ int poll4(uint4 (&v)[4], const char* a) {
    int c = 0;
    asm volatile("{.reg .pred p0, p1, p2, p3, p; .reg .u32 m, n;\n"
                 "setp.eq.u32 p0, %16, 0; setp.eq.u32 p1, %16, 0; setp.eq.u32 p2, %16, 0; setp.eq.u32 p3, %16, 0;\n"
                 "POLL_LOOP:\n"
                 POLL_LD("p0", "%0", "%1", "%2", "%3", "%17") POLL_LD("p1", "%4", "%5", "%6", "%7", "%17+%18")
                 POLL_LD("p2", "%8", "%9", "%10", "%11", "%17+%19") POLL_LD("p3", "%12", "%13", "%14", "%15", "%17+%20")
                 "add.u32 %16, %16, 1;\n"
                 POLL_CK("p0", "%0", "%1", "%2", "%3") POLL_CK("p1", "%4", "%5", "%6", "%7") POLL_CK("p2", "%8", "%9", "%10", "%11") POLL_CK("p3", "%12", "%13", "%14", "%15")
                 "or.pred p, p0, p1; or.pred p, p, p2; or.pred p, p, p3; setp.lt.and.u32 p, %16, 0x10000, p; vote.sync.any.pred p, p, 0xFFFFFFFF;\n"
                 "@p bra.uni POLL_LOOP;}" : POLL_IO(v[0]), POLL_IO(v[1]), POLL_IO(v[2]), POLL_IO(v[3]), "+r"(c) : "l"(a), "n"(ST), "n"(2 * ST), "n"(3 * ST) : "memory");
    return c;
}
__device__ __forceinline__ uint32_t add_bf16x2(uint32_t a, uint32_t b) { uint32_t r; asm("add.rn.bf16x2 %0, %1, %2;" : "=r"(r) : "r"(a), "r"(b)); return r; }
__device__ __forceinline__ uint32_t max_bf16x2(uint32_t a, uint32_t b) { uint32_t r; asm("max.bf16x2 %0, %1, %2;" : "=r"(r) : "r"(a), "r"(b)); return r; }
template <class F> __device__ __forceinline__ void softmax40(uint32_t (&pw)[6], uint32_t sa, F mid) {
    const float LOG2E = 1.4426950408889634f;
    uint32_t w[5];
    float e[10];
#pragma unroll
    for (int i = 0; i < 5; i++) w[i] = lds32(sa + i * 128);
    uint32_t m = max_bf16x2(max_bf16x2(max_bf16x2(w[0], w[1]), max_bf16x2(w[2], w[3])), w[4]);
    m = max_bf16x2(m, __shfl_xor_sync(~0u, m, 1));
    m = max_bf16x2(m, __shfl_xor_sync(~0u, m, 2));
    const float mb2 = fmaxf(bf_lo(m), bf_hi(m)) * LOG2E;
#pragma unroll
    for (int i = 0; i < 5; i++) {
        e[2 * i] = ex2_approx(fmaf(bf_lo(w[i]), LOG2E, -mb2));
        e[2 * i + 1] = ex2_approx(fmaf(bf_hi(w[i]), LOG2E, -mb2));
    }
    mid();
#pragma unroll
    for (int i = 0; i < 5; i++) pw[i] = pack_bf16(e[2 * i], e[2 * i + 1]);
    const float sum = (((e[0] + e[1]) + (e[2] + e[3])) + ((e[4] + e[5]) + (e[6] + e[7]))) + (e[8] + e[9]);
    const float hi = bf_hi(__float_as_uint(sum));
    pw[5] = pack_bf16(sum - hi, hi);
}
template <bool NORM, class F> __device__ __forceinline__ void pv32(uint32_t (&w)[4], float (&inv)[2], const uint32_t (&va)[2][2][4], const uint32_t (&vm)[4], const uint32_t (&pw)[6], F mid) {
    float o[2][3][4], t[4] = {0.f, 0.f, 0.f, 0.f};
#pragma unroll
    for (int i = 0; i < 3; i++)
#pragma unroll
        for (int m = 0; m < 2; m++) {
            o[m][i][0] = o[m][i][1] = o[m][i][2] = o[m][i][3] = 0.f;
            if (i < 2) mma16816(o[m][i], va[m][i & 1], pw[2 * i], pw[2 * i + 1]);
            else mma1688(o[m][i], vm[2 * m], vm[2 * m + 1], pw[4]);
        }
    mma1688(t, 0x3F803F80u, 0x3F803F80u, pw[5]);
    mid();
    if (NORM) { inv[0] = rcp_approx(t[0]); inv[1] = rcp_approx(t[1]); }
#pragma unroll
    for (int i = 0; i < 4; i++) {
        const float a = (o[i >> 1][0][2 * (i & 1)] + o[i >> 1][1][2 * (i & 1)]) + o[i >> 1][2][2 * (i & 1)];
        const float b = (o[i >> 1][0][2 * (i & 1) + 1] + o[i >> 1][1][2 * (i & 1) + 1]) + o[i >> 1][2][2 * (i & 1) + 1];
        w[i] = NORM ? pack_bf16(a * inv[0], b * inv[1]) : pack_bf16(a, b);
    }
    if (!NORM) { inv[0] = t[0]; inv[1] = t[1]; }
}
__device__ __forceinline__ uint32_t scale_scores(float a, float b) {
    const float scale = 0.08838834764831845f;
    const uint32_t w = pack_bf16(a, b);
    return pack_bf16(bf_lo(w) * scale, bf_hi(w) * scale);
}

#define TL(i) do {} while (0)
#define TLB(i) do {} while (0)
#define TLC(i) do {} while (0)

#define OPQ_LANE 1
#define CLAIM_T 64
#define PAD_A 0
#define PAD_B 0
#define PAD_C 0
template <int N> __device__ __forceinline__ void code_pad() {
#pragma unroll
    for (int i = 0; i < N; i++) asm volatile("pmevent 0;");
}
__global__ void __cluster_dims__(2, 1, 1) __launch_bounds__(384, 1)
chain_kernel(const __grid_constant__ CUtensorMap mapX, const __grid_constant__ CUtensorMap mapT32, const __grid_constant__ CUtensorMap mapT16,
             const __grid_constant__ CUtensorMap mapTQ, const __grid_constant__ CUtensorMap mapKV,
             const __grid_constant__ CUtensorMap mapWq, const __grid_constant__ CUtensorMap mapWk, const __grid_constant__ CUtensorMap mapWv,
             const __grid_constant__ CUtensorMap mapWo, const bf16* __restrict__ mem0, char* __restrict__ mbox) {
    KT_START(2);
    extern __shared__ __align__(1024) uint8_t smem_chain[];
    constexpr uint32_t SB0 = 1024;
    if (smem_u32(smem_chain) != (SB0 | ((blockIdx.x & 1) << 24))) __trap();
    const int kh = blockIdx.x & 1;
    if (threadIdx.x == 0) {
        const uint32_t sb = smem_u32(smem_chain);
        for (int i = 0; i < 14; i++) mbar_init(sb + SM_BARS + 8 * i, 1);
        mbar_init(sb + MB_P, 4); mbar_init(sb + MB_V, 4); mbar_init(sb + MB_STG, 8); mbar_init(sb + MB_ROLE, 1); mbar_init(sb + MB_W4, 1); mbar_init(sb + MB_W5, 1);
        mbar_expect_tx(sb + MB_ROLE, 4);
        asm volatile("fence.mbarrier_init.release.cluster;" ::: "memory");
    }
    if (threadIdx.x == 32) { prefetch_map(&mapWv); prefetch_map(&mapWq); prefetch_map(&mapWk); prefetch_map(&mapWo); prefetch_map(&mapX); }
    __syncwarp();
    asm volatile("barrier.cluster.arrive.relaxed.aligned;" ::: "memory");
    unsigned claimed = 0;
    if (threadIdx.x == CLAIM_T && kh == 0) claimed = claim_pair(g_reg) & 255;
    __syncwarp();
    asm volatile("barrier.cluster.wait.acquire.aligned;" ::: "memory");
    if (threadIdx.x == CLAIM_T && kh == 0) {
        st_async1((SB0 | (1u << 24)) + SM_ROLE, claimed, (SB0 | (1u << 24)) + MB_ROLE);
        st_async1(SB0 + SM_ROLE, claimed, SB0 + MB_ROLE);
    }
    __syncwarp();
    mbar_wait_w(smem_u32(smem_chain) + MB_ROLE, 0);
    const int pair = uniform(lds32(smem_u32(smem_chain) + SM_ROLE));
#define YFLIP_() (uniform(lds32(sb + SM_ROLE + 4)) ^ YFLIP)
    if (pair >= 64) return;
    if (threadIdx.x == 0) KT_MARK(5);
    const int h = pair >> 1, nh = pair & 1, j = 2 * nh + kh, role = 2 * pair + kh;
#define WG_ORDER 0x210
    const int warp = uniform(((WG_ORDER >> (4 * (threadIdx.x >> 7))) & 3) * 4 + ((threadIdx.x >> 5) & 3));
    const uint32_t g = warp & 3, sb = SB0 | (kh << 24), rsb = sb ^ (1u << 24), cls = pair >> 5, kflip = ZFLIP ^ kh;
    const uint32_t mlo = (uint32_t)(uintptr_t)mbox, mhi = (uint32_t)((uintptr_t)mbox >> 32);
    auto lane16 = [&]() {
        uint32_t t;
        asm volatile("{.reg .u32 l, x; mov.u32 l, %%laneid; xor.b32 x, l, 1; shl.b32 x, x, 4; shfl.sync.bfly.b32 %0, x, 1, 0x1f, 0xffffffff;}" : "=r"(t));
        return t;
    };
#define PHASE(k) uint32_t L; asm volatile("{.reg .u32 t; shr.u32 t, %1, %3; add.u32 %0, %2, t;}" : "=r"(L) : "r"(it), "r"(l16), "n"(8 + (k)))
#define ROWPAT() ((((L << 3) & 0x380) | ((L << 2) & 0x400)) | ((L ^ (L >> 3)) & 0x10) | (L & 0x60))
#define FRAG() (ROWPAT() ^ (g << 5))
#define QFRAG() ((((L >> 1) & 0x80) | (L & 0x70)) + ((L & 0x80) ? SM_KV + 16384 + kvo : SM_QKV))
#define VFRAG() (ROWPAT() ^ ((g & 1) << 6))
#define VBASE() (sb + SM_KV + 8192 + (g >> 1) * 4096 + kvo)
#define XTLO() ((uint32_t)make_desc(SB0 + SM_XT, 16, 1024) + (ui & 1) * 2048)
    if (warp >= 8) {
        asm volatile("setmaxnreg.dec.sync.aligned.u32 %0;" ::"n"(REG_C));
        code_pad<PAD_C>();
        const uint32_t l16 = lane16(), lane = l16 >> 4;
        auto load_xt = [&](int seg, int half) {
            const uint32_t bar = sb + MB_XT + (seg & 1) * 8;
            if (half == 0) mbar_expect_tx(bar, 32768);
            asm volatile("cp.async.bulk.tensor.3d.shared::cluster.global.mbarrier::complete_tx::bytes [%0], [%1, {%3, %4, %5}], [%2];"
                         ::"r"(sb + SM_XT + (seg & 1) * 32768 + half * 16384), "l"(&mapX), "r"(bar), "r"(0), "r"(seg * SEG), "r"(8 * kh + 4 * (half ^ kflip)) : "memory");
        };
        if (warp == 8) {
            const CUtensorMap* ws = kh ? &mapWq : &mapWk;
            const CUtensorMap* wn = kh ? &mapWk : &mapWq;
            const uint64_t pol = EF_W ? policy_evict_first() : policy_evict_normal();
            const int col = h * DH + 64 * nh, row = 512 * kh;
            if (lane == 0) { mbar_expect_tx(sb + MB_W0, 49152); mbar_expect_tx(sb + MB_W1, 49152); mbar_expect_tx(sb + MB_W4, 49152); mbar_expect_tx(sb + MB_W2, 49152); mbar_expect_tx(sb + MB_W3, PRO3 ? 65536 : 32768); }
            __syncwarp();
            if (lane < 24) {
                const int k = lane ^ (16 * kflip);
                tma_load_2d(sb + STG_V + lane * 2048, &mapWv, col, row + 16 * k, sb + MB_W0, pol);
                tma_load_2d(sb + stg_qk(0, lane), ws, col, row + 16 * k, sb + MB_W1, pol);
                tma_load_2d(sb + stg_qk(1, lane), wn, col, row + 16 * k, sb + MB_W4, pol);
            }
            if (lane < 8) {
                const int k = (24 + lane) ^ (16 * kflip);
                tma_load_2d(sb + SM_WQK + lane * 4096, ws, col, row + 16 * k, sb + MB_W2, pol);
                tma_load_2d(sb + SM_WQK + lane * 4096 + 2048, wn, col, row + 16 * k, sb + MB_W2, pol);
                tma_load_2d(sb + SM_WV + lane * 2048, &mapWv, col, row + 16 * k, sb + MB_W2, pol);
            }
            __syncwarp();
        }
        if (warp == 9) {
            bar_sync(BAR_XT0, 160);
            if (lane == 0) { load_xt(0, 0); load_xt(0, 1); }
            __syncwarp();
        }
        if (warp == 10 && lane == 0) {
            wait_prerequisites();
            launch_dependents();
            sts32(sb + SM_ROLE + 4, g_reg[1]);
        }
        __syncwarp();
        bar_sync(BAR_PDONE, 384);
        KT_MARK(9);
        if (warp == 8) {
            const uint32_t dst = lane < 14 ? stg_wo(lane) : lane < 16 ? SM_WO1 + (lane - 8) * 2048 : SM_WO2 + (lane - 16) * 2048;
            tma_load_2d(sb + dst, &mapWo, 256 * j + 64 * (lane >> 3), h * DH + 16 * (lane & 7), sb + MB_W3, EF_W ? policy_evict_first() : policy_evict_normal());
        }
        if ((warp & 1) == 0) for (int c = (warp - 8) * 16 + lane; c < 512; c += 64) {
            uint32_t w[4];
#pragma unroll
            for (int r = 0; r < 4; r++) {
                const uint32_t lo = reinterpret_cast<const uint16_t*>(mem0)[(2 * r) * DM + 512 * kh + c], hi = reinterpret_cast<const uint16_t*>(mem0)[(2 * r + 1) * DM + 512 * kh + c];
                w[r] = lo | (hi << 16);
            }
            sts128(sb + SM_Z + (c ^ (256 * kflip)) * 16, make_uint4(w[0], w[1], w[2], w[3]));
        }
        if (!PRO3 && warp == 8) mbar_wait_w(sb + MB_W5, 0);
        auto tok_start = [&](int s) {
            if (lane == 0) {
                if (TS_AT == 0) TL(21);
                if (s > -3 && s + 2 < NSEG) {
                    mbar_wait(sb + MB_STG, (s + 2) & 1);
                    if (TS_AT == 1) TL(21);
                    if (XT_FIRST && s + 4 < NSEG) load_xt(s + 4, 0);
                    if (TS_AT == 2) TL(21);
                    asm volatile("fence.proxy.async.shared::cta;" ::: "memory");
                    if (TS_AT == 3) TL(21);
                    const int r = ((s + 2) & 3) * NH + h;
                    tma_store_2d(kh ? &mapT32 : &mapTQ, sb + SM_STG, kh ? 64 * nh : 256 * nh, kh ? r * 96 + 32 : r * 12);
                    tma_store_2d(&mapT16, sb + SM_STG + 4096, 64 * nh, r * 96 + 64 + 16 * kh);
                    asm volatile("cp.async.bulk.commit_group;" ::: "memory");
                    if (TS_AT == 4) TL(21);
                }
                if ((TS_LATE < 3 || s < 0) && (!XT_FIRST || s == -3) && s + 4 < NSEG) load_xt(s + 4, 0);
                if (!LATE_RD || s < 0) asm volatile("cp.async.bulk.wait_group.read 0;" ::: "memory");
                if (s < 0) {
                    asm volatile("mbarrier.arrive.shared::cluster.b64 _, [%0];" ::"r"(rsb + MB_FREE) : "memory");
                    mbar_wait(sb + MB_FREE, (s + 3) & 1);
                }
            }
            __syncwarp();
        };
        auto tok_mid = [&](int s) {
            if (lane == 0) {
                if (s + 4 < NSEG) load_xt(s + 4, 1);
                if (s > -3 && s + 2 < NSEG) {
                    asm volatile("cp.async.bulk.wait_group 0;" ::: "memory");
                    if (s == 8 || s == 16) asm volatile("fence.acq_rel.gpu;" ::: "memory");
                    st_relaxed_u32(g_xflag + role, s + 3);
                }
            }
            __syncwarp();
        };
        auto kv_check = [&](int s) {
            if (s + 1 < NSEG) {
                if (lane < 4) {
                    unsigned f; int guard = 0;
                    do {
                        asm volatile("ld.acquire.gpu.global.u32 %0, [%1];" : "=r"(f) : "l"(g_xflag + h * 4 + lane) : "memory");
                        if (++guard > (1 << 20)) __trap();
                    } while (f <= (unsigned)(s + 1));
                }
                __syncwarp();
                asm volatile("fence.proxy.async.global;" ::: "memory");
            }
        };
        auto kv_load = [&](int s) {
            if (lane == 0 && s + 1 < NSEG) {
                const uint32_t bar = sb + MB_KV + ((s + 1) & 1) * 8, dst = sb + SM_KV + ((s + 1) & 1) * KV_BYTES;
                const int row = (((s + 1) & 3) * NH + h) * 96;
                mbar_expect_tx(bar, KV_BYTES);
                asm volatile("cp.async.bulk.tensor.3d.shared::cluster.global.mbarrier::complete_tx::bytes.multicast::cluster [%0], [%1, {%3, %4, %3}], [%2], %5;"
                             ::"r"(dst + kh * 8192), "l"(&mapKV), "r"(bar), "r"(0), "r"(row + 32 + 32 * kh), "h"((uint16_t)3) : "memory");
                bulk_load(dst + 16384, g_tok + row * DH + j * 1024, 2048, bar);
            }
            __syncwarp();
        };
        if (warp == 9) {
            if (!PRO2 && lane == 0) { load_xt(0, 0); load_xt(0, 1); }
#pragma unroll 1
            for (int s = -3; s < 0; s++) { tok_start(s); KT_MARK(13 + s); bar_arrive(BAR_PRO, 288); tok_mid(s); }
        }
        if (warp == 11) { kv_check(-1); kv_load(-1); }
        bar_arrive(BAR_MEM, 384);
        const uint32_t ybox = mlo + page_off(role & 63, cls ^ YFLIP_()), xoth = mlo + WIN + page_off((pair & 31) ^ 1, cls ^ XFLIP);
        const uint32_t zline = mlo + WIN + page_off(32 + ((role >> 5) & 1), cls ^ ZFLIP) + (role & 31) * 128, zbox = mlo + WIN + (page_off(32 + kh, 0) & ~4096u);
        const uint32_t xtype = g == GV ? 2 : g == 2 ? 0 : 1;
        const uint32_t ydst = (lane >> 3) * 128 + ((lane & 7) ^ (lane >> 3)) * 16, ysrc = lane * 128 + ((2 * g) ^ (lane & 7)) * 16;
#pragma unroll 1
        for (int s = 0; s < NSEG; s++) {
            const uint32_t slot = (s & 3) << 14;
            spin_cycles(DLY_T);
            if (g == 3) {
                spin_cycles(DLY_K);
                kv_check(s);
                if (TS_AT == 9) TL(21);
                const uint32_t L = l16, kvo = (s & 1) * KV_BYTES, qa = QFRAG(), sa = sb + SM_S + 512 + (L >> 2);
                float sc[4] = {0.f, 0.f, 0.f, 0.f}, sd[4] = {0.f, 0.f, 0.f, 0.f};
                uint32_t a[4][4], kb[2][4];
                mbar_wait_w(sb + MB_KV + (s & 1) * 8, (s >> 1) & 1);
                mbar_wait_w(sb + MB_P, s & 1);
#pragma unroll
                for (int c = 0; c < 2; c++) {
                    const uint32_t qc = qa + (sb + (nh ^ c) * 1024), kc = L + (sb + SM_QKV + 2048 + (nh ^ c) * 1024);
                    if (TS_AT == 7 && c) TL(21);
                    if (c) bar_sync(BAR_QK, 224);
                    ldsm4t(kb[0], kc); ldsm4t(a[0], qc); ldsm4t(a[1], qc + 256);
                    ldsm4t(kb[1], kc + 512); ldsm4t(a[2], qc + 512); ldsm4t(a[3], qc + 768);
                    mma16816v(sc, a[0], kb[0][0], kb[0][1]);
                    mma16816v(sd, a[1], kb[0][2], kb[0][3]);
                    mma16816v(sc, a[2], kb[1][0], kb[1][1]);
                    mma16816v(sd, a[3], kb[1][2], kb[1][3]);
                }
                sts32(sa, scale_scores(sc[0] + sd[0], sc[1] + sd[1]));
                sts32(sa + 768, scale_scores(sc[2] + sd[2], sc[3] + sd[3]));
                bar_arrive(BAR_S, 160);
                TL(25);
                bar_sync(BAR_SV, NSV);
                kv_load(s);
            } else {
                if (g == 1 && (TS_LATE == 0 || TS_LATE >= 3)) { spin_cycles(DLY_S); tok_start(s); if (TS_AT == 5) TL(21); if (s == 0) KT_MARK(13); }
                const char* p = make_ptr(l16 + (xoth + xtype * 1024 + slot), mhi);
                uint4 v[2];
                const uint32_t dst = l16 + (sb + SM_QKV + xtype * 2048 + (nh ^ 1) * 1024);
                asm volatile("" ::"l"(p));
                poll_init(v[0]); poll_init(v[1]);
                if (g == GV) {
                    bar_sync(BAR_PUBV, 160);
                    mbar_wait_w(sb + MB_V, s & 1);
                    spin_cycles(DLY_V);
                } else {
                    bar_sync(BAR_PUB, 192);
                    spin_cycles(DLY_X);
                }
                const int r = poll2(v, p);
                sts128(dst, v[0]); sts128(dst + 512, v[1]);
                STAT(1, r > 1 && warp == 10);
                if (g != GV) bar_arrive(BAR_QK, 224);
                if (TS_AT == 6 && g == 0) TL(21);
                if (g == GV) { bar_arrive(BAR_V, 160); if (GV == 0) bar_arrive(BAR_SV, NSV); TL(17); }
                if (g == 1) {
                    TL(31);
                    if (TS_LATE == 1) { tok_start(s); if (TS_AT == 5) TL(21); }
                    if (TS_LATE == 3 && lane == 0 && s + 4 < NSEG) load_xt(s + 4, 0);
                    if (LATE_RD && (TS_LATE == 0 || TS_LATE >= 3)) asm volatile("cp.async.bulk.wait_group.read 0;" ::: "memory");
                    bar_sync(BAR_SV, NSV);
                    if (TS_LATE == 2) { tok_start(s); if (TS_AT == 5) TL(21); }
                    if (TS_LATE == 4 && lane == 0 && s + 4 < NSEG) load_xt(s + 4, 0);
                    tok_mid(s);
                    TL(22);
                }
                if (g == 2 && s >= 1) {
                    TL(16);
                    const uint32_t prev = (slot - 0x4000) & 0xC000;
                    const char* y = make_ptr(l16 + (ybox + prev), mhi);
                    const char* x = make_ptr(l16 + (xoth + prev + kh * (XP ? 2048 : 1536)), mhi);
#pragma unroll
                    for (int i = 0; i < 8; i++) st_sent(y + i * 512);
#pragma unroll
                    for (int i = 0; i < (XP ? 4 : 3); i++) st_sent(x + i * 512);
                    st_relaxed_u32(make_ptr(lane * 4 + (zline + (slot ^ 0x8000)), mhi), SENT);
                    TL(23);
                }
            }
            if (s + 1 == NSEG) break;
            {
                const char* p = make_ptr(l16 + (ybox + g * 1024 + slot), mhi);
                char* zdst = make_ptr(lane * 4 + (zline + g * 32 + slot), mhi);
                const uint32_t dst = ydst + (sb + SM_Z + g * 1024), dst1 = (ydst ^ 64) + (sb + SM_Z + g * 1024 + 512), src = ysrc + (sb + SM_Z), src1 = (ysrc ^ 16) + (sb + SM_Z);
                asm volatile("" ::"l"(p), "l"(zdst));
                uint4 v[2];
                poll_init(v[0]); poll_init(v[1]);
                bar_sync(BAR_SENTC, 384);
                spin_cycles(DLY_Y);
                const int r = poll2(v, p);
                STAT(2, r > 1 && warp == 8);
                sts128(dst, v[0]); sts128(dst1, v[1]);
                bar_sync(BAR_Y, 128);
                TL(18);
                uint32_t b[2][4];
                ldsm4t(b[0], src); ldsm4t(b[1], src1);
                const uint32_t one = 0x3F803F80u;
                float d0[4] = {0.f, 0.f, 0.f, 0.f}, d1[4] = {0.f, 0.f, 0.f, 0.f};
                mma16816(d0, one, one, one, one, b[0][0], b[0][1]);
                mma16816(d1, one, one, one, one, b[1][0], b[1][1]);
                mma16816(d0, one, one, one, one, b[0][2], b[0][3]);
                mma16816(d1, one, one, one, one, b[1][2], b[1][3]);
                const uint32_t w = (lane & 4) ? pack_bf16(d1[0], d1[1]) : pack_bf16(d0[0], d0[1]);
                asm volatile("{.reg .pred p; setp.lt.u32 p, %2, 128; @p st.relaxed.gpu.global.u32 [%0], %1;}" ::"l"(zdst), "r"(w), "r"(l16) : "memory");
                if (s + 3 < NSEG) bar_arrive(BAR_ZP, 256);
                TL(19);
            }
            {
                const char* p = make_ptr(l16 + (zbox + g * 512 + slot), mhi);
                const uint32_t dst = l16 + (sb + SM_Z + g * 512);
                asm volatile("" ::"l"(p));
                uint4 v[4];
                poll_init(v[0]); poll_init(v[1]); poll_init(v[2]); poll_init(v[3]);
                bar_sync(BAR_COMM, 128);
                spin_cycles(DLY_Z);
                const int r = poll4<2048>(v, p);
                STAT(0, r > 1 && warp == 8);
#pragma unroll
                for (int i = 0; i < 4; i++) sts128(dst + i * 2048, v[i]);
                bar_arrive(BAR_MEM, 384);
                TL(20);
            }
        }
    } else if (warp < 4) {
        asm volatile("setmaxnreg.inc.sync.aligned.u32 %0;" ::"n"(REG_A));
        code_pad<PAD_A>();
        const uint32_t l16 = lane16();
        uint32_t wa[2][24][4];
        {
            const uint32_t L = l16, fa = sb + FRAG();
            mbar_wait_w(sb + MB_W1, 0);
            KT_MARK(7);
#pragma unroll
            for (int t = 0; t < 2; t++) {
#pragma unroll
                for (int r = 0; r < 24; r++) ldsm4t(wa[t][r], fa + stg_qk(t, r));
                if (PRO2 && t == 0) { bar_arrive(BAR_XT0, 160); mbar_wait_w(sb + MB_W4, 0); }
            }
            mbar_wait_w(sb + MB_W2, 0);
            if (EARLY_ROLE) bar_sync(BAR_PDONE, 384); else bar_arrive(BAR_PDONE, 384);
        }
        auto batch1 = [&](float (&d)[16], uint32_t lo, auto tc, auto k0c, auto k1c) {
            constexpr int t = decltype(tc)::value;
            const uint64_t da = make_desc(SB0 + SM_WQK, 16, 1024);
            wg_fence();
            static_for<decltype(k0c)::value, decltype(k1c)::value>([&](auto kc) {
                constexpr int i = decltype(kc)::value, k = kstep(t ? ORD1 : ORD0, i), off = (k >> 2) * 256 + (k & 3) * 2;
                if constexpr (k >= 24) wgmma_ss32u<off, i != 0 || t != 0>(d, da + ((k - 24) * 2 + t) * 128, lo);
                else wgmma_rs32u<off, i != 0 || t != 0>(d, wa[t][k], lo);
            });
            wg_commit();
        };
        const uint32_t xbox = mlo + WIN + page_off(pair & 31, cls ^ XFLIP);
        const uint32_t ybox = mlo + page_off(24 + 2 * g + 32 * nh, kh ^ YFLIP_()) + h * 128;
#pragma unroll 1
        for (uint32_t it = 0; it < NSEG + 3; it++) {
            const int s = (int)it - 3;
            const uint32_t ui = uniform(it), slot = ((ui + 1) & 3) << 14, kvo = (~ui & 1) * KV_BYTES, xtlo = XTLO();
            {
                PHASE(5);
                const uint32_t first = L | (g << 9);
                if (s >= 0) mbar_expect_tx_if0(first, sb + MB_R1, 2048);
                if (s + 3 < NSEG) {
                    mbar_expect_tx_if0(first, sb + MB_RT0, (RT_BF & 1) ? 4096 : RT0_N * 2048);
                    mbar_wait_w(sb + MB_XT + (ui & 1) * 8, (it >> 1) & 1);
                }
            }
            if (s >= 0) {
                PHASE(0);
                const uint32_t mb = L + (sb + SM_Z), ra = L + (sb + g * 512), r1 = L + (rsb + SM_R1 + g * 512), r1b = rsb + MB_R1;
                sched_fence(r1);
                bar_sync(BAR_MEM, 384);
                TLB(0);
                float acc[2][2][4];
#pragma unroll
                for (int t = 0; t < 4; t++) { acc[t >> 1][t & 1][0] = acc[t >> 1][t & 1][1] = acc[t >> 1][t & 1][2] = acc[t >> 1][t & 1][3] = 0.f; }
                uint32_t b[4][4];
                uint4 u0, u1;
#pragma unroll
                for (int p = 0; p < 4; p++) ldsm4t(b[p], mb + p * 512);
#pragma unroll
                for (int p = 0; p < 12; p++) {
#pragma unroll
                    for (int u = 0; u < 2; u++) {
                        mma16816v(acc[0][u], wa[0][2 * p + u], b[p & 3][2 * u], b[p & 3][2 * u + 1]);
                        mma16816v(acc[1][u], wa[1][2 * p + u], b[p & 3][2 * u], b[p & 3][2 * u + 1]);
                    }
                    if (p + 4 < 12) ldsm4t(b[p & 3], mb + (p + 4) * 512);
                    if (p == Q3_AT) {
                        bar_sync(BAR_Q3, 256);
                        u0 = lds128(ra + SM_R3); u1 = lds128(ra + SM_O);
                    }
                }
                st_async4(r1, (acc[0][0][0] + __uint_as_float(u0.x)) + acc[0][1][0], (acc[0][0][1] + __uint_as_float(u0.y)) + acc[0][1][1],
                          (acc[0][0][2] + __uint_as_float(u0.z)) + acc[0][1][2], (acc[0][0][3] + __uint_as_float(u0.w)) + acc[0][1][3], r1b);
                TL(1);
                const float o0 = (acc[1][0][0] + __uint_as_float(u1.x)) + acc[1][1][0], o1 = (acc[1][0][1] + __uint_as_float(u1.y)) + acc[1][1][1];
                const float o2 = (acc[1][0][2] + __uint_as_float(u1.z)) + acc[1][1][2], o3 = (acc[1][0][3] + __uint_as_float(u1.w)) + acc[1][1][3];
                const uint32_t l4 = L >> 2, qo = SM_QKV + kh * 2048 + nh * 1024 + g * 256, qr = l4 + (rsb + qo), ql = l4 + (sb + qo), pb = rsb + MB_P;
                char* xd = make_ptr(l4 + (xbox + kh * 1024 + g * 256 + slot), mhi);
                asm volatile("" ::"l"(xd), "r"(qr), "r"(pb), "r"(qr + 128), "f"(o0), "f"(o1), "f"(o2), "f"(o3));
                mbar_wait_w(sb + MB_R1, s & 1);
                const uint4 v = lds128(ra + SM_R1);
                const uint32_t w0 = pack_bf16(o0 + __uint_as_float(v.x), o1 + __uint_as_float(v.y)), w1 = pack_bf16(o2 + __uint_as_float(v.z), o3 + __uint_as_float(v.w));
                st_relaxed_u32(xd, w0);
                st_relaxed_u32(xd + 128, w1);
                bar_arrive(BAR_PUB, 192);
                st_async1(qr, w0, pb);
                st_async1(qr + 128, w1, pb);
                sts32(ql, w0);
                sts32(ql + 128, w1);
                __syncwarp();
                mbar_expect_tx_if0(L, sb + MB_P, 256);
                if (!XB_EARLY) TL(2);
                if (XB_EARLY || s + 3 < NSEG) bar_sync(BAR_VP, 256);
            } else {
                bar_sync(BAR_PRO, 288);
            }
            if (s + 3 < NSEG) {
                float d[16];
                batch1(d, xtlo, std::integral_constant<int, 0>(), std::integral_constant<int, 0>(), std::integral_constant<int, 32>());
                PHASE(1);
                const uint32_t rt = L + (rsb + SM_RT + g * 2048);
                wg_wait<0>();
                TL(7);
                if (RT_BF & 1) {
#pragma unroll
                    for (int i = 0; i < 2; i++)
                        st_async4(rt + i * 512, __uint_as_float(pack_bf16(d[8 * i], d[8 * i + 1])), __uint_as_float(pack_bf16(d[8 * i + 2], d[8 * i + 3])),
                                  __uint_as_float(pack_bf16(d[8 * i + 4], d[8 * i + 5])), __uint_as_float(pack_bf16(d[8 * i + 6], d[8 * i + 7])), rsb + MB_RT0);
                } else {
#pragma unroll
                for (int i = 0; i < RT0_N; i++) st_async4(rt + i * 512, d[4 * i], d[4 * i + 1], d[4 * i + 2], d[4 * i + 3], rsb + MB_RT0);
                }
            }
            if (s + 1 == NSEG) { bar_arrive(BAR_SV, NSV); break; }
            if (s >= 0) {
                PHASE(2);
                const uint32_t fo = FRAG() + (sb + SM_WO2 + 16384), lo = L + (sb + SM_O), yo = (L >> 2) + (ybox + slot);
                uint32_t a1[8][4];
                bar_sync(BAR_SV, NSV);
#pragma unroll
                for (int k = 0; k < 8; k++) ldsm4t(a1[k], fo + k * 2048);
                sched_fence(yo);
                bar_sync(BAR_O2, 256);
                TLB(14);
                float y0[4] = {0.f, 0.f, 0.f, 0.f}, y1[4] = {0.f, 0.f, 0.f, 0.f};
                uint32_t b[2][4];
                ldsm4t(b[0], lo); ldsm4t(b[1], lo + 512);
                sched_fence(L);
#pragma unroll
                for (int p = 0; p < 4; p++) {
                    mma16816v(y0, a1[2 * p], b[p & 1][0], b[p & 1][1]);
                    mma16816v(y1, a1[2 * p + 1], b[p & 1][2], b[p & 1][3]);
                    if (p < 2) ldsm4t(b[p & 1], lo + (p + 2) * 512);
                }
                bar_sync(BAR_INV, 256);
                float i0, i1;
                asm volatile("ld.shared.v2.f32 {%0, %1}, [%2];" : "=f"(i0), "=f"(i1) : "r"(((L >> 1) & 0x18) + (sb + SM_INV + g * 32)) : "memory");
                st_relaxed_u32(make_ptr(yo, mhi), pack_bf16((y0[0] + y1[0]) * i0, (y0[1] + y1[1]) * i1));
                st_relaxed_u32(make_ptr(yo ^ 4096, mhi) + 0x2000, pack_bf16((y0[2] + y1[2]) * i0, (y0[3] + y1[3]) * i1));
                bar_arrive(BAR_SENTC, 384);
                TL(6);
            }
            if (s + 3 < NSEG) {
                PHASE(4);
                float d[16];
                const uint32_t rt = L + (sb + SM_RT + g * 2048);
                if (SENT_EARLY && s >= 0) bar_sync(BAR_SENT, 256);
                mbar_wait_w(sb + MB_RT0, it & 1);
                if (RT_BF & 1) {
#pragma unroll
                    for (int i = 0; i < 2; i++) {
                        const uint4 v = lds128(rt + i * 512);
                        d[8 * i] = bf_lo(v.x); d[8 * i + 1] = bf_hi(v.x); d[8 * i + 2] = bf_lo(v.y); d[8 * i + 3] = bf_hi(v.y);
                        d[8 * i + 4] = bf_lo(v.z); d[8 * i + 5] = bf_hi(v.z); d[8 * i + 6] = bf_lo(v.w); d[8 * i + 7] = bf_hi(v.w);
                    }
                } else
#pragma unroll
                for (int i = 0; i < 4; i++) {
                    const uint4 v = lds128(rt + i * 512);
                    d[4 * i] = __uint_as_float(v.x); d[4 * i + 1] = __uint_as_float(v.y); d[4 * i + 2] = __uint_as_float(v.z); d[4 * i + 3] = __uint_as_float(v.w);
                }
                if (!SENT_EARLY && s >= 0) bar_sync(BAR_SENT, 256);
                if (SPLIT > 0) batch1(d, xtlo, std::integral_constant<int, 1>(), std::integral_constant<int, 0>(), std::integral_constant<int, SPLIT>());
                if (s >= 0) bar_sync(BAR_ZP, 256);
                TLB(30);
                batch1(d, xtlo, std::integral_constant<int, 1>(), std::integral_constant<int, SPLIT>(), std::integral_constant<int, 32>());
                const uint32_t so = (kh ? FRAG() : ((L & 0x100) << 2) + (L & 0xF0) + g * 256) + (sb + SM_STG);
                wg_wait<0>();
                TL(8);
                uint32_t w[8];
#pragma unroll
                for (int i = 0; i < 8; i++) w[i] = pack_bf16(d[2 * i], d[2 * i + 1]);
                if (kh) {
                    stsm4t(so, w[0], w[1], w[2], w[3]);
                    stsm4t(so + 2048, w[4], w[5], w[6], w[7]);
                } else {
                    stsm4(so, w[0], w[1], w[2], w[3]);
                    stsm4(so + 2048, w[4], w[5], w[6], w[7]);
                }
                __syncwarp();
                mbar_arrive_if0(L, sb + MB_STG);
                TL(9);
            } else {
                bar_arrive(BAR_SENT, 256);
            }
        }
    } else {
        asm volatile("setmaxnreg.inc.sync.aligned.u32 %0;" ::"n"(REG_B));
        code_pad<PAD_B>();
        const uint32_t l16 = lane16();
        uint32_t wv[24][4], wo[8 + WO_RF1][4];
        {
            const uint32_t L = l16, fa = sb + FRAG();
            mbar_wait_w(sb + MB_W0, 0);
            KT_MARK(6);
#pragma unroll
            for (int r = 0; r < 24; r++) ldsm4t(wv[r], fa + STG_V + r * 2048);
#pragma unroll
            for (int r = 0; r < 8 + WO_RF1; r++) asm volatile("" : "=r"(wo[r][0]), "=r"(wo[r][1]), "=r"(wo[r][2]), "=r"(wo[r][3]));
            mbar_wait_w(sb + MB_W2, 0);
            if (EARLY_ROLE) bar_sync(BAR_PDONE, 384); else bar_arrive(BAR_PDONE, 384);
        }
        const uint32_t xbox = XP ? mlo + WIN + page_off(34 + ((pair & 31) >> 1), cls ^ XFLIP) + nh * 2048 : mlo + WIN + page_off(pair & 31, cls ^ XFLIP);
        const uint32_t ybox = mlo + page_off(2 * g + 32 * nh, kh ^ YFLIP_()) + h * 128;
#pragma unroll 1
        for (uint32_t it = 0; it < NSEG + 3; it++) {
            const int s = (int)it - 3;
            const uint32_t ui = uniform(it), slot = ((ui + 1) & 3) << 14, kvo = (~ui & 1) * KV_BYTES, xtlo = XTLO();
            {
                PHASE(5);
                const uint32_t first = L | (g << 9);
                if (s >= 0) mbar_expect_tx_if0(first, sb + MB_R2, 1024);
                if (s + 3 < NSEG) {
                    mbar_expect_tx_if0(first, sb + MB_RT1, (RT_BF & 2) ? 2048 : 4096);
                    mbar_wait_w(sb + MB_XT + (ui & 1) * 8, (it >> 1) & 1);
                }
            }
            if (s >= 0) {
                PHASE(0);
                const uint32_t fo = FRAG() + sb, l4 = L >> 2;
                {
                    const uint32_t mb = L + (sb + SM_Z), aw = fo + SM_WQK, ra = L + (sb + g * 512), r2 = (L >> 1) + (rsb + SM_R2 + g * 256), r2b = rsb + MB_R2;
                    uint32_t a[NA][4], b[4][4];
#pragma unroll
                    for (int i = 0; i < NA; i++) ldsm4t(a[i], aw + i * 2048);
                    sched_fence(L);
                    TL(24);
                    bar_sync(BAR_MEM, 384);
#pragma unroll
                    for (int p = 0; p < 4; p++) ldsm4t(b[p], mb + (12 + p) * 512);
                    sched_fence(L);
                    float c[2][4] = {{0.f, 0.f, 0.f, 0.f}, {0.f, 0.f, 0.f, 0.f}};
#pragma unroll
                    for (int i = 0; i < 16; i++) {
                        mma16816v(c[i & 1], a[i % NA], b[i >> 2][i & 2], b[i >> 2][(i & 2) + 1]);
                        ldsm4t(a[i % NA], aw + (i + NA) * 2048);
                    }
                    sts128(ra + SM_R3, make_uint4(__float_as_uint(c[0][0]), __float_as_uint(c[0][1]), __float_as_uint(c[0][2]), __float_as_uint(c[0][3])));
                    sts128(ra + SM_O, make_uint4(__float_as_uint(c[1][0]), __float_as_uint(c[1][1]), __float_as_uint(c[1][2]), __float_as_uint(c[1][3])));
                    bar_arrive(BAR_Q3, 256);
                    TL(29);
                    float acc[4][4];
#pragma unroll
                    for (int t = 0; t < 4; t++) { acc[t][0] = acc[t][1] = acc[t][2] = acc[t][3] = 0.f; }
#pragma unroll
                    for (int i = 16; i < 24; i++) {
                        mma16816v(acc[i & 1], a[i % NA], b[(i - 16) >> 1][2 * (i & 1)], b[(i - 16) >> 1][2 * (i & 1) + 1]);
                        if (i + NA < 24) ldsm4t(a[i % NA], aw + (i + NA) * 2048);
                        else ldsm4t(a[i % NA], mb + (i + NA - 24) * 512);
                    }
#pragma unroll
                    for (int p = 0; p < 12; p++) {
                        mma16816v(acc[(2 * p) & 3], wv[2 * p], a[(24 + p) % NA][0], a[(24 + p) % NA][1]);
                        mma16816v(acc[(2 * p + 1) & 3], wv[2 * p + 1], a[(24 + p) % NA][2], a[(24 + p) % NA][3]);
                        if (p + NA < 12) ldsm4t(a[(24 + p) % NA], mb + (p + NA) * 512);
                    }
                    if (XB_EARLY || s + 3 < NSEG) bar_arrive(BAR_VP, 256);
                    float o[4];
#pragma unroll
                    for (int i = 0; i < 4; i++) o[i] = (acc[0][i] + acc[1][i]) + (acc[2][i] + acc[3][i]);
                    st_async2(r2, kh ? o[0] : o[2], kh ? o[1] : o[3], r2b);
                    TL(10);
                    const float o0 = kh ? o[2] : o[0], o1 = kh ? o[3] : o[1];
                    const uint32_t qo = SM_QKV + 4096 + nh * 1024 + (2 * g + kh) * 128, qr = l4 + (rsb + qo), ql = l4 + (sb + qo), vb = rsb + MB_V, rl = (L >> 1) + (sb + SM_R2 + g * 256);
                    char* xd = make_ptr(l4 + (xbox + 2048 + (2 * g + kh) * 128 + slot), mhi);
                    asm volatile("" ::"l"(xd), "r"(qr), "r"(vb), "f"(o0), "f"(o1));
                    mbar_wait_w(sb + MB_R2, s & 1);
                    uint32_t vx, vy;
                    asm volatile("ld.shared.v2.u32 {%0,%1}, [%2];" : "=r"(vx), "=r"(vy) : "r"(rl) : "memory");
                    const uint32_t w0 = pack_bf16(o0 + __uint_as_float(vx), o1 + __uint_as_float(vy));
                    st_relaxed_u32(xd, w0);
                    bar_arrive(BAR_PUBV, 160);
                    st_async1(qr, w0, vb);
                    sts32(ql, w0);
                    __syncwarp();
                    mbar_expect_tx_if0(L, sb + MB_V, 128);
                    TL(11);
                }
                const uint32_t vma = L + (sb + SM_QKV + 4096 + g * 512), yo = l4 + (ybox + slot);
                uint32_t va[2][2][4];
                {
                    const uint32_t qa = QFRAG(), vf = VFRAG(), va0 = vf + VBASE(), va1 = (vf ^ 32) + VBASE();
                    const uint32_t kf = ((L << 3) & 0x380) | ((L ^ (L >> 3)) & 0x30) | (L & 0x40), kb0 = sb + SM_KV + kvo + g * 1024;
                    const int d = (int)(L >> 6) - (int)((L >> 3) & 6) + 8 * (j - (int)g);
                    const uint32_t keep = (d < 0 ? 0u : 0xFFFFu) | (d < 1 ? 0u : 0xFFFF0000u), sa = l4 + (sb + SM_S + g * 128);
                    const uint32_t q0 = qa + (sb + nh * 1024), q1 = qa + (sb + (nh ^ 1) * 1024);
                    float sc[4] = {0.f, 0.f, 0.f, 0.f}, sd[4] = {0.f, 0.f, 0.f, 0.f};
                    uint32_t a[4][4], kb[2][4];
                    mbar_wait_w(sb + MB_KV + (~ui & 1) * 8, (s >> 1) & 1);
                    ldsm4(kb[0], kf + (kb0 + nh * 4096)); ldsm4(kb[1], (kf ^ 64) + (kb0 + nh * 4096));
                    mbar_wait_w(sb + MB_P, s & 1);
                    TL(12);
#pragma unroll
                    for (int k = 0; k < 4; k++) ldsm4t(a[k], q0 + k * 256);
#pragma unroll
                    for (int k = 0; k < 4; k++) mma16816v((k & 1) ? sd : sc, a[k], kb[k >> 1][2 * (k & 1)], kb[k >> 1][2 * (k & 1) + 1]);
                    ldsm4(kb[0], kf + (kb0 + (nh ^ 1) * 4096)); ldsm4(kb[1], (kf ^ 64) + (kb0 + (nh ^ 1) * 4096));
                    sched_fence(vf | yo);
                    if (TS_AT == 8) TL(21);
                    bar_sync(BAR_QK, 224);
                    TLB(3);
#pragma unroll
                    for (int k = 0; k < 4; k++) ldsm4t(a[k], q1 + k * 256);
                    sched_fence(L);
#pragma unroll
                    for (int k = 0; k < 4; k++) mma16816v((k & 1) ? sd : sc, a[k], kb[k >> 1][2 * (k & 1)], kb[k >> 1][2 * (k & 1) + 1]);
                    ldsm4t(va[0][0], va0); ldsm4t(va[0][1], va0 + 2048);
                    sts32(sa, scale_scores(sc[0] + sd[0], sc[1] + sd[1]));
                    sts32(sa + 768, (scale_scores(sc[2] + sd[2], sc[3] + sd[3]) & keep) | (0xFF80FF80u & ~keep));
                    bar_arrive(BAR_SV, NSV);
                    ldsm4t(va[1][0], va1); ldsm4t(va[1][1], va1 + 2048);
                }
                bar_sync(BAR_S, 160);
                TLB(4);
                uint32_t pw[6], vm[4];
                if (s + 1 < NSEG) {
                softmax40(pw, l4 + (sb + SM_S), [&]() {
                    bar_sync(BAR_V, 160);
                    ldsm4(vm, vma);
                });
                uint32_t a1[NP2][4];
                float inv[2];
                {
                    uint32_t w[4];
                    pv32<false>(w, inv, va, vm, pw, [&]() {
                        sched_fence(L);
#pragma unroll
                        for (int k = 0; k < NP2; k++) ldsm4t(a1[k], fo + SM_WO2 + k * 2048);
                    });
#pragma unroll
                    for (int i = 0; i < 4; i++) sts32(l4 + (sb + SM_O + g * 512) + i * 128, w[i]);
                }
                const uint32_t lo = L + (sb + SM_O);
                bar_arrive(BAR_O2, 256);
                bar_sync(BAR_O, 128);
                TLB(5);
                {
                    float y0[4] = {0.f, 0.f, 0.f, 0.f}, y1[4] = {0.f, 0.f, 0.f, 0.f}, y2[4] = {0.f, 0.f, 0.f, 0.f};
                    uint32_t b[4][4];
#pragma unroll
                    for (int p = 0; p < 4; p++) ldsm4t(b[p], lo + p * 512);
                    inv[0] = rcp_approx(inv[0]); inv[1] = rcp_approx(inv[1]);
                    asm volatile("st.shared.v2.f32 [%0], {%1, %2};" ::"r"(((L >> 1) & 0x18) + (sb + SM_INV + g * 32)), "f"(inv[0]), "f"(inv[1]) : "memory");
                    bar_arrive(BAR_INV, 256);
                    sched_fence(L);
#pragma unroll
                    for (int k = 0; k < 8; k++) {
                        const int p = k >> 1, u = k & 1;
                        mma16816v(y2, a1[k % NP2], b[p][2 * u], b[p][2 * u + 1]);
                        if (k + NP2 < 8) ldsm4t(a1[k % NP2], fo + SM_WO2 + (k + NP2) * 2048);
                        else if (k + NP2 < 16 - WO_RF1) ldsm4t(a1[k % NP2], fo + SM_WO1 + (k + NP2 - 8 + WO_RF1) * 2048);
                        mma16816v(y0, wo[k], b[p][2 * u], b[p][2 * u + 1]);
                        if (k < WO_RF1) mma16816v(y1, wo[8 + (k < WO_RF1 ? k : 0)], b[p][2 * u], b[p][2 * u + 1]);
                        else mma16816v(y1, a1[(k + 8 - WO_RF1) % NP2], b[p][2 * u], b[p][2 * u + 1]);
                        if (k < P2_FENCE) sched_fence(L);
                    }
                    char* yd = make_ptr(yo, mhi);
                    char* yd1 = make_ptr(yo ^ 4096, mhi);
                    st_relaxed_u32(yd1 + 0x80000, pack_bf16(y2[0] * inv[0], y2[1] * inv[1]));
                    st_relaxed_u32(yd + 0x82000, pack_bf16(y2[2] * inv[0], y2[3] * inv[1]));
                    st_relaxed_u32(yd, pack_bf16(y0[0] * inv[0], y0[1] * inv[1]));
                    st_relaxed_u32(yd1 + 0x2000, pack_bf16(y0[2] * inv[0], y0[3] * inv[1]));
                    st_relaxed_u32(yd + 0x40000, pack_bf16(y1[0] * inv[0], y1[1] * inv[1]));
                    st_relaxed_u32(yd1 + 0x42000, pack_bf16(y1[2] * inv[0], y1[3] * inv[1]));
                }
                bar_arrive(BAR_SENTC, 384);
                TL(13);
                bar_sync(BAR_SENT, 256);
                } else {
                    bar_sync(BAR_V, 160);
                }
            } else {
                if (it == WO_IT) {
                    PHASE(2);
                    const uint32_t fa = sb + FRAG();
                    mbar_wait_w(sb + MB_W3, 0);
                    KT_MARK(8);
#pragma unroll
                    for (int r = 0; r < 8 + WO_RF1; r++) ldsm4t(wo[r], fa + stg_wo(r));
                }
                bar_sync(BAR_PRO, 288);
            }
            float o[8];
            {
                PHASE(1);
                float d[16];
                const uint64_t da = make_desc(SB0 + SM_WV, 16, 1024);
                auto batch = [&](auto k0c, auto k1c) {
                    static_for<decltype(k0c)::value, decltype(k1c)::value>([&](auto kc) {
                        constexpr int i = decltype(kc)::value, k = kstep(ORDV, i), off = (k >> 2) * 256 + (k & 3) * 2;
                        if constexpr (k >= 24) wgmma_ss32u<off, i != 0>(d, da + (k - 24) * 128, xtlo);
                        else wgmma_rs32u<off, i != 0>(d, wv[k], xtlo);
                    });
                };
                const uint32_t vf = VFRAG(), va0 = vf + VBASE(), va1 = (vf ^ 32) + VBASE(), vma = L + (sb + SM_QKV + 4096 + g * 512), sa = (L >> 2) + (sb + SM_S + 768);
                const uint32_t rt = L + (rsb + SM_RT + 8192 + g * 1024);
                uint32_t va[2][2][4], vm[4], pw[6], w[4];
                wg_fence();
                batch(std::integral_constant<int, 0>(), std::integral_constant<int, TA0>());
                wg_commit();
                batch(std::integral_constant<int, TA0>(), std::integral_constant<int, 32>());
                wg_commit();
                wg_wait<1>();
                softmax40(pw, sa, [&]() {});
                ldsm4t(va[0][0], va0); ldsm4t(va[0][1], va0 + 2048);
                ldsm4t(va[1][0], va1); ldsm4t(va[1][1], va1 + 2048);
                ldsm4(vm, vma);
                wg_wait<0>();
                TL(27);
                float inv[2];
                pv32<true>(w, inv, va, vm, pw, [&]() {
                    if (RT_BF & 2) {
                        uint32_t q[4];
#pragma unroll
                        for (int i = 0; i < 4; i++) q[i] = pack_bf16(kh ? d[2 * i] : d[8 + 2 * i], kh ? d[2 * i + 1] : d[9 + 2 * i]);
                        if (s + 3 < NSEG) st_async4(rt, __uint_as_float(q[0]), __uint_as_float(q[1]), __uint_as_float(q[2]), __uint_as_float(q[3]), rsb + MB_RT1);
                    } else if (s + 3 < NSEG) {
#pragma unroll
                        for (int i = 0; i < 2; i++)
                            st_async4(rt + i * 512, kh ? d[4 * i] : d[8 + 4 * i], kh ? d[4 * i + 1] : d[9 + 4 * i], kh ? d[4 * i + 2] : d[10 + 4 * i], kh ? d[4 * i + 3] : d[11 + 4 * i], rsb + MB_RT1);
                    }
#pragma unroll
                    for (int i = 0; i < 8; i++) o[i] = kh ? d[8 + i] : d[i];
                });
                stsm4t((L & 0x70) * 5 + ((L >> 3) & 0x30) + (sb + SM_TO + g * 640), w[0], w[1], w[2], w[3]);
                __syncwarp();
                const uint4 r = lds128(((L >> 2) & 0x70) * 5 + (L & 0x30) + (sb + SM_TO + g * 640));
                if (s >= 0) stg128(reinterpret_cast<char*>(g_ox) + (((L & 0x1C0) << 7) + (L & 0x30) + (((ui - 3) * SEG + 8 * j) * HD + h * DH + 32 * g) * 2), r);
                TL(26);
            }
            if (s + 3 < NSEG) {
                PHASE(3);
                const uint32_t rt = L + (sb + SM_RT + 8192 + g * 1024), so = FRAG() + (sb + SM_STG + 4096);
                mbar_wait_w(sb + MB_RT1, it & 1);
                TL(28);
                uint32_t w[4];
                if (RT_BF & 2) {
                    const uint4 v = lds128(rt);
                    w[0] = pack_bf16(o[0] + bf_lo(v.x), o[1] + bf_hi(v.x)); w[1] = pack_bf16(o[2] + bf_lo(v.y), o[3] + bf_hi(v.y));
                    w[2] = pack_bf16(o[4] + bf_lo(v.z), o[5] + bf_hi(v.z)); w[3] = pack_bf16(o[6] + bf_lo(v.w), o[7] + bf_hi(v.w));
                } else
#pragma unroll
                for (int i = 0; i < 2; i++) {
                    const uint4 v = lds128(rt + i * 512);
                    w[2 * i] = pack_bf16(o[4 * i] + __uint_as_float(v.x), o[4 * i + 1] + __uint_as_float(v.y));
                    w[2 * i + 1] = pack_bf16(o[4 * i + 2] + __uint_as_float(v.z), o[4 * i + 3] + __uint_as_float(v.w));
                }
                stsm4t(so, w[0], w[1], w[2], w[3]);
                __syncwarp();
                mbar_arrive_if0(L, sb + MB_STG);
                TL(15);
            }
        }
    }
    KT_END(2);
    asm volatile("barrier.cluster.arrive.relaxed; barrier.cluster.wait;" ::: "memory");
}
constexpr int B_UCH = 73 * 64;
constexpr int B_SCH = 33 * 64;
constexpr int B_KLEN = 2128;
constexpr int B_KCH = 2 * B_KLEN * 2 + 64;
constexpr int B_KBOX = 136 * 32;
constexpr int B_SM_U = 0;
constexpr int B_SM_S = 8 * B_UCH;
constexpr int B_SM_K = B_SM_S + 8 * B_SCH;
constexpr int B_SM_KT = B_SM_K + 8 * B_KCH;
constexpr int B_SM_VT = B_SM_KT + 8 * B_KBOX;
constexpr int B_SM_QT = B_SM_VT + 32768;
constexpr int B_SM_BAR = B_SM_QT + 32768;
constexpr int B_SMEM = B_SM_BAR + 128 + 512;
static_assert(B_SM_KT % 256 == 0 && B_SM_S % 512 == 0 && B_SMEM <= 232448, "tiles");
constexpr int PROBE_N = 4;
#define PROBE_R 2
constexpr int B_C = 2056;

__device__ __forceinline__ uint32_t atomic_round_trip(char* p) {
    uint32_t t0, t1, v;
    asm volatile("{.reg .pred p;\n"
                 "mov.u32 %0, %%clock;\n"
                 "atom.relaxed.gpu.global.add.u32 %2, [%3], 1;\n"
                 "setp.ne.u32 p, %2, 0x7FFFFFFF;\n"
                 "mov.u32 %1, 0;\n"
                 "@p mov.u32 %1, %%clock;}" : "=&r"(t0), "=&r"(t1), "=&r"(v) : "l"(p) : "memory");
    return t1 - t0;
}
__device__ __forceinline__ uint32_t round_trips(char* a, char* b, uint32_t stride, int lane) {
    for (int i = lane >> 3; i < 2 * PROBE_N; i += 4) stg128(((i & 1) ? b : a) + (i >> 1) * stride + (lane & 7) * 16, make_uint4(0, 0, 0, 0));
    __syncwarp();
    uint32_t ta = 0xFFFF, tb = 0xFFFF;
    if (lane == 0) {
        __threadfence();
#pragma unroll 1
        for (int i = 0; i < PROBE_N; i++) { ta = min(ta, atomic_round_trip(a + i * stride)); tb = min(tb, atomic_round_trip(b + i * stride)); }
    }
    __syncwarp();
    return ta | (tb << 16);
}
__device__ __forceinline__ void measure_distance(char* mbox, int lane) {
    const uint32_t b = blockIdx.x;
    unsigned smid;
    asm volatile("mov.u32 %0, %%smid;" : "=r"(smid));
    char* w1 = mbox + WIN + (b & 31) * 128;
    uint32_t r = 0xFFFFFFFF;
#pragma unroll 1
    for (int i = 0; i < PROBE_R; i++) r = __vminu2(r, round_trips(w1 + page_off(50 + 5 * i + (b >> 5), 0), w1 + page_off(50 + 5 * i + (b >> 5), 1), 16384, lane));
    if (lane == 0) g_cls[smid] = r;
    if (b == 128) {
        char *p = mbox + page_off(0, 0), *q = mbox + page_off(0, 1);
        uint32_t r0 = 0xFFFFFFFF;
#pragma unroll 1
        for (int i = 0; i < PROBE_R; i++) r0 = __vminu2(r0, round_trips(p, q, 128, lane));
        if (lane == 0) { g_reg[1] = ((r0 & 0xFFFF) > (r0 >> 16)) != ((r & 0xFFFF) > (r >> 16)); if (!EARLY_ROLE) g_reg[0] = 0; g_reg[2] = 0; }
        const uint4 sent = make_uint4(SENT, SENT, SENT, SENT);
        stg128(p + lane * 16, sent); stg128(q + lane * 16, sent);
    }
    if (b == 129) for (int i = lane; i < 128; i += 32) g_xflag[i] = 0;
}

#define SP(i)
#define SP2(i)
#define OUT_STG 0
#define PF_STOP 1
#define SENT_AT 3
#define Q_LATE 1
#define PF_DEPTH 4
#define PF_STRIDE 256
struct ChainInputs { const char* w[4]; const char *x, *mem0; };
#define EF_MASK 15
#define EF(i) (((EF_MASK >> (i)) & 1) ? policy_evict_first() : policy_evict_normal())
__device__ __forceinline__ void l2_prefetch(const char* p, uint32_t bytes) {
    asm volatile("cp.async.bulk.prefetch.L2.global [%0], %1;" ::"l"(p), "r"(bytes) : "memory");
}
#define WG_CONV(N, LIST, A0, A1, A2, A3, LO, OF, ...) \
    if constexpr (NN == N) asm volatile("{.reg .b32 l; .reg .b64 e; add.u32 l, %" #LO ", %" #OF "; mov.b64 e, {l, 0x80000020};\n" \
        "wgmma.mma_async.sync.aligned.m64n" #N "k16.f32.bf16.bf16 {" LIST "}, {%" #A0 ",%" #A1 ",%" #A2 ",%" #A3 "}, e, 1, 1, 1, 0;}" \
        : __VA_ARGS__ : "r"(a[0]), "r"(a[1]), "r"(a[2]), "r"(a[3]), "r"(lo), "n"(OFF));
#define WL4 "%0,%1,%2,%3"
#define WL8 WL4 ",%4,%5,%6,%7"
#define WL12 WL8 ",%8,%9,%10,%11"
#define WL16 WL12 ",%12,%13,%14,%15"
#define WL20 WL16 ",%16,%17,%18,%19"
#define WL24 WL20 ",%20,%21,%22,%23"
#define WL28 WL24 ",%24,%25,%26,%27"
#define WL32 WL28 ",%28,%29,%30,%31"
template <int NN, int OFF> __device__ __forceinline__ void wgmma_conv(float (&d)[32], const uint32_t (&a)[4], uint32_t lo) {
    WG_CONV(8, WL4, 4, 5, 6, 7, 8, 9, R4(0))
    WG_CONV(16, WL8, 8, 9, 10, 11, 12, 13, R4(0), R4(4))
    WG_CONV(24, WL12, 12, 13, 14, 15, 16, 17, R4(0), R4(4), R4(8))
    WG_CONV(32, WL16, 16, 17, 18, 19, 20, 21, R16(0))
    WG_CONV(40, WL20, 20, 21, 22, 23, 24, 25, R16(0), R4(16))
    WG_CONV(48, WL24, 24, 25, 26, 27, 28, 29, R16(0), R4(16), R4(20))
    WG_CONV(56, WL28, 28, 29, 30, 31, 32, 33, R16(0), R4(16), R4(20), R4(24))
    WG_CONV(64, WL32, 32, 33, 34, 35, 36, 37, R16(0), R16(16))
}
__device__ __forceinline__ void copy_to_peer(uint32_t dst, uint32_t src, uint32_t bytes, uint32_t bar) {
    asm volatile("cp.async.bulk.shared::cluster.shared::cta.mbarrier::complete_tx::bytes [%0], [%1], %2, [%3];" ::"r"(dst), "r"(src), "r"(bytes), "r"(bar) : "memory");
}
__device__ __forceinline__ uint32_t lds_volatile(uint32_t a) {
    uint32_t v;
    asm volatile("ld.volatile.shared.u32 %0, [%1];" : "=r"(v) : "r"(a) : "memory");
    return v;
}
__device__ __forceinline__ uint32_t swz64(uint32_t a) { return a ^ ((a >> 3) & 0x30); }
__device__ __forceinline__ void fence_async() { asm volatile("fence.proxy.async.shared::cta;" ::: "memory"); }

__global__ void __cluster_dims__(2, 1, 1) __launch_bounds__(576, 1)
ssm_kernel(const __grid_constant__ CUtensorMap mapK, const __grid_constant__ CUtensorMap mapV, const __grid_constant__ CUtensorMap mapQ,
           const __grid_constant__ CUtensorMap mapO, const bf16* __restrict__ shiftk, const bf16* __restrict__ ssmk, const bf16* __restrict__ Dv,
           char* __restrict__ mbox, const __grid_constant__ ChainInputs ci, bf16* __restrict__ outp) {
    extern __shared__ __align__(128) uint8_t smem_raw[];
    const uint32_t sb = (smem_u32(smem_raw) + 511) & ~511u;
    const int rank = blockIdx.x & 1, ch0 = blockIdx.x * 8, c16 = ch0 & ~15, t0 = rank * 1024;
    const int t = threadIdx.x, warp = t >> 5, lane = t & 31;
    const uint32_t bar = sb + B_SM_BAR, barQ = bar + 64, barU = bar + 72, barY = bar + 80, flag = bar + 88;
    SP(0);
    if (lane == 0 && warp < 16 && blockIdx.x < 128) {
        const int i = warp >> 1;
        if (warp & 1) {
            if (i < 3) { mbar_init(barQ + i * 8, 1); mbar_expect_tx(barQ + i * 8, i ? 16384 : 32768); }
            if (i == 3) sts32(flag, 0);
        } else {
            mbar_init(bar + i * 8, 1);
            asm volatile("fence.mbarrier_init.release.cluster;" ::: "memory");
            mbar_expect_tx(bar + i * 8, B_KBOX + 4096);
            tma_load_2d(sb + B_SM_KT + i * B_KBOX, &mapK, c16, t0 + i * 128 - 8, bar + i * 8, EF(0));
            tma_load_2d(sb + B_SM_VT + i * 4096, &mapV, c16, t0 + i * 128, bar + i * 8, EF(0));
        }
        asm volatile("fence.mbarrier_init.release.cluster;" ::: "memory");
    }
    __syncwarp();
    if (warp == 14) SP2(14);
    KT_START(1);
    if (warp == 17) {
        launch_dependents();
        asm volatile("barrier.cluster.arrive.relaxed.aligned;" ::: "memory");
        measure_distance(mbox, lane);
        asm volatile("barrier.cluster.wait.aligned;" ::: "memory");
        KT_MARK(14);
        return;
    }
    if (blockIdx.x >= 128) return;
    if (warp == 16) {
        asm volatile("barrier.cluster.arrive.relaxed.aligned; barrier.cluster.wait.aligned;" ::: "memory");
        SP2(8);
        if (Q_LATE) for (int i = 0; i < 8; i++) { mbar_wait_w(bar + i * 8, 0); SP2(i); }
        if (lane < 8) tma_load_2d(sb + B_SM_QT + lane * 4096, &mapQ, c16, t0 + lane * 128, barQ, EF(3));
        if (!Q_LATE) for (int i = 0; i < 8; i++) mbar_wait_w(bar + i * 8, 0);
        if (lane == 0) {
            l2_prefetch(ci.x + blockIdx.x * 2048, 2048);
            if (blockIdx.x < 8) l2_prefetch(ci.mem0 + blockIdx.x * 2048, 2048);
        }
        uint32_t v[PF_DEPTH], acc = 0;
#pragma unroll
        for (int u = 0; u < PF_DEPTH; u++) v[u] = 0;
        constexpr int PER = 32 * PF_STRIDE, NW = 65536 / PER;
#define PF_N (4 * NW)
        int i = 0;
#pragma unroll 1
        for (; i < PF_N && lds_volatile(flag) == 0; i += PF_DEPTH) {
#pragma unroll
            for (int u = 0; u < PF_DEPTH; u++) {
                const char* a = ci.w[(i + u) / NW] + blockIdx.x * 65536 + ((i + u) % NW) * PER + lane * PF_STRIDE;
                acc |= v[u];
                asm volatile("ld.global.cg.L2::256B.u32 %0, [%1];" : "=r"(v[u]) : "l"(a) : "memory");
            }
        }
#pragma unroll
        for (int u = 0; u < PF_DEPTH; u++) acc |= v[u];
        if (acc == 0x7FFF7FFFu && v[0] == 0x7FFEu) g_err = 1;
        SP2(12);
        KT_MARK(15);
        return;
    }
    asm volatile("barrier.cluster.arrive.relaxed.aligned;" ::: "memory");
    const int far = warp & 1, unit = rank ^ far;
    uint32_t w[4];
    uint32_t d2;
    asm volatile("ld.global.nc.u32 %0, [%1];" : "=r"(d2) : "l"(Dv + ch0 + (warp >> 2) * 2));
    {
        const int ch = warp & 7, half = warp >> 3;
        const uint32_t kb = sb + B_SM_K + ch * B_KCH;
        const uint4* src = reinterpret_cast<const uint4*>(ssmk + (size_t)(ch0 + ch) * S_LEN);
        uint4 kr[4];
#pragma unroll
        for (int i = 0; i < 4; i++) kr[i] = ldg128(src + half * 128 + i * 32 + lane, EF(1));
        const uint32_t edge = half ? 0u : __ldg(reinterpret_cast<const uint32_t*>(src + 128));
        const uint2 sw = __ldg(reinterpret_cast<const uint2*>(shiftk + (size_t)(c16 + unit * 8 + (lane >> 2)) * 4));
        w[0] = __byte_perm(sw.x, 0, 0x1010); w[1] = __byte_perm(sw.x, 0, 0x3232); w[2] = __byte_perm(sw.y, 0, 0x1010); w[3] = __byte_perm(sw.y, 0, 0x3232);
        if (half) sts128(sb + B_SM_U + ch * B_UCH + 4096 + lane * 16, make_uint4(0, 0, 0, 0));
#pragma unroll
        for (int i = 0; i < 4; i++) {
            const uint4 lo = kr[i];
            const uint32_t nx = __shfl_down_sync(~0u, lo.x, 1), n0 = (i < 3) ? __shfl_sync(~0u, kr[i < 3 ? i + 1 : 3].x, 0) : edge;
            const uint32_t hix = (lane < 31) ? nx : n0;
            const int c = 256 - (half * 128 + 32 * i + lane);
            sts128(kb + c * 16, make_uint4(__byte_perm(hix, lo.w, 0x7610), __byte_perm(lo.w, lo.z, 0x7610), __byte_perm(lo.z, lo.y, 0x7610), __byte_perm(lo.y, lo.x, 0x7610)));
            sts128(kb + B_KLEN * 2 + 64 + c * 16, make_uint4(__byte_perm(lo.w, lo.w, 0x1032), __byte_perm(lo.z, lo.z, 0x1032), __byte_perm(lo.y, lo.y, 0x1032), __byte_perm(lo.x, lo.x, 0x1032)));
        }
        const uint32_t k0w = __shfl_sync(~0u, kr[0].x, 0);
        if (half == 0 && lane < 8) {
            sts128(kb + (257 + lane) * 16, make_uint4(lane == 0 ? (k0w & 0xFFFFu) : 0u, 0u, 0u, 0u));
            sts128(kb + B_KLEN * 2 + 64 + (257 + lane) * 16, make_uint4(0u, 0u, 0u, 0u));
        }
    }
    auto sentinels = [&]() {
        const uint4 sent = make_uint4(SENT, SENT, SENT, SENT);
        char* p0 = mbox + blockIdx.x * 16384 + t * 16;
        if (blockIdx.x != 0 || (t & 255) >= 32) stg128(p0, sent);
        stg128(p0 + 8192, sent);
        char* p1 = mbox + WIN + blockIdx.x * 12800 + t * 16;
        stg128(p1, sent);
        if (t < 288) stg128(p1 + 8192, sent);
    };
    if (SENT_AT == 1) sentinels();
    asm volatile("barrier.cluster.wait.acquire.aligned;" ::: "memory");
    SP(1);
    {
        const int box = warp >> 1, row0 = 63 - 32 * rank - 4 * box;
        const uint32_t kt = sb + B_SM_KT + box * B_KBOX + 256 + lane * 32, s0 = (unit ^ ((lane >> 2) & 1)) * 16;
        const uint32_t a0 = kt + s0, a2 = kt - 64 + (unit ^ (((lane + 6) >> 2) & 1)) * 16, a4 = kt - 128 + (s0 ^ 16), av = sb + B_SM_VT + box * 4096 + lane * 32 + s0;
        const uint32_t ul = (lane & 7) * B_UCH + row0 * 64 + (lane >> 3) * 16;
        const uint32_t ud = sb + (far ? B_SM_S + (lane & 7) * (B_SCH - B_UCH) - (1 - rank) * 2048 : B_SM_U);
        mbar_wait_w(bar + box * 8, 0);
        SP(2);
#pragma unroll
        for (int i = 0; i < 4; i++) {
            uint32_t k0[4], k2[4], k4[4], vv[4], o[4];
            ldsm4t(k0, a0 + i * 1024); ldsm4t(k2, a2 + i * 1024); ldsm4t(k4, a4 + i * 1024); ldsm4t(vv, av + i * 1024);
#pragma unroll
            for (int j = 0; j < 4; j++) {
                uint32_t a = bf16_mul(__byte_perm(k4[j], k2[j], 0x5432), w[3]);
                a = bf16_add(a, bf16_mul(k2[j], w[2]));
                a = bf16_add(a, bf16_mul(__byte_perm(k2[j], k0[j], 0x5432), w[1]));
                a = bf16_add(a, bf16_mul(k0[j], w[0]));
                o[j] = bf16_mul(a, vv[j]);
            }
            stsm4(ud + swz64(ul - i * 64), o[0], o[1], o[2], o[3]);
        }
        fence_async();
        __syncwarp();
        if (far && lane < 8) {
            const uint32_t o = lane * B_UCH + (row0 - 3) * 64;
            copy_to_peer(peer_addr(sb + B_SM_U + o, rank ^ 1), ud + o, 256, peer_addr(barU, rank ^ 1));
        }
    }
    bar_sync(1, 512);
    mbar_wait_w(barU, 0);
    if (SENT_AT == 2) sentinels();
    SP(3);
    const int wg = warp >> 2, wq = warp & 3, hi = wq >> 1, g = lane >> 2, tq = lane & 3;
    const uint32_t zero = lds32(sb + B_SM_U + 4096);
#pragma unroll 1
    for (int cc = 0; cc < 2; cc++) {
        const int ch = 2 * wg + cc;
        const uint32_t kb = sb + B_SM_K + ch * B_KCH, ub = sb + B_SM_U + ch * B_UCH;
        const uint32_t dw = __byte_perm(d2, 0, cc ? 0x3232 : 0x1010);
        const int e0 = B_C - g + 2 * tq;
        const uint32_t f0 = ((e0 & 1) ? (kb + B_KLEN * 2 + 64 + (e0 - 1) * 2) : (kb + e0 * 2)) - 32 * wq;
        const uint32_t lo = uniform((ub >> 4) | 0x10000);
        float d[32];
#pragma unroll
        for (int i = 0; i < 32; i++) d[i] = 0.f;
        uint32_t A[2][2][4];
        static_for<0, 32>([&](auto jc) {
            constexpr int j = decltype(jc)::value, N = 64 - 8 * (j / 4);
            if (j >= 2) wg_wait<1>();
            uint32_t(&a)[4] = A[j & 1][0];
            uint32_t(&b)[4] = A[j & 1][1];
            a[0] = lds32(f0 - 128 * j); a[1] = lds32(f0 - 128 * j - 16); a[2] = lds32(f0 - 128 * j + 16);
            b[0] = lds32(f0 - 128 * j + 32); b[2] = lds32(f0 - 128 * j + 48);
            a[3] = a[0] ^ zero; b[1] = a[2] ^ zero; b[3] = b[0] ^ zero;
            wg_fence();
            wgmma_conv<N, 8 * j>(d, a, lo);
            wgmma_conv<N, 8 * j + 2>(d, b, lo);
            wg_commit();
        });
        wg_wait<0>();
        if (cc) SP(4);
        if (PF_STOP == 1 && cc && t == 0) sts32(flag, 1);
        bar_sync(2 + wg, 128);
        if (!hi && tq == 3) { float x = d[13]; d[13] = d[29]; d[29] = x; x = d[15]; d[15] = d[31]; d[31] = x; }
        if (hi && tq == 0) { d[0] = 0.f; d[2] = 0.f; }
        {
            const uint32_t xs = kb + (wq ^ 2) * 2048 + lane * 4;
            const uint32_t xn = hi ? xs + (tq ? 124 : 140) : xs + (tq < 3 ? 4 : -12), wrap = hi ? (tq ? 0 : -1) : (tq < 3 ? 0 : 1);
#pragma unroll
            for (int nb = 0; nb < 4; nb++) {
                const uint32_t xw = xn + ((nb + wrap) & 3) * 512;
#pragma unroll
                for (int i = 0; i < 2; i++) {
                    const float e0v = hi ? d[4 * nb + 2 * i] : d[16 + 4 * nb + 2 * i], e1v = hi ? d[4 * nb + 2 * i + 1] : d[16 + 4 * nb + 2 * i + 1];
                    sts32(hi ? xw + i * 256 : xs + nb * 512 + i * 256 + 128, __float_as_uint(e0v));
                    sts32(hi ? xs + nb * 512 + i * 256 : xw + i * 256, __float_as_uint(e1v));
                }
            }
        }
        bar_sync(2 + wg, 128);
#pragma unroll
        for (int p = 0; p < 2; p++) {
            int row = 16 * p + (lane >> 4) * 8 + (lane & 7);
            row = hi ? row + 31 : row == 31 ? 63 : row;
            const uint32_t a = sb + B_SM_U + swz64(ch * B_UCH + row * 64 + ((wq & 1) * 2 + ((lane >> 3) & 1)) * 16);
            uint32_t u[4];
            ldsm4t(u, a);
#pragma unroll
            for (int b = 0; b < 4; b++) {
                const int r = 8 * p + 2 * b;
                const float y0 = (hi ? d[16 + r] : d[r]) + __uint_as_float(lds32(kb + wq * 2048 + r * 128 + lane * 4));
                const float y1 = (hi ? d[17 + r] : d[r + 1]) + __uint_as_float(lds32(kb + wq * 2048 + r * 128 + 128 + lane * 4));
                u[b] = bf16_add(pack_bf16(y0, y1), bf16_mul(u[b], dw));
            }
            stsm4t(a, u[0], u[1], u[2], u[3]);
        }
        fence_async();
        bar_sync(2 + wg, 128);
        if (SENT_AT == 3 && cc == 0) sentinels();
        if (wq == 0 && lane == 0) copy_to_peer(peer_addr(sb + B_SM_S + ch * B_SCH, rank ^ 1), ub + rank * 2048, 2048, peer_addr(barY, rank ^ 1));
    }
    if (PF_STOP == 2 && t == 0) sts32(flag, 1);
    SP(5);
    mbar_wait_w(barQ, 0);
    bar_sync(1, 512);
    mbar_wait_w(barY, 0);
    asm volatile("barrier.cluster.arrive.relaxed.aligned;" ::: "memory");
    SP(6);
#pragma unroll
    for (int i = 0; i < 4; i++) {
        const int fr = i & 1, row = 63 - 32 * rank - 2 * warp - (i >> 1);
        const uint32_t qa = sb + B_SM_QT + warp * 2048 + (i >> 1) * 1024 + lane * 32 + ((rank ^ fr ^ (lane >> 2)) & 1) * 16;
        uint32_t y[4], q[4];
        ldsm4t(y, sb + (fr ? B_SM_S + (lane & 7) * (B_SCH - B_UCH) - (1 - rank) * 2048 : B_SM_U) + swz64((lane & 7) * B_UCH + row * 64 + (lane >> 3) * 16));
        ldsm4(q, qa);
        stsm4(qa, bf16_mul(q[0], y[0]), bf16_mul(q[1], y[1]), bf16_mul(q[2], y[2]), bf16_mul(q[3], y[3]));
    }
    fence_async();
    __syncwarp();
    if (lane == 0) {
        asm volatile("cp.async.bulk.tensor.2d.global.shared::cta.bulk_group.L2::cache_hint [%0, {%2, %3}], [%1], %4;"
                     ::"l"(&mapO), "r"(sb + B_SM_QT + warp * 2048), "r"(DM + c16), "r"(t0 + warp * 64), "l"(EF(4)) : "memory");
        asm volatile("cp.async.bulk.commit_group;" ::: "memory");
    }
    if (SENT_AT == 0) sentinels();
    if (warp == 0) SP2(10);
    if (lane == 0) asm volatile("cp.async.bulk.wait_group.read 0;" ::: "memory");
    __syncwarp();
    if (warp == 0) SP2(11);
    asm volatile("barrier.cluster.wait.aligned;" ::: "memory");
    SP(7);
    KT_END(1);
}

typedef CUresult (*EncodeFn)(CUtensorMap*, CUtensorMapDataType, cuuint32_t, void*, const cuuint64_t*, const cuuint64_t*, const cuuint32_t*,
                             const cuuint32_t*, CUtensorMapInterleave, CUtensorMapSwizzle, CUtensorMapL2promotion, CUtensorMapFloatOOBfill);

static void make_map(EncodeFn fn, CUtensorMap* m, const void* ptr, uint64_t inner, uint64_t outer, uint32_t box_in, uint32_t box_out,
                     CUtensorMapL2promotion promo = CU_TENSOR_MAP_L2_PROMOTION_L2_256B) {
    cuuint64_t dims[2] = {inner, outer};
    cuuint64_t strides[1] = {inner * 2};
    cuuint32_t box[2] = {box_in, box_out};
    cuuint32_t es[2] = {1, 1};
    fn(m, CU_TENSOR_MAP_DATA_TYPE_BFLOAT16, 2, const_cast<void*>(ptr), dims, strides, box, es, CU_TENSOR_MAP_INTERLEAVE_NONE,
       CU_TENSOR_MAP_SWIZZLE_128B, promo, CU_TENSOR_MAP_FLOAT_OOB_FILL_NONE);
}

#define G2_ST 7
#define PROMO_W CU_TENSOR_MAP_L2_PROMOTION_L2_256B
#define PROMO_O CU_TENSOR_MAP_L2_PROMOTION_L2_256B
#define SSM_PROMO CU_TENSOR_MAP_L2_PROMOTION_NONE
extern "C" void kernel_launch(void* const* d_in, const int* in_sizes, int n_in, void* d_out, int out_size) {
    const bf16* x = (const bf16*)d_in[0];
    const bf16* mem0 = (const bf16*)d_in[1];
    const bf16* Wq = (const bf16*)d_in[2];
    const bf16* Wk = (const bf16*)d_in[3];
    const bf16* Wv = (const bf16*)d_in[4];
    const bf16* Wo = (const bf16*)d_in[5];
    const bf16* Bq = (const bf16*)d_in[7];
    const bf16* Bk = (const bf16*)d_in[8];
    const bf16* Bv = (const bf16*)d_in[9];
    const bf16* Bsh = (const bf16*)d_in[10];
    const bf16* Bssm = (const bf16*)d_in[11];
    const bf16* BD = (const bf16*)d_in[12];
    bf16* out = (bf16*)d_out;

    static bool init = false;
    static EncodeFn enc = nullptr;
    static void *p_tok, *p_ox, *p_mbox;
    static int nclusters = 64;
    if (!init) {
        cudaDriverEntryPointQueryResult qr;
        cudaGetDriverEntryPoint("cuTensorMapEncodeTiled", (void**)&enc, cudaEnableDefault, &qr);
        cudaGetSymbolAddress(&p_tok, g_tok);
        cudaGetSymbolAddress(&p_ox, g_ox);
        cudaGetSymbolAddress(&p_mbox, g_mbox);
        cudaFuncSetAttribute(proj_kernel<96, G2_ST>, cudaFuncAttributeMaxDynamicSharedMemorySize, PROJ_SMEM);
        cudaFuncSetAttribute(proj_kernel<128, 7>, cudaFuncAttributeMaxDynamicSharedMemorySize, PROJ_SMEM);
        cudaFuncSetAttribute(chain_kernel, cudaFuncAttributeMaxDynamicSharedMemorySize, CHAIN_SMEM);
        cudaFuncSetAttribute(ssm_kernel, cudaFuncAttributeMaxDynamicSharedMemorySize, B_SMEM);
        cudaLaunchConfig_t cfg = {};
        cfg.gridDim = dim3(132); cfg.blockDim = dim3(384); cfg.dynamicSmemBytes = CHAIN_SMEM;
        cudaLaunchAttribute at[1];
        at[0].id = cudaLaunchAttributeClusterDimension; at[0].val.clusterDim.x = 2; at[0].val.clusterDim.y = 1; at[0].val.clusterDim.z = 1;
        cfg.attrs = at; cfg.numAttrs = 1;
        int n = 0;
        if (cudaOccupancyMaxActiveClusters(&n, chain_kernel, &cfg) == cudaSuccess && n > 64) nclusters = n < 66 ? n : 66;
        (void)cudaGetLastError();
        init = true;
    }
    char* mbox = (char*)(((uintptr_t)p_mbox + 2 * WIN - 1) & ~(uintptr_t)(2 * WIN - 1));
    CUtensorMap mX, mT32, mT16, mTQ, mKV, mWq, mWk, mWv, mWoC, mWo, mOxE, mOutE, mOx, mOut;
    {
        cuuint64_t dims[3] = {64, S_LEN, DM / 64};
        cuuint64_t strides[2] = {DM * 2, 128};
        cuuint32_t box[3] = {64, 32, 4};
        cuuint32_t es[3] = {1, 1, 1};
        enc(&mX, CU_TENSOR_MAP_DATA_TYPE_BFLOAT16, 3, const_cast<bf16*>(x), dims, strides, box, es, CU_TENSOR_MAP_INTERLEAVE_NONE,
            CU_TENSOR_MAP_SWIZZLE_128B, CU_TENSOR_MAP_L2_PROMOTION_L2_256B, CU_TENSOR_MAP_FLOAT_OOB_FILL_NONE);
    }
    make_map(enc, &mT32, p_tok, DH, 4 * NH * 3 * SEG, 64, 32, CU_TENSOR_MAP_L2_PROMOTION_L2_128B);
    make_map(enc, &mT16, p_tok, DH, 4 * NH * 3 * SEG, 64, 16, CU_TENSOR_MAP_L2_PROMOTION_L2_128B);
    {
        cuuint64_t dims[2] = {512, 4 * NH * 12};
        cuuint64_t strides[1] = {2048};
        cuuint32_t box[2] = {256, 4};
        cuuint32_t es[2] = {1, 1};
        enc(&mTQ, CU_TENSOR_MAP_DATA_TYPE_UINT32, 2, p_tok, dims, strides, box, es, CU_TENSOR_MAP_INTERLEAVE_NONE,
            CU_TENSOR_MAP_SWIZZLE_NONE, CU_TENSOR_MAP_L2_PROMOTION_L2_128B, CU_TENSOR_MAP_FLOAT_OOB_FILL_NONE);
    }
    {
        cuuint64_t dims[3] = {64, 4 * NH * 3 * SEG, 2};
        cuuint64_t strides[2] = {DH * 2, 128};
        cuuint32_t box[3] = {64, 32, 2};
        cuuint32_t es[3] = {1, 1, 1};
        enc(&mKV, CU_TENSOR_MAP_DATA_TYPE_BFLOAT16, 3, p_tok, dims, strides, box, es, CU_TENSOR_MAP_INTERLEAVE_NONE,
            CU_TENSOR_MAP_SWIZZLE_128B, CU_TENSOR_MAP_L2_PROMOTION_L2_128B, CU_TENSOR_MAP_FLOAT_OOB_FILL_NONE);
    }
    make_map(enc, &mWq, Wq, HD, DM, 64, 16, CU_TENSOR_MAP_L2_PROMOTION_L2_128B);
    make_map(enc, &mWk, Wk, HD, DM, 64, 16, CU_TENSOR_MAP_L2_PROMOTION_L2_128B);
    make_map(enc, &mWv, Wv, HD, DM, 64, 16, CU_TENSOR_MAP_L2_PROMOTION_L2_128B);
    make_map(enc, &mWoC, Wo, DM, HD, 64, PRO3 ? 16 : 128, CU_TENSOR_MAP_L2_PROMOTION_L2_128B);
    const bool early = nclusters >= 66;
    make_map(enc, &mWo, Wo, DM, HD, 64, 64, PROMO_W);
    make_map(enc, &mOxE, p_ox, HD, S_LEN, 64, EARLY_NT / 2);
    make_map(enc, &mOutE, out, OUT_LD, S_LEN, 64, EARLY_NT);
    make_map(enc, &mOx, p_ox, HD, S_LEN, 64, (early ? 96 : 128) >> FIN_SO, PROMO_O);
    make_map(enc, &mOut, out, OUT_LD, S_LEN, 64, early ? 96 : 128);

    CUtensorMap mB[4];
    for (int i = 0; i < 4; i++) {
        cuuint64_t dims[2] = {(cuuint64_t)(i < 3 ? DM : OUT_LD), S_LEN};
        cuuint64_t strides[1] = {dims[0] * 2};
        cuuint32_t box[2] = {16, i == 0 ? 136u : i < 3 ? 128u : 64u};
        cuuint32_t es[2] = {1, 1};
        enc(&mB[i], CU_TENSOR_MAP_DATA_TYPE_BFLOAT16, 2, const_cast<bf16*>(i == 0 ? Bk : i == 1 ? Bv : i == 2 ? Bq : out), dims, strides, box, es,
            CU_TENSOR_MAP_INTERLEAVE_NONE, CU_TENSOR_MAP_SWIZZLE_32B, SSM_PROMO, CU_TENSOR_MAP_FLOAT_OOB_FILL_NONE);
    }
    cudaStream_t st = cudaStreamPerThread;
    const ChainInputs ci = {{(const char*)Wv, (const char*)Wk, (const char*)Wq, (const char*)Wo}, (const char*)x, (const char*)mem0};
    ssm_kernel<<<132, 576, B_SMEM, st>>>(mB[0], mB[1], mB[2], mB[3], Bsh, Bssm, BD, mbox, ci, out);
    cudaLaunchAttribute pdl[1];
    pdl[0].id = cudaLaunchAttributeProgrammaticStreamSerialization; pdl[0].val.programmaticStreamSerializationAllowed = 1;
    cudaLaunchConfig_t lc = {};
    lc.stream = st; lc.attrs = pdl;
    lc.gridDim = dim3(2 * nclusters); lc.blockDim = dim3(384); lc.dynamicSmemBytes = CHAIN_SMEM; lc.numAttrs = PDL & 1;
    cudaLaunchKernelEx(&lc, chain_kernel, mX, mT32, mT16, mTQ, mKV, mWq, mWk, mWv, mWoC, mem0, mbox);
    lc.gridDim = dim3(2 * nclusters); lc.blockDim = dim3(PROJ_THREADS); lc.dynamicSmemBytes = PROJ_SMEM; lc.numAttrs = (PDL >> 1) & 1;
    cudaLaunchKernelEx(&lc, early ? proj_kernel<96, G2_ST> : proj_kernel<128, 7>, mWo, mOx, mOut, mOxE, mOutE);
}
```

```cpp
#include <cuda_runtime.h>
#include <cuda_bf16.h>
#include <cuda.h>
#include <stdint.h>
#include <type_traits>

typedef __nv_bfloat16 bf16;

constexpr int S_LEN = 2048, DM = 1024, NH = 32, DH = 128, NSEG = 64, SEG = 32;
constexpr int HD = NH * DH;
constexpr int OUT_LD = 2048;
constexpr unsigned SENT = 0xFFFFFFFFu;

__device__ bf16 g_tok[4 * NH * 3 * SEG * DH];
__device__ bf16 g_ox[(size_t)S_LEN * HD];
__device__ uint4 g_mbox[4 * 131072];
__device__ unsigned g_xflag[128];
__device__ unsigned g_reg[4];
__device__ __align__(16) unsigned g_cls[256];
__device__ unsigned g_err;
constexpr uint32_t WIN = 2u << 20;
__host__ __device__ constexpr uint32_t page_off(uint32_t idx, uint32_t c) {
    return ((idx & 1) << 13) | ((idx >> 1) << 16) | (((c ^ idx ^ (idx >> 1) ^ (idx >> 2) ^ (idx >> 4)) & 1) << 12);
}
#define STAT(i, c) (void)(c)
#define EARLY_ROLE 1
#define PDL 3

__device__ __forceinline__ void launch_dependents() { asm volatile("griddepcontrol.launch_dependents;" ::: "memory"); }
__device__ __forceinline__ void wait_prerequisites() { asm volatile("griddepcontrol.wait;" ::: "memory"); }
__device__ __forceinline__ void prefetch_map(const CUtensorMap* m) { asm volatile("prefetch.tensormap [%0];" ::"l"(m) : "memory"); }
#define KT_MARK(k)
#define KT_START(k)
#define KT_END(k)

__device__ __forceinline__ uint32_t smem_u32(const void* p) { return (uint32_t)__cvta_generic_to_shared(p); }
__device__ __forceinline__ void ldsm4(uint32_t& r0, uint32_t& r1, uint32_t& r2, uint32_t& r3, uint32_t a) {
    asm volatile("ldmatrix.sync.aligned.m8n8.x4.shared.b16 {%0,%1,%2,%3}, [%4];" : "=r"(r0), "=r"(r1), "=r"(r2), "=r"(r3) : "r"(a) : "memory");
}
__device__ __forceinline__ void ldsm4t(uint32_t& r0, uint32_t& r1, uint32_t& r2, uint32_t& r3, uint32_t a) {
    asm volatile("ldmatrix.sync.aligned.m8n8.x4.trans.shared.b16 {%0,%1,%2,%3}, [%4];" : "=r"(r0), "=r"(r1), "=r"(r2), "=r"(r3) : "r"(a) : "memory");
}
__device__ __forceinline__ void ldsm2(uint32_t& r0, uint32_t& r1, uint32_t a) {
    asm volatile("ldmatrix.sync.aligned.m8n8.x2.shared.b16 {%0,%1}, [%2];" : "=r"(r0), "=r"(r1) : "r"(a) : "memory");
}
__device__ __forceinline__ void stg128(void* p, uint4 v) {
    asm volatile("st.global.v4.u32 [%0], {%1,%2,%3,%4};" ::"l"(p), "r"(v.x), "r"(v.y), "r"(v.z), "r"(v.w) : "memory");
}
__device__ __forceinline__ void stsm4(uint32_t a, uint32_t r0, uint32_t r1, uint32_t r2, uint32_t r3) {
    asm volatile("stmatrix.sync.aligned.m8n8.x4.shared.b16 [%0], {%1,%2,%3,%4};" ::"r"(a), "r"(r0), "r"(r1), "r"(r2), "r"(r3) : "memory");
}
__device__ __forceinline__ void mma16816(float (&d)[4], uint32_t a0, uint32_t a1, uint32_t a2, uint32_t a3, uint32_t b0, uint32_t b1) {
    asm("mma.sync.aligned.m16n8k16.row.col.f32.bf16.bf16.f32 {%0,%1,%2,%3},{%4,%5,%6,%7},{%8,%9},{%0,%1,%2,%3};"
                 : "+f"(d[0]), "+f"(d[1]), "+f"(d[2]), "+f"(d[3])
                 : "r"(a0), "r"(a1), "r"(a2), "r"(a3), "r"(b0), "r"(b1));
}
__device__ __forceinline__ void mma1688(float (&d)[4], uint32_t a0, uint32_t a1, uint32_t b0) {
    asm("mma.sync.aligned.m16n8k8.row.col.f32.bf16.bf16.f32 {%0,%1,%2,%3},{%4,%5},{%6},{%0,%1,%2,%3};"
        : "+f"(d[0]), "+f"(d[1]), "+f"(d[2]), "+f"(d[3]) : "r"(a0), "r"(a1), "r"(b0));
}
__device__ __forceinline__ uint32_t movmat(uint32_t a) {
    uint32_t d;
    asm volatile("movmatrix.sync.aligned.m8n8.trans.b16 %0, %1;" : "=r"(d) : "r"(a));
    return d;
}
__device__ __forceinline__ uint32_t pack_bf16(float lo, float hi) {
    uint32_t r;
    asm("cvt.rn.bf16x2.f32 %0, %1, %2;" : "=r"(r) : "f"(hi), "f"(lo));
    return r;
}
__device__ __forceinline__ uint32_t bf16_mul(uint32_t a, uint32_t b) {
    uint32_t d;
    asm("mul.rn.bf16x2 %0, %1, %2;" : "=r"(d) : "r"(a), "r"(b));
    return d;
}
__device__ __forceinline__ uint32_t bf16_add(uint32_t a, uint32_t b) {
    uint32_t d;
    asm("add.rn.bf16x2 %0, %1, %2;" : "=r"(d) : "r"(a), "r"(b));
    return d;
}

__device__ __forceinline__ float bf16_round(float x) { return __bfloat162float(__float2bfloat16_rn(x)); }
__device__ __forceinline__ float bf_lo(uint32_t w) { return __uint_as_float(w << 16); }
__device__ __forceinline__ float bf_hi(uint32_t w) { return __uint_as_float(w & 0xFFFF0000u); }
__device__ __forceinline__ void bar_sync(int id, int n) { asm volatile("bar.sync %0, %1;" ::"r"(id), "r"(n) : "memory"); }
__device__ __forceinline__ void bar_sync_keep(int id, int n, uint32_t a, uint32_t b) {
    asm volatile("bar.sync %0, %1; // %2 %3" ::"r"(id), "r"(n), "r"(a), "r"(b) : "memory");
}
__device__ __forceinline__ bool bar_red_or(int id, int n, bool p) {
    uint32_t r;
    asm volatile("{.reg .pred p, q; setp.ne.u32 p, %3, 0; bar.red.or.pred q, %1, %2, p; selp.u32 %0, 1, 0, q;}" : "=r"(r) : "r"(id), "r"(n), "r"((uint32_t)p) : "memory");
    return r != 0;
}
__device__ __forceinline__ void bar_arrive(int id, int n) { asm volatile("bar.arrive %0, %1;" ::"r"(id), "r"(n) : "memory"); }
__device__ __forceinline__ void cp_async16(uint32_t dst, const void* src) {
    asm volatile("cp.async.cg.shared.global [%0], [%1], 16;" ::"r"(dst), "l"(src) : "memory");
}
__device__ __forceinline__ void cp_commit() { asm volatile("cp.async.commit_group;" ::: "memory"); }
template <int N> __device__ __forceinline__ void cp_wait() { asm volatile("cp.async.wait_group %0;" ::"n"(N) : "memory"); }
__device__ __forceinline__ uint4 ld_relaxed_v4(const void* p) {
    uint4 v;
    asm volatile("ld.relaxed.gpu.global.v4.u32 {%0,%1,%2,%3}, [%4];" : "=r"(v.x), "=r"(v.y), "=r"(v.z), "=r"(v.w) : "l"(p) : "memory");
    return v;
}
__device__ __forceinline__ void st_relaxed_u32(void* p, uint32_t v) { asm volatile("st.relaxed.gpu.global.u32 [%0], %1;" ::"l"(p), "r"(v) : "memory"); }
__device__ __forceinline__ void st_relaxed_v2(void* p, uint32_t a, uint32_t b) {
    asm volatile("st.relaxed.gpu.global.v2.u32 [%0], {%1,%2};" ::"l"(p), "r"(a), "r"(b) : "memory");
}
__device__ __forceinline__ void sts128(uint32_t a, uint4 v) {
    asm volatile("st.shared.v4.u32 [%0], {%1,%2,%3,%4};" ::"r"(a), "r"(v.x), "r"(v.y), "r"(v.z), "r"(v.w) : "memory");
}
__device__ __forceinline__ uint4 lds128(uint32_t a) {
    uint4 v;
    asm volatile("ld.shared.v4.u32 {%0,%1,%2,%3}, [%4];" : "=r"(v.x), "=r"(v.y), "=r"(v.z), "=r"(v.w) : "r"(a) : "memory");
    return v;
}
__device__ __forceinline__ void sts32(uint32_t a, uint32_t v) { asm volatile("st.shared.u32 [%0], %1;" ::"r"(a), "r"(v) : "memory"); }
__device__ __forceinline__ uint32_t lds32(uint32_t a) {
    uint32_t v;
    asm volatile("ld.shared.u32 %0, [%1];" : "=r"(v) : "r"(a) : "memory");
    return v;
}
__device__ __forceinline__ void mbar_init(uint32_t a, uint32_t c) { asm volatile("mbarrier.init.shared::cta.b64 [%0], %1;" ::"r"(a), "r"(c) : "memory"); }
__device__ __forceinline__ void mbar_expect_tx(uint32_t a, uint32_t bytes) {
    asm volatile("mbarrier.arrive.expect_tx.shared::cta.b64 _, [%0], %1;" ::"r"(a), "r"(bytes) : "memory");
}
__device__ __forceinline__ void mbar_arrive(uint32_t a) { asm volatile("mbarrier.arrive.shared::cta.b64 _, [%0];" ::"r"(a) : "memory"); }
__device__ __forceinline__ void mbar_wait(uint32_t a, uint32_t parity) {
    asm volatile("{.reg .pred p; .reg .u32 c;\n"
                 "mov.u32 c, 0;\n"
                 "MBW_LOOP:\n"
                 "add.u32 c, c, 1;\n"
                 "setp.gt.u32 p, c, 0x10000;\n"
                 "@!p mbarrier.try_wait.parity.shared::cta.b64 p, [%0], %1;\n"
                 "@!p bra.uni MBW_LOOP;}" ::"r"(a), "r"(parity) : "memory");
}
__device__ __forceinline__ void mbar_wait_w(uint32_t a, uint32_t parity) {
    asm volatile("{.reg .pred p; .reg .u32 c;\n"
                 "mov.u32 c, 0;\n"
                 "MBW_LOOP:\n"
                 "add.u32 c, c, 1;\n"
                 "setp.gt.u32 p, c, 0x10000;\n"
                 "@!p mbarrier.try_wait.parity.shared::cta.b64 p, [%0], %1;\n"
                 "vote.sync.all.pred p, p, 0xFFFFFFFF;\n"
                 "@!p bra.uni MBW_LOOP;}" ::"r"(a), "r"(parity) : "memory");
}
__device__ __forceinline__ void mbar_expect_tx_if0(uint32_t sel, uint32_t a, uint32_t bytes) {
    asm volatile("{.reg .pred p; setp.eq.u32 p, %2, 0; @p mbarrier.arrive.expect_tx.shared::cta.b64 _, [%0], %1;}" ::"r"(a), "r"(bytes), "r"(sel) : "memory");
}
__device__ __forceinline__ void mbar_arrive_if0(uint32_t sel, uint32_t a) {
    asm volatile("{.reg .pred p; setp.eq.u32 p, %1, 0; @p mbarrier.arrive.shared::cta.b64 _, [%0];}" ::"r"(a), "r"(sel) : "memory");
}
__device__ __forceinline__ void bulk_load(uint32_t dst, const void* src, uint32_t bytes, uint32_t bar) {
    asm volatile("cp.async.bulk.shared::cluster.global.mbarrier::complete_tx::bytes [%0], [%1], %2, [%3];" ::"r"(dst), "l"(src), "r"(bytes), "r"(bar) : "memory");
}
__device__ __forceinline__ void tma_load_2d(uint32_t dst, const CUtensorMap* map, int c0, int c1, uint32_t bar) {
    asm volatile("cp.async.bulk.tensor.2d.shared::cluster.global.mbarrier::complete_tx::bytes [%0], [%1, {%3, %4}], [%2];"
                 ::"r"(dst), "l"(map), "r"(bar), "r"(c0), "r"(c1) : "memory");
}
__device__ __forceinline__ void tma_load_2d_both(uint32_t dst, const CUtensorMap* map, int c0, int c1, uint32_t bar) {
    asm volatile("cp.async.bulk.tensor.2d.shared::cluster.global.mbarrier::complete_tx::bytes.multicast::cluster [%0], [%1, {%3, %4}], [%2], %5;"
                 ::"r"(dst), "l"(map), "r"(bar), "r"(c0), "r"(c1), "h"((uint16_t)3) : "memory");
}
__device__ __forceinline__ uint64_t policy_evict_first() {
    uint64_t p;
    asm("createpolicy.fractional.L2::evict_first.b64 %0, 1.0;" : "=l"(p));
    return p;
}
__device__ __forceinline__ uint64_t policy_evict_normal() {
    uint64_t p;
    asm("createpolicy.fractional.L2::evict_normal.b64 %0, 1.0;" : "=l"(p));
    return p;
}
__device__ __forceinline__ void tma_load_2d(uint32_t dst, const CUtensorMap* map, int c0, int c1, uint32_t bar, uint64_t pol) {
    asm volatile("cp.async.bulk.tensor.2d.shared::cluster.global.mbarrier::complete_tx::bytes.L2::cache_hint [%0], [%1, {%3, %4}], [%2], %5;"
                 ::"r"(dst), "l"(map), "r"(bar), "r"(c0), "r"(c1), "l"(pol) : "memory");
}
__device__ __forceinline__ uint4 ldg128(const void* p, uint64_t pol) {
    uint4 v;
    asm("ld.global.nc.L2::cache_hint.v4.u32 {%0,%1,%2,%3}, [%4], %5;" : "=r"(v.x), "=r"(v.y), "=r"(v.z), "=r"(v.w) : "l"(p), "l"(pol));
    return v;
}
__device__ __forceinline__ void stg128(void* p, uint4 v, uint64_t pol) {
    asm volatile("st.global.L2::cache_hint.v4.u32 [%0], {%1,%2,%3,%4}, %5;" ::"l"(p), "r"(v.x), "r"(v.y), "r"(v.z), "r"(v.w), "l"(pol) : "memory");
}
__device__ __forceinline__ void tma_store_2d(const CUtensorMap* map, uint32_t src, int c0, int c1) {
    asm volatile("cp.async.bulk.tensor.2d.global.shared::cta.bulk_group [%0, {%2, %3}], [%1];" ::"l"(map), "r"(src), "r"(c0), "r"(c1) : "memory");
}
__device__ __forceinline__ char* make_ptr(uint32_t lo, uint32_t hi) {
    uint64_t p;
    asm("mov.b64 %0, {%1, %2};" : "=l"(p) : "r"(lo), "r"(hi));
    return reinterpret_cast<char*>(p);
}
__device__ __forceinline__ uint64_t make_desc(uint32_t saddr, uint32_t lbo, uint32_t sbo) {
    return (uint64_t)((saddr & 0x3FFFF) >> 4) | ((uint64_t)((lbo >> 4) & 0x3FFF) << 16) | ((uint64_t)((sbo >> 4) & 0x3FFF) << 32) | ((uint64_t)1 << 62);
}
__device__ __forceinline__ void wg_fence() { asm volatile("wgmma.fence.sync.aligned;" ::: "memory"); }
__device__ __forceinline__ void wg_commit() { asm volatile("wgmma.commit_group.sync.aligned;" ::: "memory"); }
template <int N> __device__ __forceinline__ void wg_wait() { asm volatile("wgmma.wait_group.sync.aligned %0;" ::"n"(N) : "memory"); }

#define R4(b) "+f"(d[b + 0]), "+f"(d[b + 1]), "+f"(d[b + 2]), "+f"(d[b + 3])
#define R16(b) R4(b), R4(b + 4), R4(b + 8), R4(b + 12)
template <int N> __device__ __forceinline__ void wgmma_proj(float (&d)[N / 2], uint64_t da, uint64_t db) {
    if constexpr (N == 96)
        asm volatile("wgmma.mma_async.sync.aligned.m64n96k16.f32.bf16.bf16 {"
            "%0,%1,%2,%3,%4,%5,%6,%7,%8,%9,%10,%11,%12,%13,%14,%15,%16,%17,%18,%19,%20,%21,%22,%23,%24,%25,%26,%27,%28,%29,%30,%31,%32,%33,%34,%35,%36,%37,%38,%39,"
            "%40,%41,%42,%43,%44,%45,%46,%47"
            "}, %48, %49, 1, 1, 1, 1, 0;" : R16(0), R16(16), R16(32) : "l"(da), "l"(db));
    if constexpr (N == 128)
        asm volatile("wgmma.mma_async.sync.aligned.m64n128k16.f32.bf16.bf16 {"
            "%0,%1,%2,%3,%4,%5,%6,%7,%8,%9,%10,%11,%12,%13,%14,%15,%16,%17,%18,%19,%20,%21,%22,%23,%24,%25,%26,%27,%28,%29,%30,%31,%32,%33,%34,%35,%36,%37,%38,%39,"
            "%40,%41,%42,%43,%44,%45,%46,%47,%48,%49,%50,%51,%52,%53,%54,%55,%56,%57,%58,%59,%60,%61,%62,%63"
            "}, %64, %65, 1, 1, 1, 1, 0;" : R16(0), R16(16), R16(32), R16(48) : "l"(da), "l"(db));
    if constexpr (N == 256)
        asm volatile("wgmma.mma_async.sync.aligned.m64n256k16.f32.bf16.bf16 {"
            "%0,%1,%2,%3,%4,%5,%6,%7,%8,%9,%10,%11,%12,%13,%14,%15,%16,%17,%18,%19,%20,%21,%22,%23,%24,%25,%26,%27,%28,%29,%30,%31,%32,%33,%34,%35,%36,%37,%38,%39,"
            "%40,%41,%42,%43,%44,%45,%46,%47,%48,%49,%50,%51,%52,%53,%54,%55,%56,%57,%58,%59,%60,%61,%62,%63,%64,%65,%66,%67,%68,%69,%70,%71,%72,%73,%74,%75,%76,%7"
            "7,%78,%79,%80,%81,%82,%83,%84,%85,%86,%87,%88,%89,%90,%91,%92,%93,%94,%95,%96,%97,%98,%99,%100,%101,%102,%103,%104,%105,%106,%107,%108,%109,%110,%111,"
            "%112,%113,%114,%115,%116,%117,%118,%119,%120,%121,%122,%123,%124,%125,%126,%127"
            "}, %128, %129, 1, 1, 1, 1, 0;" : R16(0), R16(16), R16(32), R16(48), R16(64), R16(80), R16(96), R16(112) : "l"(da), "l"(db));
}

__device__ __forceinline__ void wgmma_rs32(float (&d)[16], const uint32_t (&a)[4], uint64_t db, bool acc) {
    asm volatile(
        "{.reg .pred p; setp.ne.b32 p, %21, 0;\n"
        "wgmma.mma_async.sync.aligned.m64n32k16.f32.bf16.bf16 {%0,%1,%2,%3,%4,%5,%6,%7,%8,%9,%10,%11,%12,%13,%14,%15}, {%16,%17,%18,%19}, %20, p, 1, 1, 0;}"
        : R16(0) : "r"(a[0]), "r"(a[1]), "r"(a[2]), "r"(a[3]), "l"(db), "n"(1) );
}
__device__ __forceinline__ void wgmma_rs32_first(float (&d)[16], const uint32_t (&a)[4], uint64_t db) {
    asm volatile(
        "{.reg .pred p; setp.ne.b32 p, %21, 0;\n"
        "wgmma.mma_async.sync.aligned.m64n32k16.f32.bf16.bf16 {%0,%1,%2,%3,%4,%5,%6,%7,%8,%9,%10,%11,%12,%13,%14,%15}, {%16,%17,%18,%19}, %20, p, 1, 1, 0;}"
        : R16(0) : "r"(a[0]), "r"(a[1]), "r"(a[2]), "r"(a[3]), "l"(db), "n"(0) );
}
__device__ __forceinline__ void wgmma_ss32(float (&d)[16], uint64_t da, uint64_t db) {
    asm volatile(
        "wgmma.mma_async.sync.aligned.m64n32k16.f32.bf16.bf16 {%0,%1,%2,%3,%4,%5,%6,%7,%8,%9,%10,%11,%12,%13,%14,%15}, %16, %17, 1, 1, 1, 1, 0;"
        : R16(0) : "l"(da), "l"(db));
}
template <int OFF, int ACC> __device__ __forceinline__ void wgmma_rs32u(float (&d)[16], const uint32_t (&a)[4], uint32_t lo) {
    asm volatile(
        "{.reg .pred p; .reg .b32 l; .reg .b64 e; setp.ne.b32 p, %22, 0; add.u32 l, %20, %21; mov.b64 e, {l, 0x40000040};\n"
        "wgmma.mma_async.sync.aligned.m64n32k16.f32.bf16.bf16 {%0,%1,%2,%3,%4,%5,%6,%7,%8,%9,%10,%11,%12,%13,%14,%15}, {%16,%17,%18,%19}, e, p, 1, 1, 0;}"
        : R16(0) : "r"(a[0]), "r"(a[1]), "r"(a[2]), "r"(a[3]), "r"(lo), "n"(OFF), "n"(ACC));
}
template <int OFF, int ACC> __device__ __forceinline__ void wgmma_ss32u(float (&d)[16], uint64_t da, uint32_t lo) {
    asm volatile(
        "{.reg .pred p; .reg .b32 l; .reg .b64 e; setp.ne.b32 p, %19, 0; add.u32 l, %17, %18; mov.b64 e, {l, 0x40000040};\n"
        "wgmma.mma_async.sync.aligned.m64n32k16.f32.bf16.bf16 {%0,%1,%2,%3,%4,%5,%6,%7,%8,%9,%10,%11,%12,%13,%14,%15}, %16, e, p, 1, 1, 1, 0;}"
        : R16(0) : "l"(da), "r"(lo), "n"(OFF), "n"(ACC));
}
template <int K0, int K1, class F> __device__ __forceinline__ void static_for(F f) {
    if constexpr (K0 < K1) { f(std::integral_constant<int, K0>()); static_for<K0 + 1, K1>(f); }
}
__device__ __forceinline__ void st_async4(uint32_t a, float x, float y, float z, float w, uint32_t bar) {
    asm volatile("st.async.weak.shared::cluster.mbarrier::complete_tx::bytes.v4.f32 [%0], {%1,%2,%3,%4}, [%5];" ::"r"(a), "f"(x), "f"(y), "f"(z), "f"(w), "r"(bar) : "memory");
}
__device__ __forceinline__ void st_async2(uint32_t a, float x, float y, uint32_t bar) {
    asm volatile("st.async.weak.shared::cluster.mbarrier::complete_tx::bytes.v2.f32 [%0], {%1,%2}, [%3];" ::"r"(a), "f"(x), "f"(y), "r"(bar) : "memory");
}
__device__ __forceinline__ void st_async1(uint32_t a, uint32_t x, uint32_t bar) {
    asm volatile("st.async.weak.shared::cluster.mbarrier::complete_tx::bytes.b32 [%0], %1, [%2];" ::"r"(a), "r"(x), "r"(bar) : "memory");
}
__device__ __forceinline__ uint32_t peer_addr(uint32_t a, uint32_t rank) {
    uint32_t r;
    asm("mapa.shared::cluster.u32 %0, %1, %2;" : "=r"(r) : "r"(a), "r"(rank));
    return r;
}
__device__ __forceinline__ void stsm4t(uint32_t a, uint32_t r0, uint32_t r1, uint32_t r2, uint32_t r3) {
    asm volatile("stmatrix.sync.aligned.m8n8.x4.trans.shared.b16 [%0], {%1,%2,%3,%4};" ::"r"(a), "r"(r0), "r"(r1), "r"(r2), "r"(r3) : "memory");
}
__device__ __forceinline__ void ldsm4t(uint32_t (&r)[4], uint32_t a) { ldsm4t(r[0], r[1], r[2], r[3], a); }
__device__ __forceinline__ void ldsm4(uint32_t (&r)[4], uint32_t a) { ldsm4(r[0], r[1], r[2], r[3], a); }
__device__ __forceinline__ void mma16816(float (&d)[4], const uint32_t (&a)[4], uint32_t b0, uint32_t b1) { mma16816(d, a[0], a[1], a[2], a[3], b0, b1); }
__device__ __forceinline__ void sched_fence(uint32_t v) {
    asm volatile("{.reg .pred p; setp.ne.u32 p, %0, 0xFFFFFFFF; vote.sync.all.pred p, p, 0xFFFFFFFF; @p bra.uni SF_OK; exit; SF_OK:}" ::"r"(v) : "memory");
}
__device__ __forceinline__ void mma16816v(float (&d)[4], const uint32_t (&a)[4], uint32_t b0, uint32_t b1) {
    asm volatile("mma.sync.aligned.m16n8k16.row.col.f32.bf16.bf16.f32 {%0,%1,%2,%3},{%4,%5,%6,%7},{%8,%9},{%0,%1,%2,%3};"
                 : "+f"(d[0]), "+f"(d[1]), "+f"(d[2]), "+f"(d[3]) : "r"(a[0]), "r"(a[1]), "r"(a[2]), "r"(a[3]), "r"(b0), "r"(b1));
}
__device__ __forceinline__ uint32_t uniform(uint32_t v) { return __reduce_max_sync(~0u, v); }

#define WPRE 0
#define G2_X 0
#define G2_K 4
#define FIN_SO 0
#define PROJ_FAST 1
#define KROT 0
#define WFIRST 0
template <int NT, int STAGES> struct ProjCfg {
    static constexpr int STAGE_BYTES = 16384 + NT * 128;
    static constexpr int EPI = NT == 256 ? STAGES * STAGE_BYTES : 0;
    static constexpr int BARS = 229376 + (NT == 256 ? 192 : 0);
    static_assert(STAGES * STAGE_BYTES <= 229376 && EPI + NT * 256 <= 229376 && STAGES <= 12, "smem");
};
constexpr int PROJ_ROLE = 229376 + 384, PROJ_SMEM = PROJ_ROLE + 16;
__device__ __forceinline__ unsigned claim_pair(unsigned* reg) {
    unsigned smid, ncl = gridDim.x >> 1;
    asm volatile("mov.u32 %0, %%smid;" : "=r"(smid));
    uint2 m;
    for (int guard = 0; guard < 1024; guard++) {
        asm volatile("ld.relaxed.gpu.global.v2.u32 {%0, %1}, [%2];" : "=r"(m.x), "=r"(m.y) : "l"(g_cls + (smid & ~1u)) : "memory");
        if (m.x && m.y) break;
    }
    const unsigned r = __vminu2(m.x, m.y), c = (r & 0xFFFF) > (r >> 16);
    unsigned n = atomicAdd(reg, c ? 0x10000u : 1u);
    const unsigned i = c ? n >> 16 : n & 0xFFFF, order = ((n >> 16) + (n & 0xFFFF)) << 8;
    if (i < 32) return c * 32 + i + order;
    for (int guard = 0; guard < (1 << 20); guard++) {
        asm volatile("ld.relaxed.gpu.global.u32 %0, [%1];" : "=r"(n) : "l"(reg) : "memory");
        if ((n >> 16) + (n & 0xFFFF) >= ncl) break;
    }
    const unsigned k = (c ? n & 0xFFFF : n >> 16) + i - 32;
    return (k < 32 ? (c ^ 1) * 32 + k : 64) + order;
}
template <int NT, int STAGES> __device__ __forceinline__ void proj_init(uint32_t sb) {
    for (int i = 0; i < STAGES; i++) { mbar_init(sb + ProjCfg<NT, STAGES>::BARS + 8 * i, 1); mbar_init(sb + ProjCfg<NT, STAGES>::BARS + 8 * (STAGES + i), 16); }
    asm volatile("fence.mbarrier_init.release.cluster;" ::: "memory");
}
template <int NT, int STAGES, bool SHARE_O, class T, class R>
__device__ __forceinline__ void proj_tiles(uint32_t sb, int warp, uint32_t rank, int ntiles, const CUtensorMap* mapW, const CUtensorMap* mapO,
                                           const CUtensorMap* mapOut, T tile, R ready, int rot = 0) {
    using Cfg = ProjCfg<NT, STAGES>;
    const uint32_t bars = sb + Cfg::BARS;
    const int lane = threadIdx.x & 31;
    if (warp == 8) {
        int st = 0; uint32_t ph = 1;
        for (int i = 0; i < ntiles; i++) {
            int col, tok;
            tile(i, col, tok);
            constexpr bool PRE = WPRE && !SHARE_O;
            if (PRE && lane == 0)
                for (int kb = 0; kb < STAGES; kb++) {
                    mbar_expect_tx(bars + 8 * kb, Cfg::STAGE_BYTES);
                    tma_load_2d_both(sb + kb * Cfg::STAGE_BYTES + rank * 8192, mapW, col + rank * 64, kb * 64, bars + 8 * kb);
                }
            ready(i);
            if (lane == 0) {
                if (PRE) {
                    for (int kb = 0; kb < STAGES; kb++) tma_load_2d(sb + kb * Cfg::STAGE_BYTES + 16384, mapO, kb * 64, tok, bars + 8 * kb);
                    ph = 0;
                }
                for (int kb = PRE ? STAGES : 0; kb < HD / 64; kb++) {
                    mbar_wait(bars + 8 * (STAGES + st), ph);
                    const uint32_t full = bars + 8 * st, sa = sb + st * Cfg::STAGE_BYTES;
                    mbar_expect_tx(full, SHARE_O ? Cfg::STAGE_BYTES : G2_X == 1 ? 16384 : G2_X == 2 ? NT * 128 : Cfg::STAGE_BYTES);
                    if (SHARE_O) {
                        tma_load_2d(sa, mapW, col, kb * 64, full);
                        tma_load_2d(sa + 8192, mapW, col + 64, kb * 64, full);
                        tma_load_2d_both(sa + 16384 + rank * (NT * 64), mapO, kb * 64, tok + rank * (NT / 2), full);
                    } else {
                        const int k0 = ((kb + rot) & 63) * 64;
                        if (WFIRST) tma_load_2d_both(sa + rank * 8192, mapW, col + rank * 64, k0, full);
                        if (G2_X != 1) tma_load_2d(sa + 16384, mapO, k0, G2_X == 3 ? tok & 511 : tok, full);
                        if (!WFIRST && G2_X != 2) tma_load_2d_both(sa + rank * 8192, mapW, col + rank * 64, k0, full);
                    }
                    if (++st == STAGES) { st = 0; ph ^= 1; }
                }
            }
            __syncwarp();
        }
    } else if (warp < 8) {
        const int wg = warp >> 2;
        uint32_t peer_empty;
        asm volatile("mapa.shared::cluster.u32 %0, %1, %2;" : "=r"(peer_empty) : "r"(bars + 8 * STAGES), "r"(rank ^ 1));
        auto release = [&](int stg) {
            if (lane == 0) {
                mbar_arrive(bars + 8 * (STAGES + stg));
                asm volatile("mbarrier.arrive.shared::cluster.b64 _, [%0];" ::"r"(peer_empty + 8 * stg) : "memory");
            }
        };
        const uint32_t ew = sb + Cfg::EPI + wg * (NT * 128);
        int st = 0; uint32_t ph = 0;
        for (int i = 0; i < ntiles; i++) {
            int col, tok;
            tile(i, col, tok);
            float d[NT / 2];
#pragma unroll
            for (int r = 0; r < NT / 2; r++) d[r] = 0.f;
            int prev = -1;
            for (int kb = 0; kb < HD / 64; kb++) {
                mbar_wait(bars + 8 * st, ph);
                const uint32_t sa = sb + st * Cfg::STAGE_BYTES;
                const uint64_t da = make_desc(sa + wg * 8192, 16, 1024), db = make_desc(sa + 16384, 16, 1024);
                wg_fence();
#pragma unroll
                for (int k = 0; k < (NT == 256 ? 4 : G2_K); k++) wgmma_proj<NT>(d, da + k * 128, db + k * 2);
                wg_commit();
                if (prev >= 0) { wg_wait<1>(); release(prev); }
                prev = st;
                if (++st == STAGES) { st = 0; ph ^= 1; }
            }
            wg_wait<0>();
            release(prev);
            if ((warp & 3) == 0 && lane == 0) asm volatile("cp.async.bulk.wait_group.read 0;" ::: "memory");
            if (Cfg::EPI) bar_sync(1 + wg, 128); else bar_sync(3, 256);
            const uint32_t ea = ew + ((lane >> 4) * 8 + (lane & 7)) * 128 + ((((warp & 3) * 2 + ((lane >> 3) & 1)) ^ (lane & 7)) * 16);
#pragma unroll
            for (int r = 0; r < NT / 16; r++)
                stsm4t(ea + r * 2048, pack_bf16(d[8 * r], d[8 * r + 1]), pack_bf16(d[8 * r + 2], d[8 * r + 3]), pack_bf16(d[8 * r + 4], d[8 * r + 5]), pack_bf16(d[8 * r + 6], d[8 * r + 7]));
            asm volatile("fence.proxy.async.shared::cta;" ::: "memory");
            bar_sync(1 + wg, 128);
            if ((warp & 3) == 0 && lane == 0) {
                tma_store_2d(mapOut, ew, col + wg * 64, tok);
                asm volatile("cp.async.bulk.commit_group;" ::: "memory");
            }
        }
        if ((warp & 3) == 0 && lane == 0) asm volatile("cp.async.bulk.wait_group 0;" ::: "memory");
    }
    __syncwarp();
}
constexpr int EARLY_NT = 256, EARLY_STAGES = 3;
constexpr int PROJ_THREADS = 288;

template <int NT, int STAGES>
__global__ void __cluster_dims__(2, 1, 1) __launch_bounds__(PROJ_THREADS, 1)
proj_kernel(const __grid_constant__ CUtensorMap mapW, const __grid_constant__ CUtensorMap mapO, const __grid_constant__ CUtensorMap mapOut,
            const __grid_constant__ CUtensorMap mapOE, const __grid_constant__ CUtensorMap mapOutE) {
    KT_START(3);
    extern __shared__ __align__(1024) uint8_t smem_proj[];
    const uint32_t sb = smem_u32(smem_proj), role = sb + PROJ_ROLE;
    if (sb & 1023) __trap();
    const uint32_t rank = blockIdx.x & 1;
    const int warp = threadIdx.x >> 5;
    if (threadIdx.x == 0) {
        mbar_init(role + 8, 1);
        mbar_expect_tx(role + 8, 4);
        proj_init<NT, STAGES>(sb);
        proj_init<EARLY_NT, EARLY_STAGES>(sb);
    }
    if (threadIdx.x == 32) { prefetch_map(&mapO); prefetch_map(&mapW); prefetch_map(&mapOut); }
    __syncwarp();
    asm volatile("barrier.cluster.arrive.relaxed.aligned;" ::: "memory");
    unsigned claimed = 0;
    if (threadIdx.x == 256 && rank == 0) claimed = claim_pair(g_reg + 2);
    __syncwarp();
    asm volatile("barrier.cluster.wait.acquire.aligned;" ::: "memory");
    if (threadIdx.x == 256 && rank == 0) {
        st_async1(peer_addr(role, 1), claimed, peer_addr(role + 8, 1));
        st_async1(peer_addr(role, 0), claimed, peer_addr(role + 8, 0));
        if ((claimed >> 8) + 1 == gridDim.x >> 1) {
            g_reg[0] = 0;
            for (int i = 0; i < 64; i++) reinterpret_cast<uint4*>(g_cls)[i] = make_uint4(0, 0, 0, 0);
        }
    }
    __syncwarp();
    mbar_wait_w(role + 8, 0);
    const int p = lds32(role) & 255, order = lds32(role) >> 8;
    if (NT == 96 && order < 2) {
        proj_tiles<EARLY_NT, EARLY_STAGES, true>(sb, warp, rank, 4, &mapW, &mapOE, &mapOutE,
            [&](int i, int& col, int& tok) { col = ((i & 1) * 4 + order * 2 + rank) * 128; tok = (i >> 1) * EARLY_NT; },
            [&](int i) {
                const unsigned need = 8 * (i >> 1) + 8 + 3;
                for (int guard = 0; guard < (1 << 16); guard++) {
                    const uint4 f = ld_relaxed_v4(g_xflag + (threadIdx.x & 31) * 4);
                    if (__all_sync(~0u, min(min(f.x, f.y), min(f.z, f.w)) >= need)) break;
                    __nanosleep(1000);
                }
                asm volatile("fence.acq_rel.gpu; fence.proxy.async.global;" ::: "memory");
            });
        __syncthreads();
        asm volatile("barrier.cluster.arrive.relaxed.aligned; barrier.cluster.wait.aligned;" ::: "memory");
    }
    if (p >= 64) return;
    proj_tiles<NT, STAGES, false>(sb, warp, rank, 1, &mapW, &mapO, &mapOut,
                                  [&](int, int& col, int& tok) { col = (p & 7) * 128; tok = S_LEN - 16 * NT + ((p >> 3) * 2 + rank) * NT; },
                                  [&](int) { wait_prerequisites();
                                  }, KROT == 0 ? 0 : KROT == 1 ? (p & 7) * 8 : KROT == 2 ? (p >> 3) * 8 : KROT == 3 ? ((p & 7) + (p >> 3)) * 8 : (p >> 5) * 32);
    KT_END(3);
    asm volatile("barrier.cluster.arrive.relaxed; barrier.cluster.wait;" ::: "memory");
}

#define WO_RF1 6
constexpr int SM_KV = 0, KV_BYTES = 18432;
constexpr int SM_XT = 2 * KV_BYTES;
constexpr int SM_STG = SM_XT + 65536;
constexpr int SM_Z = SM_STG + 6144;
#define HS 6
constexpr int SM_RT = SM_Z + 8192;
constexpr int SM_QKV = SM_RT + (HS == 6 ? 10240 : 12288);
constexpr int SM_R1 = SM_QKV + 6144;
constexpr int SM_Y = HS == 6 ? SM_R1 : SM_Z;
constexpr int SM_R2 = SM_R1 + (HS == 6 ? 4096 : 2048);
constexpr int SM_R3 = SM_R2 + 1024;
constexpr int SM_O = SM_R3 + 2048;
constexpr int SM_S = SM_O + 2048;
constexpr int SM_INV = SM_S + 1536;
constexpr int SM_TO = SM_R3;
constexpr int SM_WORK_END = SM_S + 2048;
constexpr int STG_QK = 0, STG_V = 98304;
#define PRO2 1
#define PRO3 1
#define WO_IT 2
#define XP 0
__host__ __device__ constexpr int stg_wo(int r) { return r < 9 ? KV_BYTES + r * 2048 : r < 13 ? SM_QKV + (r - 9) * 2048 : SM_S; }
static_assert(WO_RF1 == 6 && SM_QKV % 1024 == 0 && SM_S % 1024 == 0 && SM_QKV + 8192 <= SM_TO, "staging of Wo");
__host__ __device__ constexpr int stg_qk(int t, int r) { return !PRO2 ? STG_QK + (t * 24 + r) * 2048 : t == 0 ? SM_XT + r * 2048 : r < SM_XT / 2048 ? r * 2048 : (r + 24) * 2048; }
constexpr int SM_WO1 = SM_WORK_END - WO_RF1 * 2048;
constexpr int STG_WO = SM_WO1 - 16384;
constexpr int SM_WQK = (SM_WO1 + 16384 > STG_V + 49152) ? SM_WO1 + 16384 : STG_V + 49152;
constexpr int SM_WV = SM_WQK + 32768;
constexpr int SM_WO2 = SM_WV + 16384;
constexpr int SM_BARS = SM_WO2 + 32768;
enum { MB_W0 = SM_BARS, MB_W1 = SM_BARS + 8, MB_W2 = SM_BARS + 16, MB_W3 = SM_BARS + 24, MB_XT = SM_BARS + 32  , MB_KV = SM_BARS + 48  ,
       MB_R3 = SM_BARS + 64, MB_R1 = SM_BARS + 72, MB_R2 = SM_BARS + 80, MB_RT0 = SM_BARS + 88, MB_RT1 = SM_BARS + 96, MB_FREE = SM_BARS + 104,
       MB_P = SM_BARS + 112, MB_V = SM_BARS + 120, MB_STG = SM_BARS + 128, MB_ROLE = SM_BARS + 136, MB_W4 = SM_BARS + 144, MB_W5 = SM_BARS + 152, SM_ROLE = SM_BARS + 160   };
constexpr int CHAIN_SMEM = SM_ROLE + 8;
static_assert(SM_WORK_END % 1024 == 0 && STG_WO >= STG_V, "work area");
static_assert(SM_Y % 128 == 0, "exchange Y");
static_assert(CHAIN_SMEM <= 232448 && WO_RF1 >= 6, "smem");

#define DLY_X 300
#define DLY_V 0
#define DLY_Y 330
#define DLY_Z 300
#define DLY_T 0
#define DLY_K 0
#define DLY_S 0
#define LATE_RD 1
#define TS_AT 5
#define TS_LATE 0
#define XB_EARLY 0
#define RT0_N 4
#define ORD0 2
#define ORD1 0
#define ORDV 0
#define RT_BF 2
__host__ __device__ constexpr int kstep(int ord, int i) { return ord == 0 ? i : ord == 1 ? (i + 24) % 32 : ord == 2 ? (i % 4 == 3 ? 24 + i / 4 : i / 4 * 3 + i % 4) : ord == 3 ? (i < 16 ? (i % 2 ? 24 + i / 2 : i / 2) : i - 8) : (i < 8 ? i : i < 16 ? i + 16 : i - 8); }
#define RT0_AT 4
#define RT1_LATE 0
#define RT_BULK 2
#define FENCE_W 0

#define XT_FIRST 0
#define GV 1
#define NSV (GV ? 320 : 352)
#define Q3_AT 9
#define NA 7
#define NP2 6
#define P2_FENCE 0
#define SPLIT 8
#define TA0 16
#define SENT_EARLY 1
#define Y_CHAIN 1
#define EF_W 1
#define XFLIP 0
#define YFLIP 0
#define ZFLIP 1
#define OFENCE 2
#define REG_A 240
#define REG_B 216
#define REG_C (3 * 168 - REG_A - REG_B)

enum { BAR_Y, BAR_MEM, BAR_PUB, BAR_QK, BAR_S, BAR_O, BAR_SENT, BAR_COMM, BAR_PUBV, BAR_PV, BAR_PDONE, BAR_VP, BAR_ZP, BAR_PRO, BAR_O2, BAR_SV,
       BAR_V = BAR_PV, BAR_SENTC = BAR_PDONE, BAR_Q3 = BAR_PRO, BAR_INV = BAR_PRO, BAR_XT0 = BAR_Y };

__device__ __forceinline__ uint32_t umax4(const uint4& v) { return max(max(v.x, v.y), max(v.z, v.w)); }
__device__ __forceinline__ unsigned gtime() { unsigned t; asm volatile("mov.u32 %0, %%globaltimer_lo;" : "=r"(t)::"memory"); return t; }
__device__ __forceinline__ unsigned clock32() { unsigned t; asm volatile("mov.u32 %0, %%clock;" : "=r"(t)::"memory"); return t; }
__device__ __forceinline__ void spin_cycles(int d) {
    if (d > 0) { const unsigned c0 = clock32(); while (clock32() - c0 < (unsigned)d) {} }
}
__device__ __forceinline__ float ex2_approx(float x) { float y; asm("ex2.approx.ftz.f32 %0, %1;" : "=f"(y) : "f"(x)); return y; }
__device__ __forceinline__ float rcp_approx(float x) { float y; asm("rcp.approx.ftz.f32 %0, %1;" : "=f"(y) : "f"(x)); return y; }
__device__ __forceinline__ void st_sent(const void* p) { asm volatile("st.relaxed.gpu.global.v4.u32 [%0], {%1,%1,%1,%1};" ::"l"(p), "r"(SENT) : "memory"); }
#define POLL_LD(p, a, b, c, d, addr) "@" p " ld.relaxed.gpu.global.v4.u32 {" a "," b "," c "," d "}, [" addr "];\n"
#define POLL_CK(p, a, b, c, d) "max.u32 m, " a "," b "; max.u32 n, " c "," d "; max.u32 m, m, n; setp.eq.u32 " p ", m, 0xFFFFFFFF;\n"
#define POLL_IO(v) "+r"(v.x), "+r"(v.y), "+r"(v.z), "+r"(v.w)
__device__ __forceinline__ void poll_init(uint4& v) { v = make_uint4(SENT, SENT, SENT, SENT); asm volatile("" : POLL_IO(v)); }
__device__ __forceinline__ int poll2(uint4 (&v)[2], const char* a) {
    int c = 0;
    asm volatile("{.reg .pred p0, p1, p; .reg .u32 m, n;\n"
                 "setp.eq.u32 p0, %8, 0; setp.eq.u32 p1, %8, 0;\n"
                 "POLL_LOOP:\n"
                 POLL_LD("p0", "%0", "%1", "%2", "%3", "%9") POLL_LD("p1", "%4", "%5", "%6", "%7", "%9+512")
                 "add.u32 %8, %8, 1;\n"
                 POLL_CK("p0", "%0", "%1", "%2", "%3") POLL_CK("p1", "%4", "%5", "%6", "%7")
                 "or.pred p, p0, p1; setp.lt.and.u32 p, %8, 0x10000, p; vote.sync.any.pred p, p, 0xFFFFFFFF;\n"
                 "@p bra.uni POLL_LOOP;}" : POLL_IO(v[0]), POLL_IO(v[1]), "+r"(c) : "l"(a) : "memory");
    return c;
}
__device__ __forceinline__ int poll2_bar(uint4 (&v)[2], const char* a, uint32_t bar, uint32_t parity) {
    int c = 0;
    asm volatile("{.reg .pred p0, p1, p, q; .reg .u32 m, n;\n"
                 "setp.eq.u32 p0, %8, 0; setp.eq.u32 p1, %8, 0;\n"
                 "POLL_LOOP:\n"
                 POLL_LD("p0", "%0", "%1", "%2", "%3", "%9") POLL_LD("p1", "%4", "%5", "%6", "%7", "%9+512")
                 "mbarrier.try_wait.parity.shared::cta.b64 q, [%10], %11;\n"
                 "add.u32 %8, %8, 1;\n"
                 POLL_CK("p0", "%0", "%1", "%2", "%3") POLL_CK("p1", "%4", "%5", "%6", "%7")
                 "or.pred p, p0, p1; or.pred p, p, !q; setp.lt.and.u32 p, %8, 0x10000, p; vote.sync.any.pred p, p, 0xFFFFFFFF;\n"
                 "@p bra.uni POLL_LOOP;}" : POLL_IO(v[0]), POLL_IO(v[1]), "+r"(c) : "l"(a), "r"(bar), "r"(parity) : "memory");
    return c;
}
template <int ST> __device__ __forceinline__ int poll4(uint4 (&v)[4], const char* a) {
    int c = 0;
    asm volatile("{.reg .pred p0, p1, p2, p3, p; .reg .u32 m, n;\n"
                 "setp.eq.u32 p0, %16, 0; setp.eq.u32 p1, %16, 0; setp.eq.u32 p2, %16, 0; setp.eq.u32 p3, %16, 0;\n"
                 "POLL_LOOP:\n"
                 POLL_LD("p0", "%0", "%1", "%2", "%3", "%17") POLL_LD("p1", "%4", "%5", "%6", "%7", "%17+%18")
                 POLL_LD("p2", "%8", "%9", "%10", "%11", "%17+%19") POLL_LD("p3", "%12", "%13", "%14", "%15", "%17+%20")
                 "add.u32 %16, %16, 1;\n"
                 POLL_CK("p0", "%0", "%1", "%2", "%3") POLL_CK("p1", "%4", "%5", "%6", "%7") POLL_CK("p2", "%8", "%9", "%10", "%11") POLL_CK("p3", "%12", "%13", "%14", "%15")
                 "or.pred p, p0, p1; or.pred p, p, p2; or.pred p, p, p3; setp.lt.and.u32 p, %16, 0x10000, p; vote.sync.any.pred p, p, 0xFFFFFFFF;\n"
                 "@p bra.uni POLL_LOOP;}" : POLL_IO(v[0]), POLL_IO(v[1]), POLL_IO(v[2]), POLL_IO(v[3]), "+r"(c) : "l"(a), "n"(ST), "n"(2 * ST), "n"(3 * ST) : "memory");
    return c;
}
__device__ __forceinline__ uint32_t add_bf16x2(uint32_t a, uint32_t b) { uint32_t r; asm("add.rn.bf16x2 %0, %1, %2;" : "=r"(r) : "r"(a), "r"(b)); return r; }
__device__ __forceinline__ uint32_t max_bf16x2(uint32_t a, uint32_t b) { uint32_t r; asm("max.bf16x2 %0, %1, %2;" : "=r"(r) : "r"(a), "r"(b)); return r; }
template <class F> __device__ __forceinline__ void softmax40(uint32_t (&pw)[6], uint32_t sa, F mid) {
    const float LOG2E = 1.4426950408889634f;
    uint32_t w[5];
    float e[10];
#pragma unroll
    for (int i = 0; i < 5; i++) w[i] = lds32(sa + i * 128);
    uint32_t m = max_bf16x2(max_bf16x2(max_bf16x2(w[0], w[1]), max_bf16x2(w[2], w[3])), w[4]);
    m = max_bf16x2(m, __shfl_xor_sync(~0u, m, 1));
    m = max_bf16x2(m, __shfl_xor_sync(~0u, m, 2));
    const float mb2 = fmaxf(bf_lo(m), bf_hi(m)) * LOG2E;
#pragma unroll
    for (int i = 0; i < 5; i++) {
        e[2 * i] = ex2_approx(fmaf(bf_lo(w[i]), LOG2E, -mb2));
        e[2 * i + 1] = ex2_approx(fmaf(bf_hi(w[i]), LOG2E, -mb2));
    }
    mid();
#pragma unroll
    for (int i = 0; i < 5; i++) pw[i] = pack_bf16(e[2 * i], e[2 * i + 1]);
    const float sum = (((e[0] + e[1]) + (e[2] + e[3])) + ((e[4] + e[5]) + (e[6] + e[7]))) + (e[8] + e[9]);
    const float hi = bf_hi(__float_as_uint(sum));
    pw[5] = pack_bf16(sum - hi, hi);
}
template <bool NORM, class F> __device__ __forceinline__ void pv32(uint32_t (&w)[4], float (&inv)[2], const uint32_t (&va)[2][2][4], const uint32_t (&vm)[4], const uint32_t (&pw)[6], F mid) {
    float o[2][3][4], t[4] = {0.f, 0.f, 0.f, 0.f};
#pragma unroll
    for (int i = 0; i < 3; i++)
#pragma unroll
        for (int m = 0; m < 2; m++) {
            o[m][i][0] = o[m][i][1] = o[m][i][2] = o[m][i][3] = 0.f;
            if (i < 2) mma16816(o[m][i], va[m][i & 1], pw[2 * i], pw[2 * i + 1]);
            else mma1688(o[m][i], vm[2 * m], vm[2 * m + 1], pw[4]);
        }
    mma1688(t, 0x3F803F80u, 0x3F803F80u, pw[5]);
    mid();
    if (NORM) { inv[0] = rcp_approx(t[0]); inv[1] = rcp_approx(t[1]); }
#pragma unroll
    for (int i = 0; i < 4; i++) {
        const float a = (o[i >> 1][0][2 * (i & 1)] + o[i >> 1][1][2 * (i & 1)]) + o[i >> 1][2][2 * (i & 1)];
        const float b = (o[i >> 1][0][2 * (i & 1) + 1] + o[i >> 1][1][2 * (i & 1) + 1]) + o[i >> 1][2][2 * (i & 1) + 1];
        w[i] = NORM ? pack_bf16(a * inv[0], b * inv[1]) : pack_bf16(a, b);
    }
    if (!NORM) { inv[0] = t[0]; inv[1] = t[1]; }
}
__device__ __forceinline__ uint32_t scale_scores(float a, float b) {
    const float scale = 0.08838834764831845f;
    const uint32_t w = pack_bf16(a, b);
    return pack_bf16(bf_lo(w) * scale, bf_hi(w) * scale);
}

#define TL(i) do {} while (0)
#define TLB(i) do {} while (0)
#define TLC(i) do {} while (0)

#define OPQ_LANE 1
#define CLAIM_T 64
#define PAD_A 0
#define PAD_B 0
#define PAD_C 0
template <int N> __device__ __forceinline__ void code_pad() {
#pragma unroll
    for (int i = 0; i < N; i++) asm volatile("pmevent 0;");
}
__global__ void __cluster_dims__(2, 1, 1) __launch_bounds__(384, 1)
chain_kernel(const __grid_constant__ CUtensorMap mapX, const __grid_constant__ CUtensorMap mapT32, const __grid_constant__ CUtensorMap mapT16,
             const __grid_constant__ CUtensorMap mapTQ, const __grid_constant__ CUtensorMap mapKV,
             const __grid_constant__ CUtensorMap mapWq, const __grid_constant__ CUtensorMap mapWk, const __grid_constant__ CUtensorMap mapWv,
             const __grid_constant__ CUtensorMap mapWo, const bf16* __restrict__ mem0, char* __restrict__ mbox) {
    KT_START(2);
    extern __shared__ __align__(1024) uint8_t smem_chain[];
    constexpr uint32_t SB0 = 1024;
    if (smem_u32(smem_chain) != (SB0 | ((blockIdx.x & 1) << 24))) __trap();
    const int kh = blockIdx.x & 1;
    if (threadIdx.x == 0) {
        const uint32_t sb = smem_u32(smem_chain);
        for (int i = 0; i < 14; i++) mbar_init(sb + SM_BARS + 8 * i, 1);
        mbar_init(sb + MB_P, 4); mbar_init(sb + MB_V, 4); mbar_init(sb + MB_STG, 8); mbar_init(sb + MB_ROLE, 1); mbar_init(sb + MB_W4, 1); mbar_init(sb + MB_W5, 1);
        mbar_expect_tx(sb + MB_ROLE, 4);
        asm volatile("fence.mbarrier_init.release.cluster;" ::: "memory");
    }
    if (threadIdx.x == 32) { prefetch_map(&mapWv); prefetch_map(&mapWq); prefetch_map(&mapWk); prefetch_map(&mapWo); prefetch_map(&mapX); }
    __syncwarp();
    asm volatile("barrier.cluster.arrive.relaxed.aligned;" ::: "memory");
    unsigned claimed = 0;
    if (threadIdx.x == CLAIM_T && kh == 0) claimed = claim_pair(g_reg) & 255;
    __syncwarp();
    asm volatile("barrier.cluster.wait.acquire.aligned;" ::: "memory");
    if (threadIdx.x == CLAIM_T && kh == 0) {
        st_async1((SB0 | (1u << 24)) + SM_ROLE, claimed, (SB0 | (1u << 24)) + MB_ROLE);
        st_async1(SB0 + SM_ROLE, claimed, SB0 + MB_ROLE);
    }
    __syncwarp();
    mbar_wait_w(smem_u32(smem_chain) + MB_ROLE, 0);
    const int pair = uniform(lds32(smem_u32(smem_chain) + SM_ROLE));
#define YFLIP_() (uniform(lds32(sb + SM_ROLE + 4)) ^ YFLIP)
    if (pair >= 64) return;
    if (threadIdx.x == 0) KT_MARK(5);
    const int h = pair >> 1, nh = pair & 1, j = 2 * nh + kh, role = 2 * pair + kh;
#define WG_ORDER 0x210
    const int warp = uniform(((WG_ORDER >> (4 * (threadIdx.x >> 7))) & 3) * 4 + ((threadIdx.x >> 5) & 3));
    const uint32_t g = warp & 3, sb = SB0 | (kh << 24), rsb = sb ^ (1u << 24), cls = pair >> 5, kflip = ZFLIP ^ kh;
    const uint32_t mlo = (uint32_t)(uintptr_t)mbox, mhi = (uint32_t)((uintptr_t)mbox >> 32);
    auto lane16 = [&]() {
        uint32_t t;
        asm volatile("{.reg .u32 l, x; mov.u32 l, %%laneid; xor.b32 x, l, 1; shl.b32 x, x, 4; shfl.sync.bfly.b32 %0, x, 1, 0x1f, 0xffffffff;}" : "=r"(t));
        return t;
    };
#define PHASE(k) uint32_t L; asm volatile("{.reg .u32 t; shr.u32 t, %1, %3; add.u32 %0, %2, t;}" : "=r"(L) : "r"(it), "r"(l16), "n"(8 + (k)))
#define ROWPAT() ((((L << 3) & 0x380) | ((L << 2) & 0x400)) | ((L ^ (L >> 3)) & 0x10) | (L & 0x60))
#define FRAG() (ROWPAT() ^ (g << 5))
#define QFRAG() ((((L >> 1) & 0x80) | (L & 0x70)) + ((L & 0x80) ? SM_KV + 16384 + kvo : SM_QKV))
#define VFRAG() (ROWPAT() ^ ((g & 1) << 6))
#define VBASE() (sb + SM_KV + 8192 + (g >> 1) * 4096 + kvo)
#define XTLO() ((uint32_t)make_desc(SB0 + SM_XT, 16, 1024) + (ui & 1) * 2048)
    if (warp >= 8) {
        asm volatile("setmaxnreg.dec.sync.aligned.u32 %0;" ::"n"(REG_C));
        code_pad<PAD_C>();
        const uint32_t l16 = lane16(), lane = l16 >> 4;
        auto load_xt = [&](int seg, int half) {
            const uint32_t bar = sb + MB_XT + (seg & 1) * 8;
            if (half == 0) mbar_expect_tx(bar, 32768);
            asm volatile("cp.async.bulk.tensor.3d.shared::cluster.global.mbarrier::complete_tx::bytes [%0], [%1, {%3, %4, %5}], [%2];"
                         ::"r"(sb + SM_XT + (seg & 1) * 32768 + half * 16384), "l"(&mapX), "r"(bar), "r"(0), "r"(seg * SEG), "r"(8 * kh + 4 * (half ^ kflip)) : "memory");
        };
        if (warp == 8) {
            const CUtensorMap* ws = kh ? &mapWq : &mapWk;
            const CUtensorMap* wn = kh ? &mapWk : &mapWq;
            const uint64_t pol = EF_W ? policy_evict_first() : policy_evict_normal();
            const int col = h * DH + 64 * nh, row = 512 * kh;
            if (lane == 0) { mbar_expect_tx(sb + MB_W0, 49152); mbar_expect_tx(sb + MB_W1, 49152); mbar_expect_tx(sb + MB_W4, 49152); mbar_expect_tx(sb + MB_W2, 49152); mbar_expect_tx(sb + MB_W3, PRO3 ? 65536 : 32768); }
            __syncwarp();
            if (lane < 24) {
                const int k = lane ^ (16 * kflip);
                tma_load_2d(sb + STG_V + lane * 2048, &mapWv, col, row + 16 * k, sb + MB_W0, pol);
                tma_load_2d(sb + stg_qk(0, lane), ws, col, row + 16 * k, sb + MB_W1, pol);
                tma_load_2d(sb + stg_qk(1, lane), wn, col, row + 16 * k, sb + MB_W4, pol);
            }
            if (lane < 8) {
                const int k = (24 + lane) ^ (16 * kflip);
                tma_load_2d(sb + SM_WQK + lane * 4096, ws, col, row + 16 * k, sb + MB_W2, pol);
                tma_load_2d(sb + SM_WQK + lane * 4096 + 2048, wn, col, row + 16 * k, sb + MB_W2, pol);
                tma_load_2d(sb + SM_WV + lane * 2048, &mapWv, col, row + 16 * k, sb + MB_W2, pol);
            }
            __syncwarp();
        }
        if (warp == 9) {
            bar_sync(BAR_XT0, 160);
            if (lane == 0) { load_xt(0, 0); load_xt(0, 1); }
            __syncwarp();
        }
        if (warp == 10 && lane == 0) {
            wait_prerequisites();
            launch_dependents();
            sts32(sb + SM_ROLE + 4, g_reg[1]);
        }
        __syncwarp();
        bar_sync(BAR_PDONE, 384);
        KT_MARK(9);
        if (warp == 8) {
            const uint32_t dst = lane < 14 ? stg_wo(lane) : lane < 16 ? SM_WO1 + (lane - 8) * 2048 : SM_WO2 + (lane - 16) * 2048;
            tma_load_2d(sb + dst, &mapWo, 256 * j + 64 * (lane >> 3), h * DH + 16 * (lane & 7), sb + MB_W3, EF_W ? policy_evict_first() : policy_evict_normal());
        }
        if ((warp & 1) == 0) for (int c = (warp - 8) * 16 + lane; c < 512; c += 64) {
            uint32_t w[4];
#pragma unroll
            for (int r = 0; r < 4; r++) {
                const uint32_t lo = reinterpret_cast<const uint16_t*>(mem0)[(2 * r) * DM + 512 * kh + c], hi = reinterpret_cast<const uint16_t*>(mem0)[(2 * r + 1) * DM + 512 * kh + c];
                w[r] = lo | (hi << 16);
            }
            sts128(sb + SM_Z + (c ^ (256 * kflip)) * 16, make_uint4(w[0], w[1], w[2], w[3]));
        }
        if (!PRO3 && warp == 8) mbar_wait_w(sb + MB_W5, 0);
        auto tok_start = [&](int s) {
            if (lane == 0) {
                if (TS_AT == 0) TL(21);
                if (s > -3 && s + 2 < NSEG) {
                    mbar_wait(sb + MB_STG, (s + 2) & 1);
                    if (TS_AT == 1) TL(21);
                    if (XT_FIRST && s + 4 < NSEG) load_xt(s + 4, 0);
                    if (TS_AT == 2) TL(21);
                    asm volatile("fence.proxy.async.shared::cta;" ::: "memory");
                    if (TS_AT == 3) TL(21);
                    const int r = ((s + 2) & 3) * NH + h;
                    tma_store_2d(kh ? &mapT32 : &mapTQ, sb + SM_STG, kh ? 64 * nh : 256 * nh, kh ? r * 96 + 32 : r * 12);
                    tma_store_2d(&mapT16, sb + SM_STG + 4096, 64 * nh, r * 96 + 64 + 16 * kh);
                    asm volatile("cp.async.bulk.commit_group;" ::: "memory");
                    if (TS_AT == 4) TL(21);
                }
                if ((TS_LATE < 3 || s < 0) && (!XT_FIRST || s == -3) && s + 4 < NSEG) load_xt(s + 4, 0);
                if (!LATE_RD || s < 0) asm volatile("cp.async.bulk.wait_group.read 0;" ::: "memory");
                if (s < 0) {
                    asm volatile("mbarrier.arrive.shared::cluster.b64 _, [%0];" ::"r"(rsb + MB_FREE) : "memory");
                    mbar_wait(sb + MB_FREE, (s + 3) & 1);
                }
            }
            __syncwarp();
        };
        auto tok_mid = [&](int s) {
            if (lane == 0) {
                if (s + 4 < NSEG) load_xt(s + 4, 1);
                if (s > -3 && s + 2 < NSEG) {
                    asm volatile("cp.async.bulk.wait_group 0;" ::: "memory");
                    if (s == 8 || s == 16) asm volatile("fence.acq_rel.gpu;" ::: "memory");
                    st_relaxed_u32(g_xflag + role, s + 3);
                }
            }
            __syncwarp();
        };
        auto kv_check = [&](int s) {
            if (s + 1 < NSEG) {
                if (lane < 4) {
                    unsigned f; int guard = 0;
                    do {
                        asm volatile("ld.acquire.gpu.global.u32 %0, [%1];" : "=r"(f) : "l"(g_xflag + h * 4 + lane) : "memory");
                        if (++guard > (1 << 20)) __trap();
                    } while (f <= (unsigned)(s + 1));
                }
                __syncwarp();
                asm volatile("fence.proxy.async.global;" ::: "memory");
            }
        };
        auto kv_load = [&](int s) {
            if (lane == 0 && s + 1 < NSEG) {
                const uint32_t bar = sb + MB_KV + ((s + 1) & 1) * 8, dst = sb + SM_KV + ((s + 1) & 1) * KV_BYTES;
                const int row = (((s + 1) & 3) * NH + h) * 96;
                mbar_expect_tx(bar, KV_BYTES);
                asm volatile("cp.async.bulk.tensor.3d.shared::cluster.global.mbarrier::complete_tx::bytes.multicast::cluster [%0], [%1, {%3, %4, %3}], [%2], %5;"
                             ::"r"(dst + kh * 8192), "l"(&mapKV), "r"(bar), "r"(0), "r"(row + 32 + 32 * kh), "h"((uint16_t)3) : "memory");
                bulk_load(dst + 16384, g_tok + row * DH + j * 1024, 2048, bar);
            }
            __syncwarp();
        };
        if (warp == 9) {
            if (!PRO2 && lane == 0) { load_xt(0, 0); load_xt(0, 1); }
#pragma unroll 1
            for (int s = -3; s < 0; s++) { tok_start(s); KT_MARK(13 + s); bar_arrive(BAR_PRO, 288); tok_mid(s); }
        }
        if (warp == 11) { kv_check(-1); kv_load(-1); }
        bar_arrive(BAR_MEM, 384);
        const uint32_t idx = HS == 6 ? (pair & 31) + 32 * (kh ^ 1) : role & 63;
        const uint32_t ybox = mlo + page_off(idx, cls ^ YFLIP_()), xoth = mlo + WIN + page_off((pair & 31) ^ 1, cls ^ XFLIP);
        const uint32_t zline = mlo + WIN + page_off(32 + (idx >> 5), cls ^ ZFLIP) + (idx & 31) * 128, zbox = mlo + WIN + (page_off(32 + kh, 0) & ~4096u);
        const uint32_t xtype = g == GV ? 2 : g == 2 ? 0 : 1;
        const uint32_t ydst = (lane >> 3) * 128 + ((lane & 7) ^ (lane >> 3)) * 16, ysrc = lane * 128 + ((2 * g) ^ (lane & 7)) * 16;
#pragma unroll 1
        for (int s = 0; s < NSEG; s++) {
            const uint32_t slot = (s & 3) << 14;
            spin_cycles(DLY_T);
            if (g == 3) {
                spin_cycles(DLY_K);
                kv_check(s);
                if (TS_AT == 9) TL(21);
                const uint32_t L = l16, kvo = (s & 1) * KV_BYTES, qa = QFRAG(), sa = sb + SM_S + 512 + (L >> 2);
                float sc[4] = {0.f, 0.f, 0.f, 0.f}, sd[4] = {0.f, 0.f, 0.f, 0.f};
                uint32_t a[4][4], kb[2][4];
                mbar_wait_w(sb + MB_KV + (s & 1) * 8, (s >> 1) & 1);
                mbar_wait_w(sb + MB_P, s & 1);
#pragma unroll
                for (int c = 0; c < 2; c++) {
                    const uint32_t qc = qa + (sb + (nh ^ c) * 1024), kc = L + (sb + SM_QKV + 2048 + (nh ^ c) * 1024);
                    if (TS_AT == 7 && c) TL(21);
                    if (c) bar_sync(BAR_QK, 224);
                    ldsm4t(kb[0], kc); ldsm4t(a[0], qc); ldsm4t(a[1], qc + 256);
                    ldsm4t(kb[1], kc + 512); ldsm4t(a[2], qc + 512); ldsm4t(a[3], qc + 768);
                    mma16816v(sc, a[0], kb[0][0], kb[0][1]);
                    mma16816v(sd, a[1], kb[0][2], kb[0][3]);
                    mma16816v(sc, a[2], kb[1][0], kb[1][1]);
                    mma16816v(sd, a[3], kb[1][2], kb[1][3]);
                }
                sts32(sa, scale_scores(sc[0] + sd[0], sc[1] + sd[1]));
                sts32(sa + 768, scale_scores(sc[2] + sd[2], sc[3] + sd[3]));
                bar_arrive(BAR_S, 160);
                TL(25);
                bar_sync(BAR_SV, NSV);
                if (RT_BULK == 2) kv_load(s);
                if (RT_BULK && lane == 0 && s + 3 < NSEG) {
                    if (!FENCE_W) asm volatile("fence.proxy.async.shared::cta;" ::: "memory");
                    asm volatile("cp.async.bulk.shared::cluster.shared::cta.mbarrier::complete_tx::bytes [%0], [%1], %2, [%3];" ::"r"(rsb + SM_RT), "r"(sb + SM_Z), "n"(8192), "r"(rsb + MB_RT0) : "memory");
                    if (TS_AT == 10) { mbar_wait(sb + MB_RT0, (s + 3) & 1); TL(21); }
                }
                __syncwarp();
                if (RT_BULK != 2) kv_load(s);
            } else {
                if (g == 1 && (TS_LATE == 0 || TS_LATE >= 3)) { spin_cycles(DLY_S); tok_start(s); if (TS_AT == 5) TL(21); if (s == 0) KT_MARK(13); }
                const char* p = make_ptr(l16 + (xoth + xtype * 1024 + slot), mhi);
                uint4 v[2];
                const uint32_t dst = l16 + (sb + SM_QKV + xtype * 2048 + (nh ^ 1) * 1024);
                asm volatile("" ::"l"(p));
                poll_init(v[0]); poll_init(v[1]);
                if (g == GV) {
                    bar_sync(BAR_PUBV, 160);
                    mbar_wait_w(sb + MB_V, s & 1);
                    spin_cycles(DLY_V);
                } else {
                    bar_sync(BAR_PUB, 192);
                    spin_cycles(DLY_X);
                }
                const int r = poll2(v, p);
                sts128(dst, v[0]); sts128(dst + 512, v[1]);
                STAT(1, r > 1 && warp == 10);
                if (g != GV) bar_arrive(BAR_QK, 224);
                if (TS_AT == 6 && g == 0) TL(21);
                if (g == GV) { bar_arrive(BAR_V, 160); if (GV == 0) bar_arrive(BAR_SV, NSV); TL(17); }
                if (g == 1) {
                    TL(31);
                    if (TS_LATE == 1) { tok_start(s); if (TS_AT == 5) TL(21); }
                    if (TS_LATE == 3 && lane == 0 && s + 4 < NSEG) load_xt(s + 4, 0);
                    if (LATE_RD && (TS_LATE == 0 || TS_LATE >= 3)) asm volatile("cp.async.bulk.wait_group.read 0;" ::: "memory");
                    bar_sync(BAR_SV, NSV);
                    if (TS_LATE == 2) { tok_start(s); if (TS_AT == 5) TL(21); }
                    if (TS_LATE == 4 && lane == 0 && s + 4 < NSEG) load_xt(s + 4, 0);
                    tok_mid(s);
                    TL(22);
                }
                if (g == 2 && s >= 1) {
                    TL(16);
                    const uint32_t prev = (slot - 0x4000) & 0xC000;
                    const char* y = make_ptr(l16 + (ybox + prev), mhi);
                    const char* x = make_ptr(l16 + (xoth + prev + kh * (XP ? 2048 : 1536)), mhi);
#pragma unroll
                    for (int i = 0; i < 8; i++) st_sent(y + i * 512);
#pragma unroll
                    for (int i = 0; i < (XP ? 4 : 3); i++) st_sent(x + i * 512);
                    st_relaxed_u32(make_ptr(lane * 4 + (zline + (slot ^ 0x8000)), mhi), SENT);
                    TL(23);
                }
            }
            if (s + 1 == NSEG) break;
            {
                const char* p = make_ptr(l16 + (ybox + g * 1024 + slot), mhi);
                char* zdst = make_ptr(lane * 4 + (zline + g * 32 + slot), mhi);
                const uint32_t dst = ydst + (sb + SM_Y + g * 1024), dst1 = (ydst ^ 64) + (sb + SM_Y + g * 1024 + 512), src = ysrc + (sb + SM_Y), src1 = (ysrc ^ 16) + (sb + SM_Y);
                asm volatile("" ::"l"(p), "l"(zdst));
                uint4 v[2];
                poll_init(v[0]); poll_init(v[1]);
                bar_sync(BAR_SENTC, 384);
                spin_cycles(DLY_Y);
                const int r = poll2(v, p);
                STAT(2, r > 1 && warp == 8);
                sts128(dst, v[0]); sts128(dst1, v[1]);
                bar_sync(BAR_Y, HS == 6 ? 256 : 128);
                TL(18);
                uint32_t b[2][4];
                ldsm4t(b[0], src); ldsm4t(b[1], src1);
                const uint32_t one = 0x3F803F80u;
                float d0[4] = {0.f, 0.f, 0.f, 0.f}, d1[4] = {0.f, 0.f, 0.f, 0.f};
                mma16816(d0, one, one, one, one, b[0][0], b[0][1]);
                mma16816(d1, one, one, one, one, b[1][0], b[1][1]);
                mma16816(d0, one, one, one, one, b[0][2], b[0][3]);
                mma16816(d1, one, one, one, one, b[1][2], b[1][3]);
                const uint32_t w = (lane & 4) ? pack_bf16(d1[0], d1[1]) : pack_bf16(d0[0], d0[1]);
                asm volatile("{.reg .pred p; setp.lt.u32 p, %2, 128; @p st.relaxed.gpu.global.u32 [%0], %1;}" ::"l"(zdst), "r"(w), "r"(l16) : "memory");
                if (s + 3 < NSEG) bar_arrive(BAR_ZP, 256);
                TL(19);
            }
            {
                const char* p = make_ptr(l16 + (zbox + g * 512 + slot), mhi);
                const uint32_t dst = l16 + (sb + SM_Z + g * 512);
                asm volatile("" ::"l"(p));
                uint4 v[4];
                poll_init(v[0]); poll_init(v[1]); poll_init(v[2]); poll_init(v[3]);
                bar_sync(BAR_COMM, 128);
                spin_cycles(DLY_Z);
                const int r = poll4<2048>(v, p);
                STAT(0, r > 1 && warp == 8);
#pragma unroll
                for (int i = 0; i < 4; i++) sts128(dst + i * 2048, v[i]);
                bar_arrive(BAR_MEM, 384);
                TL(20);
            }
        }
    } else if (warp < 4) {
        asm volatile("setmaxnreg.inc.sync.aligned.u32 %0;" ::"n"(REG_A));
        code_pad<PAD_A>();
        const uint32_t l16 = lane16();
        uint32_t wa[2][24][4];
        {
            const uint32_t L = l16, fa = sb + FRAG();
            mbar_wait_w(sb + MB_W1, 0);
            KT_MARK(7);
#pragma unroll
            for (int t = 0; t < 2; t++) {
#pragma unroll
                for (int r = 0; r < 24; r++) ldsm4t(wa[t][r], fa + stg_qk(t, r));
                if (PRO2 && t == 0) { bar_arrive(BAR_XT0, 160); mbar_wait_w(sb + MB_W4, 0); }
            }
            mbar_wait_w(sb + MB_W2, 0);
            if (EARLY_ROLE) bar_sync(BAR_PDONE, 384); else bar_arrive(BAR_PDONE, 384);
        }
        auto batch1 = [&](float (&d)[16], uint32_t lo, auto tc, auto k0c, auto k1c) {
            constexpr int t = decltype(tc)::value;
            const uint64_t da = make_desc(SB0 + SM_WQK, 16, 1024);
            wg_fence();
            static_for<decltype(k0c)::value, decltype(k1c)::value>([&](auto kc) {
                constexpr int i = decltype(kc)::value, k = kstep(t ? ORD1 : ORD0, i), off = (k >> 2) * 256 + (k & 3) * 2;
                if constexpr (k >= 24) wgmma_ss32u<off, i != 0 || t != 0>(d, da + ((k - 24) * 2 + t) * 128, lo);
                else wgmma_rs32u<off, i != 0 || t != 0>(d, wa[t][k], lo);
            });
            wg_commit();
        };
        const uint32_t xbox = mlo + WIN + page_off(pair & 31, cls ^ XFLIP);
        const uint32_t ybox = mlo + page_off(24 + 2 * g + 32 * nh, kh ^ YFLIP_()) + h * 128;
#pragma unroll 1
        for (uint32_t it = 0; it < NSEG + 3; it++) {
            const int s = (int)it - 3;
            const uint32_t ui = uniform(it), slot = ((ui + 1) & 3) << 14, kvo = (~ui & 1) * KV_BYTES, xtlo = XTLO();
            {
                PHASE(5);
                const uint32_t first = L | (g << 9);
                if (s >= 0) mbar_expect_tx_if0(first, sb + MB_R1, 2048);
                if (s + 3 < NSEG) {
                    mbar_expect_tx_if0(first, sb + MB_RT0, (RT_BF & 1) ? 4096 : RT0_N * 2048);
                    mbar_wait_w(sb + MB_XT + (ui & 1) * 8, (it >> 1) & 1);
                }
            }
            if (s >= 0) {
                PHASE(0);
                const uint32_t mb = L + (sb + SM_Z), ra = L + (sb + g * 512), r1 = L + (rsb + SM_R1 + g * 512), r1b = rsb + MB_R1;
                sched_fence(r1);
                bar_sync(BAR_MEM, 384);
                TLB(0);
                float acc[2][2][4];
#pragma unroll
                for (int t = 0; t < 4; t++) { acc[t >> 1][t & 1][0] = acc[t >> 1][t & 1][1] = acc[t >> 1][t & 1][2] = acc[t >> 1][t & 1][3] = 0.f; }
                uint32_t b[4][4];
                uint4 u0, u1;
#pragma unroll
                for (int p = 0; p < 4; p++) ldsm4t(b[p], mb + p * 512);
#pragma unroll
                for (int p = 0; p < 12; p++) {
#pragma unroll
                    for (int u = 0; u < 2; u++) {
                        mma16816v(acc[0][u], wa[0][2 * p + u], b[p & 3][2 * u], b[p & 3][2 * u + 1]);
                        mma16816v(acc[1][u], wa[1][2 * p + u], b[p & 3][2 * u], b[p & 3][2 * u + 1]);
                    }
                    if (p + 4 < 12) ldsm4t(b[p & 3], mb + (p + 4) * 512);
                    if (p == Q3_AT) {
                        bar_sync(BAR_Q3, 256);
                        u0 = lds128(ra + SM_R3); u1 = lds128(ra + SM_O);
                    }
                }
                st_async4(r1, (acc[0][0][0] + __uint_as_float(u0.x)) + acc[0][1][0], (acc[0][0][1] + __uint_as_float(u0.y)) + acc[0][1][1],
                          (acc[0][0][2] + __uint_as_float(u0.z)) + acc[0][1][2], (acc[0][0][3] + __uint_as_float(u0.w)) + acc[0][1][3], r1b);
                TL(1);
                const float o0 = (acc[1][0][0] + __uint_as_float(u1.x)) + acc[1][1][0], o1 = (acc[1][0][1] + __uint_as_float(u1.y)) + acc[1][1][1];
                const float o2 = (acc[1][0][2] + __uint_as_float(u1.z)) + acc[1][1][2], o3 = (acc[1][0][3] + __uint_as_float(u1.w)) + acc[1][1][3];
                const uint32_t l4 = L >> 2, qo = SM_QKV + kh * 2048 + nh * 1024 + g * 256, qr = l4 + (rsb + qo), ql = l4 + (sb + qo), pb = rsb + MB_P;
                char* xd = make_ptr(l4 + (xbox + kh * 1024 + g * 256 + slot), mhi);
                asm volatile("" ::"l"(xd), "r"(qr), "r"(pb), "r"(qr + 128), "f"(o0), "f"(o1), "f"(o2), "f"(o3));
                mbar_wait_w(sb + MB_R1, s & 1);
                const uint4 v = lds128(ra + SM_R1);
                const uint32_t w0 = pack_bf16(o0 + __uint_as_float(v.x), o1 + __uint_as_float(v.y)), w1 = pack_bf16(o2 + __uint_as_float(v.z), o3 + __uint_as_float(v.w));
                st_relaxed_u32(xd, w0);
                st_relaxed_u32(xd + 128, w1);
                bar_arrive(BAR_PUB, 192);
                st_async1(qr, w0, pb);
                st_async1(qr + 128, w1, pb);
                sts32(ql, w0);
                sts32(ql + 128, w1);
                __syncwarp();
                mbar_expect_tx_if0(L, sb + MB_P, 256);
                if (!XB_EARLY) TL(2);
                if (XB_EARLY || s + 3 < NSEG) bar_sync(BAR_VP, 256);
            } else {
                bar_sync(BAR_PRO, 288);
            }
            if (s + 3 < NSEG) {
                float d[16];
                batch1(d, xtlo, std::integral_constant<int, 0>(), std::integral_constant<int, 0>(), std::integral_constant<int, 32>());
                PHASE(1);
                const uint32_t rt = L + (rsb + SM_RT + g * 2048);
                wg_wait<0>();
                TL(7);
                if (RT_BF & 1) {
#pragma unroll
                    for (int i = 0; i < 2; i++)
                        st_async4(rt + i * 512, __uint_as_float(pack_bf16(d[8 * i], d[8 * i + 1])), __uint_as_float(pack_bf16(d[8 * i + 2], d[8 * i + 3])),
                                  __uint_as_float(pack_bf16(d[8 * i + 4], d[8 * i + 5])), __uint_as_float(pack_bf16(d[8 * i + 6], d[8 * i + 7])), rsb + MB_RT0);
                } else if (RT_BULK && s >= 0) {
                    const uint32_t pk = L + (sb + SM_Z + g * 2048);
#pragma unroll
                    for (int i = 0; i < 4; i++) sts128(pk + i * 512, make_uint4(__float_as_uint(d[4 * i]), __float_as_uint(d[4 * i + 1]), __float_as_uint(d[4 * i + 2]), __float_as_uint(d[4 * i + 3])));
                    if (FENCE_W) asm volatile("fence.proxy.async.shared::cta;" ::: "memory");
                } else {
#pragma unroll
                for (int i = 0; i < RT0_N; i++) {
                    if (i == RT0_AT && s >= 0) bar_sync(BAR_SV, NSV);
                    st_async4(rt + i * 512, d[4 * i], d[4 * i + 1], d[4 * i + 2], d[4 * i + 3], rsb + MB_RT0);
                }
                }
            }
            if (s + 1 == NSEG) { bar_arrive(BAR_SV, NSV); break; }
            if (s >= 0) {
                PHASE(2);
                const uint32_t fo = FRAG() + (sb + SM_WO2 + 16384), lo = L + (sb + SM_O), yo = (L >> 2) + (ybox + slot);
                uint32_t a1[8][4];
                if (RT0_AT >= 4 || s + 3 >= NSEG) bar_sync(BAR_SV, NSV);
#pragma unroll
                for (int k = 0; k < 8; k++) ldsm4t(a1[k], fo + k * 2048);
                sched_fence(yo);
                bar_sync(BAR_O2, 256);
                TLB(14);
                float y0[4] = {0.f, 0.f, 0.f, 0.f}, y1[4] = {0.f, 0.f, 0.f, 0.f};
                uint32_t b[2][4];
                ldsm4t(b[0], lo); ldsm4t(b[1], lo + 512);
                sched_fence(L);
#pragma unroll
                for (int p = 0; p < 4; p++) {
                    mma16816v(y0, a1[2 * p], b[p & 1][0], b[p & 1][1]);
                    mma16816v(y1, a1[2 * p + 1], b[p & 1][2], b[p & 1][3]);
                    if (p < 2) ldsm4t(b[p & 1], lo + (p + 2) * 512);
                }
                bar_sync(BAR_INV, 256);
                float i0, i1;
                asm volatile("ld.shared.v2.f32 {%0, %1}, [%2];" : "=f"(i0), "=f"(i1) : "r"(((L >> 1) & 0x18) + (sb + SM_INV + g * 32)) : "memory");
                st_relaxed_u32(make_ptr(yo, mhi), pack_bf16((y0[0] + y1[0]) * i0, (y0[1] + y1[1]) * i1));
                st_relaxed_u32(make_ptr(yo ^ 4096, mhi) + 0x2000, pack_bf16((y0[2] + y1[2]) * i0, (y0[3] + y1[3]) * i1));
                bar_arrive(BAR_SENTC, 384);
                TL(6);
            }
            if (s + 3 < NSEG) {
                PHASE(4);
                float d[16];
                const uint32_t rt = L + (sb + SM_RT + g * 2048);
                if (SENT_EARLY && s >= 0) bar_sync(BAR_SENT, 256);
                mbar_wait_w(sb + MB_RT0, it & 1);
                if (HS == 6 && s >= 0) bar_arrive(BAR_Y, 256);
                if (RT_BF & 1) {
#pragma unroll
                    for (int i = 0; i < 2; i++) {
                        const uint4 v = lds128(rt + i * 512);
                        d[8 * i] = bf_lo(v.x); d[8 * i + 1] = bf_hi(v.x); d[8 * i + 2] = bf_lo(v.y); d[8 * i + 3] = bf_hi(v.y);
                        d[8 * i + 4] = bf_lo(v.z); d[8 * i + 5] = bf_hi(v.z); d[8 * i + 6] = bf_lo(v.w); d[8 * i + 7] = bf_hi(v.w);
                    }
                } else
#pragma unroll
                for (int i = 0; i < 4; i++) {
                    const uint4 v = lds128(rt + i * 512);
                    d[4 * i] = __uint_as_float(v.x); d[4 * i + 1] = __uint_as_float(v.y); d[4 * i + 2] = __uint_as_float(v.z); d[4 * i + 3] = __uint_as_float(v.w);
                }
                if (!SENT_EARLY && s >= 0) bar_sync(BAR_SENT, 256);
                if (SPLIT > 0) batch1(d, xtlo, std::integral_constant<int, 1>(), std::integral_constant<int, 0>(), std::integral_constant<int, SPLIT>());
                if (s >= 0) bar_sync(BAR_ZP, 256);
                TLB(30);
                batch1(d, xtlo, std::integral_constant<int, 1>(), std::integral_constant<int, SPLIT>(), std::integral_constant<int, 32>());
                const uint32_t so = (kh ? FRAG() : ((L & 0x100) << 2) + (L & 0xF0) + g * 256) + (sb + SM_STG);
                wg_wait<0>();
                TL(8);
                uint32_t w[8];
#pragma unroll
                for (int i = 0; i < 8; i++) w[i] = pack_bf16(d[2 * i], d[2 * i + 1]);
                if (kh) {
                    stsm4t(so, w[0], w[1], w[2], w[3]);
                    stsm4t(so + 2048, w[4], w[5], w[6], w[7]);
                } else {
                    stsm4(so, w[0], w[1], w[2], w[3]);
                    stsm4(so + 2048, w[4], w[5], w[6], w[7]);
                }
                __syncwarp();
                mbar_arrive_if0(L, sb + MB_STG);
                TL(9);
            } else {
                bar_arrive(BAR_SENT, 256);
                if (HS == 6) bar_arrive(BAR_Y, 256);
            }
        }
    } else {
        asm volatile("setmaxnreg.inc.sync.aligned.u32 %0;" ::"n"(REG_B));
        code_pad<PAD_B>();
        const uint32_t l16 = lane16();
        uint32_t wv[24][4], wo[8 + WO_RF1][4];
        {
            const uint32_t L = l16, fa = sb + FRAG();
            mbar_wait_w(sb + MB_W0, 0);
            KT_MARK(6);
#pragma unroll
            for (int r = 0; r < 24; r++) ldsm4t(wv[r], fa + STG_V + r * 2048);
#pragma unroll
            for (int r = 0; r < 8 + WO_RF1; r++) asm volatile("" : "=r"(wo[r][0]), "=r"(wo[r][1]), "=r"(wo[r][2]), "=r"(wo[r][3]));
            mbar_wait_w(sb + MB_W2, 0);
            if (EARLY_ROLE) bar_sync(BAR_PDONE, 384); else bar_arrive(BAR_PDONE, 384);
        }
        const uint32_t xbox = XP ? mlo + WIN + page_off(34 + ((pair & 31) >> 1), cls ^ XFLIP) + nh * 2048 : mlo + WIN + page_off(pair & 31, cls ^ XFLIP);
        const uint32_t ybox = mlo + page_off(2 * g + 32 * nh, kh ^ YFLIP_()) + h * 128;
#pragma unroll 1
        for (uint32_t it = 0; it < NSEG + 3; it++) {
            const int s = (int)it - 3;
            const uint32_t ui = uniform(it), slot = ((ui + 1) & 3) << 14, kvo = (~ui & 1) * KV_BYTES, xtlo = XTLO();
            {
                PHASE(5);
                const uint32_t first = L | (g << 9);
                if (s >= 0) mbar_expect_tx_if0(first, sb + MB_R2, 1024);
                if (s + 3 < NSEG) {
                    mbar_expect_tx_if0(first, sb + MB_RT1, (RT_BF & 2) ? 2048 : 4096);
                    mbar_wait_w(sb + MB_XT + (ui & 1) * 8, (it >> 1) & 1);
                }
            }
            if (s >= 0) {
                PHASE(0);
                const uint32_t fo = FRAG() + sb, l4 = L >> 2;
                {
                    const uint32_t mb = L + (sb + SM_Z), aw = fo + SM_WQK, ra = L + (sb + g * 512), r2 = (L >> 1) + (rsb + SM_R2 + g * 256), r2b = rsb + MB_R2;
                    uint32_t a[NA][4], b[4][4];
#pragma unroll
                    for (int i = 0; i < NA; i++) ldsm4t(a[i], aw + i * 2048);
                    sched_fence(L);
                    TL(24);
                    bar_sync(BAR_MEM, 384);
#pragma unroll
                    for (int p = 0; p < 4; p++) ldsm4t(b[p], mb + (12 + p) * 512);
                    sched_fence(L);
                    float c[2][4] = {{0.f, 0.f, 0.f, 0.f}, {0.f, 0.f, 0.f, 0.f}};
#pragma unroll
                    for (int i = 0; i < 16; i++) {
                        mma16816v(c[i & 1], a[i % NA], b[i >> 2][i & 2], b[i >> 2][(i & 2) + 1]);
                        ldsm4t(a[i % NA], aw + (i + NA) * 2048);
                    }
                    sts128(ra + SM_R3, make_uint4(__float_as_uint(c[0][0]), __float_as_uint(c[0][1]), __float_as_uint(c[0][2]), __float_as_uint(c[0][3])));
                    sts128(ra + SM_O, make_uint4(__float_as_uint(c[1][0]), __float_as_uint(c[1][1]), __float_as_uint(c[1][2]), __float_as_uint(c[1][3])));
                    bar_arrive(BAR_Q3, 256);
                    TL(29);
                    float acc[4][4];
#pragma unroll
                    for (int t = 0; t < 4; t++) { acc[t][0] = acc[t][1] = acc[t][2] = acc[t][3] = 0.f; }
#pragma unroll
                    for (int i = 16; i < 24; i++) {
                        mma16816v(acc[i & 1], a[i % NA], b[(i - 16) >> 1][2 * (i & 1)], b[(i - 16) >> 1][2 * (i & 1) + 1]);
                        if (i + NA < 24) ldsm4t(a[i % NA], aw + (i + NA) * 2048);
                        else ldsm4t(a[i % NA], mb + (i + NA - 24) * 512);
                    }
#pragma unroll
                    for (int p = 0; p < 12; p++) {
                        mma16816v(acc[(2 * p) & 3], wv[2 * p], a[(24 + p) % NA][0], a[(24 + p) % NA][1]);
                        mma16816v(acc[(2 * p + 1) & 3], wv[2 * p + 1], a[(24 + p) % NA][2], a[(24 + p) % NA][3]);
                        if (p + NA < 12) ldsm4t(a[(24 + p) % NA], mb + (p + NA) * 512);
                    }
                    if (XB_EARLY || s + 3 < NSEG) bar_arrive(BAR_VP, 256);
                    float o[4];
#pragma unroll
                    for (int i = 0; i < 4; i++) o[i] = (acc[0][i] + acc[1][i]) + (acc[2][i] + acc[3][i]);
                    st_async2(r2, kh ? o[0] : o[2], kh ? o[1] : o[3], r2b);
                    TL(10);
                    const float o0 = kh ? o[2] : o[0], o1 = kh ? o[3] : o[1];
                    const uint32_t qo = SM_QKV + 4096 + nh * 1024 + (2 * g + kh) * 128, qr = l4 + (rsb + qo), ql = l4 + (sb + qo), vb = rsb + MB_V, rl = (L >> 1) + (sb + SM_R2 + g * 256);
                    char* xd = make_ptr(l4 + (xbox + 2048 + (2 * g + kh) * 128 + slot), mhi);
                    asm volatile("" ::"l"(xd), "r"(qr), "r"(vb), "f"(o0), "f"(o1));
                    mbar_wait_w(sb + MB_R2, s & 1);
                    uint32_t vx, vy;
                    asm volatile("ld.shared.v2.u32 {%0,%1}, [%2];" : "=r"(vx), "=r"(vy) : "r"(rl) : "memory");
                    const uint32_t w0 = pack_bf16(o0 + __uint_as_float(vx), o1 + __uint_as_float(vy));
                    st_relaxed_u32(xd, w0);
                    bar_arrive(BAR_PUBV, 160);
                    st_async1(qr, w0, vb);
                    sts32(ql, w0);
                    __syncwarp();
                    mbar_expect_tx_if0(L, sb + MB_V, 128);
                    TL(11);
                }
                const uint32_t vma = L + (sb + SM_QKV + 4096 + g * 512), yo = l4 + (ybox + slot);
                uint32_t va[2][2][4];
                {
                    const uint32_t qa = QFRAG(), vf = VFRAG(), va0 = vf + VBASE(), va1 = (vf ^ 32) + VBASE();
                    const uint32_t kf = ((L << 3) & 0x380) | ((L ^ (L >> 3)) & 0x30) | (L & 0x40), kb0 = sb + SM_KV + kvo + g * 1024;
                    const int d = (int)(L >> 6) - (int)((L >> 3) & 6) + 8 * (j - (int)g);
                    const uint32_t keep = (d < 0 ? 0u : 0xFFFFu) | (d < 1 ? 0u : 0xFFFF0000u), sa = l4 + (sb + SM_S + g * 128);
                    const uint32_t q0 = qa + (sb + nh * 1024), q1 = qa + (sb + (nh ^ 1) * 1024);
                    float sc[4] = {0.f, 0.f, 0.f, 0.f}, sd[4] = {0.f, 0.f, 0.f, 0.f};
                    uint32_t a[4][4], kb[2][4];
                    mbar_wait_w(sb + MB_KV + (~ui & 1) * 8, (s >> 1) & 1);
                    ldsm4(kb[0], kf + (kb0 + nh * 4096)); ldsm4(kb[1], (kf ^ 64) + (kb0 + nh * 4096));
                    mbar_wait_w(sb + MB_P, s & 1);
                    TL(12);
#pragma unroll
                    for (int k = 0; k < 4; k++) ldsm4t(a[k], q0 + k * 256);
#pragma unroll
                    for (int k = 0; k < 4; k++) mma16816v((k & 1) ? sd : sc, a[k], kb[k >> 1][2 * (k & 1)], kb[k >> 1][2 * (k & 1) + 1]);
                    ldsm4(kb[0], kf + (kb0 + (nh ^ 1) * 4096)); ldsm4(kb[1], (kf ^ 64) + (kb0 + (nh ^ 1) * 4096));
                    sched_fence(vf | yo);
                    if (TS_AT == 8) TL(21);
                    bar_sync(BAR_QK, 224);
                    TLB(3);
#pragma unroll
                    for (int k = 0; k < 4; k++) ldsm4t(a[k], q1 + k * 256);
                    sched_fence(L);
#pragma unroll
                    for (int k = 0; k < 4; k++) mma16816v((k & 1) ? sd : sc, a[k], kb[k >> 1][2 * (k & 1)], kb[k >> 1][2 * (k & 1) + 1]);
                    ldsm4t(va[0][0], va0); ldsm4t(va[0][1], va0 + 2048);
                    sts32(sa, scale_scores(sc[0] + sd[0], sc[1] + sd[1]));
                    sts32(sa + 768, (scale_scores(sc[2] + sd[2], sc[3] + sd[3]) & keep) | (0xFF80FF80u & ~keep));
                    bar_arrive(BAR_SV, NSV);
                    ldsm4t(va[1][0], va1); ldsm4t(va[1][1], va1 + 2048);
                }
                bar_sync(BAR_S, 160);
                TLB(4);
                uint32_t pw[6], vm[4];
                if (s + 1 < NSEG) {
                softmax40(pw, l4 + (sb + SM_S), [&]() {
                    bar_sync(BAR_V, 160);
                    ldsm4(vm, vma);
                });
                uint32_t a1[NP2][4];
                float inv[2];
                {
                    uint32_t w[4];
                    pv32<false>(w, inv, va, vm, pw, [&]() {
                        sched_fence(L);
#pragma unroll
                        for (int k = 0; k < NP2; k++) ldsm4t(a1[k], fo + SM_WO2 + k * 2048);
                    });
#pragma unroll
                    for (int i = 0; i < 4; i++) sts32(l4 + (sb + SM_O + g * 512) + i * 128, w[i]);
                }
                const uint32_t lo = L + (sb + SM_O);
                bar_arrive(BAR_O2, 256);
                bar_sync(BAR_O, 128);
                TLB(5);
                {
                    float y0[4] = {0.f, 0.f, 0.f, 0.f}, y1[4] = {0.f, 0.f, 0.f, 0.f}, y2[4] = {0.f, 0.f, 0.f, 0.f};
                    uint32_t b[4][4];
#pragma unroll
                    for (int p = 0; p < 4; p++) ldsm4t(b[p], lo + p * 512);
                    inv[0] = rcp_approx(inv[0]); inv[1] = rcp_approx(inv[1]);
                    asm volatile("st.shared.v2.f32 [%0], {%1, %2};" ::"r"(((L >> 1) & 0x18) + (sb + SM_INV + g * 32)), "f"(inv[0]), "f"(inv[1]) : "memory");
                    bar_arrive(BAR_INV, 256);
                    sched_fence(L);
#pragma unroll
                    for (int k = 0; k < 8; k++) {
                        const int p = k >> 1, u = k & 1;
                        mma16816v(y2, a1[k % NP2], b[p][2 * u], b[p][2 * u + 1]);
                        if (k + NP2 < 8) ldsm4t(a1[k % NP2], fo + SM_WO2 + (k + NP2) * 2048);
                        else if (k + NP2 < 16 - WO_RF1) ldsm4t(a1[k % NP2], fo + SM_WO1 + (k + NP2 - 8 + WO_RF1) * 2048);
                        mma16816v(y0, wo[k], b[p][2 * u], b[p][2 * u + 1]);
                        if (k < WO_RF1) mma16816v(y1, wo[8 + (k < WO_RF1 ? k : 0)], b[p][2 * u], b[p][2 * u + 1]);
                        else mma16816v(y1, a1[(k + 8 - WO_RF1) % NP2], b[p][2 * u], b[p][2 * u + 1]);
                        if (k < P2_FENCE) sched_fence(L);
                    }
                    char* yd = make_ptr(yo, mhi);
                    char* yd1 = make_ptr(yo ^ 4096, mhi);
                    st_relaxed_u32(yd1 + 0x80000, pack_bf16(y2[0] * inv[0], y2[1] * inv[1]));
                    st_relaxed_u32(yd + 0x82000, pack_bf16(y2[2] * inv[0], y2[3] * inv[1]));
                    st_relaxed_u32(yd, pack_bf16(y0[0] * inv[0], y0[1] * inv[1]));
                    st_relaxed_u32(yd1 + 0x2000, pack_bf16(y0[2] * inv[0], y0[3] * inv[1]));
                    st_relaxed_u32(yd + 0x40000, pack_bf16(y1[0] * inv[0], y1[1] * inv[1]));
                    st_relaxed_u32(yd1 + 0x42000, pack_bf16(y1[2] * inv[0], y1[3] * inv[1]));
                }
                bar_arrive(BAR_SENTC, 384);
                TL(13);
                bar_sync(BAR_SENT, 256);
                } else {
                    bar_sync(BAR_V, 160);
                }
            } else {
                if (it == WO_IT) {
                    PHASE(2);
                    const uint32_t fa = sb + FRAG();
                    mbar_wait_w(sb + MB_W3, 0);
                    KT_MARK(8);
#pragma unroll
                    for (int r = 0; r < 8 + WO_RF1; r++) ldsm4t(wo[r], fa + stg_wo(r));
                }
                bar_sync(BAR_PRO, 288);
            }
            float o[8];
            {
                PHASE(1);
                float d[16];
                const uint64_t da = make_desc(SB0 + SM_WV, 16, 1024);
                auto batch = [&](auto k0c, auto k1c) {
                    static_for<decltype(k0c)::value, decltype(k1c)::value>([&](auto kc) {
                        constexpr int i = decltype(kc)::value, k = kstep(ORDV, i), off = (k >> 2) * 256 + (k & 3) * 2;
                        if constexpr (k >= 24) wgmma_ss32u<off, i != 0>(d, da + (k - 24) * 128, xtlo);
                        else wgmma_rs32u<off, i != 0>(d, wv[k], xtlo);
                    });
                };
                const uint32_t vf = VFRAG(), va0 = vf + VBASE(), va1 = (vf ^ 32) + VBASE(), vma = L + (sb + SM_QKV + 4096 + g * 512), sa = (L >> 2) + (sb + SM_S + 768);
                const uint32_t rt = L + (rsb + SM_RT + 8192 + g * (HS == 6 ? 512 : 1024));
                uint32_t va[2][2][4], vm[4], pw[6], w[4];
                wg_fence();
                batch(std::integral_constant<int, 0>(), std::integral_constant<int, TA0>());
                wg_commit();
                batch(std::integral_constant<int, TA0>(), std::integral_constant<int, 32>());
                wg_commit();
                wg_wait<1>();
                softmax40(pw, sa, [&]() {});
                ldsm4t(va[0][0], va0); ldsm4t(va[0][1], va0 + 2048);
                ldsm4t(va[1][0], va1); ldsm4t(va[1][1], va1 + 2048);
                ldsm4(vm, vma);
                wg_wait<0>();
                TL(27);
                float inv[2];
                uint32_t q[4];
                pv32<true>(w, inv, va, vm, pw, [&]() {
                    if (RT_BF & 2) {
#pragma unroll
                        for (int i = 0; i < 4; i++) q[i] = pack_bf16(kh ? d[2 * i] : d[8 + 2 * i], kh ? d[2 * i + 1] : d[9 + 2 * i]);
                        if (!RT1_LATE && s + 3 < NSEG) st_async4(rt, __uint_as_float(q[0]), __uint_as_float(q[1]), __uint_as_float(q[2]), __uint_as_float(q[3]), rsb + MB_RT1);
                    } else if (s + 3 < NSEG) {
#pragma unroll
                        for (int i = 0; i < 2; i++)
                            st_async4(rt + i * 512, kh ? d[4 * i] : d[8 + 4 * i], kh ? d[4 * i + 1] : d[9 + 4 * i], kh ? d[4 * i + 2] : d[10 + 4 * i], kh ? d[4 * i + 3] : d[11 + 4 * i], rsb + MB_RT1);
                    }
#pragma unroll
                    for (int i = 0; i < 8; i++) o[i] = kh ? d[8 + i] : d[i];
                });
                if (RT1_LATE == 1 && s + 3 < NSEG) st_async4(rt, __uint_as_float(q[0]), __uint_as_float(q[1]), __uint_as_float(q[2]), __uint_as_float(q[3]), rsb + MB_RT1);
                stsm4t((L & 0x70) * 5 + ((L >> 3) & 0x30) + (sb + SM_TO + g * 640), w[0], w[1], w[2], w[3]);
                __syncwarp();
                const uint4 r = lds128(((L >> 2) & 0x70) * 5 + (L & 0x30) + (sb + SM_TO + g * 640));
                if (s >= 0) stg128(reinterpret_cast<char*>(g_ox) + (((L & 0x1C0) << 7) + (L & 0x30) + (((ui - 3) * SEG + 8 * j) * HD + h * DH + 32 * g) * 2), r);
                TL(26);
            }
            if (s + 3 < NSEG) {
                PHASE(3);
                const uint32_t rt = L + (sb + SM_RT + 8192 + g * (HS == 6 ? 512 : 1024)), so = FRAG() + (sb + SM_STG + 4096);
                mbar_wait_w(sb + MB_RT1, it & 1);
                TL(28);
                uint32_t w[4];
                if (RT_BF & 2) {
                    const uint4 v = lds128(rt);
                    w[0] = pack_bf16(o[0] + bf_lo(v.x), o[1] + bf_hi(v.x)); w[1] = pack_bf16(o[2] + bf_lo(v.y), o[3] + bf_hi(v.y));
                    w[2] = pack_bf16(o[4] + bf_lo(v.z), o[5] + bf_hi(v.z)); w[3] = pack_bf16(o[6] + bf_lo(v.w), o[7] + bf_hi(v.w));
                } else
#pragma unroll
                for (int i = 0; i < 2; i++) {
                    const uint4 v = lds128(rt + i * 512);
                    w[2 * i] = pack_bf16(o[4 * i] + __uint_as_float(v.x), o[4 * i + 1] + __uint_as_float(v.y));
                    w[2 * i + 1] = pack_bf16(o[4 * i + 2] + __uint_as_float(v.z), o[4 * i + 3] + __uint_as_float(v.w));
                }
                stsm4t(so, w[0], w[1], w[2], w[3]);
                __syncwarp();
                mbar_arrive_if0(L, sb + MB_STG);
                TL(15);
            }
        }
    }
    KT_END(2);
    asm volatile("barrier.cluster.arrive.relaxed; barrier.cluster.wait;" ::: "memory");
}
constexpr int B_UCH = 73 * 64;
constexpr int B_SCH = 33 * 64;
constexpr int B_KLEN = 2128;
constexpr int B_KCH = 2 * B_KLEN * 2 + 64;
constexpr int B_KBOX = 136 * 32;
constexpr int B_SM_U = 0;
constexpr int B_SM_S = 8 * B_UCH;
constexpr int B_SM_K = B_SM_S + 8 * B_SCH;
constexpr int B_SM_KT = B_SM_K + 8 * B_KCH;
constexpr int B_SM_VT = B_SM_KT + 8 * B_KBOX;
constexpr int B_SM_QT = B_SM_VT + 32768;
constexpr int B_SM_BAR = B_SM_QT + 32768;
constexpr int B_SMEM = B_SM_BAR + 128 + 512;
static_assert(B_SM_KT % 256 == 0 && B_SM_S % 512 == 0 && B_SMEM <= 232448, "tiles");
constexpr int PROBE_N = 4;
#define PROBE_R 2
constexpr int B_C = 2056;

__device__ __forceinline__ uint32_t atomic_round_trip(char* p) {
    uint32_t t0, t1, v;
    asm volatile("{.reg .pred p;\n"
                 "mov.u32 %0, %%clock;\n"
                 "atom.relaxed.gpu.global.add.u32 %2, [%3], 1;\n"
                 "setp.ne.u32 p, %2, 0x7FFFFFFF;\n"
                 "mov.u32 %1, 0;\n"
                 "@p mov.u32 %1, %%clock;}" : "=&r"(t0), "=&r"(t1), "=&r"(v) : "l"(p) : "memory");
    return t1 - t0;
}
__device__ __forceinline__ uint32_t round_trips(char* a, char* b, uint32_t stride, int lane) {
    for (int i = lane >> 3; i < 2 * PROBE_N; i += 4) stg128(((i & 1) ? b : a) + (i >> 1) * stride + (lane & 7) * 16, make_uint4(0, 0, 0, 0));
    __syncwarp();
    uint32_t ta = 0xFFFF, tb = 0xFFFF;
    if (lane == 0) {
        __threadfence();
#pragma unroll 1
        for (int i = 0; i < PROBE_N; i++) { ta = min(ta, atomic_round_trip(a + i * stride)); tb = min(tb, atomic_round_trip(b + i * stride)); }
    }
    __syncwarp();
    return ta | (tb << 16);
}
__device__ __forceinline__ void measure_distance(char* mbox, int lane) {
    const uint32_t b = blockIdx.x;
    unsigned smid;
    asm volatile("mov.u32 %0, %%smid;" : "=r"(smid));
    char* w1 = mbox + WIN + (b & 31) * 128;
    uint32_t r = 0xFFFFFFFF;
#pragma unroll 1
    for (int i = 0; i < PROBE_R; i++) r = __vminu2(r, round_trips(w1 + page_off(50 + 5 * i + (b >> 5), 0), w1 + page_off(50 + 5 * i + (b >> 5), 1), 16384, lane));
    if (lane == 0) g_cls[smid] = r;
    if (b == 128) {
        char *p = mbox + page_off(0, 0), *q = mbox + page_off(0, 1);
        uint32_t r0 = 0xFFFFFFFF;
#pragma unroll 1
        for (int i = 0; i < PROBE_R; i++) r0 = __vminu2(r0, round_trips(p, q, 128, lane));
        if (lane == 0) { g_reg[1] = ((r0 & 0xFFFF) > (r0 >> 16)) != ((r & 0xFFFF) > (r >> 16)); if (!EARLY_ROLE) g_reg[0] = 0; g_reg[2] = 0; }
        const uint4 sent = make_uint4(SENT, SENT, SENT, SENT);
        stg128(p + lane * 16, sent); stg128(q + lane * 16, sent);
    }
    if (b == 129) for (int i = lane; i < 128; i += 32) g_xflag[i] = 0;
}

#define SP(i)
#define SP2(i)
#define OUT_STG 0
#define PF_STOP 1
#define SENT_AT 3
#define Q_LATE 1
#define PF_DEPTH 4
#define PF_STRIDE 256
struct ChainInputs { const char* w[4]; const char *x, *mem0; };
#define EF_MASK 15
#define EF(i) (((EF_MASK >> (i)) & 1) ? policy_evict_first() : policy_evict_normal())
__device__ __forceinline__ void l2_prefetch(const char* p, uint32_t bytes) {
    asm volatile("cp.async.bulk.prefetch.L2.global [%0], %1;" ::"l"(p), "r"(bytes) : "memory");
}
#define WG_CONV(N, LIST, A0, A1, A2, A3, LO, OF, ...) \
    if constexpr (NN == N) asm volatile("{.reg .b32 l; .reg .b64 e; add.u32 l, %" #LO ", %" #OF "; mov.b64 e, {l, 0x80000020};\n" \
        "wgmma.mma_async.sync.aligned.m64n" #N "k16.f32.bf16.bf16 {" LIST "}, {%" #A0 ",%" #A1 ",%" #A2 ",%" #A3 "}, e, 1, 1, 1, 0;}" \
        : __VA_ARGS__ : "r"(a[0]), "r"(a[1]), "r"(a[2]), "r"(a[3]), "r"(lo), "n"(OFF));
#define WL4 "%0,%1,%2,%3"
#define WL8 WL4 ",%4,%5,%6,%7"
#define WL12 WL8 ",%8,%9,%10,%11"
#define WL16 WL12 ",%12,%13,%14,%15"
#define WL20 WL16 ",%16,%17,%18,%19"
#define WL24 WL20 ",%20,%21,%22,%23"
#define WL28 WL24 ",%24,%25,%26,%27"
#define WL32 WL28 ",%28,%29,%30,%31"
template <int NN, int OFF> __device__ __forceinline__ void wgmma_conv(float (&d)[32], const uint32_t (&a)[4], uint32_t lo) {
    WG_CONV(8, WL4, 4, 5, 6, 7, 8, 9, R4(0))
    WG_CONV(16, WL8, 8, 9, 10, 11, 12, 13, R4(0), R4(4))
    WG_CONV(24, WL12, 12, 13, 14, 15, 16, 17, R4(0), R4(4), R4(8))
    WG_CONV(32, WL16, 16, 17, 18, 19, 20, 21, R16(0))
    WG_CONV(40, WL20, 20, 21, 22, 23, 24, 25, R16(0), R4(16))
    WG_CONV(48, WL24, 24, 25, 26, 27, 28, 29, R16(0), R4(16), R4(20))
    WG_CONV(56, WL28, 28, 29, 30, 31, 32, 33, R16(0), R4(16), R4(20), R4(24))
    WG_CONV(64, WL32, 32, 33, 34, 35, 36, 37, R16(0), R16(16))
}
__device__ __forceinline__ void copy_to_peer(uint32_t dst, uint32_t src, uint32_t bytes, uint32_t bar) {
    asm volatile("cp.async.bulk.shared::cluster.shared::cta.mbarrier::complete_tx::bytes [%0], [%1], %2, [%3];" ::"r"(dst), "r"(src), "r"(bytes), "r"(bar) : "memory");
}
__device__ __forceinline__ uint32_t lds_volatile(uint32_t a) {
    uint32_t v;
    asm volatile("ld.volatile.shared.u32 %0, [%1];" : "=r"(v) : "r"(a) : "memory");
    return v;
}
__device__ __forceinline__ uint32_t swz64(uint32_t a) { return a ^ ((a >> 3) & 0x30); }
__device__ __forceinline__ void fence_async() { asm volatile("fence.proxy.async.shared::cta;" ::: "memory"); }

__global__ void __cluster_dims__(2, 1, 1) __launch_bounds__(576, 1)
ssm_kernel(const __grid_constant__ CUtensorMap mapK, const __grid_constant__ CUtensorMap mapV, const __grid_constant__ CUtensorMap mapQ,
           const __grid_constant__ CUtensorMap mapO, const bf16* __restrict__ shiftk, const bf16* __restrict__ ssmk, const bf16* __restrict__ Dv,
           char* __restrict__ mbox, const __grid_constant__ ChainInputs ci, bf16* __restrict__ outp) {
    extern __shared__ __align__(128) uint8_t smem_raw[];
    const uint32_t sb = (smem_u32(smem_raw) + 511) & ~511u;
    const int rank = blockIdx.x & 1, ch0 = blockIdx.x * 8, c16 = ch0 & ~15, t0 = rank * 1024;
    const int t = threadIdx.x, warp = t >> 5, lane = t & 31;
    const uint32_t bar = sb + B_SM_BAR, barQ = bar + 64, barU = bar + 72, barY = bar + 80, flag = bar + 88;
    SP(0);
    if (lane == 0 && warp < 16 && blockIdx.x < 128) {
        const int i = warp >> 1;
        if (warp & 1) {
            if (i < 3) { mbar_init(barQ + i * 8, 1); mbar_expect_tx(barQ + i * 8, i ? 16384 : 32768); }
            if (i == 3) sts32(flag, 0);
        } else {
            mbar_init(bar + i * 8, 1);
            asm volatile("fence.mbarrier_init.release.cluster;" ::: "memory");
            mbar_expect_tx(bar + i * 8, B_KBOX + 4096);
            tma_load_2d(sb + B_SM_KT + i * B_KBOX, &mapK, c16, t0 + i * 128 - 8, bar + i * 8, EF(0));
            tma_load_2d(sb + B_SM_VT + i * 4096, &mapV, c16, t0 + i * 128, bar + i * 8, EF(0));
        }
        asm volatile("fence.mbarrier_init.release.cluster;" ::: "memory");
    }
    __syncwarp();
    if (warp == 14) SP2(14);
    KT_START(1);
    if (warp == 17) {
        launch_dependents();
        asm volatile("barrier.cluster.arrive.relaxed.aligned;" ::: "memory");
        measure_distance(mbox, lane);
        asm volatile("barrier.cluster.wait.aligned;" ::: "memory");
        KT_MARK(14);
        return;
    }
    if (blockIdx.x >= 128) return;
    if (warp == 16) {
        asm volatile("barrier.cluster.arrive.relaxed.aligned; barrier.cluster.wait.aligned;" ::: "memory");
        SP2(8);
        if (Q_LATE) for (int i = 0; i < 8; i++) { mbar_wait_w(bar + i * 8, 0); SP2(i); }
        if (lane < 8) tma_load_2d(sb + B_SM_QT + lane * 4096, &mapQ, c16, t0 + lane * 128, barQ, EF(3));
        if (!Q_LATE) for (int i = 0; i < 8; i++) mbar_wait_w(bar + i * 8, 0);
        if (lane == 0) {
            l2_prefetch(ci.x + blockIdx.x * 2048, 2048);
            if (blockIdx.x < 8) l2_prefetch(ci.mem0 + blockIdx.x * 2048, 2048);
        }
        uint32_t v[PF_DEPTH], acc = 0;
#pragma unroll
        for (int u = 0; u < PF_DEPTH; u++) v[u] = 0;
        constexpr int PER = 32 * PF_STRIDE, NW = 65536 / PER;
#define PF_N (4 * NW)
        int i = 0;
#pragma unroll 1
        for (; i < PF_N && lds_volatile(flag) == 0; i += PF_DEPTH) {
#pragma unroll
            for (int u = 0; u < PF_DEPTH; u++) {
                const char* a = ci.w[(i + u) / NW] + blockIdx.x * 65536 + ((i + u) % NW) * PER + lane * PF_STRIDE;
                acc |= v[u];
                asm volatile("ld.global.cg.L2::256B.u32 %0, [%1];" : "=r"(v[u]) : "l"(a) : "memory");
            }
        }
#pragma unroll
        for (int u = 0; u < PF_DEPTH; u++) acc |= v[u];
        if (acc == 0x7FFF7FFFu && v[0] == 0x7FFEu) g_err = 1;
        SP2(12);
        KT_MARK(15);
        return;
    }
    asm volatile("barrier.cluster.arrive.relaxed.aligned;" ::: "memory");
    const int far = warp & 1, unit = rank ^ far;
    uint32_t w[4];
    uint32_t d2;
    asm volatile("ld.global.nc.u32 %0, [%1];" : "=r"(d2) : "l"(Dv + ch0 + (warp >> 2) * 2));
    {
        const int ch = warp & 7, half = warp >> 3;
        const uint32_t kb = sb + B_SM_K + ch * B_KCH;
        const uint4* src = reinterpret_cast<const uint4*>(ssmk + (size_t)(ch0 + ch) * S_LEN);
        uint4 kr[4];
#pragma unroll
        for (int i = 0; i < 4; i++) kr[i] = ldg128(src + half * 128 + i * 32 + lane, EF(1));
        const uint32_t edge = half ? 0u : __ldg(reinterpret_cast<const uint32_t*>(src + 128));
        const uint2 sw = __ldg(reinterpret_cast<const uint2*>(shiftk + (size_t)(c16 + unit * 8 + (lane >> 2)) * 4));
        w[0] = __byte_perm(sw.x, 0, 0x1010); w[1] = __byte_perm(sw.x, 0, 0x3232); w[2] = __byte_perm(sw.y, 0, 0x1010); w[3] = __byte_perm(sw.y, 0, 0x3232);
        if (half) sts128(sb + B_SM_U + ch * B_UCH + 4096 + lane * 16, make_uint4(0, 0, 0, 0));
#pragma unroll
        for (int i = 0; i < 4; i++) {
            const uint4 lo = kr[i];
            const uint32_t nx = __shfl_down_sync(~0u, lo.x, 1), n0 = (i < 3) ? __shfl_sync(~0u, kr[i < 3 ? i + 1 : 3].x, 0) : edge;
            const uint32_t hix = (lane < 31) ? nx : n0;
            const int c = 256 - (half * 128 + 32 * i + lane);
            sts128(kb + c * 16, make_uint4(__byte_perm(hix, lo.w, 0x7610), __byte_perm(lo.w, lo.z, 0x7610), __byte_perm(lo.z, lo.y, 0x7610), __byte_perm(lo.y, lo.x, 0x7610)));
            sts128(kb + B_KLEN * 2 + 64 + c * 16, make_uint4(__byte_perm(lo.w, lo.w, 0x1032), __byte_perm(lo.z, lo.z, 0x1032), __byte_perm(lo.y, lo.y, 0x1032), __byte_perm(lo.x, lo.x, 0x1032)));
        }
        const uint32_t k0w = __shfl_sync(~0u, kr[0].x, 0);
        if (half == 0 && lane < 8) {
            sts128(kb + (257 + lane) * 16, make_uint4(lane == 0 ? (k0w & 0xFFFFu) : 0u, 0u, 0u, 0u));
            sts128(kb + B_KLEN * 2 + 64 + (257 + lane) * 16, make_uint4(0u, 0u, 0u, 0u));
        }
    }
    auto sentinels = [&]() {
        const uint4 sent = make_uint4(SENT, SENT, SENT, SENT);
        char* p0 = mbox + blockIdx.x * 16384 + t * 16;
        if (blockIdx.x != 0 || (t & 255) >= 32) stg128(p0, sent);
        stg128(p0 + 8192, sent);
        char* p1 = mbox + WIN + blockIdx.x * 12800 + t * 16;
        stg128(p1, sent);
        if (t < 288) stg128(p1 + 8192, sent);
    };
    if (SENT_AT == 1) sentinels();
    asm volatile("barrier.cluster.wait.acquire.aligned;" ::: "memory");
    SP(1);
    {
        const int box = warp >> 1, row0 = 63 - 32 * rank - 4 * box;
        const uint32_t kt = sb + B_SM_KT + box * B_KBOX + 256 + lane * 32, s0 = (unit ^ ((lane >> 2) & 1)) * 16;
        const uint32_t a0 = kt + s0, a2 = kt - 64 + (unit ^ (((lane + 6) >> 2) & 1)) * 16, a4 = kt - 128 + (s0 ^ 16), av = sb + B_SM_VT + box * 4096 + lane * 32 + s0;
        const uint32_t ul = (lane & 7) * B_UCH + row0 * 64 + (lane >> 3) * 16;
        const uint32_t ud = sb + (far ? B_SM_S + (lane & 7) * (B_SCH - B_UCH) - (1 - rank) * 2048 : B_SM_U);
        mbar_wait_w(bar + box * 8, 0);
        SP(2);
#pragma unroll
        for (int i = 0; i < 4; i++) {
            uint32_t k0[4], k2[4], k4[4], vv[4], o[4];
            ldsm4t(k0, a0 + i * 1024); ldsm4t(k2, a2 + i * 1024); ldsm4t(k4, a4 + i * 1024); ldsm4t(vv, av + i * 1024);
#pragma unroll
            for (int j = 0; j < 4; j++) {
                uint32_t a = bf16_mul(__byte_perm(k4[j], k2[j], 0x5432), w[3]);
                a = bf16_add(a, bf16_mul(k2[j], w[2]));
                a = bf16_add(a, bf16_mul(__byte_perm(k2[j], k0[j], 0x5432), w[1]));
                a = bf16_add(a, bf16_mul(k0[j], w[0]));
                o[j] = bf16_mul(a, vv[j]);
            }
            stsm4(ud + swz64(ul - i * 64), o[0], o[1], o[2], o[3]);
        }
        fence_async();
        __syncwarp();
        if (far && lane < 8) {
            const uint32_t o = lane * B_UCH + (row0 - 3) * 64;
            copy_to_peer(peer_addr(sb + B_SM_U + o, rank ^ 1), ud + o, 256, peer_addr(barU, rank ^ 1));
        }
    }
    bar_sync(1, 512);
    mbar_wait_w(barU, 0);
    if (SENT_AT == 2) sentinels();
    SP(3);
    const int wg = warp >> 2, wq = warp & 3, hi = wq >> 1, g = lane >> 2, tq = lane & 3;
    const uint32_t zero = lds32(sb + B_SM_U + 4096);
#pragma unroll 1
    for (int cc = 0; cc < 2; cc++) {
        const int ch = 2 * wg + cc;
        const uint32_t kb = sb + B_SM_K + ch * B_KCH, ub = sb + B_SM_U + ch * B_UCH;
        const uint32_t dw = __byte_perm(d2, 0, cc ? 0x3232 : 0x1010);
        const int e0 = B_C - g + 2 * tq;
        const uint32_t f0 = ((e0 & 1) ? (kb + B_KLEN * 2 + 64 + (e0 - 1) * 2) : (kb + e0 * 2)) - 32 * wq;
        const uint32_t lo = uniform((ub >> 4) | 0x10000);
        float d[32];
#pragma unroll
        for (int i = 0; i < 32; i++) d[i] = 0.f;
        uint32_t A[2][2][4];
        static_for<0, 32>([&](auto jc) {
            constexpr int j = decltype(jc)::value, N = 64 - 8 * (j / 4);
            if (j >= 2) wg_wait<1>();
            uint32_t(&a)[4] = A[j & 1][0];
            uint32_t(&b)[4] = A[j & 1][1];
            a[0] = lds32(f0 - 128 * j); a[1] = lds32(f0 - 128 * j - 16); a[2] = lds32(f0 - 128 * j + 16);
            b[0] = lds32(f0 - 128 * j + 32); b[2] = lds32(f0 - 128 * j + 48);
            a[3] = a[0] ^ zero; b[1] = a[2] ^ zero; b[3] = b[0] ^ zero;
            wg_fence();
            wgmma_conv<N, 8 * j>(d, a, lo);
            wgmma_conv<N, 8 * j + 2>(d, b, lo);
            wg_commit();
        });
        wg_wait<0>();
        if (cc) SP(4);
        if (PF_STOP == 1 && cc && t == 0) sts32(flag, 1);
        bar_sync(2 + wg, 128);
        if (!hi && tq == 3) { float x = d[13]; d[13] = d[29]; d[29] = x; x = d[15]; d[15] = d[31]; d[31] = x; }
        if (hi && tq == 0) { d[0] = 0.f; d[2] = 0.f; }
        {
            const uint32_t xs = kb + (wq ^ 2) * 2048 + lane * 4;
            const uint32_t xn = hi ? xs + (tq ? 124 : 140) : xs + (tq < 3 ? 4 : -12), wrap = hi ? (tq ? 0 : -1) : (tq < 3 ? 0 : 1);
#pragma unroll
            for (int nb = 0; nb < 4; nb++) {
                const uint32_t xw = xn + ((nb + wrap) & 3) * 512;
#pragma unroll
                for (int i = 0; i < 2; i++) {
                    const float e0v = hi ? d[4 * nb + 2 * i] : d[16 + 4 * nb + 2 * i], e1v = hi ? d[4 * nb + 2 * i + 1] : d[16 + 4 * nb + 2 * i + 1];
                    sts32(hi ? xw + i * 256 : xs + nb * 512 + i * 256 + 128, __float_as_uint(e0v));
                    sts32(hi ? xs + nb * 512 + i * 256 : xw + i * 256, __float_as_uint(e1v));
                }
            }
        }
        bar_sync(2 + wg, 128);
#pragma unroll
        for (int p = 0; p < 2; p++) {
            int row = 16 * p + (lane >> 4) * 8 + (lane & 7);
            row = hi ? row + 31 : row == 31 ? 63 : row;
            const uint32_t a = sb + B_SM_U + swz64(ch * B_UCH + row * 64 + ((wq & 1) * 2 + ((lane >> 3) & 1)) * 16);
            uint32_t u[4];
            ldsm4t(u, a);
#pragma unroll
            for (int b = 0; b < 4; b++) {
                const int r = 8 * p + 2 * b;
                const float y0 = (hi ? d[16 + r] : d[r]) + __uint_as_float(lds32(kb + wq * 2048 + r * 128 + lane * 4));
                const float y1 = (hi ? d[17 + r] : d[r + 1]) + __uint_as_float(lds32(kb + wq * 2048 + r * 128 + 128 + lane * 4));
                u[b] = bf16_add(pack_bf16(y0, y1), bf16_mul(u[b], dw));
            }
            stsm4t(a, u[0], u[1], u[2], u[3]);
        }
        fence_async();
        bar_sync(2 + wg, 128);
        if (SENT_AT == 3 && cc == 0) sentinels();
        if (wq == 0 && lane == 0) copy_to_peer(peer_addr(sb + B_SM_S + ch * B_SCH, rank ^ 1), ub + rank * 2048, 2048, peer_addr(barY, rank ^ 1));
    }
    if (PF_STOP == 2 && t == 0) sts32(flag, 1);
    SP(5);
    mbar_wait_w(barQ, 0);
    bar_sync(1, 512);
    mbar_wait_w(barY, 0);
    asm volatile("barrier.cluster.arrive.relaxed.aligned;" ::: "memory");
    SP(6);
#pragma unroll
    for (int i = 0; i < 4; i++) {
        const int fr = i & 1, row = 63 - 32 * rank - 2 * warp - (i >> 1);
        const uint32_t qa = sb + B_SM_QT + warp * 2048 + (i >> 1) * 1024 + lane * 32 + ((rank ^ fr ^ (lane >> 2)) & 1) * 16;
        uint32_t y[4], q[4];
        ldsm4t(y, sb + (fr ? B_SM_S + (lane & 7) * (B_SCH - B_UCH) - (1 - rank) * 2048 : B_SM_U) + swz64((lane & 7) * B_UCH + row * 64 + (lane >> 3) * 16));
        ldsm4(q, qa);
        stsm4(qa, bf16_mul(q[0], y[0]), bf16_mul(q[1], y[1]), bf16_mul(q[2], y[2]), bf16_mul(q[3], y[3]));
    }
    fence_async();
    __syncwarp();
    if (lane == 0) {
        asm volatile("cp.async.bulk.tensor.2d.global.shared::cta.bulk_group.L2::cache_hint [%0, {%2, %3}], [%1], %4;"
                     ::"l"(&mapO), "r"(sb + B_SM_QT + warp * 2048), "r"(DM + c16), "r"(t0 + warp * 64), "l"(EF(4)) : "memory");
        asm volatile("cp.async.bulk.commit_group;" ::: "memory");
    }
    if (SENT_AT == 0) sentinels();
    if (warp == 0) SP2(10);
    if (lane == 0) asm volatile("cp.async.bulk.wait_group.read 0;" ::: "memory");
    __syncwarp();
    if (warp == 0) SP2(11);
    asm volatile("barrier.cluster.wait.aligned;" ::: "memory");
    SP(7);
    KT_END(1);
}

typedef CUresult (*EncodeFn)(CUtensorMap*, CUtensorMapDataType, cuuint32_t, void*, const cuuint64_t*, const cuuint64_t*, const cuuint32_t*,
                             const cuuint32_t*, CUtensorMapInterleave, CUtensorMapSwizzle, CUtensorMapL2promotion, CUtensorMapFloatOOBfill);

static void make_map(EncodeFn fn, CUtensorMap* m, const void* ptr, uint64_t inner, uint64_t outer, uint32_t box_in, uint32_t box_out,
                     CUtensorMapL2promotion promo = CU_TENSOR_MAP_L2_PROMOTION_L2_256B) {
    cuuint64_t dims[2] = {inner, outer};
    cuuint64_t strides[1] = {inner * 2};
    cuuint32_t box[2] = {box_in, box_out};
    cuuint32_t es[2] = {1, 1};
    fn(m, CU_TENSOR_MAP_DATA_TYPE_BFLOAT16, 2, const_cast<void*>(ptr), dims, strides, box, es, CU_TENSOR_MAP_INTERLEAVE_NONE,
       CU_TENSOR_MAP_SWIZZLE_128B, promo, CU_TENSOR_MAP_FLOAT_OOB_FILL_NONE);
}

#define G2_ST 7
#define PROMO_W CU_TENSOR_MAP_L2_PROMOTION_L2_256B
#define PROMO_O CU_TENSOR_MAP_L2_PROMOTION_L2_256B
#define SSM_PROMO CU_TENSOR_MAP_L2_PROMOTION_NONE
extern "C" void kernel_launch(void* const* d_in, const int* in_sizes, int n_in, void* d_out, int out_size) {
    const bf16* x = (const bf16*)d_in[0];
    const bf16* mem0 = (const bf16*)d_in[1];
    const bf16* Wq = (const bf16*)d_in[2];
    const bf16* Wk = (const bf16*)d_in[3];
    const bf16* Wv = (const bf16*)d_in[4];
    const bf16* Wo = (const bf16*)d_in[5];
    const bf16* Bq = (const bf16*)d_in[7];
    const bf16* Bk = (const bf16*)d_in[8];
    const bf16* Bv = (const bf16*)d_in[9];
    const bf16* Bsh = (const bf16*)d_in[10];
    const bf16* Bssm = (const bf16*)d_in[11];
    const bf16* BD = (const bf16*)d_in[12];
    bf16* out = (bf16*)d_out;

    static bool init = false;
    static EncodeFn enc = nullptr;
    static void *p_tok, *p_ox, *p_mbox;
    static int nclusters = 64;
    if (!init) {
        cudaDriverEntryPointQueryResult qr;
        cudaGetDriverEntryPoint("cuTensorMapEncodeTiled", (void**)&enc, cudaEnableDefault, &qr);
        cudaGetSymbolAddress(&p_tok, g_tok);
        cudaGetSymbolAddress(&p_ox, g_ox);
        cudaGetSymbolAddress(&p_mbox, g_mbox);
        cudaFuncSetAttribute(proj_kernel<96, G2_ST>, cudaFuncAttributeMaxDynamicSharedMemorySize, PROJ_SMEM);
        cudaFuncSetAttribute(proj_kernel<128, 7>, cudaFuncAttributeMaxDynamicSharedMemorySize, PROJ_SMEM);
        cudaFuncSetAttribute(chain_kernel, cudaFuncAttributeMaxDynamicSharedMemorySize, CHAIN_SMEM);
        cudaFuncSetAttribute(ssm_kernel, cudaFuncAttributeMaxDynamicSharedMemorySize, B_SMEM);
        cudaLaunchConfig_t cfg = {};
        cfg.gridDim = dim3(132); cfg.blockDim = dim3(384); cfg.dynamicSmemBytes = CHAIN_SMEM;
        cudaLaunchAttribute at[1];
        at[0].id = cudaLaunchAttributeClusterDimension; at[0].val.clusterDim.x = 2; at[0].val.clusterDim.y = 1; at[0].val.clusterDim.z = 1;
        cfg.attrs = at; cfg.numAttrs = 1;
        int n = 0;
        if (cudaOccupancyMaxActiveClusters(&n, chain_kernel, &cfg) == cudaSuccess && n > 64) nclusters = n < 66 ? n : 66;
        (void)cudaGetLastError();
        init = true;
    }
    char* mbox = (char*)(((uintptr_t)p_mbox + 2 * WIN - 1) & ~(uintptr_t)(2 * WIN - 1));
    CUtensorMap mX, mT32, mT16, mTQ, mKV, mWq, mWk, mWv, mWoC, mWo, mOxE, mOutE, mOx, mOut;
    {
        cuuint64_t dims[3] = {64, S_LEN, DM / 64};
        cuuint64_t strides[2] = {DM * 2, 128};
        cuuint32_t box[3] = {64, 32, 4};
        cuuint32_t es[3] = {1, 1, 1};
        enc(&mX, CU_TENSOR_MAP_DATA_TYPE_BFLOAT16, 3, const_cast<bf16*>(x), dims, strides, box, es, CU_TENSOR_MAP_INTERLEAVE_NONE,
            CU_TENSOR_MAP_SWIZZLE_128B, CU_TENSOR_MAP_L2_PROMOTION_L2_256B, CU_TENSOR_MAP_FLOAT_OOB_FILL_NONE);
    }
    make_map(enc, &mT32, p_tok, DH, 4 * NH * 3 * SEG, 64, 32, CU_TENSOR_MAP_L2_PROMOTION_L2_128B);
    make_map(enc, &mT16, p_tok, DH, 4 * NH * 3 * SEG, 64, 16, CU_TENSOR_MAP_L2_PROMOTION_L2_128B);
    {
        cuuint64_t dims[2] = {512, 4 * NH * 12};
        cuuint64_t strides[1] = {2048};
        cuuint32_t box[2] = {256, 4};
        cuuint32_t es[2] = {1, 1};
        enc(&mTQ, CU_TENSOR_MAP_DATA_TYPE_UINT32, 2, p_tok, dims, strides, box, es, CU_TENSOR_MAP_INTERLEAVE_NONE,
            CU_TENSOR_MAP_SWIZZLE_NONE, CU_TENSOR_MAP_L2_PROMOTION_L2_128B, CU_TENSOR_MAP_FLOAT_OOB_FILL_NONE);
    }
    {
        cuuint64_t dims[3] = {64, 4 * NH * 3 * SEG, 2};
        cuuint64_t strides[2] = {DH * 2, 128};
        cuuint32_t box[3] = {64, 32, 2};
        cuuint32_t es[3] = {1, 1, 1};
        enc(&mKV, CU_TENSOR_MAP_DATA_TYPE_BFLOAT16, 3, p_tok, dims, strides, box, es, CU_TENSOR_MAP_INTERLEAVE_NONE,
            CU_TENSOR_MAP_SWIZZLE_128B, CU_TENSOR_MAP_L2_PROMOTION_L2_128B, CU_TENSOR_MAP_FLOAT_OOB_FILL_NONE);
    }
    make_map(enc, &mWq, Wq, HD, DM, 64, 16, CU_TENSOR_MAP_L2_PROMOTION_L2_128B);
    make_map(enc, &mWk, Wk, HD, DM, 64, 16, CU_TENSOR_MAP_L2_PROMOTION_L2_128B);
    make_map(enc, &mWv, Wv, HD, DM, 64, 16, CU_TENSOR_MAP_L2_PROMOTION_L2_128B);
    make_map(enc, &mWoC, Wo, DM, HD, 64, PRO3 ? 16 : 128, CU_TENSOR_MAP_L2_PROMOTION_L2_128B);
    const bool early = nclusters >= 66;
    make_map(enc, &mWo, Wo, DM, HD, 64, 64, PROMO_W);
    make_map(enc, &mOxE, p_ox, HD, S_LEN, 64, EARLY_NT / 2);
    make_map(enc, &mOutE, out, OUT_LD, S_LEN, 64, EARLY_NT);
    make_map(enc, &mOx, p_ox, HD, S_LEN, 64, (early ? 96 : 128) >> FIN_SO, PROMO_O);
    make_map(enc, &mOut, out, OUT_LD, S_LEN, 64, early ? 96 : 128);

    CUtensorMap mB[4];
    for (int i = 0; i < 4; i++) {
        cuuint64_t dims[2] = {(cuuint64_t)(i < 3 ? DM : OUT_LD), S_LEN};
        cuuint64_t strides[1] = {dims[0] * 2};
        cuuint32_t box[2] = {16, i == 0 ? 136u : i < 3 ? 128u : 64u};
        cuuint32_t es[2] = {1, 1};
        enc(&mB[i], CU_TENSOR_MAP_DATA_TYPE_BFLOAT16, 2, const_cast<bf16*>(i == 0 ? Bk : i == 1 ? Bv : i == 2 ? Bq : out), dims, strides, box, es,
            CU_TENSOR_MAP_INTERLEAVE_NONE, CU_TENSOR_MAP_SWIZZLE_32B, SSM_PROMO, CU_TENSOR_MAP_FLOAT_OOB_FILL_NONE);
    }
    cudaStream_t st = cudaStreamPerThread;
    const ChainInputs ci = {{(const char*)Wv, (const char*)Wk, (const char*)Wq, (const char*)Wo}, (const char*)x, (const char*)mem0};
    ssm_kernel<<<132, 576, B_SMEM, st>>>(mB[0], mB[1], mB[2], mB[3], Bsh, Bssm, BD, mbox, ci, out);
    cudaLaunchAttribute pdl[1];
    pdl[0].id = cudaLaunchAttributeProgrammaticStreamSerialization; pdl[0].val.programmaticStreamSerializationAllowed = 1;
    cudaLaunchConfig_t lc = {};
    lc.stream = st; lc.attrs = pdl;
    lc.gridDim = dim3(2 * nclusters); lc.blockDim = dim3(384); lc.dynamicSmemBytes = CHAIN_SMEM; lc.numAttrs = PDL & 1;
    cudaLaunchKernelEx(&lc, chain_kernel, mX, mT32, mT16, mTQ, mKV, mWq, mWk, mWv, mWoC, mem0, mbox);
    lc.gridDim = dim3(2 * nclusters); lc.blockDim = dim3(PROJ_THREADS); lc.dynamicSmemBytes = PROJ_SMEM; lc.numAttrs = (PDL >> 1) & 1;
    cudaLaunchKernelEx(&lc, early ? proj_kernel<96, G2_ST> : proj_kernel<128, 7>, mWo, mOx, mOut, mOxE, mOutE);
}
```

```cpp
#include <cuda_runtime.h>
#include <cuda_bf16.h>
#include <cuda.h>
#include <stdint.h>
#include <type_traits>

typedef __nv_bfloat16 bf16;

constexpr int S_LEN = 2048, DM = 1024, NH = 32, DH = 128, NSEG = 64, SEG = 32;
constexpr int HD = NH * DH;
constexpr int OUT_LD = 2048;
constexpr unsigned SENT = 0xFFFFFFFFu;

__device__ bf16 g_tok[4 * NH * 3 * SEG * DH];
__device__ bf16 g_ox[(size_t)S_LEN * HD];
__device__ uint4 g_mbox[4 * 131072];
__device__ unsigned g_xflag[128];
__device__ unsigned g_reg[4];
__device__ __align__(16) unsigned g_cls[256];
__device__ unsigned g_err;
constexpr uint32_t WIN = 2u << 20;
__host__ __device__ constexpr uint32_t page_off(uint32_t idx, uint32_t c) {
    return ((idx & 1) << 13) | ((idx >> 1) << 16) | (((c ^ idx ^ (idx >> 1) ^ (idx >> 2) ^ (idx >> 4)) & 1) << 12);
}
#define STAT(i, c) (void)(c)
#define EARLY_ROLE 1
#define PDL 3

__device__ __forceinline__ void launch_dependents() { asm volatile("griddepcontrol.launch_dependents;" ::: "memory"); }
__device__ __forceinline__ void wait_prerequisites() { asm volatile("griddepcontrol.wait;" ::: "memory"); }
__device__ __forceinline__ void prefetch_map(const CUtensorMap* m) { asm volatile("prefetch.tensormap [%0];" ::"l"(m) : "memory"); }
#define KT_MARK(k)
#define KT_START(k)
#define KT_END(k)

__device__ __forceinline__ uint32_t smem_u32(const void* p) { return (uint32_t)__cvta_generic_to_shared(p); }
__device__ __forceinline__ void ldsm4(uint32_t& r0, uint32_t& r1, uint32_t& r2, uint32_t& r3, uint32_t a) {
    asm volatile("ldmatrix.sync.aligned.m8n8.x4.shared.b16 {%0,%1,%2,%3}, [%4];" : "=r"(r0), "=r"(r1), "=r"(r2), "=r"(r3) : "r"(a) : "memory");
}
__device__ __forceinline__ void ldsm4t(uint32_t& r0, uint32_t& r1, uint32_t& r2, uint32_t& r3, uint32_t a) {
    asm volatile("ldmatrix.sync.aligned.m8n8.x4.trans.shared.b16 {%0,%1,%2,%3}, [%4];" : "=r"(r0), "=r"(r1), "=r"(r2), "=r"(r3) : "r"(a) : "memory");
}
__device__ __forceinline__ void ldsm2(uint32_t& r0, uint32_t& r1, uint32_t a) {
    asm volatile("ldmatrix.sync.aligned.m8n8.x2.shared.b16 {%0,%1}, [%2];" : "=r"(r0), "=r"(r1) : "r"(a) : "memory");
}
__device__ __forceinline__ void stg128(void* p, uint4 v) {
    asm volatile("st.global.v4.u32 [%0], {%1,%2,%3,%4};" ::"l"(p), "r"(v.x), "r"(v.y), "r"(v.z), "r"(v.w) : "memory");
}
__device__ __forceinline__ void stsm4(uint32_t a, uint32_t r0, uint32_t r1, uint32_t r2, uint32_t r3) {
    asm volatile("stmatrix.sync.aligned.m8n8.x4.shared.b16 [%0], {%1,%2,%3,%4};" ::"r"(a), "r"(r0), "r"(r1), "r"(r2), "r"(r3) : "memory");
}
__device__ __forceinline__ void mma16816(float (&d)[4], uint32_t a0, uint32_t a1, uint32_t a2, uint32_t a3, uint32_t b0, uint32_t b1) {
    asm("mma.sync.aligned.m16n8k16.row.col.f32.bf16.bf16.f32 {%0,%1,%2,%3},{%4,%5,%6,%7},{%8,%9},{%0,%1,%2,%3};"
                 : "+f"(d[0]), "+f"(d[1]), "+f"(d[2]), "+f"(d[3])
                 : "r"(a0), "r"(a1), "r"(a2), "r"(a3), "r"(b0), "r"(b1));
}
__device__ __forceinline__ void mma1688(float (&d)[4], uint32_t a0, uint32_t a1, uint32_t b0) {
    asm("mma.sync.aligned.m16n8k8.row.col.f32.bf16.bf16.f32 {%0,%1,%2,%3},{%4,%5},{%6},{%0,%1,%2,%3};"
        : "+f"(d[0]), "+f"(d[1]), "+f"(d[2]), "+f"(d[3]) : "r"(a0), "r"(a1), "r"(b0));
}
__device__ __forceinline__ uint32_t movmat(uint32_t a) {
    uint32_t d;
    asm volatile("movmatrix.sync.aligned.m8n8.trans.b16 %0, %1;" : "=r"(d) : "r"(a));
    return d;
}
__device__ __forceinline__ uint32_t pack_bf16(float lo, float hi) {
    uint32_t r;
    asm("cvt.rn.bf16x2.f32 %0, %1, %2;" : "=r"(r) : "f"(hi), "f"(lo));
    return r;
}
__device__ __forceinline__ uint32_t bf16_mul(uint32_t a, uint32_t b) {
    uint32_t d;
    asm("mul.rn.bf16x2 %0, %1, %2;" : "=r"(d) : "r"(a), "r"(b));
    return d;
}
__device__ __forceinline__ uint32_t bf16_add(uint32_t a, uint32_t b) {
    uint32_t d;
    asm("add.rn.bf16x2 %0, %1, %2;" : "=r"(d) : "r"(a), "r"(b));
    return d;
}

__device__ __forceinline__ float bf16_round(float x) { return __bfloat162float(__float2bfloat16_rn(x)); }
__device__ __forceinline__ float bf_lo(uint32_t w) { return __uint_as_float(w << 16); }
__device__ __forceinline__ float bf_hi(uint32_t w) { return __uint_as_float(w & 0xFFFF0000u); }
__device__ __forceinline__ void bar_sync(int id, int n) { asm volatile("bar.sync %0, %1;" ::"r"(id), "r"(n) : "memory"); }
__device__ __forceinline__ void bar_sync_keep(int id, int n, uint32_t a, uint32_t b) {
    asm volatile("bar.sync %0, %1; // %2 %3" ::"r"(id), "r"(n), "r"(a), "r"(b) : "memory");
}
__device__ __forceinline__ bool bar_red_or(int id, int n, bool p) {
    uint32_t r;
    asm volatile("{.reg .pred p, q; setp.ne.u32 p, %3, 0; bar.red.or.pred q, %1, %2, p; selp.u32 %0, 1, 0, q;}" : "=r"(r) : "r"(id), "r"(n), "r"((uint32_t)p) : "memory");
    return r != 0;
}
__device__ __forceinline__ void bar_arrive(int id, int n) { asm volatile("bar.arrive %0, %1;" ::"r"(id), "r"(n) : "memory"); }
__device__ __forceinline__ void cp_async16(uint32_t dst, const void* src) {
    asm volatile("cp.async.cg.shared.global [%0], [%1], 16;" ::"r"(dst), "l"(src) : "memory");
}
__device__ __forceinline__ void cp_commit() { asm volatile("cp.async.commit_group;" ::: "memory"); }
template <int N> __device__ __forceinline__ void cp_wait() { asm volatile("cp.async.wait_group %0;" ::"n"(N) : "memory"); }
__device__ __forceinline__ uint4 ld_relaxed_v4(const void* p) {
    uint4 v;
    asm volatile("ld.relaxed.gpu.global.v4.u32 {%0,%1,%2,%3}, [%4];" : "=r"(v.x), "=r"(v.y), "=r"(v.z), "=r"(v.w) : "l"(p) : "memory");
    return v;
}
__device__ __forceinline__ void st_relaxed_u32(void* p, uint32_t v) { asm volatile("st.relaxed.gpu.global.u32 [%0], %1;" ::"l"(p), "r"(v) : "memory"); }
__device__ __forceinline__ void st_relaxed_v2(void* p, uint32_t a, uint32_t b) {
    asm volatile("st.relaxed.gpu.global.v2.u32 [%0], {%1,%2};" ::"l"(p), "r"(a), "r"(b) : "memory");
}
__device__ __forceinline__ void sts128(uint32_t a, uint4 v) {
    asm volatile("st.shared.v4.u32 [%0], {%1,%2,%3,%4};" ::"r"(a), "r"(v.x), "r"(v.y), "r"(v.z), "r"(v.w) : "memory");
}
__device__ __forceinline__ uint4 lds128(uint32_t a) {
    uint4 v;
    asm volatile("ld.shared.v4.u32 {%0,%1,%2,%3}, [%4];" : "=r"(v.x), "=r"(v.y), "=r"(v.z), "=r"(v.w) : "r"(a) : "memory");
    return v;
}
__device__ __forceinline__ void sts32(uint32_t a, uint32_t v) { asm volatile("st.shared.u32 [%0], %1;" ::"r"(a), "r"(v) : "memory"); }
__device__ __forceinline__ uint32_t lds32(uint32_t a) {
    uint32_t v;
    asm volatile("ld.shared.u32 %0, [%1];" : "=r"(v) : "r"(a) : "memory");
    return v;
}
__device__ __forceinline__ void mbar_init(uint32_t a, uint32_t c) { asm volatile("mbarrier.init.shared::cta.b64 [%0], %1;" ::"r"(a), "r"(c) : "memory"); }
__device__ __forceinline__ void mbar_expect_tx(uint32_t a, uint32_t bytes) {
    asm volatile("mbarrier.arrive.expect_tx.shared::cta.b64 _, [%0], %1;" ::"r"(a), "r"(bytes) : "memory");
}
__device__ __forceinline__ void mbar_arrive(uint32_t a) { asm volatile("mbarrier.arrive.shared::cta.b64 _, [%0];" ::"r"(a) : "memory"); }
__device__ __forceinline__ void mbar_wait(uint32_t a, uint32_t parity) {
    asm volatile("{.reg .pred p; .reg .u32 c;\n"
                 "mov.u32 c, 0;\n"
                 "MBW_LOOP:\n"
                 "add.u32 c, c, 1;\n"
                 "setp.gt.u32 p, c, 0x10000;\n"
                 "@!p mbarrier.try_wait.parity.shared::cta.b64 p, [%0], %1;\n"
                 "@!p bra.uni MBW_LOOP;}" ::"r"(a), "r"(parity) : "memory");
}
__device__ __forceinline__ void mbar_wait_w(uint32_t a, uint32_t parity) {
    asm volatile("{.reg .pred p; .reg .u32 c;\n"
                 "mov.u32 c, 0;\n"
                 "MBW_LOOP:\n"
                 "add.u32 c, c, 1;\n"
                 "setp.gt.u32 p, c, 0x10000;\n"
                 "@!p mbarrier.try_wait.parity.shared::cta.b64 p, [%0], %1;\n"
                 "vote.sync.all.pred p, p, 0xFFFFFFFF;\n"
                 "@!p bra.uni MBW_LOOP;}" ::"r"(a), "r"(parity) : "memory");
}
__device__ __forceinline__ void mbar_expect_tx_if0(uint32_t sel, uint32_t a, uint32_t bytes) {
    asm volatile("{.reg .pred p; setp.eq.u32 p, %2, 0; @p mbarrier.arrive.expect_tx.shared::cta.b64 _, [%0], %1;}" ::"r"(a), "r"(bytes), "r"(sel) : "memory");
}
__device__ __forceinline__ void mbar_arrive_if0(uint32_t sel, uint32_t a) {
    asm volatile("{.reg .pred p; setp.eq.u32 p, %1, 0; @p mbarrier.arrive.shared::cta.b64 _, [%0];}" ::"r"(a), "r"(sel) : "memory");
}
__device__ __forceinline__ void bulk_load(uint32_t dst, const void* src, uint32_t bytes, uint32_t bar) {
    asm volatile("cp.async.bulk.shared::cluster.global.mbarrier::complete_tx::bytes [%0], [%1], %2, [%3];" ::"r"(dst), "l"(src), "r"(bytes), "r"(bar) : "memory");
}
__device__ __forceinline__ void tma_load_2d(uint32_t dst, const CUtensorMap* map, int c0, int c1, uint32_t bar) {
    asm volatile("cp.async.bulk.tensor.2d.shared::cluster.global.mbarrier::complete_tx::bytes [%0], [%1, {%3, %4}], [%2];"
                 ::"r"(dst), "l"(map), "r"(bar), "r"(c0), "r"(c1) : "memory");
}
__device__ __forceinline__ void tma_load_2d_both(uint32_t dst, const CUtensorMap* map, int c0, int c1, uint32_t bar) {
    asm volatile("cp.async.bulk.tensor.2d.shared::cluster.global.mbarrier::complete_tx::bytes.multicast::cluster [%0], [%1, {%3, %4}], [%2], %5;"
                 ::"r"(dst), "l"(map), "r"(bar), "r"(c0), "r"(c1), "h"((uint16_t)3) : "memory");
}
__device__ __forceinline__ uint64_t policy_evict_first() {
    uint64_t p;
    asm("createpolicy.fractional.L2::evict_first.b64 %0, 1.0;" : "=l"(p));
    return p;
}
__device__ __forceinline__ uint64_t policy_evict_normal() {
    uint64_t p;
    asm("createpolicy.fractional.L2::evict_normal.b64 %0, 1.0;" : "=l"(p));
    return p;
}
__device__ __forceinline__ void tma_load_2d(uint32_t dst, const CUtensorMap* map, int c0, int c1, uint32_t bar, uint64_t pol) {
    asm volatile("cp.async.bulk.tensor.2d.shared::cluster.global.mbarrier::complete_tx::bytes.L2::cache_hint [%0], [%1, {%3, %4}], [%2], %5;"
                 ::"r"(dst), "l"(map), "r"(bar), "r"(c0), "r"(c1), "l"(pol) : "memory");
}
__device__ __forceinline__ uint4 ldg128(const void* p, uint64_t pol) {
    uint4 v;
    asm("ld.global.nc.L2::cache_hint.v4.u32 {%0,%1,%2,%3}, [%4], %5;" : "=r"(v.x), "=r"(v.y), "=r"(v.z), "=r"(v.w) : "l"(p), "l"(pol));
    return v;
}
__device__ __forceinline__ void stg128(void* p, uint4 v, uint64_t pol) {
    asm volatile("st.global.L2::cache_hint.v4.u32 [%0], {%1,%2,%3,%4}, %5;" ::"l"(p), "r"(v.x), "r"(v.y), "r"(v.z), "r"(v.w), "l"(pol) : "memory");
}
__device__ __forceinline__ void tma_store_2d(const CUtensorMap* map, uint32_t src, int c0, int c1) {
    asm volatile("cp.async.bulk.tensor.2d.global.shared::cta.bulk_group [%0, {%2, %3}], [%1];" ::"l"(map), "r"(src), "r"(c0), "r"(c1) : "memory");
}
__device__ __forceinline__ char* make_ptr(uint32_t lo, uint32_t hi) {
    uint64_t p;
    asm("mov.b64 %0, {%1, %2};" : "=l"(p) : "r"(lo), "r"(hi));
    return reinterpret_cast<char*>(p);
}
__device__ __forceinline__ uint64_t make_desc(uint32_t saddr, uint32_t lbo, uint32_t sbo) {
    return (uint64_t)((saddr & 0x3FFFF) >> 4) | ((uint64_t)((lbo >> 4) & 0x3FFF) << 16) | ((uint64_t)((sbo >> 4) & 0x3FFF) << 32) | ((uint64_t)1 << 62);
}
__device__ __forceinline__ void wg_fence() { asm volatile("wgmma.fence.sync.aligned;" ::: "memory"); }
__device__ __forceinline__ void wg_commit() { asm volatile("wgmma.commit_group.sync.aligned;" ::: "memory"); }
template <int N> __device__ __forceinline__ void wg_wait() { asm volatile("wgmma.wait_group.sync.aligned %0;" ::"n"(N) : "memory"); }

#define R4(b) "+f"(d[b + 0]), "+f"(d[b + 1]), "+f"(d[b + 2]), "+f"(d[b + 3])
#define R16(b) R4(b), R4(b + 4), R4(b + 8), R4(b + 12)
template <int N> __device__ __forceinline__ void wgmma_proj(float (&d)[N / 2], uint64_t da, uint64_t db) {
    if constexpr (N == 96)
        asm volatile("wgmma.mma_async.sync.aligned.m64n96k16.f32.bf16.bf16 {"
            "%0,%1,%2,%3,%4,%5,%6,%7,%8,%9,%10,%11,%12,%13,%14,%15,%16,%17,%18,%19,%20,%21,%22,%23,%24,%25,%26,%27,%28,%29,%30,%31,%32,%33,%34,%35,%36,%37,%38,%39,"
            "%40,%41,%42,%43,%44,%45,%46,%47"
            "}, %48, %49, 1, 1, 1, 1, 0;" : R16(0), R16(16), R16(32) : "l"(da), "l"(db));
    if constexpr (N == 128)
        asm volatile("wgmma.mma_async.sync.aligned.m64n128k16.f32.bf16.bf16 {"
            "%0,%1,%2,%3,%4,%5,%6,%7,%8,%9,%10,%11,%12,%13,%14,%15,%16,%17,%18,%19,%20,%21,%22,%23,%24,%25,%26,%27,%28,%29,%30,%31,%32,%33,%34,%35,%36,%37,%38,%39,"
            "%40,%41,%42,%43,%44,%45,%46,%47,%48,%49,%50,%51,%52,%53,%54,%55,%56,%57,%58,%59,%60,%61,%62,%63"
            "}, %64, %65, 1, 1, 1, 1, 0;" : R16(0), R16(16), R16(32), R16(48) : "l"(da), "l"(db));
    if constexpr (N == 256)
        asm volatile("wgmma.mma_async.sync.aligned.m64n256k16.f32.bf16.bf16 {"
            "%0,%1,%2,%3,%4,%5,%6,%7,%8,%9,%10,%11,%12,%13,%14,%15,%16,%17,%18,%19,%20,%21,%22,%23,%24,%25,%26,%27,%28,%29,%30,%31,%32,%33,%34,%35,%36,%37,%38,%39,"
            "%40,%41,%42,%43,%44,%45,%46,%47,%48,%49,%50,%51,%52,%53,%54,%55,%56,%57,%58,%59,%60,%61,%62,%63,%64,%65,%66,%67,%68,%69,%70,%71,%72,%73,%74,%75,%76,%7"
            "7,%78,%79,%80,%81,%82,%83,%84,%85,%86,%87,%88,%89,%90,%91,%92,%93,%94,%95,%96,%97,%98,%99,%100,%101,%102,%103,%104,%105,%106,%107,%108,%109,%110,%111,"
            "%112,%113,%114,%115,%116,%117,%118,%119,%120,%121,%122,%123,%124,%125,%126,%127"
            "}, %128, %129, 1, 1, 1, 1, 0;" : R16(0), R16(16), R16(32), R16(48), R16(64), R16(80), R16(96), R16(112) : "l"(da), "l"(db));
}

__device__ __forceinline__ void wgmma_rs32(float (&d)[16], const uint32_t (&a)[4], uint64_t db, bool acc) {
    asm volatile(
        "{.reg .pred p; setp.ne.b32 p, %21, 0;\n"
        "wgmma.mma_async.sync.aligned.m64n32k16.f32.bf16.bf16 {%0,%1,%2,%3,%4,%5,%6,%7,%8,%9,%10,%11,%12,%13,%14,%15}, {%16,%17,%18,%19}, %20, p, 1, 1, 0;}"
        : R16(0) : "r"(a[0]), "r"(a[1]), "r"(a[2]), "r"(a[3]), "l"(db), "n"(1) );
}
__device__ __forceinline__ void wgmma_rs32_first(float (&d)[16], const uint32_t (&a)[4], uint64_t db) {
    asm volatile(
        "{.reg .pred p; setp.ne.b32 p, %21, 0;\n"
        "wgmma.mma_async.sync.aligned.m64n32k16.f32.bf16.bf16 {%0,%1,%2,%3,%4,%5,%6,%7,%8,%9,%10,%11,%12,%13,%14,%15}, {%16,%17,%18,%19}, %20, p, 1, 1, 0;}"
        : R16(0) : "r"(a[0]), "r"(a[1]), "r"(a[2]), "r"(a[3]), "l"(db), "n"(0) );
}
__device__ __forceinline__ void wgmma_ss32(float (&d)[16], uint64_t da, uint64_t db) {
    asm volatile(
        "wgmma.mma_async.sync.aligned.m64n32k16.f32.bf16.bf16 {%0,%1,%2,%3,%4,%5,%6,%7,%8,%9,%10,%11,%12,%13,%14,%15}, %16, %17, 1, 1, 1, 1, 0;"
        : R16(0) : "l"(da), "l"(db));
}
template <int OFF, int ACC> __device__ __forceinline__ void wgmma_rs32u(float (&d)[16], const uint32_t (&a)[4], uint32_t lo) {
    asm volatile(
        "{.reg .pred p; .reg .b32 l; .reg .b64 e; setp.ne.b32 p, %22, 0; add.u32 l, %20, %21; mov.b64 e, {l, 0x40000040};\n"
        "wgmma.mma_async.sync.aligned.m64n32k16.f32.bf16.bf16 {%0,%1,%2,%3,%4,%5,%6,%7,%8,%9,%10,%11,%12,%13,%14,%15}, {%16,%17,%18,%19}, e, p, 1, 1, 0;}"
        : R16(0) : "r"(a[0]), "r"(a[1]), "r"(a[2]), "r"(a[3]), "r"(lo), "n"(OFF), "n"(ACC));
}
template <int OFF, int ACC> __device__ __forceinline__ void wgmma_ss32u(float (&d)[16], uint64_t da, uint32_t lo) {
    asm volatile(
        "{.reg .pred p; .reg .b32 l; .reg .b64 e; setp.ne.b32 p, %19, 0; add.u32 l, %17, %18; mov.b64 e, {l, 0x40000040};\n"
        "wgmma.mma_async.sync.aligned.m64n32k16.f32.bf16.bf16 {%0,%1,%2,%3,%4,%5,%6,%7,%8,%9,%10,%11,%12,%13,%14,%15}, %16, e, p, 1, 1, 1, 0;}"
        : R16(0) : "l"(da), "r"(lo), "n"(OFF), "n"(ACC));
}
template <int K0, int K1, class F> __device__ __forceinline__ void static_for(F f) {
    if constexpr (K0 < K1) { f(std::integral_constant<int, K0>()); static_for<K0 + 1, K1>(f); }
}
__device__ __forceinline__ void st_async4(uint32_t a, float x, float y, float z, float w, uint32_t bar) {
    asm volatile("st.async.weak.shared::cluster.mbarrier::complete_tx::bytes.v4.f32 [%0], {%1,%2,%3,%4}, [%5];" ::"r"(a), "f"(x), "f"(y), "f"(z), "f"(w), "r"(bar) : "memory");
}
__device__ __forceinline__ void st_async2(uint32_t a, float x, float y, uint32_t bar) {
    asm volatile("st.async.weak.shared::cluster.mbarrier::complete_tx::bytes.v2.f32 [%0], {%1,%2}, [%3];" ::"r"(a), "f"(x), "f"(y), "r"(bar) : "memory");
}
__device__ __forceinline__ void st_async1(uint32_t a, uint32_t x, uint32_t bar) {
    asm volatile("st.async.weak.shared::cluster.mbarrier::complete_tx::bytes.b32 [%0], %1, [%2];" ::"r"(a), "r"(x), "r"(bar) : "memory");
}
__device__ __forceinline__ uint32_t peer_addr(uint32_t a, uint32_t rank) {
    uint32_t r;
    asm("mapa.shared::cluster.u32 %0, %1, %2;" : "=r"(r) : "r"(a), "r"(rank));
    return r;
}
__device__ __forceinline__ void stsm4t(uint32_t a, uint32_t r0, uint32_t r1, uint32_t r2, uint32_t r3) {
    asm volatile("stmatrix.sync.aligned.m8n8.x4.trans.shared.b16 [%0], {%1,%2,%3,%4};" ::"r"(a), "r"(r0), "r"(r1), "r"(r2), "r"(r3) : "memory");
}
__device__ __forceinline__ void ldsm4t(uint32_t (&r)[4], uint32_t a) { ldsm4t(r[0], r[1], r[2], r[3], a); }
__device__ __forceinline__ void ldsm4(uint32_t (&r)[4], uint32_t a) { ldsm4(r[0], r[1], r[2], r[3], a); }
__device__ __forceinline__ void mma16816(float (&d)[4], const uint32_t (&a)[4], uint32_t b0, uint32_t b1) { mma16816(d, a[0], a[1], a[2], a[3], b0, b1); }
__device__ __forceinline__ void sched_fence(uint32_t v) {
    asm volatile("{.reg .pred p; setp.ne.u32 p, %0, 0xFFFFFFFF; vote.sync.all.pred p, p, 0xFFFFFFFF; @p bra.uni SF_OK; exit; SF_OK:}" ::"r"(v) : "memory");
}
__device__ __forceinline__ void mma16816v(float (&d)[4], const uint32_t (&a)[4], uint32_t b0, uint32_t b1) {
    asm volatile("mma.sync.aligned.m16n8k16.row.col.f32.bf16.bf16.f32 {%0,%1,%2,%3},{%4,%5,%6,%7},{%8,%9},{%0,%1,%2,%3};"
                 : "+f"(d[0]), "+f"(d[1]), "+f"(d[2]), "+f"(d[3]) : "r"(a[0]), "r"(a[1]), "r"(a[2]), "r"(a[3]), "r"(b0), "r"(b1));
}
__device__ __forceinline__ uint32_t uniform(uint32_t v) { return __reduce_max_sync(~0u, v); }

#define WPRE 0
#define G2_X 0
#define G2_K 4
#define FIN_SO 0
#define PROJ_FAST 1
#define KROT 0
#define WFIRST 0
template <int NT, int STAGES> struct ProjCfg {
    static constexpr int STAGE_BYTES = 16384 + NT * 128;
    static constexpr int EPI = NT == 256 ? STAGES * STAGE_BYTES : 0;
    static constexpr int BARS = 229376 + (NT == 256 ? 192 : 0);
    static_assert(STAGES * STAGE_BYTES <= 229376 && EPI + NT * 256 <= 229376 && STAGES <= 12, "smem");
};
constexpr int PROJ_ROLE = 229376 + 384, PROJ_SMEM = PROJ_ROLE + 16;
__device__ __forceinline__ unsigned claim_pair(unsigned* reg) {
    unsigned smid, ncl = gridDim.x >> 1;
    asm volatile("mov.u32 %0, %%smid;" : "=r"(smid));
    uint2 m;
    for (int guard = 0; guard < 1024; guard++) {
        asm volatile("ld.relaxed.gpu.global.v2.u32 {%0, %1}, [%2];" : "=r"(m.x), "=r"(m.y) : "l"(g_cls + (smid & ~1u)) : "memory");
        if (m.x && m.y) break;
    }
    const unsigned r = __vminu2(m.x, m.y), c = (r & 0xFFFF) > (r >> 16);
    unsigned n = atomicAdd(reg, c ? 0x10000u : 1u);
    const unsigned i = c ? n >> 16 : n & 0xFFFF, order = ((n >> 16) + (n & 0xFFFF)) << 8;
    if (i < 32) return c * 32 + i + order;
    for (int guard = 0; guard < (1 << 20); guard++) {
        asm volatile("ld.relaxed.gpu.global.u32 %0, [%1];" : "=r"(n) : "l"(reg) : "memory");
        if ((n >> 16) + (n & 0xFFFF) >= ncl) break;
    }
    const unsigned k = (c ? n & 0xFFFF : n >> 16) + i - 32;
    return (k < 32 ? (c ^ 1) * 32 + k : 64) + order;
}
template <int NT, int STAGES> __device__ __forceinline__ void proj_init(uint32_t sb) {
    for (int i = 0; i < STAGES; i++) { mbar_init(sb + ProjCfg<NT, STAGES>::BARS + 8 * i, 1); mbar_init(sb + ProjCfg<NT, STAGES>::BARS + 8 * (STAGES + i), 16); }
    asm volatile("fence.mbarrier_init.release.cluster;" ::: "memory");
}
template <int NT, int STAGES, bool SHARE_O, class T, class R>
__device__ __forceinline__ void proj_tiles(uint32_t sb, int warp, uint32_t rank, int ntiles, const CUtensorMap* mapW, const CUtensorMap* mapO,
                                           const CUtensorMap* mapOut, T tile, R ready, int rot = 0) {
    using Cfg = ProjCfg<NT, STAGES>;
    const uint32_t bars = sb + Cfg::BARS;
    const int lane = threadIdx.x & 31;
    if (warp == 8) {
        int st = 0; uint32_t ph = 1;
        for (int i = 0; i < ntiles; i++) {
            int col, tok;
            tile(i, col, tok);
            constexpr bool PRE = WPRE && !SHARE_O;
            if (PRE && lane == 0)
                for (int kb = 0; kb < STAGES; kb++) {
                    mbar_expect_tx(bars + 8 * kb, Cfg::STAGE_BYTES);
                    tma_load_2d_both(sb + kb * Cfg::STAGE_BYTES + rank * 8192, mapW, col + rank * 64, kb * 64, bars + 8 * kb);
                }
            ready(i);
            if (lane == 0) {
                if (PRE) {
                    for (int kb = 0; kb < STAGES; kb++) tma_load_2d(sb + kb * Cfg::STAGE_BYTES + 16384, mapO, kb * 64, tok, bars + 8 * kb);
                    ph = 0;
                }
                for (int kb = PRE ? STAGES : 0; kb < HD / 64; kb++) {
                    mbar_wait(bars + 8 * (STAGES + st), ph);
                    const uint32_t full = bars + 8 * st, sa = sb + st * Cfg::STAGE_BYTES;
                    mbar_expect_tx(full, SHARE_O ? Cfg::STAGE_BYTES : G2_X == 1 ? 16384 : G2_X == 2 ? NT * 128 : Cfg::STAGE_BYTES);
                    if (SHARE_O) {
                        tma_load_2d(sa, mapW, col, kb * 64, full);
                        tma_load_2d(sa + 8192, mapW, col + 64, kb * 64, full);
                        tma_load_2d_both(sa + 16384 + rank * (NT * 64), mapO, kb * 64, tok + rank * (NT / 2), full);
                    } else {
                        const int k0 = ((kb + rot) & 63) * 64;
                        if (WFIRST) tma_load_2d_both(sa + rank * 8192, mapW, col + rank * 64, k0, full);
                        if (G2_X != 1) tma_load_2d(sa + 16384, mapO, k0, G2_X == 3 ? tok & 511 : tok, full);
                        if (!WFIRST && G2_X != 2) tma_load_2d_both(sa + rank * 8192, mapW, col + rank * 64, k0, full);
                    }
                    if (++st == STAGES) { st = 0; ph ^= 1; }
                }
            }
            __syncwarp();
        }
    } else if (warp < 8) {
        const int wg = warp >> 2;
        uint32_t peer_empty;
        asm volatile("mapa.shared::cluster.u32 %0, %1, %2;" : "=r"(peer_empty) : "r"(bars + 8 * STAGES), "r"(rank ^ 1));
        auto release = [&](int stg) {
            if (lane == 0) {
                mbar_arrive(bars + 8 * (STAGES + stg));
                asm volatile("mbarrier.arrive.shared::cluster.b64 _, [%0];" ::"r"(peer_empty + 8 * stg) : "memory");
            }
        };
        const uint32_t ew = sb + Cfg::EPI + wg * (NT * 128);
        int st = 0; uint32_t ph = 0;
        for (int i = 0; i < ntiles; i++) {
            int col, tok;
            tile(i, col, tok);
            float d[NT / 2];
#pragma unroll
            for (int r = 0; r < NT / 2; r++) d[r] = 0.f;
            int prev = -1;
            for (int kb = 0; kb < HD / 64; kb++) {
                mbar_wait(bars + 8 * st, ph);
                const uint32_t sa = sb + st * Cfg::STAGE_BYTES;
                const uint64_t da = make_desc(sa + wg * 8192, 16, 1024), db = make_desc(sa + 16384, 16, 1024);
                wg_fence();
#pragma unroll
                for (int k = 0; k < (NT == 256 ? 4 : G2_K); k++) wgmma_proj<NT>(d, da + k * 128, db + k * 2);
                wg_commit();
                if (prev >= 0) { wg_wait<1>(); release(prev); }
                prev = st;
                if (++st == STAGES) { st = 0; ph ^= 1; }
            }
            wg_wait<0>();
            release(prev);
            if ((warp & 3) == 0 && lane == 0) asm volatile("cp.async.bulk.wait_group.read 0;" ::: "memory");
            if (Cfg::EPI) bar_sync(1 + wg, 128); else bar_sync(3, 256);
            const uint32_t ea = ew + ((lane >> 4) * 8 + (lane & 7)) * 128 + ((((warp & 3) * 2 + ((lane >> 3) & 1)) ^ (lane & 7)) * 16);
#pragma unroll
            for (int r = 0; r < NT / 16; r++)
                stsm4t(ea + r * 2048, pack_bf16(d[8 * r], d[8 * r + 1]), pack_bf16(d[8 * r + 2], d[8 * r + 3]), pack_bf16(d[8 * r + 4], d[8 * r + 5]), pack_bf16(d[8 * r + 6], d[8 * r + 7]));
            asm volatile("fence.proxy.async.shared::cta;" ::: "memory");
            bar_sync(1 + wg, 128);
            if ((warp & 3) == 0 && lane == 0) {
                tma_store_2d(mapOut, ew, col + wg * 64, tok);
                asm volatile("cp.async.bulk.commit_group;" ::: "memory");
            }
        }
        if ((warp & 3) == 0 && lane == 0) asm volatile("cp.async.bulk.wait_group 0;" ::: "memory");
    }
    __syncwarp();
}
constexpr int EARLY_NT = 256, EARLY_STAGES = 3;
constexpr int PROJ_THREADS = 288;

template <int NT, int STAGES>
__global__ void __cluster_dims__(2, 1, 1) __launch_bounds__(PROJ_THREADS, 1)
proj_kernel(const __grid_constant__ CUtensorMap mapW, const __grid_constant__ CUtensorMap mapO, const __grid_constant__ CUtensorMap mapOut,
            const __grid_constant__ CUtensorMap mapOE, const __grid_constant__ CUtensorMap mapOutE) {
    KT_START(3);
    extern __shared__ __align__(1024) uint8_t smem_proj[];
    const uint32_t sb = smem_u32(smem_proj), role = sb + PROJ_ROLE;
    if (sb & 1023) __trap();
    const uint32_t rank = blockIdx.x & 1;
    const int warp = threadIdx.x >> 5;
    if (threadIdx.x == 0) {
        mbar_init(role + 8, 1);
        mbar_expect_tx(role + 8, 4);
        proj_init<NT, STAGES>(sb);
        proj_init<EARLY_NT, EARLY_STAGES>(sb);
    }
    if (threadIdx.x == 32) { prefetch_map(&mapO); prefetch_map(&mapW); prefetch_map(&mapOut); }
    __syncwarp();
    asm volatile("barrier.cluster.arrive.relaxed.aligned;" ::: "memory");
    unsigned claimed = 0;
    if (threadIdx.x == 256 && rank == 0) claimed = claim_pair(g_reg + 2);
    __syncwarp();
    asm volatile("barrier.cluster.wait.acquire.aligned;" ::: "memory");
    if (threadIdx.x == 256 && rank == 0) {
        st_async1(peer_addr(role, 1), claimed, peer_addr(role + 8, 1));
        st_async1(peer_addr(role, 0), claimed, peer_addr(role + 8, 0));
        if ((claimed >> 8) + 1 == gridDim.x >> 1) {
            g_reg[0] = 0;
            for (int i = 0; i < 64; i++) reinterpret_cast<uint4*>(g_cls)[i] = make_uint4(0, 0, 0, 0);
        }
    }
    __syncwarp();
    mbar_wait_w(role + 8, 0);
    const int p = lds32(role) & 255, order = lds32(role) >> 8;
    if (NT == 96 && order < 2) {
        proj_tiles<EARLY_NT, EARLY_STAGES, true>(sb, warp, rank, 4, &mapW, &mapOE, &mapOutE,
            [&](int i, int& col, int& tok) { col = ((i & 1) * 4 + order * 2 + rank) * 128; tok = (i >> 1) * EARLY_NT; },
            [&](int i) {
                const unsigned need = 8 * (i >> 1) + 8 + 3;
                for (int guard = 0; guard < (1 << 16); guard++) {
                    const uint4 f = ld_relaxed_v4(g_xflag + (threadIdx.x & 31) * 4);
                    if (__all_sync(~0u, min(min(f.x, f.y), min(f.z, f.w)) >= need)) break;
                    __nanosleep(1000);
                }
                asm volatile("fence.acq_rel.gpu; fence.proxy.async.global;" ::: "memory");
            });
        __syncthreads();
        asm volatile("barrier.cluster.arrive.relaxed.aligned; barrier.cluster.wait.aligned;" ::: "memory");
    }
    if (p >= 64) return;
    proj_tiles<NT, STAGES, false>(sb, warp, rank, 1, &mapW, &mapO, &mapOut,
                                  [&](int, int& col, int& tok) { col = (p & 7) * 128; tok = S_LEN - 16 * NT + ((p >> 3) * 2 + rank) * NT; },
                                  [&](int) { wait_prerequisites();
                                  }, KROT == 0 ? 0 : KROT == 1 ? (p & 7) * 8 : KROT == 2 ? (p >> 3) * 8 : KROT == 3 ? ((p & 7) + (p >> 3)) * 8 : (p >> 5) * 32);
    KT_END(3);
    asm volatile("barrier.cluster.arrive.relaxed; barrier.cluster.wait;" ::: "memory");
}

#define WO_RF1 6
constexpr int SM_KV = 0, KV_BYTES = 18432;
constexpr int SM_XT = 2 * KV_BYTES;
constexpr int SM_STG = SM_XT + 65536;
constexpr int SM_Z = SM_STG + 6144;
#define HS 6
constexpr int SM_RT = SM_Z + 8192;
constexpr int SM_QKV = SM_RT + (HS == 6 ? 10240 : 12288);
constexpr int SM_R1 = SM_QKV + 6144;
constexpr int SM_Y = HS == 6 ? SM_R1 : SM_Z;
constexpr int SM_R2 = SM_R1 + (HS == 6 ? 4096 : 2048);
constexpr int SM_R3 = SM_R2 + 1024;
constexpr int SM_O = SM_R3 + 2048;
constexpr int SM_S = SM_O + 2048;
constexpr int SM_INV = SM_S + 1536;
constexpr int SM_TO = SM_R3;
constexpr int SM_WORK_END = SM_S + 2048;
constexpr int STG_QK = 0, STG_V = 98304;
#define PRO2 1
#define PRO3 1
#define WO_IT 2
#define XP 0
__host__ __device__ constexpr int stg_wo(int r) { return r < 9 ? KV_BYTES + r * 2048 : r < 13 ? SM_QKV + (r - 9) * 2048 : SM_S; }
static_assert(WO_RF1 == 6 && SM_QKV % 1024 == 0 && SM_S % 1024 == 0 && SM_QKV + 8192 <= SM_TO, "staging of Wo");
__host__ __device__ constexpr int stg_qk(int t, int r) { return !PRO2 ? STG_QK + (t * 24 + r) * 2048 : t == 0 ? SM_XT + r * 2048 : r < SM_XT / 2048 ? r * 2048 : (r + 24) * 2048; }
constexpr int SM_WO1 = SM_WORK_END - WO_RF1 * 2048;
constexpr int STG_WO = SM_WO1 - 16384;
constexpr int SM_WQK = (SM_WO1 + 16384 > STG_V + 49152) ? SM_WO1 + 16384 : STG_V + 49152;
constexpr int SM_WV = SM_WQK + 32768;
constexpr int SM_WO2 = SM_WV + 16384;
constexpr int SM_BARS = SM_WO2 + 32768;
enum { MB_W0 = SM_BARS, MB_W1 = SM_BARS + 8, MB_W2 = SM_BARS + 16, MB_W3 = SM_BARS + 24, MB_XT = SM_BARS + 32  , MB_KV = SM_BARS + 48  ,
       MB_R3 = SM_BARS + 64, MB_R1 = SM_BARS + 72, MB_R2 = SM_BARS + 80, MB_RT0 = SM_BARS + 88, MB_RT1 = SM_BARS + 96, MB_FREE = SM_BARS + 104,
       MB_P = SM_BARS + 112, MB_V = SM_BARS + 120, MB_STG = SM_BARS + 128, MB_ROLE = SM_BARS + 136, MB_W4 = SM_BARS + 144, MB_W5 = SM_BARS + 152, SM_ROLE = SM_BARS + 160   };
constexpr int CHAIN_SMEM = SM_ROLE + 8;
static_assert(SM_WORK_END % 1024 == 0 && STG_WO >= STG_V, "work area");
static_assert(SM_Y % 128 == 0, "exchange Y");
static_assert(CHAIN_SMEM <= 232448 && WO_RF1 >= 6, "smem");

#define DLY_X 250
#define DLY_V 0
#define DLY_Y 320
#define DLY_Z 280
#define DLY_T 0
#define DLY_K 0
#define DLY_S 0
#define LATE_RD 1
#define TS_AT 5
#define TS_LATE 0
#define XB_EARLY 0
#define RT0_N 4
#define ORD0 2
#define ORD1 2
#define ORDV 2
#define RT_BF 2
__host__ __device__ constexpr int kstep(int ord, int i) { return ord == 0 ? i : ord == 1 ? (i + 24) % 32 : ord == 2 ? (i % 4 == 3 ? 24 + i / 4 : i / 4 * 3 + i % 4) : ord == 3 ? (i < 16 ? (i % 2 ? 24 + i / 2 : i / 2) : i - 8) : (i < 8 ? i : i < 16 ? i + 16 : i - 8); }
#define RT0_AT 4
#define RT1_LATE 0
#define RT_BULK 2
#define FENCE_W 0

#define XT_FIRST 0
#define GV 1
#define NSV (GV ? 320 : 352)
#define Q3_AT 9
#define NA 7
#define NP2 6
#define P2_FENCE 0
#define SPLIT 5
#define TA0 16
#define SENT_EARLY 1
#define Y_CHAIN 1
#define EF_W 1
#define XFLIP 0
#define YFLIP 0
#define ZFLIP 1
#define OFENCE 2
#define REG_A 240
#define REG_B 216
#define REG_C (3 * 168 - REG_A - REG_B)

enum { BAR_Y, BAR_MEM, BAR_PUB, BAR_QK, BAR_S, BAR_O, BAR_SENT, BAR_COMM, BAR_PUBV, BAR_PV, BAR_PDONE, BAR_VP, BAR_ZP, BAR_PRO, BAR_O2, BAR_SV,
       BAR_V = BAR_PV, BAR_SENTC = BAR_PDONE, BAR_Q3 = BAR_PRO, BAR_INV = BAR_PRO, BAR_XT0 = BAR_Y };

__device__ __forceinline__ uint32_t umax4(const uint4& v) { return max(max(v.x, v.y), max(v.z, v.w)); }
__device__ __forceinline__ unsigned gtime() { unsigned t; asm volatile("mov.u32 %0, %%globaltimer_lo;" : "=r"(t)::"memory"); return t; }
__device__ __forceinline__ unsigned clock32() { unsigned t; asm volatile("mov.u32 %0, %%clock;" : "=r"(t)::"memory"); return t; }
__device__ __forceinline__ void spin_cycles(int d) {
    if (d > 0) { const unsigned c0 = clock32(); while (clock32() - c0 < (unsigned)d) {} }
}
__device__ __forceinline__ float ex2_approx(float x) { float y; asm("ex2.approx.ftz.f32 %0, %1;" : "=f"(y) : "f"(x)); return y; }
__device__ __forceinline__ float rcp_approx(float x) { float y; asm("rcp.approx.ftz.f32 %0, %1;" : "=f"(y) : "f"(x)); return y; }
__device__ __forceinline__ void st_sent(const void* p) { asm volatile("st.relaxed.gpu.global.v4.u32 [%0], {%1,%1,%1,%1};" ::"l"(p), "r"(SENT) : "memory"); }
#define POLL_LD(p, a, b, c, d, addr) "@" p " ld.relaxed.gpu.global.v4.u32 {" a "," b "," c "," d "}, [" addr "];\n"
#define POLL_CK(p, a, b, c, d) "max.u32 m, " a "," b "; max.u32 n, " c "," d "; max.u32 m, m, n; setp.eq.u32 " p ", m, 0xFFFFFFFF;\n"
#define POLL_IO(v) "+r"(v.x), "+r"(v.y), "+r"(v.z), "+r"(v.w)
__device__ __forceinline__ void poll_init(uint4& v) { v = make_uint4(SENT, SENT, SENT, SENT); asm volatile("" : POLL_IO(v)); }
__device__ __forceinline__ int poll2(uint4 (&v)[2], const char* a) {
    int c = 0;
    asm volatile("{.reg .pred p0, p1, p; .reg .u32 m, n;\n"
                 "setp.eq.u32 p0, %8, 0; setp.eq.u32 p1, %8, 0;\n"
                 "POLL_LOOP:\n"
                 POLL_LD("p0", "%0", "%1", "%2", "%3", "%9") POLL_LD("p1", "%4", "%5", "%6", "%7", "%9+512")
                 "add.u32 %8, %8, 1;\n"
                 POLL_CK("p0", "%0", "%1", "%2", "%3") POLL_CK("p1", "%4", "%5", "%6", "%7")
                 "or.pred p, p0, p1; setp.lt.and.u32 p, %8, 0x10000, p; vote.sync.any.pred p, p, 0xFFFFFFFF;\n"
                 "@p bra.uni POLL_LOOP;}" : POLL_IO(v[0]), POLL_IO(v[1]), "+r"(c) : "l"(a) : "memory");
    return c;
}
__device__ __forceinline__ int poll2_bar(uint4 (&v)[2], const char* a, uint32_t bar, uint32_t parity) {
    int c = 0;
    asm volatile("{.reg .pred p0, p1, p, q; .reg .u32 m, n;\n"
                 "setp.eq.u32 p0, %8, 0; setp.eq.u32 p1, %8, 0;\n"
                 "POLL_LOOP:\n"
                 POLL_LD("p0", "%0", "%1", "%2", "%3", "%9") POLL_LD("p1", "%4", "%5", "%6", "%7", "%9+512")
                 "mbarrier.try_wait.parity.shared::cta.b64 q, [%10], %11;\n"
                 "add.u32 %8, %8, 1;\n"
                 POLL_CK("p0", "%0", "%1", "%2", "%3") POLL_CK("p1", "%4", "%5", "%6", "%7")
                 "or.pred p, p0, p1; or.pred p, p, !q; setp.lt.and.u32 p, %8, 0x10000, p; vote.sync.any.pred p, p, 0xFFFFFFFF;\n"
                 "@p bra.uni POLL_LOOP;}" : POLL_IO(v[0]), POLL_IO(v[1]), "+r"(c) : "l"(a), "r"(bar), "r"(parity) : "memory");
    return c;
}
template <int ST> __device__ __forceinline__ int poll4(uint4 (&v)[4], const char* a) {
    int c = 0;
    asm volatile("{.reg .pred p0, p1, p2, p3, p; .reg .u32 m, n;\n"
                 "setp.eq.u32 p0, %16, 0; setp.eq.u32 p1, %16, 0; setp.eq.u32 p2, %16, 0; setp.eq.u32 p3, %16, 0;\n"
                 "POLL_LOOP:\n"
                 POLL_LD("p0", "%0", "%1", "%2", "%3", "%17") POLL_LD("p1", "%4", "%5", "%6", "%7", "%17+%18")
                 POLL_LD("p2", "%8", "%9", "%10", "%11", "%17+%19") POLL_LD("p3", "%12", "%13", "%14", "%15", "%17+%20")
                 "add.u32 %16, %16, 1;\n"
                 POLL_CK("p0", "%0", "%1", "%2", "%3") POLL_CK("p1", "%4", "%5", "%6", "%7") POLL_CK("p2", "%8", "%9", "%10", "%11") POLL_CK("p3", "%12", "%13", "%14", "%15")
                 "or.pred p, p0, p1; or.pred p, p, p2; or.pred p, p, p3; setp.lt.and.u32 p, %16, 0x10000, p; vote.sync.any.pred p, p, 0xFFFFFFFF;\n"
                 "@p bra.uni POLL_LOOP;}" : POLL_IO(v[0]), POLL_IO(v[1]), POLL_IO(v[2]), POLL_IO(v[3]), "+r"(c) : "l"(a), "n"(ST), "n"(2 * ST), "n"(3 * ST) : "memory");
    return c;
}
__device__ __forceinline__ uint32_t add_bf16x2(uint32_t a, uint32_t b) { uint32_t r; asm("add.rn.bf16x2 %0, %1, %2;" : "=r"(r) : "r"(a), "r"(b)); return r; }
__device__ __forceinline__ uint32_t max_bf16x2(uint32_t a, uint32_t b) { uint32_t r; asm("max.bf16x2 %0, %1, %2;" : "=r"(r) : "r"(a), "r"(b)); return r; }
template <class F> __device__ __forceinline__ void softmax40(uint32_t (&pw)[6], uint32_t sa, F mid) {
    const float LOG2E = 1.4426950408889634f;
    uint32_t w[5];
    float e[10];
#pragma unroll
    for (int i = 0; i < 5; i++) w[i] = lds32(sa + i * 128);
    uint32_t m = max_bf16x2(max_bf16x2(max_bf16x2(w[0], w[1]), max_bf16x2(w[2], w[3])), w[4]);
    m = max_bf16x2(m, __shfl_xor_sync(~0u, m, 1));
    m = max_bf16x2(m, __shfl_xor_sync(~0u, m, 2));
    const float mb2 = fmaxf(bf_lo(m), bf_hi(m)) * LOG2E;
#pragma unroll
    for (int i = 0; i < 5; i++) {
        e[2 * i] = ex2_approx(fmaf(bf_lo(w[i]), LOG2E, -mb2));
        e[2 * i + 1] = ex2_approx(fmaf(bf_hi(w[i]), LOG2E, -mb2));
    }
    mid();
#pragma unroll
    for (int i = 0; i < 5; i++) pw[i] = pack_bf16(e[2 * i], e[2 * i + 1]);
    const float sum = (((e[0] + e[1]) + (e[2] + e[3])) + ((e[4] + e[5]) + (e[6] + e[7]))) + (e[8] + e[9]);
    const float hi = bf_hi(__float_as_uint(sum));
    pw[5] = pack_bf16(sum - hi, hi);
}
template <bool NORM, class F> __device__ __forceinline__ void pv32(uint32_t (&w)[4], float (&inv)[2], const uint32_t (&va)[2][2][4], const uint32_t (&vm)[4], const uint32_t (&pw)[6], F mid) {
    float o[2][3][4], t[4] = {0.f, 0.f, 0.f, 0.f};
#pragma unroll
    for (int i = 0; i < 3; i++)
#pragma unroll
        for (int m = 0; m < 2; m++) {
            o[m][i][0] = o[m][i][1] = o[m][i][2] = o[m][i][3] = 0.f;
            if (i < 2) mma16816(o[m][i], va[m][i & 1], pw[2 * i], pw[2 * i + 1]);
            else mma1688(o[m][i], vm[2 * m], vm[2 * m + 1], pw[4]);
        }
    mma1688(t, 0x3F803F80u, 0x3F803F80u, pw[5]);
    mid();
    if (NORM) { inv[0] = rcp_approx(t[0]); inv[1] = rcp_approx(t[1]); }
#pragma unroll
    for (int i = 0; i < 4; i++) {
        const float a = (o[i >> 1][0][2 * (i & 1)] + o[i >> 1][1][2 * (i & 1)]) + o[i >> 1][2][2 * (i & 1)];
        const float b = (o[i >> 1][0][2 * (i & 1) + 1] + o[i >> 1][1][2 * (i & 1) + 1]) + o[i >> 1][2][2 * (i & 1) + 1];
        w[i] = NORM ? pack_bf16(a * inv[0], b * inv[1]) : pack_bf16(a, b);
    }
    if (!NORM) { inv[0] = t[0]; inv[1] = t[1]; }
}
__device__ __forceinline__ uint32_t scale_scores(float a, float b) {
    const float scale = 0.08838834764831845f;
    const uint32_t w = pack_bf16(a, b);
    return pack_bf16(bf_lo(w) * scale, bf_hi(w) * scale);
}

#define TL(i) do {} while (0)
#define TLB(i) do {} while (0)
#define TLC(i) do {} while (0)

#define OPQ_LANE 1
#define CLAIM_T 64
#define PAD_A 0
#define PAD_B 0
#define PAD_C 0
template <int N> __device__ __forceinline__ void code_pad() {
#pragma unroll
    for (int i = 0; i < N; i++) asm volatile("pmevent 0;");
}
__global__ void __cluster_dims__(2, 1, 1) __launch_bounds__(384, 1)
chain_kernel(const __grid_constant__ CUtensorMap mapX, const __grid_constant__ CUtensorMap mapT32, const __grid_constant__ CUtensorMap mapT16,
             const __grid_constant__ CUtensorMap mapTQ, const __grid_constant__ CUtensorMap mapKV,
             const __grid_constant__ CUtensorMap mapWq, const __grid_constant__ CUtensorMap mapWk, const __grid_constant__ CUtensorMap mapWv,
             const __grid_constant__ CUtensorMap mapWo, const bf16* __restrict__ mem0, char* __restrict__ mbox) {
    KT_START(2);
    extern __shared__ __align__(1024) uint8_t smem_chain[];
    constexpr uint32_t SB0 = 1024;
    if (smem_u32(smem_chain) != (SB0 | ((blockIdx.x & 1) << 24))) __trap();
    const int kh = blockIdx.x & 1;
    if (threadIdx.x == 0) {
        const uint32_t sb = smem_u32(smem_chain);
        for (int i = 0; i < 14; i++) mbar_init(sb + SM_BARS + 8 * i, 1);
        mbar_init(sb + MB_P, 4); mbar_init(sb + MB_V, 4); mbar_init(sb + MB_STG, 8); mbar_init(sb + MB_ROLE, 1); mbar_init(sb + MB_W4, 1); mbar_init(sb + MB_W5, 1);
        mbar_expect_tx(sb + MB_ROLE, 4);
        asm volatile("fence.mbarrier_init.release.cluster;" ::: "memory");
    }
    if (threadIdx.x == 32) { prefetch_map(&mapWv); prefetch_map(&mapWq); prefetch_map(&mapWk); prefetch_map(&mapWo); prefetch_map(&mapX); }
    __syncwarp();
    asm volatile("barrier.cluster.arrive.relaxed.aligned;" ::: "memory");
    unsigned claimed = 0;
    if (threadIdx.x == CLAIM_T && kh == 0) claimed = claim_pair(g_reg) & 255;
    __syncwarp();
    asm volatile("barrier.cluster.wait.acquire.aligned;" ::: "memory");
    if (threadIdx.x == CLAIM_T && kh == 0) {
        st_async1((SB0 | (1u << 24)) + SM_ROLE, claimed, (SB0 | (1u << 24)) + MB_ROLE);
        st_async1(SB0 + SM_ROLE, claimed, SB0 + MB_ROLE);
    }
    __syncwarp();
    mbar_wait_w(smem_u32(smem_chain) + MB_ROLE, 0);
    const int pair = uniform(lds32(smem_u32(smem_chain) + SM_ROLE));
#define YFLIP_() (uniform(lds32(sb + SM_ROLE + 4)) ^ YFLIP)
    if (pair >= 64) return;
    if (threadIdx.x == 0) KT_MARK(5);
    const int h = pair >> 1, nh = pair & 1, j = 2 * nh + kh, role = 2 * pair + kh;
#define WG_ORDER 0x210
    const int warp = uniform(((WG_ORDER >> (4 * (threadIdx.x >> 7))) & 3) * 4 + ((threadIdx.x >> 5) & 3));
    const uint32_t g = warp & 3, sb = SB0 | (kh << 24), rsb = sb ^ (1u << 24), cls = pair >> 5, kflip = ZFLIP ^ kh;
    const uint32_t mlo = (uint32_t)(uintptr_t)mbox, mhi = (uint32_t)((uintptr_t)mbox >> 32);
    auto lane16 = [&]() {
        uint32_t t;
        asm volatile("{.reg .u32 l, x; mov.u32 l, %%laneid; xor.b32 x, l, 1; shl.b32 x, x, 4; shfl.sync.bfly.b32 %0, x, 1, 0x1f, 0xffffffff;}" : "=r"(t));
        return t;
    };
#define PHASE(k) uint32_t L; asm volatile("{.reg .u32 t; shr.u32 t, %1, %3; add.u32 %0, %2, t;}" : "=r"(L) : "r"(it), "r"(l16), "n"(8 + (k)))
#define ROWPAT() ((((L << 3) & 0x380) | ((L << 2) & 0x400)) | ((L ^ (L >> 3)) & 0x10) | (L & 0x60))
#define FRAG() (ROWPAT() ^ (g << 5))
#define QFRAG() ((((L >> 1) & 0x80) | (L & 0x70)) + ((L & 0x80) ? SM_KV + 16384 + kvo : SM_QKV))
#define VFRAG() (ROWPAT() ^ ((g & 1) << 6))
#define VBASE() (sb + SM_KV + 8192 + (g >> 1) * 4096 + kvo)
#define XTLO() ((uint32_t)make_desc(SB0 + SM_XT, 16, 1024) + (ui & 1) * 2048)
    if (warp >= 8) {
        asm volatile("setmaxnreg.dec.sync.aligned.u32 %0;" ::"n"(REG_C));
        code_pad<PAD_C>();
        const uint32_t l16 = lane16(), lane = l16 >> 4;
        auto load_xt = [&](int seg, int half) {
            const uint32_t bar = sb + MB_XT + (seg & 1) * 8;
            if (half == 0) mbar_expect_tx(bar, 32768);
            asm volatile("cp.async.bulk.tensor.3d.shared::cluster.global.mbarrier::complete_tx::bytes [%0], [%1, {%3, %4, %5}], [%2];"
                         ::"r"(sb + SM_XT + (seg & 1) * 32768 + half * 16384), "l"(&mapX), "r"(bar), "r"(0), "r"(seg * SEG), "r"(8 * kh + 4 * (half ^ kflip)) : "memory");
        };
        if (warp == 8) {
            const CUtensorMap* ws = kh ? &mapWq : &mapWk;
            const CUtensorMap* wn = kh ? &mapWk : &mapWq;
            const uint64_t pol = EF_W ? policy_evict_first() : policy_evict_normal();
            const int col = h * DH + 64 * nh, row = 512 * kh;
            if (lane == 0) { mbar_expect_tx(sb + MB_W0, 49152); mbar_expect_tx(sb + MB_W1, 49152); mbar_expect_tx(sb + MB_W4, 49152); mbar_expect_tx(sb + MB_W2, 49152); mbar_expect_tx(sb + MB_W3, PRO3 ? 65536 : 32768); }
            __syncwarp();
            if (lane < 24) {
                const int k = lane ^ (16 * kflip);
                tma_load_2d(sb + STG_V + lane * 2048, &mapWv, col, row + 16 * k, sb + MB_W0, pol);
                tma_load_2d(sb + stg_qk(0, lane), ws, col, row + 16 * k, sb + MB_W1, pol);
                tma_load_2d(sb + stg_qk(1, lane), wn, col, row + 16 * k, sb + MB_W4, pol);
            }
            if (lane < 8) {
                const int k = (24 + lane) ^ (16 * kflip);
                tma_load_2d(sb + SM_WQK + lane * 4096, ws, col, row + 16 * k, sb + MB_W2, pol);
                tma_load_2d(sb + SM_WQK + lane * 4096 + 2048, wn, col, row + 16 * k, sb + MB_W2, pol);
                tma_load_2d(sb + SM_WV + lane * 2048, &mapWv, col, row + 16 * k, sb + MB_W2, pol);
            }
            __syncwarp();
        }
        if (warp == 9) {
            bar_sync(BAR_XT0, 160);
            if (lane == 0) { load_xt(0, 0); load_xt(0, 1); }
            __syncwarp();
        }
        if (warp == 10 && lane == 0) {
            wait_prerequisites();
            launch_dependents();
            sts32(sb + SM_ROLE + 4, g_reg[1]);
        }
        __syncwarp();
        bar_sync(BAR_PDONE, 384);
        KT_MARK(9);
        if (warp == 8) {
            const uint32_t dst = lane < 14 ? stg_wo(lane) : lane < 16 ? SM_WO1 + (lane - 8) * 2048 : SM_WO2 + (lane - 16) * 2048;
            tma_load_2d(sb + dst, &mapWo, 256 * j + 64 * (lane >> 3), h * DH + 16 * (lane & 7), sb + MB_W3, EF_W ? policy_evict_first() : policy_evict_normal());
        }
        if ((warp & 1) == 0) for (int c = (warp - 8) * 16 + lane; c < 512; c += 64) {
            uint32_t w[4];
#pragma unroll
            for (int r = 0; r < 4; r++) {
                const uint32_t lo = reinterpret_cast<const uint16_t*>(mem0)[(2 * r) * DM + 512 * kh + c], hi = reinterpret_cast<const uint16_t*>(mem0)[(2 * r + 1) * DM + 512 * kh + c];
                w[r] = lo | (hi << 16);
            }
            sts128(sb + SM_Z + (c ^ (256 * kflip)) * 16, make_uint4(w[0], w[1], w[2], w[3]));
        }
        if (!PRO3 && warp == 8) mbar_wait_w(sb + MB_W5, 0);
        auto tok_start = [&](int s) {
            if (lane == 0) {
                if (TS_AT == 0) TL(21);
                if (s > -3 && s + 2 < NSEG) {
                    mbar_wait(sb + MB_STG, (s + 2) & 1);
                    if (TS_AT == 1) TL(21);
                    if (XT_FIRST && s + 4 < NSEG) load_xt(s + 4, 0);
                    if (TS_AT == 2) TL(21);
                    asm volatile("fence.proxy.async.shared::cta;" ::: "memory");
                    if (TS_AT == 3) TL(21);
                    const int r = ((s + 2) & 3) * NH + h;
                    tma_store_2d(kh ? &mapT32 : &mapTQ, sb + SM_STG, kh ? 64 * nh : 256 * nh, kh ? r * 96 + 32 : r * 12);
                    tma_store_2d(&mapT16, sb + SM_STG + 4096, 64 * nh, r * 96 + 64 + 16 * kh);
                    asm volatile("cp.async.bulk.commit_group;" ::: "memory");
                    if (TS_AT == 4) TL(21);
                }
                if ((TS_LATE < 3 || s < 0) && (!XT_FIRST || s == -3) && s + 4 < NSEG) load_xt(s + 4, 0);
                if (!LATE_RD || s < 0) asm volatile("cp.async.bulk.wait_group.read 0;" ::: "memory");
                if (s < 0) {
                    asm volatile("mbarrier.arrive.shared::cluster.b64 _, [%0];" ::"r"(rsb + MB_FREE) : "memory");
                    mbar_wait(sb + MB_FREE, (s + 3) & 1);
                }
            }
            __syncwarp();
        };
        auto tok_mid = [&](int s) {
            if (lane == 0) {
                if (s + 4 < NSEG) load_xt(s + 4, 1);
                if (s > -3 && s + 2 < NSEG) {
                    asm volatile("cp.async.bulk.wait_group 0;" ::: "memory");
                    if (s == 8 || s == 16) asm volatile("fence.acq_rel.gpu;" ::: "memory");
                    st_relaxed_u32(g_xflag + role, s + 3);
                }
            }
            __syncwarp();
        };
        auto kv_check = [&](int s) {
            if (s + 1 < NSEG) {
                if (lane < 4) {
                    unsigned f; int guard = 0;
                    do {
                        asm volatile("ld.acquire.gpu.global.u32 %0, [%1];" : "=r"(f) : "l"(g_xflag + h * 4 + lane) : "memory");
                        if (++guard > (1 << 20)) __trap();
                    } while (f <= (unsigned)(s + 1));
                }
                __syncwarp();
                asm volatile("fence.proxy.async.global;" ::: "memory");
            }
        };
        auto kv_load = [&](int s) {
            if (lane == 0 && s + 1 < NSEG) {
                const uint32_t bar = sb + MB_KV + ((s + 1) & 1) * 8, dst = sb + SM_KV + ((s + 1) & 1) * KV_BYTES;
                const int row = (((s + 1) & 3) * NH + h) * 96;
                mbar_expect_tx(bar, KV_BYTES);
                asm volatile("cp.async.bulk.tensor.3d.shared::cluster.global.mbarrier::complete_tx::bytes.multicast::cluster [%0], [%1, {%3, %4, %3}], [%2], %5;"
                             ::"r"(dst + kh * 8192), "l"(&mapKV), "r"(bar), "r"(0), "r"(row + 32 + 32 * kh), "h"((uint16_t)3) : "memory");
                bulk_load(dst + 16384, g_tok + row * DH + j * 1024, 2048, bar);
            }
            __syncwarp();
        };
        if (warp == 9) {
            if (!PRO2 && lane == 0) { load_xt(0, 0); load_xt(0, 1); }
#pragma unroll 1
            for (int s = -3; s < 0; s++) { tok_start(s); KT_MARK(13 + s); bar_arrive(BAR_PRO, 288); tok_mid(s); }
        }
        if (warp == 11) { kv_check(-1); kv_load(-1); }
        bar_arrive(BAR_MEM, 384);
        const uint32_t idx = HS == 6 ? (pair & 31) + 32 * (kh ^ 1) : role & 63;
        const uint32_t ybox = mlo + page_off(idx, cls ^ YFLIP_()), xoth = mlo + WIN + page_off((pair & 31) ^ 1, cls ^ XFLIP);
        const uint32_t zline = mlo + WIN + page_off(32 + (idx >> 5), cls ^ ZFLIP) + (idx & 31) * 128, zbox = mlo + WIN + (page_off(32 + kh, 0) & ~4096u);
        const uint32_t xtype = g == GV ? 2 : g == 2 ? 0 : 1;
        const uint32_t ydst = (lane >> 3) * 128 + ((lane & 7) ^ (lane >> 3)) * 16, ysrc = lane * 128 + ((2 * g) ^ (lane & 7)) * 16;
#pragma unroll 1
        for (int s = 0; s < NSEG; s++) {
            const uint32_t slot = (s & 3) << 14;
            spin_cycles(DLY_T);
            if (g == 3) {
                spin_cycles(DLY_K);
                kv_check(s);
                if (TS_AT == 9) TL(21);
                const uint32_t L = l16, kvo = (s & 1) * KV_BYTES, qa = QFRAG(), sa = sb + SM_S + 512 + (L >> 2);
                float sc[4] = {0.f, 0.f, 0.f, 0.f}, sd[4] = {0.f, 0.f, 0.f, 0.f};
                uint32_t a[4][4], kb[2][4];
                mbar_wait_w(sb + MB_KV + (s & 1) * 8, (s >> 1) & 1);
                mbar_wait_w(sb + MB_P, s & 1);
#pragma unroll
                for (int c = 0; c < 2; c++) {
                    const uint32_t qc = qa + (sb + (nh ^ c) * 1024), kc = L + (sb + SM_QKV + 2048 + (nh ^ c) * 1024);
                    if (TS_AT == 7 && c) TL(21);
                    if (c) bar_sync(BAR_QK, 224);
                    ldsm4t(kb[0], kc); ldsm4t(a[0], qc); ldsm4t(a[1], qc + 256);
                    ldsm4t(kb[1], kc + 512); ldsm4t(a[2], qc + 512); ldsm4t(a[3], qc + 768);
                    mma16816v(sc, a[0], kb[0][0], kb[0][1]);
                    mma16816v(sd, a[1], kb[0][2], kb[0][3]);
                    mma16816v(sc, a[2], kb[1][0], kb[1][1]);
                    mma16816v(sd, a[3], kb[1][2], kb[1][3]);
                }
                sts32(sa, scale_scores(sc[0] + sd[0], sc[1] + sd[1]));
                sts32(sa + 768, scale_scores(sc[2] + sd[2], sc[3] + sd[3]));
                bar_arrive(BAR_S, 160);
                TL(25);
                bar_sync(BAR_SV, NSV);
                if (RT_BULK == 2) kv_load(s);
                if (RT_BULK && lane == 0 && s + 3 < NSEG) {
                    if (!FENCE_W) asm volatile("fence.proxy.async.shared::cta;" ::: "memory");
                    asm volatile("cp.async.bulk.shared::cluster.shared::cta.mbarrier::complete_tx::bytes [%0], [%1], %2, [%3];" ::"r"(rsb + SM_RT), "r"(sb + SM_Z), "n"(8192), "r"(rsb + MB_RT0) : "memory");
                    if (TS_AT == 10) { mbar_wait(sb + MB_RT0, (s + 3) & 1); TL(21); }
                }
                __syncwarp();
                if (RT_BULK != 2) kv_load(s);
            } else {
                if (g == 1 && (TS_LATE == 0 || TS_LATE >= 3)) { spin_cycles(DLY_S); tok_start(s); if (TS_AT == 5) TL(21); if (s == 0) KT_MARK(13); }
                const char* p = make_ptr(l16 + (xoth + xtype * 1024 + slot), mhi);
                uint4 v[2];
                const uint32_t dst = l16 + (sb + SM_QKV + xtype * 2048 + (nh ^ 1) * 1024);
                asm volatile("" ::"l"(p));
                poll_init(v[0]); poll_init(v[1]);
                if (g == GV) {
                    bar_sync(BAR_PUBV, 160);
                    mbar_wait_w(sb + MB_V, s & 1);
                    spin_cycles(DLY_V);
                } else {
                    bar_sync(BAR_PUB, 192);
                    spin_cycles(DLY_X);
                }
                const int r = poll2(v, p);
                sts128(dst, v[0]); sts128(dst + 512, v[1]);
                STAT(1, r > 1 && warp == 10);
                if (g != GV) bar_arrive(BAR_QK, 224);
                if (TS_AT == 6 && g == 0) TL(21);
                if (g == GV) { bar_arrive(BAR_V, 160); if (GV == 0) bar_arrive(BAR_SV, NSV); TL(17); }
                if (g == 1) {
                    TL(31);
                    if (TS_LATE == 1) { tok_start(s); if (TS_AT == 5) TL(21); }
                    if (TS_LATE == 3 && lane == 0 && s + 4 < NSEG) load_xt(s + 4, 0);
                    if (LATE_RD && (TS_LATE == 0 || TS_LATE >= 3)) asm volatile("cp.async.bulk.wait_group.read 0;" ::: "memory");
                    bar_sync(BAR_SV, NSV);
                    if (TS_LATE == 2) { tok_start(s); if (TS_AT == 5) TL(21); }
                    if (TS_LATE == 4 && lane == 0 && s + 4 < NSEG) load_xt(s + 4, 0);
                    tok_mid(s);
                    TL(22);
                }
                if (g == 2 && s >= 1) {
                    TL(16);
                    const uint32_t prev = (slot - 0x4000) & 0xC000;
                    const char* y = make_ptr(l16 + (ybox + prev), mhi);
                    const char* x = make_ptr(l16 + (xoth + prev + kh * (XP ? 2048 : 1536)), mhi);
#pragma unroll
                    for (int i = 0; i < 8; i++) st_sent(y + i * 512);
#pragma unroll
                    for (int i = 0; i < (XP ? 4 : 3); i++) st_sent(x + i * 512);
                    st_relaxed_u32(make_ptr(lane * 4 + (zline + (slot ^ 0x8000)), mhi), SENT);
                    TL(23);
                }
            }
            if (s + 1 == NSEG) break;
            {
                const char* p = make_ptr(l16 + (ybox + g * 1024 + slot), mhi);
                char* zdst = make_ptr(lane * 4 + (zline + g * 32 + slot), mhi);
                const uint32_t dst = ydst + (sb + SM_Y + g * 1024), dst1 = (ydst ^ 64) + (sb + SM_Y + g * 1024 + 512), src = ysrc + (sb + SM_Y), src1 = (ysrc ^ 16) + (sb + SM_Y);
                asm volatile("" ::"l"(p), "l"(zdst));
                uint4 v[2];
                poll_init(v[0]); poll_init(v[1]);
                bar_sync(BAR_SENTC, 384);
                spin_cycles(DLY_Y);
                const int r = poll2(v, p);
                STAT(2, r > 1 && warp == 8);
                sts128(dst, v[0]); sts128(dst1, v[1]);
                bar_sync(BAR_Y, HS == 6 ? 256 : 128);
                TL(18);
                uint32_t b[2][4];
                ldsm4t(b[0], src); ldsm4t(b[1], src1);
                const uint32_t one = 0x3F803F80u;
                float d0[4] = {0.f, 0.f, 0.f, 0.f}, d1[4] = {0.f, 0.f, 0.f, 0.f};
                mma16816(d0, one, one, one, one, b[0][0], b[0][1]);
                mma16816(d1, one, one, one, one, b[1][0], b[1][1]);
                mma16816(d0, one, one, one, one, b[0][2], b[0][3]);
                mma16816(d1, one, one, one, one, b[1][2], b[1][3]);
                const uint32_t w = (lane & 4) ? pack_bf16(d1[0], d1[1]) : pack_bf16(d0[0], d0[1]);
                asm volatile("{.reg .pred p; setp.lt.u32 p, %2, 128; @p st.relaxed.gpu.global.u32 [%0], %1;}" ::"l"(zdst), "r"(w), "r"(l16) : "memory");
                if (s + 3 < NSEG) bar_arrive(BAR_ZP, 256);
                TL(19);
            }
            {
                const char* p = make_ptr(l16 + (zbox + g * 512 + slot), mhi);
                const uint32_t dst = l16 + (sb + SM_Z + g * 512);
                asm volatile("" ::"l"(p));
                uint4 v[4];
                poll_init(v[0]); poll_init(v[1]); poll_init(v[2]); poll_init(v[3]);
                bar_sync(BAR_COMM, 128);
                spin_cycles(DLY_Z);
                const int r = poll4<2048>(v, p);
                STAT(0, r > 1 && warp == 8);
#pragma unroll
                for (int i = 0; i < 4; i++) sts128(dst + i * 2048, v[i]);
                bar_arrive(BAR_MEM, 384);
                TL(20);
            }
        }
    } else if (warp < 4) {
        asm volatile("setmaxnreg.inc.sync.aligned.u32 %0;" ::"n"(REG_A));
        code_pad<PAD_A>();
        const uint32_t l16 = lane16();
        uint32_t wa[2][24][4];
        {
            const uint32_t L = l16, fa = sb + FRAG();
            mbar_wait_w(sb + MB_W1, 0);
            KT_MARK(7);
#pragma unroll
            for (int t = 0; t < 2; t++) {
#pragma unroll
                for (int r = 0; r < 24; r++) ldsm4t(wa[t][r], fa + stg_qk(t, r));
                if (PRO2 && t == 0) { bar_arrive(BAR_XT0, 160); mbar_wait_w(sb + MB_W4, 0); }
            }
            mbar_wait_w(sb + MB_W2, 0);
            if (EARLY_ROLE) bar_sync(BAR_PDONE, 384); else bar_arrive(BAR_PDONE, 384);
        }
        auto batch1 = [&](float (&d)[16], uint32_t lo, auto tc, auto k0c, auto k1c) {
            constexpr int t = decltype(tc)::value;
            const uint64_t da = make_desc(SB0 + SM_WQK, 16, 1024);
            wg_fence();
            static_for<decltype(k0c)::value, decltype(k1c)::value>([&](auto kc) {
                constexpr int i = decltype(kc)::value, k = kstep(t ? ORD1 : ORD0, i), off = (k >> 2) * 256 + (k & 3) * 2;
                if constexpr (k >= 24) wgmma_ss32u<off, i != 0 || t != 0>(d, da + ((k - 24) * 2 + t) * 128, lo);
                else wgmma_rs32u<off, i != 0 || t != 0>(d, wa[t][k], lo);
            });
            wg_commit();
        };
        const uint32_t xbox = mlo + WIN + page_off(pair & 31, cls ^ XFLIP);
        const uint32_t ybox = mlo + page_off(24 + 2 * g + 32 * nh, kh ^ YFLIP_()) + h * 128;
#pragma unroll 1
        for (uint32_t it = 0; it < NSEG + 3; it++) {
            const int s = (int)it - 3;
            const uint32_t ui = uniform(it), slot = ((ui + 1) & 3) << 14, kvo = (~ui & 1) * KV_BYTES, xtlo = XTLO();
            {
                PHASE(5);
                const uint32_t first = L | (g << 9);
                if (s >= 0) mbar_expect_tx_if0(first, sb + MB_R1, 2048);
                if (s + 3 < NSEG) {
                    mbar_expect_tx_if0(first, sb + MB_RT0, (RT_BF & 1) ? 4096 : RT0_N * 2048);
                    mbar_wait_w(sb + MB_XT + (ui & 1) * 8, (it >> 1) & 1);
                }
            }
            if (s >= 0) {
                PHASE(0);
                const uint32_t mb = L + (sb + SM_Z), ra = L + (sb + g * 512), r1 = L + (rsb + SM_R1 + g * 512), r1b = rsb + MB_R1;
                sched_fence(r1);
                bar_sync(BAR_MEM, 384);
                TLB(0);
                float acc[2][2][4];
#pragma unroll
                for (int t = 0; t < 4; t++) { acc[t >> 1][t & 1][0] = acc[t >> 1][t & 1][1] = acc[t >> 1][t & 1][2] = acc[t >> 1][t & 1][3] = 0.f; }
                uint32_t b[4][4];
                uint4 u0, u1;
#pragma unroll
                for (int p = 0; p < 4; p++) ldsm4t(b[p], mb + p * 512);
#pragma unroll
                for (int p = 0; p < 12; p++) {
#pragma unroll
                    for (int u = 0; u < 2; u++) {
                        mma16816v(acc[0][u], wa[0][2 * p + u], b[p & 3][2 * u], b[p & 3][2 * u + 1]);
                        mma16816v(acc[1][u], wa[1][2 * p + u], b[p & 3][2 * u], b[p & 3][2 * u + 1]);
                    }
                    if (p + 4 < 12) ldsm4t(b[p & 3], mb + (p + 4) * 512);
                    if (p == Q3_AT) {
                        bar_sync(BAR_Q3, 256);
                        u0 = lds128(ra + SM_R3); u1 = lds128(ra + SM_O);
                    }
                }
                st_async4(r1, (acc[0][0][0] + __uint_as_float(u0.x)) + acc[0][1][0], (acc[0][0][1] + __uint_as_float(u0.y)) + acc[0][1][1],
                          (acc[0][0][2] + __uint_as_float(u0.z)) + acc[0][1][2], (acc[0][0][3] + __uint_as_float(u0.w)) + acc[0][1][3], r1b);
                TL(1);
                const float o0 = (acc[1][0][0] + __uint_as_float(u1.x)) + acc[1][1][0], o1 = (acc[1][0][1] + __uint_as_float(u1.y)) + acc[1][1][1];
                const float o2 = (acc[1][0][2] + __uint_as_float(u1.z)) + acc[1][1][2], o3 = (acc[1][0][3] + __uint_as_float(u1.w)) + acc[1][1][3];
                const uint32_t l4 = L >> 2, qo = SM_QKV + kh * 2048 + nh * 1024 + g * 256, qr = l4 + (rsb + qo), ql = l4 + (sb + qo), pb = rsb + MB_P;
                char* xd = make_ptr(l4 + (xbox + kh * 1024 + g * 256 + slot), mhi);
                asm volatile("" ::"l"(xd), "r"(qr), "r"(pb), "r"(qr + 128), "f"(o0), "f"(o1), "f"(o2), "f"(o3));
                mbar_wait_w(sb + MB_R1, s & 1);
                const uint4 v = lds128(ra + SM_R1);
                const uint32_t w0 = pack_bf16(o0 + __uint_as_float(v.x), o1 + __uint_as_float(v.y)), w1 = pack_bf16(o2 + __uint_as_float(v.z), o3 + __uint_as_float(v.w));
                st_relaxed_u32(xd, w0);
                st_relaxed_u32(xd + 128, w1);
                bar_arrive(BAR_PUB, 192);
                st_async1(qr, w0, pb);
                st_async1(qr + 128, w1, pb);
                sts32(ql, w0);
                sts32(ql + 128, w1);
                __syncwarp();
                mbar_expect_tx_if0(L, sb + MB_P, 256);
                if (!XB_EARLY) TL(2);
                if (XB_EARLY || s + 3 < NSEG) bar_sync(BAR_VP, 256);
            } else {
                bar_sync(BAR_PRO, 288);
            }
            if (s + 3 < NSEG) {
                float d[16];
                batch1(d, xtlo, std::integral_constant<int, 0>(), std::integral_constant<int, 0>(), std::integral_constant<int, 32>());
                PHASE(1);
                const uint32_t rt = L + (rsb + SM_RT + g * 2048);
                wg_wait<0>();
                TL(7);
                if (RT_BF & 1) {
#pragma unroll
                    for (int i = 0; i < 2; i++)
                        st_async4(rt + i * 512, __uint_as_float(pack_bf16(d[8 * i], d[8 * i + 1])), __uint_as_float(pack_bf16(d[8 * i + 2], d[8 * i + 3])),
                                  __uint_as_float(pack_bf16(d[8 * i + 4], d[8 * i + 5])), __uint_as_float(pack_bf16(d[8 * i + 6], d[8 * i + 7])), rsb + MB_RT0);
                } else if (RT_BULK && s >= 0) {
                    const uint32_t pk = L + (sb + SM_Z + g * 2048);
#pragma unroll
                    for (int i = 0; i < 4; i++) sts128(pk + i * 512, make_uint4(__float_as_uint(d[4 * i]), __float_as_uint(d[4 * i + 1]), __float_as_uint(d[4 * i + 2]), __float_as_uint(d[4 * i + 3])));
                    if (FENCE_W) asm volatile("fence.proxy.async.shared::cta;" ::: "memory");
                } else {
#pragma unroll
                for (int i = 0; i < RT0_N; i++) {
                    if (i == RT0_AT && s >= 0) bar_sync(BAR_SV, NSV);
                    st_async4(rt + i * 512, d[4 * i], d[4 * i + 1], d[4 * i + 2], d[4 * i + 3], rsb + MB_RT0);
                }
                }
            }
            if (s + 1 == NSEG) { bar_arrive(BAR_SV, NSV); break; }
            if (s >= 0) {
                PHASE(2);
                const uint32_t fo = FRAG() + (sb + SM_WO2 + 16384), lo = L + (sb + SM_O), yo = (L >> 2) + (ybox + slot);
                uint32_t a1[8][4];
                if (RT0_AT >= 4 || s + 3 >= NSEG) bar_sync(BAR_SV, NSV);
#pragma unroll
                for (int k = 0; k < 8; k++) ldsm4t(a1[k], fo + k * 2048);
                sched_fence(yo);
                bar_sync(BAR_O2, 256);
                TLB(14);
                float y0[4] = {0.f, 0.f, 0.f, 0.f}, y1[4] = {0.f, 0.f, 0.f, 0.f};
                uint32_t b[2][4];
                ldsm4t(b[0], lo); ldsm4t(b[1], lo + 512);
                sched_fence(L);
#pragma unroll
                for (int p = 0; p < 4; p++) {
                    mma16816v(y0, a1[2 * p], b[p & 1][0], b[p & 1][1]);
                    mma16816v(y1, a1[2 * p + 1], b[p & 1][2], b[p & 1][3]);
                    if (p < 2) ldsm4t(b[p & 1], lo + (p + 2) * 512);
                }
                bar_sync(BAR_INV, 256);
                float i0, i1;
                asm volatile("ld.shared.v2.f32 {%0, %1}, [%2];" : "=f"(i0), "=f"(i1) : "r"(((L >> 1) & 0x18) + (sb + SM_INV + g * 32)) : "memory");
                st_relaxed_u32(make_ptr(yo, mhi), pack_bf16((y0[0] + y1[0]) * i0, (y0[1] + y1[1]) * i1));
                st_relaxed_u32(make_ptr(yo ^ 4096, mhi) + 0x2000, pack_bf16((y0[2] + y1[2]) * i0, (y0[3] + y1[3]) * i1));
                bar_arrive(BAR_SENTC, 384);
                TL(6);
            }
            if (s + 3 < NSEG) {
                PHASE(4);
                float d[16];
                const uint32_t rt = L + (sb + SM_RT + g * 2048);
                if (SENT_EARLY && s >= 0) bar_sync(BAR_SENT, 256);
                mbar_wait_w(sb + MB_RT0, it & 1);
                if (HS == 6 && s >= 0) bar_arrive(BAR_Y, 256);
                if (RT_BF & 1) {
#pragma unroll
                    for (int i = 0; i < 2; i++) {
                        const uint4 v = lds128(rt + i * 512);
                        d[8 * i] = bf_lo(v.x); d[8 * i + 1] = bf_hi(v.x); d[8 * i + 2] = bf_lo(v.y); d[8 * i + 3] = bf_hi(v.y);
                        d[8 * i + 4] = bf_lo(v.z); d[8 * i + 5] = bf_hi(v.z); d[8 * i + 6] = bf_lo(v.w); d[8 * i + 7] = bf_hi(v.w);
                    }
                } else
#pragma unroll
                for (int i = 0; i < 4; i++) {
                    const uint4 v = lds128(rt + i * 512);
                    d[4 * i] = __uint_as_float(v.x); d[4 * i + 1] = __uint_as_float(v.y); d[4 * i + 2] = __uint_as_float(v.z); d[4 * i + 3] = __uint_as_float(v.w);
                }
                if (!SENT_EARLY && s >= 0) bar_sync(BAR_SENT, 256);
                if (SPLIT > 0) batch1(d, xtlo, std::integral_constant<int, 1>(), std::integral_constant<int, 0>(), std::integral_constant<int, SPLIT>());
                if (s >= 0) bar_sync(BAR_ZP, 256);
                TLB(30);
                batch1(d, xtlo, std::integral_constant<int, 1>(), std::integral_constant<int, SPLIT>(), std::integral_constant<int, 32>());
                const uint32_t so = (kh ? FRAG() : ((L & 0x100) << 2) + (L & 0xF0) + g * 256) + (sb + SM_STG);
                wg_wait<0>();
                TL(8);
                uint32_t w[8];
#pragma unroll
                for (int i = 0; i < 8; i++) w[i] = pack_bf16(d[2 * i], d[2 * i + 1]);
                if (kh) {
                    stsm4t(so, w[0], w[1], w[2], w[3]);
                    stsm4t(so + 2048, w[4], w[5], w[6], w[7]);
                } else {
                    stsm4(so, w[0], w[1], w[2], w[3]);
                    stsm4(so + 2048, w[4], w[5], w[6], w[7]);
                }
                __syncwarp();
                mbar_arrive_if0(L, sb + MB_STG);
                TL(9);
            } else {
                bar_arrive(BAR_SENT, 256);
                if (HS == 6) bar_arrive(BAR_Y, 256);
            }
        }
    } else {
        asm volatile("setmaxnreg.inc.sync.aligned.u32 %0;" ::"n"(REG_B));
        code_pad<PAD_B>();
        const uint32_t l16 = lane16();
        uint32_t wv[24][4], wo[8 + WO_RF1][4];
        {
            const uint32_t L = l16, fa = sb + FRAG();
            mbar_wait_w(sb + MB_W0, 0);
            KT_MARK(6);
#pragma unroll
            for (int r = 0; r < 24; r++) ldsm4t(wv[r], fa + STG_V + r * 2048);
#pragma unroll
            for (int r = 0; r < 8 + WO_RF1; r++) asm volatile("" : "=r"(wo[r][0]), "=r"(wo[r][1]), "=r"(wo[r][2]), "=r"(wo[r][3]));
            mbar_wait_w(sb + MB_W2, 0);
            if (EARLY_ROLE) bar_sync(BAR_PDONE, 384); else bar_arrive(BAR_PDONE, 384);
        }
        const uint32_t xbox = XP ? mlo + WIN + page_off(34 + ((pair & 31) >> 1), cls ^ XFLIP) + nh * 2048 : mlo + WIN + page_off(pair & 31, cls ^ XFLIP);
        const uint32_t ybox = mlo + page_off(2 * g + 32 * nh, kh ^ YFLIP_()) + h * 128;
#pragma unroll 1
        for (uint32_t it = 0; it < NSEG + 3; it++) {
            const int s = (int)it - 3;
            const uint32_t ui = uniform(it), slot = ((ui + 1) & 3) << 14, kvo = (~ui & 1) * KV_BYTES, xtlo = XTLO();
            {
                PHASE(5);
                const uint32_t first = L | (g << 9);
                if (s >= 0) mbar_expect_tx_if0(first, sb + MB_R2, 1024);
                if (s + 3 < NSEG) {
                    mbar_expect_tx_if0(first, sb + MB_RT1, RT1_LATE == 9 ? 0 : (RT_BF & 2) ? 2048 : 4096);
                    mbar_wait_w(sb + MB_XT + (ui & 1) * 8, (it >> 1) & 1);
                }
            }
            if (s >= 0) {
                PHASE(0);
                const uint32_t fo = FRAG() + sb, l4 = L >> 2;
                {
                    const uint32_t mb = L + (sb + SM_Z), aw = fo + SM_WQK, ra = L + (sb + g * 512), r2 = (L >> 1) + (rsb + SM_R2 + g * 256), r2b = rsb + MB_R2;
                    uint32_t a[NA][4], b[4][4];
#pragma unroll
                    for (int i = 0; i < NA; i++) ldsm4t(a[i], aw + i * 2048);
                    sched_fence(L);
                    TL(24);
                    bar_sync(BAR_MEM, 384);
#pragma unroll
                    for (int p = 0; p < 4; p++) ldsm4t(b[p], mb + (12 + p) * 512);
                    sched_fence(L);
                    float c[2][4] = {{0.f, 0.f, 0.f, 0.f}, {0.f, 0.f, 0.f, 0.f}};
#pragma unroll
                    for (int i = 0; i < 16; i++) {
                        mma16816v(c[i & 1], a[i % NA], b[i >> 2][i & 2], b[i >> 2][(i & 2) + 1]);
                        ldsm4t(a[i % NA], aw + (i + NA) * 2048);
                    }
                    sts128(ra + SM_R3, make_uint4(__float_as_uint(c[0][0]), __float_as_uint(c[0][1]), __float_as_uint(c[0][2]), __float_as_uint(c[0][3])));
                    sts128(ra + SM_O, make_uint4(__float_as_uint(c[1][0]), __float_as_uint(c[1][1]), __float_as_uint(c[1][2]), __float_as_uint(c[1][3])));
                    bar_arrive(BAR_Q3, 256);
                    TL(29);
                    float acc[4][4];
#pragma unroll
                    for (int t = 0; t < 4; t++) { acc[t][0] = acc[t][1] = acc[t][2] = acc[t][3] = 0.f; }
#pragma unroll
                    for (int i = 16; i < 24; i++) {
                        mma16816v(acc[i & 1], a[i % NA], b[(i - 16) >> 1][2 * (i & 1)], b[(i - 16) >> 1][2 * (i & 1) + 1]);
                        if (i + NA < 24) ldsm4t(a[i % NA], aw + (i + NA) * 2048);
                        else ldsm4t(a[i % NA], mb + (i + NA - 24) * 512);
                    }
#pragma unroll
                    for (int p = 0; p < 12; p++) {
                        mma16816v(acc[(2 * p) & 3], wv[2 * p], a[(24 + p) % NA][0], a[(24 + p) % NA][1]);
                        mma16816v(acc[(2 * p + 1) & 3], wv[2 * p + 1], a[(24 + p) % NA][2], a[(24 + p) % NA][3]);
                        if (p + NA < 12) ldsm4t(a[(24 + p) % NA], mb + (p + NA) * 512);
                    }
                    if (XB_EARLY || s + 3 < NSEG) bar_arrive(BAR_VP, 256);
                    float o[4];
#pragma unroll
                    for (int i = 0; i < 4; i++) o[i] = (acc[0][i] + acc[1][i]) + (acc[2][i] + acc[3][i]);
                    st_async2(r2, kh ? o[0] : o[2], kh ? o[1] : o[3], r2b);
                    TL(10);
                    const float o0 = kh ? o[2] : o[0], o1 = kh ? o[3] : o[1];
                    const uint32_t qo = SM_QKV + 4096 + nh * 1024 + (2 * g + kh) * 128, qr = l4 + (rsb + qo), ql = l4 + (sb + qo), vb = rsb + MB_V, rl = (L >> 1) + (sb + SM_R2 + g * 256);
                    char* xd = make_ptr(l4 + (xbox + 2048 + (2 * g + kh) * 128 + slot), mhi);
                    asm volatile("" ::"l"(xd), "r"(qr), "r"(vb), "f"(o0), "f"(o1));
                    mbar_wait_w(sb + MB_R2, s & 1);
                    uint32_t vx, vy;
                    asm volatile("ld.shared.v2.u32 {%0,%1}, [%2];" : "=r"(vx), "=r"(vy) : "r"(rl) : "memory");
                    const uint32_t w0 = pack_bf16(o0 + __uint_as_float(vx), o1 + __uint_as_float(vy));
                    st_relaxed_u32(xd, w0);
                    bar_arrive(BAR_PUBV, 160);
                    st_async1(qr, w0, vb);
                    sts32(ql, w0);
                    __syncwarp();
                    mbar_expect_tx_if0(L, sb + MB_V, 128);
                    TL(11);
                }
                const uint32_t vma = L + (sb + SM_QKV + 4096 + g * 512), yo = l4 + (ybox + slot);
                uint32_t va[2][2][4];
                {
                    const uint32_t qa = QFRAG(), vf = VFRAG(), va0 = vf + VBASE(), va1 = (vf ^ 32) + VBASE();
                    const uint32_t kf = ((L << 3) & 0x380) | ((L ^ (L >> 3)) & 0x30) | (L & 0x40), kb0 = sb + SM_KV + kvo + g * 1024;
                    const int d = (int)(L >> 6) - (int)((L >> 3) & 6) + 8 * (j - (int)g);
                    const uint32_t keep = (d < 0 ? 0u : 0xFFFFu) | (d < 1 ? 0u : 0xFFFF0000u), sa = l4 + (sb + SM_S + g * 128);
                    const uint32_t q0 = qa + (sb + nh * 1024), q1 = qa + (sb + (nh ^ 1) * 1024);
                    float sc[4] = {0.f, 0.f, 0.f, 0.f}, sd[4] = {0.f, 0.f, 0.f, 0.f};
                    uint32_t a[4][4], kb[2][4];
                    mbar_wait_w(sb + MB_KV + (~ui & 1) * 8, (s >> 1) & 1);
                    ldsm4(kb[0], kf + (kb0 + nh * 4096)); ldsm4(kb[1], (kf ^ 64) + (kb0 + nh * 4096));
                    mbar_wait_w(sb + MB_P, s & 1);
                    TL(12);
#pragma unroll
                    for (int k = 0; k < 4; k++) ldsm4t(a[k], q0 + k * 256);
#pragma unroll
                    for (int k = 0; k < 4; k++) mma16816v((k & 1) ? sd : sc, a[k], kb[k >> 1][2 * (k & 1)], kb[k >> 1][2 * (k & 1) + 1]);
                    ldsm4(kb[0], kf + (kb0 + (nh ^ 1) * 4096)); ldsm4(kb[1], (kf ^ 64) + (kb0 + (nh ^ 1) * 4096));
                    sched_fence(vf | yo);
                    if (TS_AT == 8) TL(21);
                    bar_sync(BAR_QK, 224);
                    TLB(3);
#pragma unroll
                    for (int k = 0; k < 4; k++) ldsm4t(a[k], q1 + k * 256);
                    sched_fence(L);
#pragma unroll
                    for (int k = 0; k < 4; k++) mma16816v((k & 1) ? sd : sc, a[k], kb[k >> 1][2 * (k & 1)], kb[k >> 1][2 * (k & 1) + 1]);
                    ldsm4t(va[0][0], va0); ldsm4t(va[0][1], va0 + 2048);
                    sts32(sa, scale_scores(sc[0] + sd[0], sc[1] + sd[1]));
                    sts32(sa + 768, (scale_scores(sc[2] + sd[2], sc[3] + sd[3]) & keep) | (0xFF80FF80u & ~keep));
                    bar_arrive(BAR_SV, NSV);
                    ldsm4t(va[1][0], va1); ldsm4t(va[1][1], va1 + 2048);
                }
                bar_sync(BAR_S, 160);
                TLB(4);
                uint32_t pw[6], vm[4];
                if (s + 1 < NSEG) {
                softmax40(pw, l4 + (sb + SM_S), [&]() {
                    bar_sync(BAR_V, 160);
                    ldsm4(vm, vma);
                });
                uint32_t a1[NP2][4];
                float inv[2];
                {
                    uint32_t w[4];
                    pv32<false>(w, inv, va, vm, pw, [&]() {
                        sched_fence(L);
#pragma unroll
                        for (int k = 0; k < NP2; k++) ldsm4t(a1[k], fo + SM_WO2 + k * 2048);
                    });
#pragma unroll
                    for (int i = 0; i < 4; i++) sts32(l4 + (sb + SM_O + g * 512) + i * 128, w[i]);
                }
                const uint32_t lo = L + (sb + SM_O);
                bar_arrive(BAR_O2, 256);
                bar_sync(BAR_O, 128);
                TLB(5);
                {
                    float y0[4] = {0.f, 0.f, 0.f, 0.f}, y1[4] = {0.f, 0.f, 0.f, 0.f}, y2[4] = {0.f, 0.f, 0.f, 0.f};
                    uint32_t b[4][4];
#pragma unroll
                    for (int p = 0; p < 4; p++) ldsm4t(b[p], lo + p * 512);
                    inv[0] = rcp_approx(inv[0]); inv[1] = rcp_approx(inv[1]);
                    asm volatile("st.shared.v2.f32 [%0], {%1, %2};" ::"r"(((L >> 1) & 0x18) + (sb + SM_INV + g * 32)), "f"(inv[0]), "f"(inv[1]) : "memory");
                    bar_arrive(BAR_INV, 256);
                    sched_fence(L);
#pragma unroll
                    for (int k = 0; k < 8; k++) {
                        const int p = k >> 1, u = k & 1;
                        mma16816v(y2, a1[k % NP2], b[p][2 * u], b[p][2 * u + 1]);
                        if (k + NP2 < 8) ldsm4t(a1[k % NP2], fo + SM_WO2 + (k + NP2) * 2048);
                        else if (k + NP2 < 16 - WO_RF1) ldsm4t(a1[k % NP2], fo + SM_WO1 + (k + NP2 - 8 + WO_RF1) * 2048);
                        mma16816v(y0, wo[k], b[p][2 * u], b[p][2 * u + 1]);
                        if (k < WO_RF1) mma16816v(y1, wo[8 + (k < WO_RF1 ? k : 0)], b[p][2 * u], b[p][2 * u + 1]);
                        else mma16816v(y1, a1[(k + 8 - WO_RF1) % NP2], b[p][2 * u], b[p][2 * u + 1]);
                        if (k < P2_FENCE) sched_fence(L);
                    }
                    char* yd = make_ptr(yo, mhi);
                    char* yd1 = make_ptr(yo ^ 4096, mhi);
                    st_relaxed_u32(yd1 + 0x80000, pack_bf16(y2[0] * inv[0], y2[1] * inv[1]));
                    st_relaxed_u32(yd + 0x82000, pack_bf16(y2[2] * inv[0], y2[3] * inv[1]));
                    st_relaxed_u32(yd, pack_bf16(y0[0] * inv[0], y0[1] * inv[1]));
                    st_relaxed_u32(yd1 + 0x2000, pack_bf16(y0[2] * inv[0], y0[3] * inv[1]));
                    st_relaxed_u32(yd + 0x40000, pack_bf16(y1[0] * inv[0], y1[1] * inv[1]));
                    st_relaxed_u32(yd1 + 0x42000, pack_bf16(y1[2] * inv[0], y1[3] * inv[1]));
                }
                bar_arrive(BAR_SENTC, 384);
                TL(13);
                bar_sync(BAR_SENT, 256);
                } else {
                    bar_sync(BAR_V, 160);
                }
            } else {
                if (it == WO_IT) {
                    PHASE(2);
                    const uint32_t fa = sb + FRAG();
                    mbar_wait_w(sb + MB_W3, 0);
                    KT_MARK(8);
#pragma unroll
                    for (int r = 0; r < 8 + WO_RF1; r++) ldsm4t(wo[r], fa + stg_wo(r));
                }
                bar_sync(BAR_PRO, 288);
            }
            float o[8];
            {
                PHASE(1);
                float d[16];
                const uint64_t da = make_desc(SB0 + SM_WV, 16, 1024);
                auto batch = [&](auto k0c, auto k1c) {
                    static_for<decltype(k0c)::value, decltype(k1c)::value>([&](auto kc) {
                        constexpr int i = decltype(kc)::value, k = kstep(ORDV, i), off = (k >> 2) * 256 + (k & 3) * 2;
                        if constexpr (k >= 24) wgmma_ss32u<off, i != 0>(d, da + (k - 24) * 128, xtlo);
                        else wgmma_rs32u<off, i != 0>(d, wv[k], xtlo);
                    });
                };
                const uint32_t vf = VFRAG(), va0 = vf + VBASE(), va1 = (vf ^ 32) + VBASE(), vma = L + (sb + SM_QKV + 4096 + g * 512), sa = (L >> 2) + (sb + SM_S + 768);
                const uint32_t rt = L + (rsb + SM_RT + 8192 + g * (HS == 6 ? 512 : 1024));
                uint32_t va[2][2][4], vm[4], pw[6], w[4];
                wg_fence();
                batch(std::integral_constant<int, 0>(), std::integral_constant<int, TA0>());
                wg_commit();
                batch(std::integral_constant<int, TA0>(), std::integral_constant<int, 32>());
                wg_commit();
                wg_wait<1>();
                softmax40(pw, sa, [&]() {});
                ldsm4t(va[0][0], va0); ldsm4t(va[0][1], va0 + 2048);
                ldsm4t(va[1][0], va1); ldsm4t(va[1][1], va1 + 2048);
                ldsm4(vm, vma);
                wg_wait<0>();
                TL(27);
                float inv[2];
                uint32_t q[4];
                pv32<true>(w, inv, va, vm, pw, [&]() {
                    if (RT_BF & 2) {
#pragma unroll
                        for (int i = 0; i < 4; i++) q[i] = pack_bf16(kh ? d[2 * i] : d[8 + 2 * i], kh ? d[2 * i + 1] : d[9 + 2 * i]);
                        if (!RT1_LATE && s + 3 < NSEG) st_async4(rt, __uint_as_float(q[0]), __uint_as_float(q[1]), __uint_as_float(q[2]), __uint_as_float(q[3]), rsb + MB_RT1);
                    } else if (s + 3 < NSEG) {
#pragma unroll
                        for (int i = 0; i < 2; i++)
                            st_async4(rt + i * 512, kh ? d[4 * i] : d[8 + 4 * i], kh ? d[4 * i + 1] : d[9 + 4 * i], kh ? d[4 * i + 2] : d[10 + 4 * i], kh ? d[4 * i + 3] : d[11 + 4 * i], rsb + MB_RT1);
                    }
#pragma unroll
                    for (int i = 0; i < 8; i++) o[i] = kh ? d[8 + i] : d[i];
                });
                if (RT1_LATE == 9) asm volatile("" ::"r"(q[0]), "r"(q[1]), "r"(q[2]), "r"(q[3]));
                if (RT1_LATE == 1 && s + 3 < NSEG) st_async4(rt, __uint_as_float(q[0]), __uint_as_float(q[1]), __uint_as_float(q[2]), __uint_as_float(q[3]), rsb + MB_RT1);
                stsm4t((L & 0x70) * 5 + ((L >> 3) & 0x30) + (sb + SM_TO + g * 640), w[0], w[1], w[2], w[3]);
                __syncwarp();
                const uint4 r = lds128(((L >> 2) & 0x70) * 5 + (L & 0x30) + (sb + SM_TO + g * 640));
                if (s >= 0) stg128(reinterpret_cast<char*>(g_ox) + (((L & 0x1C0) << 7) + (L & 0x30) + (((ui - 3) * SEG + 8 * j) * HD + h * DH + 32 * g) * 2), r);
                TL(26);
            }
            if (s + 3 < NSEG) {
                PHASE(3);
                const uint32_t rt = L + (sb + SM_RT + 8192 + g * (HS == 6 ? 512 : 1024)), so = FRAG() + (sb + SM_STG + 4096);
                mbar_wait_w(sb + MB_RT1, it & 1);
                TL(28);
                uint32_t w[4];
                if (RT_BF & 2) {
                    const uint4 v = lds128(rt);
                    w[0] = pack_bf16(o[0] + bf_lo(v.x), o[1] + bf_hi(v.x)); w[1] = pack_bf16(o[2] + bf_lo(v.y), o[3] + bf_hi(v.y));
                    w[2] = pack_bf16(o[4] + bf_lo(v.z), o[5] + bf_hi(v.z)); w[3] = pack_bf16(o[6] + bf_lo(v.w), o[7] + bf_hi(v.w));
                } else
#pragma unroll
                for (int i = 0; i < 2; i++) {
                    const uint4 v = lds128(rt + i * 512);
                    w[2 * i] = pack_bf16(o[4 * i] + __uint_as_float(v.x), o[4 * i + 1] + __uint_as_float(v.y));
                    w[2 * i + 1] = pack_bf16(o[4 * i + 2] + __uint_as_float(v.z), o[4 * i + 3] + __uint_as_float(v.w));
                }
                stsm4t(so, w[0], w[1], w[2], w[3]);
                __syncwarp();
                mbar_arrive_if0(L, sb + MB_STG);
                TL(15);
            }
        }
    }
    KT_END(2);
    asm volatile("barrier.cluster.arrive.relaxed; barrier.cluster.wait;" ::: "memory");
}
constexpr int B_UCH = 73 * 64;
constexpr int B_SCH = 33 * 64;
constexpr int B_KLEN = 2128;
constexpr int B_KCH = 2 * B_KLEN * 2 + 64;
constexpr int B_KBOX = 136 * 32;
constexpr int B_SM_U = 0;
constexpr int B_SM_S = 8 * B_UCH;
constexpr int B_SM_K = B_SM_S + 8 * B_SCH;
constexpr int B_SM_KT = B_SM_K + 8 * B_KCH;
constexpr int B_SM_VT = B_SM_KT + 8 * B_KBOX;
constexpr int B_SM_QT = B_SM_VT + 32768;
constexpr int B_SM_BAR = B_SM_QT + 32768;
constexpr int B_SMEM = B_SM_BAR + 128 + 512;
static_assert(B_SM_KT % 256 == 0 && B_SM_S % 512 == 0 && B_SMEM <= 232448, "tiles");
constexpr int PROBE_N = 4;
#define PROBE_R 2
constexpr int B_C = 2056;

__device__ __forceinline__ uint32_t atomic_round_trip(char* p) {
    uint32_t t0, t1, v;
    asm volatile("{.reg .pred p;\n"
                 "mov.u32 %0, %%clock;\n"
                 "atom.relaxed.gpu.global.add.u32 %2, [%3], 1;\n"
                 "setp.ne.u32 p, %2, 0x7FFFFFFF;\n"
                 "mov.u32 %1, 0;\n"
                 "@p mov.u32 %1, %%clock;}" : "=&r"(t0), "=&r"(t1), "=&r"(v) : "l"(p) : "memory");
    return t1 - t0;
}
__device__ __forceinline__ uint32_t round_trips(char* a, char* b, uint32_t stride, int lane) {
    for (int i = lane >> 3; i < 2 * PROBE_N; i += 4) stg128(((i & 1) ? b : a) + (i >> 1) * stride + (lane & 7) * 16, make_uint4(0, 0, 0, 0));
    __syncwarp();
    uint32_t ta = 0xFFFF, tb = 0xFFFF;
    if (lane == 0) {
        __threadfence();
#pragma unroll 1
        for (int i = 0; i < PROBE_N; i++) { ta = min(ta, atomic_round_trip(a + i * stride)); tb = min(tb, atomic_round_trip(b + i * stride)); }
    }
    __syncwarp();
    return ta | (tb << 16);
}
__device__ __forceinline__ void measure_distance(char* mbox, int lane) {
    const uint32_t b = blockIdx.x;
    unsigned smid;
    asm volatile("mov.u32 %0, %%smid;" : "=r"(smid));
    char* w1 = mbox + WIN + (b & 31) * 128;
    uint32_t r = 0xFFFFFFFF;
#pragma unroll 1
    for (int i = 0; i < PROBE_R; i++) r = __vminu2(r, round_trips(w1 + page_off(50 + 5 * i + (b >> 5), 0), w1 + page_off(50 + 5 * i + (b >> 5), 1), 16384, lane));
    if (lane == 0) g_cls[smid] = r;
    if (b == 128) {
        char *p = mbox + page_off(0, 0), *q = mbox + page_off(0, 1);
        uint32_t r0 = 0xFFFFFFFF;
#pragma unroll 1
        for (int i = 0; i < PROBE_R; i++) r0 = __vminu2(r0, round_trips(p, q, 128, lane));
        if (lane == 0) { g_reg[1] = ((r0 & 0xFFFF) > (r0 >> 16)) != ((r & 0xFFFF) > (r >> 16)); if (!EARLY_ROLE) g_reg[0] = 0; g_reg[2] = 0; }
        const uint4 sent = make_uint4(SENT, SENT, SENT, SENT);
        stg128(p + lane * 16, sent); stg128(q + lane * 16, sent);
    }
    if (b == 129) for (int i = lane; i < 128; i += 32) g_xflag[i] = 0;
}

#define SP(i)
#define SP2(i)
#define OUT_STG 0
#define PF_STOP 1
#define SENT_AT 3
#define Q_LATE 1
#define PF_DEPTH 4
#define PF_STRIDE 256
struct ChainInputs { const char* w[4]; const char *x, *mem0; };
#define EF_MASK 15
#define EF(i) (((EF_MASK >> (i)) & 1) ? policy_evict_first() : policy_evict_normal())
__device__ __forceinline__ void l2_prefetch(const char* p, uint32_t bytes) {
    asm volatile("cp.async.bulk.prefetch.L2.global [%0], %1;" ::"l"(p), "r"(bytes) : "memory");
}
#define WG_CONV(N, LIST, A0, A1, A2, A3, LO, OF, ...) \
    if constexpr (NN == N) asm volatile("{.reg .b32 l; .reg .b64 e; add.u32 l, %" #LO ", %" #OF "; mov.b64 e, {l, 0x80000020};\n" \
        "wgmma.mma_async.sync.aligned.m64n" #N "k16.f32.bf16.bf16 {" LIST "}, {%" #A0 ",%" #A1 ",%" #A2 ",%" #A3 "}, e, 1, 1, 1, 0;}" \
        : __VA_ARGS__ : "r"(a[0]), "r"(a[1]), "r"(a[2]), "r"(a[3]), "r"(lo), "n"(OFF));
#define WL4 "%0,%1,%2,%3"
#define WL8 WL4 ",%4,%5,%6,%7"
#define WL12 WL8 ",%8,%9,%10,%11"
#define WL16 WL12 ",%12,%13,%14,%15"
#define WL20 WL16 ",%16,%17,%18,%19"
#define WL24 WL20 ",%20,%21,%22,%23"
#define WL28 WL24 ",%24,%25,%26,%27"
#define WL32 WL28 ",%28,%29,%30,%31"
template <int NN, int OFF> __device__ __forceinline__ void wgmma_conv(float (&d)[32], const uint32_t (&a)[4], uint32_t lo) {
    WG_CONV(8, WL4, 4, 5, 6, 7, 8, 9, R4(0))
    WG_CONV(16, WL8, 8, 9, 10, 11, 12, 13, R4(0), R4(4))
    WG_CONV(24, WL12, 12, 13, 14, 15, 16, 17, R4(0), R4(4), R4(8))
    WG_CONV(32, WL16, 16, 17, 18, 19, 20, 21, R16(0))
    WG_CONV(40, WL20, 20, 21, 22, 23, 24, 25, R16(0), R4(16))
    WG_CONV(48, WL24, 24, 25, 26, 27, 28, 29, R16(0), R4(16), R4(20))
    WG_CONV(56, WL28, 28, 29, 30, 31, 32, 33, R16(0), R4(16), R4(20), R4(24))
    WG_CONV(64, WL32, 32, 33, 34, 35, 36, 37, R16(0), R16(16))
}
__device__ __forceinline__ void copy_to_peer(uint32_t dst, uint32_t src, uint32_t bytes, uint32_t bar) {
    asm volatile("cp.async.bulk.shared::cluster.shared::cta.mbarrier::complete_tx::bytes [%0], [%1], %2, [%3];" ::"r"(dst), "r"(src), "r"(bytes), "r"(bar) : "memory");
}
__device__ __forceinline__ uint32_t lds_volatile(uint32_t a) {
    uint32_t v;
    asm volatile("ld.volatile.shared.u32 %0, [%1];" : "=r"(v) : "r"(a) : "memory");
    return v;
}
__device__ __forceinline__ uint32_t swz64(uint32_t a) { return a ^ ((a >> 3) & 0x30); }
__device__ __forceinline__ void fence_async() { asm volatile("fence.proxy.async.shared::cta;" ::: "memory"); }

__global__ void __cluster_dims__(2, 1, 1) __launch_bounds__(576, 1)
ssm_kernel(const __grid_constant__ CUtensorMap mapK, const __grid_constant__ CUtensorMap mapV, const __grid_constant__ CUtensorMap mapQ,
           const __grid_constant__ CUtensorMap mapO, const bf16* __restrict__ shiftk, const bf16* __restrict__ ssmk, const bf16* __restrict__ Dv,
           char* __restrict__ mbox, const __grid_constant__ ChainInputs ci, bf16* __restrict__ outp) {
    extern __shared__ __align__(128) uint8_t smem_raw[];
    const uint32_t sb = (smem_u32(smem_raw) + 511) & ~511u;
    const int rank = blockIdx.x & 1, ch0 = blockIdx.x * 8, c16 = ch0 & ~15, t0 = rank * 1024;
    const int t = threadIdx.x, warp = t >> 5, lane = t & 31;
    const uint32_t bar = sb + B_SM_BAR, barQ = bar + 64, barU = bar + 72, barY = bar + 80, flag = bar + 88;
    SP(0);
    if (lane == 0 && warp < 16 && blockIdx.x < 128) {
        const int i = warp >> 1;
        if (warp & 1) {
            if (i < 3) { mbar_init(barQ + i * 8, 1); mbar_expect_tx(barQ + i * 8, i ? 16384 : 32768); }
            if (i == 3) sts32(flag, 0);
        } else {
            mbar_init(bar + i * 8, 1);
            asm volatile("fence.mbarrier_init.release.cluster;" ::: "memory");
            mbar_expect_tx(bar + i * 8, B_KBOX + 4096);
            tma_load_2d(sb + B_SM_KT + i * B_KBOX, &mapK, c16, t0 + i * 128 - 8, bar + i * 8, EF(0));
            tma_load_2d(sb + B_SM_VT + i * 4096, &mapV, c16, t0 + i * 128, bar + i * 8, EF(0));
        }
        asm volatile("fence.mbarrier_init.release.cluster;" ::: "memory");
    }
    __syncwarp();
    if (warp == 14) SP2(14);
    KT_START(1);
    if (warp == 17) {
        launch_dependents();
        asm volatile("barrier.cluster.arrive.relaxed.aligned;" ::: "memory");
        measure_distance(mbox, lane);
        asm volatile("barrier.cluster.wait.aligned;" ::: "memory");
        KT_MARK(14);
        return;
    }
    if (blockIdx.x >= 128) return;
    if (warp == 16) {
        asm volatile("barrier.cluster.arrive.relaxed.aligned; barrier.cluster.wait.aligned;" ::: "memory");
        SP2(8);
        if (Q_LATE) for (int i = 0; i < 8; i++) { mbar_wait_w(bar + i * 8, 0); SP2(i); }
        if (lane < 8) tma_load_2d(sb + B_SM_QT + lane * 4096, &mapQ, c16, t0 + lane * 128, barQ, EF(3));
        if (!Q_LATE) for (int i = 0; i < 8; i++) mbar_wait_w(bar + i * 8, 0);
        if (lane == 0) {
            l2_prefetch(ci.x + blockIdx.x * 2048, 2048);
            if (blockIdx.x < 8) l2_prefetch(ci.mem0 + blockIdx.x * 2048, 2048);
        }
        uint32_t v[PF_DEPTH], acc = 0;
#pragma unroll
        for (int u = 0; u < PF_DEPTH; u++) v[u] = 0;
        constexpr int PER = 32 * PF_STRIDE, NW = 65536 / PER;
#define PF_N (4 * NW)
        int i = 0;
#pragma unroll 1
        for (; i < PF_N && lds_volatile(flag) == 0; i += PF_DEPTH) {
#pragma unroll
            for (int u = 0; u < PF_DEPTH; u++) {
                const char* a = ci.w[(i + u) / NW] + blockIdx.x * 65536 + ((i + u) % NW) * PER + lane * PF_STRIDE;
                acc |= v[u];
                asm volatile("ld.global.cg.L2::256B.u32 %0, [%1];" : "=r"(v[u]) : "l"(a) : "memory");
            }
        }
#pragma unroll
        for (int u = 0; u < PF_DEPTH; u++) acc |= v[u];
        if (acc == 0x7FFF7FFFu && v[0] == 0x7FFEu) g_err = 1;
        SP2(12);
        KT_MARK(15);
        return;
    }
    asm volatile("barrier.cluster.arrive.relaxed.aligned;" ::: "memory");
    const int far = warp & 1, unit = rank ^ far;
    uint32_t w[4];
    uint32_t d2;
    asm volatile("ld.global.nc.u32 %0, [%1];" : "=r"(d2) : "l"(Dv + ch0 + (warp >> 2) * 2));
    {
        const int ch = warp & 7, half = warp >> 3;
        const uint32_t kb = sb + B_SM_K + ch * B_KCH;
        const uint4* src = reinterpret_cast<const uint4*>(ssmk + (size_t)(ch0 + ch) * S_LEN);
        uint4 kr[4];
#pragma unroll
        for (int i = 0; i < 4; i++) kr[i] = ldg128(src + half * 128 + i * 32 + lane, EF(1));
        const uint32_t edge = half ? 0u : __ldg(reinterpret_cast<const uint32_t*>(src + 128));
        const uint2 sw = __ldg(reinterpret_cast<const uint2*>(shiftk + (size_t)(c16 + unit * 8 + (lane >> 2)) * 4));
        w[0] = __byte_perm(sw.x, 0, 0x1010); w[1] = __byte_perm(sw.x, 0, 0x3232); w[2] = __byte_perm(sw.y, 0, 0x1010); w[3] = __byte_perm(sw.y, 0, 0x3232);
        if (half) sts128(sb + B_SM_U + ch * B_UCH + 4096 + lane * 16, make_uint4(0, 0, 0, 0));
#pragma unroll
        for (int i = 0; i < 4; i++) {
            const uint4 lo = kr[i];
            const uint32_t nx = __shfl_down_sync(~0u, lo.x, 1), n0 = (i < 3) ? __shfl_sync(~0u, kr[i < 3 ? i + 1 : 3].x, 0) : edge;
            const uint32_t hix = (lane < 31) ? nx : n0;
            const int c = 256 - (half * 128 + 32 * i + lane);
            sts128(kb + c * 16, make_uint4(__byte_perm(hix, lo.w, 0x7610), __byte_perm(lo.w, lo.z, 0x7610), __byte_perm(lo.z, lo.y, 0x7610), __byte_perm(lo.y, lo.x, 0x7610)));
            sts128(kb + B_KLEN * 2 + 64 + c * 16, make_uint4(__byte_perm(lo.w, lo.w, 0x1032), __byte_perm(lo.z, lo.z, 0x1032), __byte_perm(lo.y, lo.y, 0x1032), __byte_perm(lo.x, lo.x, 0x1032)));
        }
        const uint32_t k0w = __shfl_sync(~0u, kr[0].x, 0);
        if (half == 0 && lane < 8) {
            sts128(kb + (257 + lane) * 16, make_uint4(lane == 0 ? (k0w & 0xFFFFu) : 0u, 0u, 0u, 0u));
            sts128(kb + B_KLEN * 2 + 64 + (257 + lane) * 16, make_uint4(0u, 0u, 0u, 0u));
        }
    }
    auto sentinels = [&]() {
        const uint4 sent = make_uint4(SENT, SENT, SENT, SENT);
        char* p0 = mbox + blockIdx.x * 16384 + t * 16;
        if (blockIdx.x != 0 || (t & 255) >= 32) stg128(p0, sent);
        stg128(p0 + 8192, sent);
        char* p1 = mbox + WIN + blockIdx.x * 12800 + t * 16;
        stg128(p1, sent);
        if (t < 288) stg128(p1 + 8192, sent);
    };
    if (SENT_AT == 1) sentinels();
    asm volatile("barrier.cluster.wait.acquire.aligned;" ::: "memory");
    SP(1);
    {
        const int box = warp >> 1, row0 = 63 - 32 * rank - 4 * box;
        const uint32_t kt = sb + B_SM_KT + box * B_KBOX + 256 + lane * 32, s0 = (unit ^ ((lane >> 2) & 1)) * 16;
        const uint32_t a0 = kt + s0, a2 = kt - 64 + (unit ^ (((lane + 6) >> 2) & 1)) * 16, a4 = kt - 128 + (s0 ^ 16), av = sb + B_SM_VT + box * 4096 + lane * 32 + s0;
        const uint32_t ul = (lane & 7) * B_UCH + row0 * 64 + (lane >> 3) * 16;
        const uint32_t ud = sb + (far ? B_SM_S + (lane & 7) * (B_SCH - B_UCH) - (1 - rank) * 2048 : B_SM_U);
        mbar_wait_w(bar + box * 8, 0);
        SP(2);
#pragma unroll
        for (int i = 0; i < 4; i++) {
            uint32_t k0[4], k2[4], k4[4], vv[4], o[4];
            ldsm4t(k0, a0 + i * 1024); ldsm4t(k2, a2 + i * 1024); ldsm4t(k4, a4 + i * 1024); ldsm4t(vv, av + i * 1024);
#pragma unroll
            for (int j = 0; j < 4; j++) {
                uint32_t a = bf16_mul(__byte_perm(k4[j], k2[j], 0x5432), w[3]);
                a = bf16_add(a, bf16_mul(k2[j], w[2]));
                a = bf16_add(a, bf16_mul(__byte_perm(k2[j], k0[j], 0x5432), w[1]));
                a = bf16_add(a, bf16_mul(k0[j], w[0]));
                o[j] = bf16_mul(a, vv[j]);
            }
            stsm4(ud + swz64(ul - i * 64), o[0], o[1], o[2], o[3]);
        }
        fence_async();
        __syncwarp();
        if (far && lane < 8) {
            const uint32_t o = lane * B_UCH + (row0 - 3) * 64;
            copy_to_peer(peer_addr(sb + B_SM_U + o, rank ^ 1), ud + o, 256, peer_addr(barU, rank ^ 1));
        }
    }
    bar_sync(1, 512);
    mbar_wait_w(barU, 0);
    if (SENT_AT == 2) sentinels();
    SP(3);
    const int wg = warp >> 2, wq = warp & 3, hi = wq >> 1, g = lane >> 2, tq = lane & 3;
    const uint32_t zero = lds32(sb + B_SM_U + 4096);
#pragma unroll 1
    for (int cc = 0; cc < 2; cc++) {
        const int ch = 2 * wg + cc;
        const uint32_t kb = sb + B_SM_K + ch * B_KCH, ub = sb + B_SM_U + ch * B_UCH;
        const uint32_t dw = __byte_perm(d2, 0, cc ? 0x3232 : 0x1010);
        const int e0 = B_C - g + 2 * tq;
        const uint32_t f0 = ((e0 & 1) ? (kb + B_KLEN * 2 + 64 + (e0 - 1) * 2) : (kb + e0 * 2)) - 32 * wq;
        const uint32_t lo = uniform((ub >> 4) | 0x10000);
        float d[32];
#pragma unroll
        for (int i = 0; i < 32; i++) d[i] = 0.f;
        uint32_t A[2][2][4];
        static_for<0, 32>([&](auto jc) {
            constexpr int j = decltype(jc)::value, N = 64 - 8 * (j / 4);
            if (j >= 2) wg_wait<1>();
            uint32_t(&a)[4] = A[j & 1][0];
            uint32_t(&b)[4] = A[j & 1][1];
            a[0] = lds32(f0 - 128 * j); a[1] = lds32(f0 - 128 * j - 16); a[2] = lds32(f0 - 128 * j + 16);
            b[0] = lds32(f0 - 128 * j + 32); b[2] = lds32(f0 - 128 * j + 48);
            a[3] = a[0] ^ zero; b[1] = a[2] ^ zero; b[3] = b[0] ^ zero;
            wg_fence();
            wgmma_conv<N, 8 * j>(d, a, lo);
            wgmma_conv<N, 8 * j + 2>(d, b, lo);
            wg_commit();
        });
        wg_wait<0>();
        if (cc) SP(4);
        if (PF_STOP == 1 && cc && t == 0) sts32(flag, 1);
        bar_sync(2 + wg, 128);
        if (!hi && tq == 3) { float x = d[13]; d[13] = d[29]; d[29] = x; x = d[15]; d[15] = d[31]; d[31] = x; }
        if (hi && tq == 0) { d[0] = 0.f; d[2] = 0.f; }
        {
            const uint32_t xs = kb + (wq ^ 2) * 2048 + lane * 4;
            const uint32_t xn = hi ? xs + (tq ? 124 : 140) : xs + (tq < 3 ? 4 : -12), wrap = hi ? (tq ? 0 : -1) : (tq < 3 ? 0 : 1);
#pragma unroll
            for (int nb = 0; nb < 4; nb++) {
                const uint32_t xw = xn + ((nb + wrap) & 3) * 512;
#pragma unroll
                for (int i = 0; i < 2; i++) {
                    const float e0v = hi ? d[4 * nb + 2 * i] : d[16 + 4 * nb + 2 * i], e1v = hi ? d[4 * nb + 2 * i + 1] : d[16 + 4 * nb + 2 * i + 1];
                    sts32(hi ? xw + i * 256 : xs + nb * 512 + i * 256 + 128, __float_as_uint(e0v));
                    sts32(hi ? xs + nb * 512 + i * 256 : xw + i * 256, __float_as_uint(e1v));
                }
            }
        }
        bar_sync(2 + wg, 128);
#pragma unroll
        for (int p = 0; p < 2; p++) {
            int row = 16 * p + (lane >> 4) * 8 + (lane & 7);
            row = hi ? row + 31 : row == 31 ? 63 : row;
            const uint32_t a = sb + B_SM_U + swz64(ch * B_UCH + row * 64 + ((wq & 1) * 2 + ((lane >> 3) & 1)) * 16);
            uint32_t u[4];
            ldsm4t(u, a);
#pragma unroll
            for (int b = 0; b < 4; b++) {
                const int r = 8 * p + 2 * b;
                const float y0 = (hi ? d[16 + r] : d[r]) + __uint_as_float(lds32(kb + wq * 2048 + r * 128 + lane * 4));
                const float y1 = (hi ? d[17 + r] : d[r + 1]) + __uint_as_float(lds32(kb + wq * 2048 + r * 128 + 128 + lane * 4));
                u[b] = bf16_add(pack_bf16(y0, y1), bf16_mul(u[b], dw));
            }
            stsm4t(a, u[0], u[1], u[2], u[3]);
        }
        fence_async();
        bar_sync(2 + wg, 128);
        if (SENT_AT == 3 && cc == 0) sentinels();
        if (wq == 0 && lane == 0) copy_to_peer(peer_addr(sb + B_SM_S + ch * B_SCH, rank ^ 1), ub + rank * 2048, 2048, peer_addr(barY, rank ^ 1));
    }
    if (PF_STOP == 2 && t == 0) sts32(flag, 1);
    SP(5);
    mbar_wait_w(barQ, 0);
    bar_sync(1, 512);
    mbar_wait_w(barY, 0);
    asm volatile("barrier.cluster.arrive.relaxed.aligned;" ::: "memory");
    SP(6);
#pragma unroll
    for (int i = 0; i < 4; i++) {
        const int fr = i & 1, row = 63 - 32 * rank - 2 * warp - (i >> 1);
        const uint32_t qa = sb + B_SM_QT + warp * 2048 + (i >> 1) * 1024 + lane * 32 + ((rank ^ fr ^ (lane >> 2)) & 1) * 16;
        uint32_t y[4], q[4];
        ldsm4t(y, sb + (fr ? B_SM_S + (lane & 7) * (B_SCH - B_UCH) - (1 - rank) * 2048 : B_SM_U) + swz64((lane & 7) * B_UCH + row * 64 + (lane >> 3) * 16));
        ldsm4(q, qa);
        stsm4(qa, bf16_mul(q[0], y[0]), bf16_mul(q[1], y[1]), bf16_mul(q[2], y[2]), bf16_mul(q[3], y[3]));
    }
    fence_async();
    __syncwarp();
    if (lane == 0) {
        asm volatile("cp.async.bulk.tensor.2d.global.shared::cta.bulk_group.L2::cache_hint [%0, {%2, %3}], [%1], %4;"
                     ::"l"(&mapO), "r"(sb + B_SM_QT + warp * 2048), "r"(DM + c16), "r"(t0 + warp * 64), "l"(EF(4)) : "memory");
        asm volatile("cp.async.bulk.commit_group;" ::: "memory");
    }
    if (SENT_AT == 0) sentinels();
    if (warp == 0) SP2(10);
    if (lane == 0) asm volatile("cp.async.bulk.wait_group.read 0;" ::: "memory");
    __syncwarp();
    if (warp == 0) SP2(11);
    asm volatile("barrier.cluster.wait.aligned;" ::: "memory");
    SP(7);
    KT_END(1);
}

typedef CUresult (*EncodeFn)(CUtensorMap*, CUtensorMapDataType, cuuint32_t, void*, const cuuint64_t*, const cuuint64_t*, const cuuint32_t*,
                             const cuuint32_t*, CUtensorMapInterleave, CUtensorMapSwizzle, CUtensorMapL2promotion, CUtensorMapFloatOOBfill);

static void make_map(EncodeFn fn, CUtensorMap* m, const void* ptr, uint64_t inner, uint64_t outer, uint32_t box_in, uint32_t box_out,
                     CUtensorMapL2promotion promo = CU_TENSOR_MAP_L2_PROMOTION_L2_256B) {
    cuuint64_t dims[2] = {inner, outer};
    cuuint64_t strides[1] = {inner * 2};
    cuuint32_t box[2] = {box_in, box_out};
    cuuint32_t es[2] = {1, 1};
    fn(m, CU_TENSOR_MAP_DATA_TYPE_BFLOAT16, 2, const_cast<void*>(ptr), dims, strides, box, es, CU_TENSOR_MAP_INTERLEAVE_NONE,
       CU_TENSOR_MAP_SWIZZLE_128B, promo, CU_TENSOR_MAP_FLOAT_OOB_FILL_NONE);
}

#define G2_ST 7
#define PROMO_W CU_TENSOR_MAP_L2_PROMOTION_L2_256B
#define PROMO_O CU_TENSOR_MAP_L2_PROMOTION_L2_256B
#define SSM_PROMO CU_TENSOR_MAP_L2_PROMOTION_NONE
extern "C" void kernel_launch(void* const* d_in, const int* in_sizes, int n_in, void* d_out, int out_size) {
    const bf16* x = (const bf16*)d_in[0];
    const bf16* mem0 = (const bf16*)d_in[1];
    const bf16* Wq = (const bf16*)d_in[2];
    const bf16* Wk = (const bf16*)d_in[3];
    const bf16* Wv = (const bf16*)d_in[4];
    const bf16* Wo = (const bf16*)d_in[5];
    const bf16* Bq = (const bf16*)d_in[7];
    const bf16* Bk = (const bf16*)d_in[8];
    const bf16* Bv = (const bf16*)d_in[9];
    const bf16* Bsh = (const bf16*)d_in[10];
    const bf16* Bssm = (const bf16*)d_in[11];
    const bf16* BD = (const bf16*)d_in[12];
    bf16* out = (bf16*)d_out;

    static bool init = false;
    static EncodeFn enc = nullptr;
    static void *p_tok, *p_ox, *p_mbox;
    static int nclusters = 64;
    if (!init) {
        cudaDriverEntryPointQueryResult qr;
        cudaGetDriverEntryPoint("cuTensorMapEncodeTiled", (void**)&enc, cudaEnableDefault, &qr);
        cudaGetSymbolAddress(&p_tok, g_tok);
        cudaGetSymbolAddress(&p_ox, g_ox);
        cudaGetSymbolAddress(&p_mbox, g_mbox);
        cudaFuncSetAttribute(proj_kernel<96, G2_ST>, cudaFuncAttributeMaxDynamicSharedMemorySize, PROJ_SMEM);
        cudaFuncSetAttribute(proj_kernel<128, 7>, cudaFuncAttributeMaxDynamicSharedMemorySize, PROJ_SMEM);
        cudaFuncSetAttribute(chain_kernel, cudaFuncAttributeMaxDynamicSharedMemorySize, CHAIN_SMEM);
        cudaFuncSetAttribute(ssm_kernel, cudaFuncAttributeMaxDynamicSharedMemorySize, B_SMEM);
        cudaLaunchConfig_t cfg = {};
        cfg.gridDim = dim3(132); cfg.blockDim = dim3(384); cfg.dynamicSmemBytes = CHAIN_SMEM;
        cudaLaunchAttribute at[1];
        at[0].id = cudaLaunchAttributeClusterDimension; at[0].val.clusterDim.x = 2; at[0].val.clusterDim.y = 1; at[0].val.clusterDim.z = 1;
        cfg.attrs = at; cfg.numAttrs = 1;
        int n = 0;
        if (cudaOccupancyMaxActiveClusters(&n, chain_kernel, &cfg) == cudaSuccess && n > 64) nclusters = n < 66 ? n : 66;
        (void)cudaGetLastError();
        init = true;
    }
    char* mbox = (char*)(((uintptr_t)p_mbox + 2 * WIN - 1) & ~(uintptr_t)(2 * WIN - 1));
    CUtensorMap mX, mT32, mT16, mTQ, mKV, mWq, mWk, mWv, mWoC, mWo, mOxE, mOutE, mOx, mOut;
    {
        cuuint64_t dims[3] = {64, S_LEN, DM / 64};
        cuuint64_t strides[2] = {DM * 2, 128};
        cuuint32_t box[3] = {64, 32, 4};
        cuuint32_t es[3] = {1, 1, 1};
        enc(&mX, CU_TENSOR_MAP_DATA_TYPE_BFLOAT16, 3, const_cast<bf16*>(x), dims, strides, box, es, CU_TENSOR_MAP_INTERLEAVE_NONE,
            CU_TENSOR_MAP_SWIZZLE_128B, CU_TENSOR_MAP_L2_PROMOTION_L2_256B, CU_TENSOR_MAP_FLOAT_OOB_FILL_NONE);
    }
    make_map(enc, &mT32, p_tok, DH, 4 * NH * 3 * SEG, 64, 32, CU_TENSOR_MAP_L2_PROMOTION_L2_128B);
    make_map(enc, &mT16, p_tok, DH, 4 * NH * 3 * SEG, 64, 16, CU_TENSOR_MAP_L2_PROMOTION_L2_128B);
    {
        cuuint64_t dims[2] = {512, 4 * NH * 12};
        cuuint64_t strides[1] = {2048};
        cuuint32_t box[2] = {256, 4};
        cuuint32_t es[2] = {1, 1};
        enc(&mTQ, CU_TENSOR_MAP_DATA_TYPE_UINT32, 2, p_tok, dims, strides, box, es, CU_TENSOR_MAP_INTERLEAVE_NONE,
            CU_TENSOR_MAP_SWIZZLE_NONE, CU_TENSOR_MAP_L2_PROMOTION_L2_128B, CU_TENSOR_MAP_FLOAT_OOB_FILL_NONE);
    }
    {
        cuuint64_t dims[3] = {64, 4 * NH * 3 * SEG, 2};
        cuuint64_t strides[2] = {DH * 2, 128};
        cuuint32_t box[3] = {64, 32, 2};
        cuuint32_t es[3] = {1, 1, 1};
        enc(&mKV, CU_TENSOR_MAP_DATA_TYPE_BFLOAT16, 3, p_tok, dims, strides, box, es, CU_TENSOR_MAP_INTERLEAVE_NONE,
            CU_TENSOR_MAP_SWIZZLE_128B, CU_TENSOR_MAP_L2_PROMOTION_L2_128B, CU_TENSOR_MAP_FLOAT_OOB_FILL_NONE);
    }
    make_map(enc, &mWq, Wq, HD, DM, 64, 16, CU_TENSOR_MAP_L2_PROMOTION_L2_128B);
    make_map(enc, &mWk, Wk, HD, DM, 64, 16, CU_TENSOR_MAP_L2_PROMOTION_L2_128B);
    make_map(enc, &mWv, Wv, HD, DM, 64, 16, CU_TENSOR_MAP_L2_PROMOTION_L2_128B);
    make_map(enc, &mWoC, Wo, DM, HD, 64, PRO3 ? 16 : 128, CU_TENSOR_MAP_L2_PROMOTION_L2_128B);
    const bool early = nclusters >= 66;
    make_map(enc, &mWo, Wo, DM, HD, 64, 64, PROMO_W);
    make_map(enc, &mOxE, p_ox, HD, S_LEN, 64, EARLY_NT / 2);
    make_map(enc, &mOutE, out, OUT_LD, S_LEN, 64, EARLY_NT);
    make_map(enc, &mOx, p_ox, HD, S_LEN, 64, (early ? 96 : 128) >> FIN_SO, PROMO_O);
    make_map(enc, &mOut, out, OUT_LD, S_LEN, 64, early ? 96 : 128);

    CUtensorMap mB[4];
    for (int i = 0; i < 4; i++) {
        cuuint64_t dims[2] = {(cuuint64_t)(i < 3 ? DM : OUT_LD), S_LEN};
        cuuint64_t strides[1] = {dims[0] * 2};
        cuuint32_t box[2] = {16, i == 0 ? 136u : i < 3 ? 128u : 64u};
        cuuint32_t es[2] = {1, 1};
        enc(&mB[i], CU_TENSOR_MAP_DATA_TYPE_BFLOAT16, 2, const_cast<bf16*>(i == 0 ? Bk : i == 1 ? Bv : i == 2 ? Bq : out), dims, strides, box, es,
            CU_TENSOR_MAP_INTERLEAVE_NONE, CU_TENSOR_MAP_SWIZZLE_32B, SSM_PROMO, CU_TENSOR_MAP_FLOAT_OOB_FILL_NONE);
    }
    cudaStream_t st = cudaStreamPerThread;
    const ChainInputs ci = {{(const char*)Wv, (const char*)Wk, (const char*)Wq, (const char*)Wo}, (const char*)x, (const char*)mem0};
    ssm_kernel<<<132, 576, B_SMEM, st>>>(mB[0], mB[1], mB[2], mB[3], Bsh, Bssm, BD, mbox, ci, out);
    cudaLaunchAttribute pdl[1];
    pdl[0].id = cudaLaunchAttributeProgrammaticStreamSerialization; pdl[0].val.programmaticStreamSerializationAllowed = 1;
    cudaLaunchConfig_t lc = {};
    lc.stream = st; lc.attrs = pdl;
    lc.gridDim = dim3(2 * nclusters); lc.blockDim = dim3(384); lc.dynamicSmemBytes = CHAIN_SMEM; lc.numAttrs = PDL & 1;
    cudaLaunchKernelEx(&lc, chain_kernel, mX, mT32, mT16, mTQ, mKV, mWq, mWk, mWv, mWoC, mem0, mbox);
    lc.gridDim = dim3(2 * nclusters); lc.blockDim = dim3(PROJ_THREADS); lc.dynamicSmemBytes = PROJ_SMEM; lc.numAttrs = (PDL >> 1) & 1;
    cudaLaunchKernelEx(&lc, early ? proj_kernel<96, G2_ST> : proj_kernel<128, 7>, mWo, mOx, mOut, mOxE, mOutE);
}
```

```cpp
#include <cuda_runtime.h>
#include <cuda_bf16.h>
#include <cuda.h>
#include <stdint.h>
#include <type_traits>

typedef __nv_bfloat16 bf16;

constexpr int S_LEN = 2048, DM = 1024, NH = 32, DH = 128, NSEG = 64, SEG = 32;
constexpr int HD = NH * DH;
constexpr int OUT_LD = 2048;
constexpr unsigned SENT = 0xFFFFFFFFu;

__device__ bf16 g_tok[4 * NH * 3 * SEG * DH];
__device__ bf16 g_ox[(size_t)S_LEN * HD];
__device__ uint4 g_mbox[4 * 131072];
__device__ unsigned g_xflag[128];
__device__ unsigned g_reg[4];
__device__ __align__(16) unsigned g_cls[256];
__device__ unsigned g_err;
constexpr uint32_t WIN = 2u << 20;
__host__ __device__ constexpr uint32_t page_off(uint32_t idx, uint32_t c) {
    return ((idx & 1) << 13) | ((idx >> 1) << 16) | (((c ^ idx ^ (idx >> 1) ^ (idx >> 2) ^ (idx >> 4)) & 1) << 12);
}
#define STAT(i, c) (void)(c)
#define EARLY_ROLE 1
#define PDL 3

__device__ __forceinline__ void launch_dependents() { asm volatile("griddepcontrol.launch_dependents;" ::: "memory"); }
__device__ __forceinline__ void wait_prerequisites() { asm volatile("griddepcontrol.wait;" ::: "memory"); }
__device__ __forceinline__ void prefetch_map(const CUtensorMap* m) { asm volatile("prefetch.tensormap [%0];" ::"l"(m) : "memory"); }
#define KT_MARK(k)
#define KT_START(k)
#define KT_END(k)

__device__ __forceinline__ uint32_t smem_u32(const void* p) { return (uint32_t)__cvta_generic_to_shared(p); }
__device__ __forceinline__ void ldsm4(uint32_t& r0, uint32_t& r1, uint32_t& r2, uint32_t& r3, uint32_t a) {
    asm volatile("ldmatrix.sync.aligned.m8n8.x4.shared.b16 {%0,%1,%2,%3}, [%4];" : "=r"(r0), "=r"(r1), "=r"(r2), "=r"(r3) : "r"(a) : "memory");
}
__device__ __forceinline__ void ldsm4t(uint32_t& r0, uint32_t& r1, uint32_t& r2, uint32_t& r3, uint32_t a) {
    asm volatile("ldmatrix.sync.aligned.m8n8.x4.trans.shared.b16 {%0,%1,%2,%3}, [%4];" : "=r"(r0), "=r"(r1), "=r"(r2), "=r"(r3) : "r"(a) : "memory");
}
__device__ __forceinline__ void ldsm2(uint32_t& r0, uint32_t& r1, uint32_t a) {
    asm volatile("ldmatrix.sync.aligned.m8n8.x2.shared.b16 {%0,%1}, [%2];" : "=r"(r0), "=r"(r1) : "r"(a) : "memory");
}
__device__ __forceinline__ void stg128(void* p, uint4 v) {
    asm volatile("st.global.v4.u32 [%0], {%1,%2,%3,%4};" ::"l"(p), "r"(v.x), "r"(v.y), "r"(v.z), "r"(v.w) : "memory");
}
__device__ __forceinline__ void stsm4(uint32_t a, uint32_t r0, uint32_t r1, uint32_t r2, uint32_t r3) {
    asm volatile("stmatrix.sync.aligned.m8n8.x4.shared.b16 [%0], {%1,%2,%3,%4};" ::"r"(a), "r"(r0), "r"(r1), "r"(r2), "r"(r3) : "memory");
}
__device__ __forceinline__ void mma16816(float (&d)[4], uint32_t a0, uint32_t a1, uint32_t a2, uint32_t a3, uint32_t b0, uint32_t b1) {
    asm("mma.sync.aligned.m16n8k16.row.col.f32.bf16.bf16.f32 {%0,%1,%2,%3},{%4,%5,%6,%7},{%8,%9},{%0,%1,%2,%3};"
                 : "+f"(d[0]), "+f"(d[1]), "+f"(d[2]), "+f"(d[3])
                 : "r"(a0), "r"(a1), "r"(a2), "r"(a3), "r"(b0), "r"(b1));
}
__device__ __forceinline__ void mma1688(float (&d)[4], uint32_t a0, uint32_t a1, uint32_t b0) {
    asm("mma.sync.aligned.m16n8k8.row.col.f32.bf16.bf16.f32 {%0,%1,%2,%3},{%4,%5},{%6},{%0,%1,%2,%3};"
        : "+f"(d[0]), "+f"(d[1]), "+f"(d[2]), "+f"(d[3]) : "r"(a0), "r"(a1), "r"(b0));
}
__device__ __forceinline__ uint32_t movmat(uint32_t a) {
    uint32_t d;
    asm volatile("movmatrix.sync.aligned.m8n8.trans.b16 %0, %1;" : "=r"(d) : "r"(a));
    return d;
}
__device__ __forceinline__ uint32_t pack_bf16(float lo, float hi) {
    uint32_t r;
    asm("cvt.rn.bf16x2.f32 %0, %1, %2;" : "=r"(r) : "f"(hi), "f"(lo));
    return r;
}
__device__ __forceinline__ uint32_t bf16_mul(uint32_t a, uint32_t b) {
    uint32_t d;
    asm("mul.rn.bf16x2 %0, %1, %2;" : "=r"(d) : "r"(a), "r"(b));
    return d;
}
__device__ __forceinline__ uint32_t bf16_add(uint32_t a, uint32_t b) {
    uint32_t d;
    asm("add.rn.bf16x2 %0, %1, %2;" : "=r"(d) : "r"(a), "r"(b));
    return d;
}

__device__ __forceinline__ float bf16_round(float x) { return __bfloat162float(__float2bfloat16_rn(x)); }
__device__ __forceinline__ float bf_lo(uint32_t w) { return __uint_as_float(w << 16); }
__device__ __forceinline__ float bf_hi(uint32_t w) { return __uint_as_float(w & 0xFFFF0000u); }
__device__ __forceinline__ void bar_sync(int id, int n) { asm volatile("bar.sync %0, %1;" ::"r"(id), "r"(n) : "memory"); }
__device__ __forceinline__ void bar_sync_keep(int id, int n, uint32_t a, uint32_t b) {
    asm volatile("bar.sync %0, %1; // %2 %3" ::"r"(id), "r"(n), "r"(a), "r"(b) : "memory");
}
__device__ __forceinline__ bool bar_red_or(int id, int n, bool p) {
    uint32_t r;
    asm volatile("{.reg .pred p, q; setp.ne.u32 p, %3, 0; bar.red.or.pred q, %1, %2, p; selp.u32 %0, 1, 0, q;}" : "=r"(r) : "r"(id), "r"(n), "r"((uint32_t)p) : "memory");
    return r != 0;
}
__device__ __forceinline__ void bar_arrive(int id, int n) { asm volatile("bar.arrive %0, %1;" ::"r"(id), "r"(n) : "memory"); }
__device__ __forceinline__ void cp_async16(uint32_t dst, const void* src) {
    asm volatile("cp.async.cg.shared.global [%0], [%1], 16;" ::"r"(dst), "l"(src) : "memory");
}
__device__ __forceinline__ void cp_commit() { asm volatile("cp.async.commit_group;" ::: "memory"); }
template <int N> __device__ __forceinline__ void cp_wait() { asm volatile("cp.async.wait_group %0;" ::"n"(N) : "memory"); }
__device__ __forceinline__ uint4 ld_relaxed_v4(const void* p) {
    uint4 v;
    asm volatile("ld.relaxed.gpu.global.v4.u32 {%0,%1,%2,%3}, [%4];" : "=r"(v.x), "=r"(v.y), "=r"(v.z), "=r"(v.w) : "l"(p) : "memory");
    return v;
}
__device__ __forceinline__ void st_relaxed_u32(void* p, uint32_t v) { asm volatile("st.relaxed.gpu.global.u32 [%0], %1;" ::"l"(p), "r"(v) : "memory"); }
__device__ __forceinline__ void st_relaxed_v2(void* p, uint32_t a, uint32_t b) {
    asm volatile("st.relaxed.gpu.global.v2.u32 [%0], {%1,%2};" ::"l"(p), "r"(a), "r"(b) : "memory");
}
__device__ __forceinline__ void sts128(uint32_t a, uint4 v) {
    asm volatile("st.shared.v4.u32 [%0], {%1,%2,%3,%4};" ::"r"(a), "r"(v.x), "r"(v.y), "r"(v.z), "r"(v.w) : "memory");
}
__device__ __forceinline__ uint4 lds128(uint32_t a) {
    uint4 v;
    asm volatile("ld.shared.v4.u32 {%0,%1,%2,%3}, [%4];" : "=r"(v.x), "=r"(v.y), "=r"(v.z), "=r"(v.w) : "r"(a) : "memory");
    return v;
}
__device__ __forceinline__ void sts32(uint32_t a, uint32_t v) { asm volatile("st.shared.u32 [%0], %1;" ::"r"(a), "r"(v) : "memory"); }
__device__ __forceinline__ uint32_t lds32(uint32_t a) {
    uint32_t v;
    asm volatile("ld.shared.u32 %0, [%1];" : "=r"(v) : "r"(a) : "memory");
    return v;
}
__device__ __forceinline__ void mbar_init(uint32_t a, uint32_t c) { asm volatile("mbarrier.init.shared::cta.b64 [%0], %1;" ::"r"(a), "r"(c) : "memory"); }
__device__ __forceinline__ void mbar_expect_tx(uint32_t a, uint32_t bytes) {
    asm volatile("mbarrier.arrive.expect_tx.shared::cta.b64 _, [%0], %1;" ::"r"(a), "r"(bytes) : "memory");
}
__device__ __forceinline__ void mbar_arrive(uint32_t a) { asm volatile("mbarrier.arrive.shared::cta.b64 _, [%0];" ::"r"(a) : "memory"); }
__device__ __forceinline__ void mbar_wait(uint32_t a, uint32_t parity) {
    asm volatile("{.reg .pred p; .reg .u32 c;\n"
                 "mov.u32 c, 0;\n"
                 "MBW_LOOP:\n"
                 "add.u32 c, c, 1;\n"
                 "setp.gt.u32 p, c, 0x10000;\n"
                 "@!p mbarrier.try_wait.parity.shared::cta.b64 p, [%0], %1;\n"
                 "@!p bra.uni MBW_LOOP;}" ::"r"(a), "r"(parity) : "memory");
}
__device__ __forceinline__ void mbar_wait_w(uint32_t a, uint32_t parity) {
    asm volatile("{.reg .pred p; .reg .u32 c;\n"
                 "mov.u32 c, 0;\n"
                 "MBW_LOOP:\n"
                 "add.u32 c, c, 1;\n"
                 "setp.gt.u32 p, c, 0x10000;\n"
                 "@!p mbarrier.try_wait.parity.shared::cta.b64 p, [%0], %1;\n"
                 "vote.sync.all.pred p, p, 0xFFFFFFFF;\n"
                 "@!p bra.uni MBW_LOOP;}" ::"r"(a), "r"(parity) : "memory");
}
__device__ __forceinline__ void mbar_expect_tx_if0(uint32_t sel, uint32_t a, uint32_t bytes) {
    asm volatile("{.reg .pred p; setp.eq.u32 p, %2, 0; @p mbarrier.arrive.expect_tx.shared::cta.b64 _, [%0], %1;}" ::"r"(a), "r"(bytes), "r"(sel) : "memory");
}
__device__ __forceinline__ void mbar_arrive_if0(uint32_t sel, uint32_t a) {
    asm volatile("{.reg .pred p; setp.eq.u32 p, %1, 0; @p mbarrier.arrive.shared::cta.b64 _, [%0];}" ::"r"(a), "r"(sel) : "memory");
}
__device__ __forceinline__ void bulk_load(uint32_t dst, const void* src, uint32_t bytes, uint32_t bar) {
    asm volatile("cp.async.bulk.shared::cluster.global.mbarrier::complete_tx::bytes [%0], [%1], %2, [%3];" ::"r"(dst), "l"(src), "r"(bytes), "r"(bar) : "memory");
}
__device__ __forceinline__ void tma_load_2d(uint32_t dst, const CUtensorMap* map, int c0, int c1, uint32_t bar) {
    asm volatile("cp.async.bulk.tensor.2d.shared::cluster.global.mbarrier::complete_tx::bytes [%0], [%1, {%3, %4}], [%2];"
                 ::"r"(dst), "l"(map), "r"(bar), "r"(c0), "r"(c1) : "memory");
}
__device__ __forceinline__ void tma_load_2d_both(uint32_t dst, const CUtensorMap* map, int c0, int c1, uint32_t bar) {
    asm volatile("cp.async.bulk.tensor.2d.shared::cluster.global.mbarrier::complete_tx::bytes.multicast::cluster [%0], [%1, {%3, %4}], [%2], %5;"
                 ::"r"(dst), "l"(map), "r"(bar), "r"(c0), "r"(c1), "h"((uint16_t)3) : "memory");
}
__device__ __forceinline__ uint64_t policy_evict_first() {
    uint64_t p;
    asm("createpolicy.fractional.L2::evict_first.b64 %0, 1.0;" : "=l"(p));
    return p;
}
__device__ __forceinline__ uint64_t policy_evict_normal() {
    uint64_t p;
    asm("createpolicy.fractional.L2::evict_normal.b64 %0, 1.0;" : "=l"(p));
    return p;
}
__device__ __forceinline__ void tma_load_2d(uint32_t dst, const CUtensorMap* map, int c0, int c1, uint32_t bar, uint64_t pol) {
    asm volatile("cp.async.bulk.tensor.2d.shared::cluster.global.mbarrier::complete_tx::bytes.L2::cache_hint [%0], [%1, {%3, %4}], [%2], %5;"
                 ::"r"(dst), "l"(map), "r"(bar), "r"(c0), "r"(c1), "l"(pol) : "memory");
}
__device__ __forceinline__ uint4 ldg128(const void* p, uint64_t pol) {
    uint4 v;
    asm("ld.global.nc.L2::cache_hint.v4.u32 {%0,%1,%2,%3}, [%4], %5;" : "=r"(v.x), "=r"(v.y), "=r"(v.z), "=r"(v.w) : "l"(p), "l"(pol));
    return v;
}
__device__ __forceinline__ void stg128(void* p, uint4 v, uint64_t pol) {
    asm volatile("st.global.L2::cache_hint.v4.u32 [%0], {%1,%2,%3,%4}, %5;" ::"l"(p), "r"(v.x), "r"(v.y), "r"(v.z), "r"(v.w), "l"(pol) : "memory");
}
__device__ __forceinline__ void tma_store_2d(const CUtensorMap* map, uint32_t src, int c0, int c1) {
    asm volatile("cp.async.bulk.tensor.2d.global.shared::cta.bulk_group [%0, {%2, %3}], [%1];" ::"l"(map), "r"(src), "r"(c0), "r"(c1) : "memory");
}
__device__ __forceinline__ char* make_ptr(uint32_t lo, uint32_t hi) {
    uint64_t p;
    asm("mov.b64 %0, {%1, %2};" : "=l"(p) : "r"(lo), "r"(hi));
    return reinterpret_cast<char*>(p);
}
__device__ __forceinline__ uint64_t make_desc(uint32_t saddr, uint32_t lbo, uint32_t sbo) {
    return (uint64_t)((saddr & 0x3FFFF) >> 4) | ((uint64_t)((lbo >> 4) & 0x3FFF) << 16) | ((uint64_t)((sbo >> 4) & 0x3FFF) << 32) | ((uint64_t)1 << 62);
}
__device__ __forceinline__ void wg_fence() { asm volatile("wgmma.fence.sync.aligned;" ::: "memory"); }
__device__ __forceinline__ void wg_commit() { asm volatile("wgmma.commit_group.sync.aligned;" ::: "memory"); }
template <int N> __device__ __forceinline__ void wg_wait() { asm volatile("wgmma.wait_group.sync.aligned %0;" ::"n"(N) : "memory"); }

#define R4(b) "+f"(d[b + 0]), "+f"(d[b + 1]), "+f"(d[b + 2]), "+f"(d[b + 3])
#define R16(b) R4(b), R4(b + 4), R4(b + 8), R4(b + 12)
template <int N> __device__ __forceinline__ void wgmma_proj(float (&d)[N / 2], uint64_t da, uint64_t db) {
    if constexpr (N == 96)
        asm volatile("wgmma.mma_async.sync.aligned.m64n96k16.f32.bf16.bf16 {"
            "%0,%1,%2,%3,%4,%5,%6,%7,%8,%9,%10,%11,%12,%13,%14,%15,%16,%17,%18,%19,%20,%21,%22,%23,%24,%25,%26,%27,%28,%29,%30,%31,%32,%33,%34,%35,%36,%37,%38,%39,"
            "%40,%41,%42,%43,%44,%45,%46,%47"
            "}, %48, %49, 1, 1, 1, 1, 0;" : R16(0), R16(16), R16(32) : "l"(da), "l"(db));
    if constexpr (N == 128)
        asm volatile("wgmma.mma_async.sync.aligned.m64n128k16.f32.bf16.bf16 {"
            "%0,%1,%2,%3,%4,%5,%6,%7,%8,%9,%10,%11,%12,%13,%14,%15,%16,%17,%18,%19,%20,%21,%22,%23,%24,%25,%26,%27,%28,%29,%30,%31,%32,%33,%34,%35,%36,%37,%38,%39,"
            "%40,%41,%42,%43,%44,%45,%46,%47,%48,%49,%50,%51,%52,%53,%54,%55,%56,%57,%58,%59,%60,%61,%62,%63"
            "}, %64, %65, 1, 1, 1, 1, 0;" : R16(0), R16(16), R16(32), R16(48) : "l"(da), "l"(db));
    if constexpr (N == 256)
        asm volatile("wgmma.mma_async.sync.aligned.m64n256k16.f32.bf16.bf16 {"
            "%0,%1,%2,%3,%4,%5,%6,%7,%8,%9,%10,%11,%12,%13,%14,%15,%16,%17,%18,%19,%20,%21,%22,%23,%24,%25,%26,%27,%28,%29,%30,%31,%32,%33,%34,%35,%36,%37,%38,%39,"
            "%40,%41,%42,%43,%44,%45,%46,%47,%48,%49,%50,%51,%52,%53,%54,%55,%56,%57,%58,%59,%60,%61,%62,%63,%64,%65,%66,%67,%68,%69,%70,%71,%72,%73,%74,%75,%76,%7"
            "7,%78,%79,%80,%81,%82,%83,%84,%85,%86,%87,%88,%89,%90,%91,%92,%93,%94,%95,%96,%97,%98,%99,%100,%101,%102,%103,%104,%105,%106,%107,%108,%109,%110,%111,"
            "%112,%113,%114,%115,%116,%117,%118,%119,%120,%121,%122,%123,%124,%125,%126,%127"
            "}, %128, %129, 1, 1, 1, 1, 0;" : R16(0), R16(16), R16(32), R16(48), R16(64), R16(80), R16(96), R16(112) : "l"(da), "l"(db));
}

__device__ __forceinline__ void wgmma_rs32(float (&d)[16], const uint32_t (&a)[4], uint64_t db, bool acc) {
    asm volatile(
        "{.reg .pred p; setp.ne.b32 p, %21, 0;\n"
        "wgmma.mma_async.sync.aligned.m64n32k16.f32.bf16.bf16 {%0,%1,%2,%3,%4,%5,%6,%7,%8,%9,%10,%11,%12,%13,%14,%15}, {%16,%17,%18,%19}, %20, p, 1, 1, 0;}"
        : R16(0) : "r"(a[0]), "r"(a[1]), "r"(a[2]), "r"(a[3]), "l"(db), "n"(1) );
}
__device__ __forceinline__ void wgmma_rs32_first(float (&d)[16], const uint32_t (&a)[4], uint64_t db) {
    asm volatile(
        "{.reg .pred p; setp.ne.b32 p, %21, 0;\n"
        "wgmma.mma_async.sync.aligned.m64n32k16.f32.bf16.bf16 {%0,%1,%2,%3,%4,%5,%6,%7,%8,%9,%10,%11,%12,%13,%14,%15}, {%16,%17,%18,%19}, %20, p, 1, 1, 0;}"
        : R16(0) : "r"(a[0]), "r"(a[1]), "r"(a[2]), "r"(a[3]), "l"(db), "n"(0) );
}
__device__ __forceinline__ void wgmma_ss32(float (&d)[16], uint64_t da, uint64_t db) {
    asm volatile(
        "wgmma.mma_async.sync.aligned.m64n32k16.f32.bf16.bf16 {%0,%1,%2,%3,%4,%5,%6,%7,%8,%9,%10,%11,%12,%13,%14,%15}, %16, %17, 1, 1, 1, 1, 0;"
        : R16(0) : "l"(da), "l"(db));
}
template <int OFF, int ACC> __device__ __forceinline__ void wgmma_rs32u(float (&d)[16], const uint32_t (&a)[4], uint32_t lo) {
    asm volatile(
        "{.reg .pred p; .reg .b32 l; .reg .b64 e; setp.ne.b32 p, %22, 0; add.u32 l, %20, %21; mov.b64 e, {l, 0x40000040};\n"
        "wgmma.mma_async.sync.aligned.m64n32k16.f32.bf16.bf16 {%0,%1,%2,%3,%4,%5,%6,%7,%8,%9,%10,%11,%12,%13,%14,%15}, {%16,%17,%18,%19}, e, p, 1, 1, 0;}"
        : R16(0) : "r"(a[0]), "r"(a[1]), "r"(a[2]), "r"(a[3]), "r"(lo), "n"(OFF), "n"(ACC));
}
template <int OFF, int ACC> __device__ __forceinline__ void wgmma_ss32u(float (&d)[16], uint64_t da, uint32_t lo) {
    asm volatile(
        "{.reg .pred p; .reg .b32 l; .reg .b64 e; setp.ne.b32 p, %19, 0; add.u32 l, %17, %18; mov.b64 e, {l, 0x40000040};\n"
        "wgmma.mma_async.sync.aligned.m64n32k16.f32.bf16.bf16 {%0,%1,%2,%3,%4,%5,%6,%7,%8,%9,%10,%11,%12,%13,%14,%15}, %16, e, p, 1, 1, 1, 0;}"
        : R16(0) : "l"(da), "r"(lo), "n"(OFF), "n"(ACC));
}
template <int K0, int K1, class F> __device__ __forceinline__ void static_for(F f) {
    if constexpr (K0 < K1) { f(std::integral_constant<int, K0>()); static_for<K0 + 1, K1>(f); }
}
__device__ __forceinline__ void st_async4(uint32_t a, float x, float y, float z, float w, uint32_t bar) {
    asm volatile("st.async.weak.shared::cluster.mbarrier::complete_tx::bytes.v4.f32 [%0], {%1,%2,%3,%4}, [%5];" ::"r"(a), "f"(x), "f"(y), "f"(z), "f"(w), "r"(bar) : "memory");
}
__device__ __forceinline__ void st_async2(uint32_t a, float x, float y, uint32_t bar) {
    asm volatile("st.async.weak.shared::cluster.mbarrier::complete_tx::bytes.v2.f32 [%0], {%1,%2}, [%3];" ::"r"(a), "f"(x), "f"(y), "r"(bar) : "memory");
}
__device__ __forceinline__ void st_async1(uint32_t a, uint32_t x, uint32_t bar) {
    asm volatile("st.async.weak.shared::cluster.mbarrier::complete_tx::bytes.b32 [%0], %1, [%2];" ::"r"(a), "r"(x), "r"(bar) : "memory");
}
__device__ __forceinline__ uint32_t peer_addr(uint32_t a, uint32_t rank) {
    uint32_t r;
    asm("mapa.shared::cluster.u32 %0, %1, %2;" : "=r"(r) : "r"(a), "r"(rank));
    return r;
}
__device__ __forceinline__ void stsm4t(uint32_t a, uint32_t r0, uint32_t r1, uint32_t r2, uint32_t r3) {
    asm volatile("stmatrix.sync.aligned.m8n8.x4.trans.shared.b16 [%0], {%1,%2,%3,%4};" ::"r"(a), "r"(r0), "r"(r1), "r"(r2), "r"(r3) : "memory");
}
__device__ __forceinline__ void ldsm4t(uint32_t (&r)[4], uint32_t a) { ldsm4t(r[0], r[1], r[2], r[3], a); }
__device__ __forceinline__ void ldsm4(uint32_t (&r)[4], uint32_t a) { ldsm4(r[0], r[1], r[2], r[3], a); }
__device__ __forceinline__ void mma16816(float (&d)[4], const uint32_t (&a)[4], uint32_t b0, uint32_t b1) { mma16816(d, a[0], a[1], a[2], a[3], b0, b1); }
__device__ __forceinline__ void sched_fence(uint32_t v) {
    asm volatile("{.reg .pred p; setp.ne.u32 p, %0, 0xFFFFFFFF; vote.sync.all.pred p, p, 0xFFFFFFFF; @p bra.uni SF_OK; exit; SF_OK:}" ::"r"(v) : "memory");
}
__device__ __forceinline__ void mma16816v(float (&d)[4], const uint32_t (&a)[4], uint32_t b0, uint32_t b1) {
    asm volatile("mma.sync.aligned.m16n8k16.row.col.f32.bf16.bf16.f32 {%0,%1,%2,%3},{%4,%5,%6,%7},{%8,%9},{%0,%1,%2,%3};"
                 : "+f"(d[0]), "+f"(d[1]), "+f"(d[2]), "+f"(d[3]) : "r"(a[0]), "r"(a[1]), "r"(a[2]), "r"(a[3]), "r"(b0), "r"(b1));
}
__device__ __forceinline__ uint32_t uniform(uint32_t v) { return __reduce_max_sync(~0u, v); }

#define WPRE 0
#define G2_X 0
#define G2_K 4
#define FIN_SO 0
#define PROJ_FAST 1
#define KROT 0
#define WFIRST 0
template <int NT, int STAGES> struct ProjCfg {
    static constexpr int STAGE_BYTES = 16384 + NT * 128;
    static constexpr int EPI = NT == 256 ? STAGES * STAGE_BYTES : 0;
    static constexpr int BARS = 229376 + (NT == 256 ? 192 : 0);
    static_assert(STAGES * STAGE_BYTES <= 229376 && EPI + NT * 256 <= 229376 && STAGES <= 12, "smem");
};
constexpr int PROJ_ROLE = 229376 + 384, PROJ_SMEM = PROJ_ROLE + 16;
__device__ __forceinline__ unsigned claim_pair(unsigned* reg) {
    unsigned smid, ncl = gridDim.x >> 1;
    asm volatile("mov.u32 %0, %%smid;" : "=r"(smid));
    uint2 m;
    for (int guard = 0; guard < 1024; guard++) {
        asm volatile("ld.relaxed.gpu.global.v2.u32 {%0, %1}, [%2];" : "=r"(m.x), "=r"(m.y) : "l"(g_cls + (smid & ~1u)) : "memory");
        if (m.x && m.y) break;
    }
    const unsigned r = __vminu2(m.x, m.y), c = (r & 0xFFFF) > (r >> 16);
    unsigned n = atomicAdd(reg, c ? 0x10000u : 1u);
    const unsigned i = c ? n >> 16 : n & 0xFFFF, order = ((n >> 16) + (n & 0xFFFF)) << 8;
    if (i < 32) return c * 32 + i + order;
    for (int guard = 0; guard < (1 << 20); guard++) {
        asm volatile("ld.relaxed.gpu.global.u32 %0, [%1];" : "=r"(n) : "l"(reg) : "memory");
        if ((n >> 16) + (n & 0xFFFF) >= ncl) break;
    }
    const unsigned k = (c ? n & 0xFFFF : n >> 16) + i - 32;
    return (k < 32 ? (c ^ 1) * 32 + k : 64) + order;
}
template <int NT, int STAGES> __device__ __forceinline__ void proj_init(uint32_t sb) {
    for (int i = 0; i < STAGES; i++) { mbar_init(sb + ProjCfg<NT, STAGES>::BARS + 8 * i, 1); mbar_init(sb + ProjCfg<NT, STAGES>::BARS + 8 * (STAGES + i), 16); }
    asm volatile("fence.mbarrier_init.release.cluster;" ::: "memory");
}
template <int NT, int STAGES, bool SHARE_O, class T, class R>
__device__ __forceinline__ void proj_tiles(uint32_t sb, int warp, uint32_t rank, int ntiles, const CUtensorMap* mapW, const CUtensorMap* mapO,
                                           const CUtensorMap* mapOut, T tile, R ready, int rot = 0) {
    using Cfg = ProjCfg<NT, STAGES>;
    const uint32_t bars = sb + Cfg::BARS;
    const int lane = threadIdx.x & 31;
    if (warp == 8) {
        int st = 0; uint32_t ph = 1;
        for (int i = 0; i < ntiles; i++) {
            int col, tok;
            tile(i, col, tok);
            constexpr bool PRE = WPRE && !SHARE_O;
            if (PRE && lane == 0)
                for (int kb = 0; kb < STAGES; kb++) {
                    mbar_expect_tx(bars + 8 * kb, Cfg::STAGE_BYTES);
                    tma_load_2d_both(sb + kb * Cfg::STAGE_BYTES + rank * 8192, mapW, col + rank * 64, kb * 64, bars + 8 * kb);
                }
            ready(i);
            if (lane == 0) {
                if (PRE) {
                    for (int kb = 0; kb < STAGES; kb++) tma_load_2d(sb + kb * Cfg::STAGE_BYTES + 16384, mapO, kb * 64, tok, bars + 8 * kb);
                    ph = 0;
                }
                for (int kb = PRE ? STAGES : 0; kb < HD / 64; kb++) {
                    mbar_wait(bars + 8 * (STAGES + st), ph);
                    const uint32_t full = bars + 8 * st, sa = sb + st * Cfg::STAGE_BYTES;
                    mbar_expect_tx(full, SHARE_O ? Cfg::STAGE_BYTES : G2_X == 1 ? 16384 : G2_X == 2 ? NT * 128 : Cfg::STAGE_BYTES);
                    if (SHARE_O) {
                        tma_load_2d(sa, mapW, col, kb * 64, full);
                        tma_load_2d(sa + 8192, mapW, col + 64, kb * 64, full);
                        tma_load_2d_both(sa + 16384 + rank * (NT * 64), mapO, kb * 64, tok + rank * (NT / 2), full);
                    } else {
                        const int k0 = ((kb + rot) & 63) * 64;
                        if (WFIRST) tma_load_2d_both(sa + rank * 8192, mapW, col + rank * 64, k0, full);
                        if (G2_X != 1) tma_load_2d(sa + 16384, mapO, k0, G2_X == 3 ? tok & 511 : tok, full);
                        if (!WFIRST && G2_X != 2) tma_load_2d_both(sa + rank * 8192, mapW, col + rank * 64, k0, full);
                    }
                    if (++st == STAGES) { st = 0; ph ^= 1; }
                }
            }
            __syncwarp();
        }
    } else if (warp < 8) {
        const int wg = warp >> 2;
        uint32_t peer_empty;
        asm volatile("mapa.shared::cluster.u32 %0, %1, %2;" : "=r"(peer_empty) : "r"(bars + 8 * STAGES), "r"(rank ^ 1));
        auto release = [&](int stg) {
            if (lane == 0) {
                mbar_arrive(bars + 8 * (STAGES + stg));
                asm volatile("mbarrier.arrive.shared::cluster.b64 _, [%0];" ::"r"(peer_empty + 8 * stg) : "memory");
            }
        };
        const uint32_t ew = sb + Cfg::EPI + wg * (NT * 128);
        int st = 0; uint32_t ph = 0;
        for (int i = 0; i < ntiles; i++) {
            int col, tok;
            tile(i, col, tok);
            float d[NT / 2];
#pragma unroll
            for (int r = 0; r < NT / 2; r++) d[r] = 0.f;
            int prev = -1;
            for (int kb = 0; kb < HD / 64; kb++) {
                mbar_wait(bars + 8 * st, ph);
                const uint32_t sa = sb + st * Cfg::STAGE_BYTES;
                const uint64_t da = make_desc(sa + wg * 8192, 16, 1024), db = make_desc(sa + 16384, 16, 1024);
                wg_fence();
#pragma unroll
                for (int k = 0; k < (NT == 256 ? 4 : G2_K); k++) wgmma_proj<NT>(d, da + k * 128, db + k * 2);
                wg_commit();
                if (prev >= 0) { wg_wait<1>(); release(prev); }
                prev = st;
                if (++st == STAGES) { st = 0; ph ^= 1; }
            }
            wg_wait<0>();
            release(prev);
            if ((warp & 3) == 0 && lane == 0) asm volatile("cp.async.bulk.wait_group.read 0;" ::: "memory");
            if (Cfg::EPI) bar_sync(1 + wg, 128); else bar_sync(3, 256);
            const uint32_t ea = ew + ((lane >> 4) * 8 + (lane & 7)) * 128 + ((((warp & 3) * 2 + ((lane >> 3) & 1)) ^ (lane & 7)) * 16);
#pragma unroll
            for (int r = 0; r < NT / 16; r++)
                stsm4t(ea + r * 2048, pack_bf16(d[8 * r], d[8 * r + 1]), pack_bf16(d[8 * r + 2], d[8 * r + 3]), pack_bf16(d[8 * r + 4], d[8 * r + 5]), pack_bf16(d[8 * r + 6], d[8 * r + 7]));
            asm volatile("fence.proxy.async.shared::cta;" ::: "memory");
            bar_sync(1 + wg, 128);
            if ((warp & 3) == 0 && lane == 0) {
                tma_store_2d(mapOut, ew, col + wg * 64, tok);
                asm volatile("cp.async.bulk.commit_group;" ::: "memory");
            }
        }
        if ((warp & 3) == 0 && lane == 0) asm volatile("cp.async.bulk.wait_group 0;" ::: "memory");
    }
    __syncwarp();
}
constexpr int EARLY_NT = 256, EARLY_STAGES = 3;
constexpr int PROJ_THREADS = 288;

template <int NT, int STAGES>
__global__ void __cluster_dims__(2, 1, 1) __launch_bounds__(PROJ_THREADS, 1)
proj_kernel(const __grid_constant__ CUtensorMap mapW, const __grid_constant__ CUtensorMap mapO, const __grid_constant__ CUtensorMap mapOut,
            const __grid_constant__ CUtensorMap mapOE, const __grid_constant__ CUtensorMap mapOutE) {
    KT_START(3);
    extern __shared__ __align__(1024) uint8_t smem_proj[];
    const uint32_t sb = smem_u32(smem_proj), role = sb + PROJ_ROLE;
    if (sb & 1023) __trap();
    const uint32_t rank = blockIdx.x & 1;
    const int warp = threadIdx.x >> 5;
    if (threadIdx.x == 0) {
        mbar_init(role + 8, 1);
        mbar_expect_tx(role + 8, 4);
        proj_init<NT, STAGES>(sb);
        proj_init<EARLY_NT, EARLY_STAGES>(sb);
    }
    if (threadIdx.x == 32) { prefetch_map(&mapO); prefetch_map(&mapW); prefetch_map(&mapOut); }
    __syncwarp();
    asm volatile("barrier.cluster.arrive.relaxed.aligned;" ::: "memory");
    unsigned claimed = 0;
    if (threadIdx.x == 256 && rank == 0) claimed = claim_pair(g_reg + 2);
    __syncwarp();
    asm volatile("barrier.cluster.wait.acquire.aligned;" ::: "memory");
    if (threadIdx.x == 256 && rank == 0) {
        st_async1(peer_addr(role, 1), claimed, peer_addr(role + 8, 1));
        st_async1(peer_addr(role, 0), claimed, peer_addr(role + 8, 0));
        if ((claimed >> 8) + 1 == gridDim.x >> 1) {
            g_reg[0] = 0;
            for (int i = 0; i < 64; i++) reinterpret_cast<uint4*>(g_cls)[i] = make_uint4(0, 0, 0, 0);
        }
    }
    __syncwarp();
    mbar_wait_w(role + 8, 0);
    const int p = lds32(role) & 255, order = lds32(role) >> 8;
    if (NT == 96 && order < 2) {
        proj_tiles<EARLY_NT, EARLY_STAGES, true>(sb, warp, rank, 4, &mapW, &mapOE, &mapOutE,
            [&](int i, int& col, int& tok) { col = ((i & 1) * 4 + order * 2 + rank) * 128; tok = (i >> 1) * EARLY_NT; },
            [&](int i) {
                const unsigned need = 8 * (i >> 1) + 8 + 3;
                for (int guard = 0; guard < (1 << 16); guard++) {
                    const uint4 f = ld_relaxed_v4(g_xflag + (threadIdx.x & 31) * 4);
                    if (__all_sync(~0u, min(min(f.x, f.y), min(f.z, f.w)) >= need)) break;
                    __nanosleep(1000);
                }
                asm volatile("fence.acq_rel.gpu; fence.proxy.async.global;" ::: "memory");
            });
        __syncthreads();
        asm volatile("barrier.cluster.arrive.relaxed.aligned; barrier.cluster.wait.aligned;" ::: "memory");
    }
    if (p >= 64) return;
    proj_tiles<NT, STAGES, false>(sb, warp, rank, 1, &mapW, &mapO, &mapOut,
                                  [&](int, int& col, int& tok) { col = (p & 7) * 128; tok = S_LEN - 16 * NT + ((p >> 3) * 2 + rank) * NT; },
                                  [&](int) { wait_prerequisites();
                                  }, KROT == 0 ? 0 : KROT == 1 ? (p & 7) * 8 : KROT == 2 ? (p >> 3) * 8 : KROT == 3 ? ((p & 7) + (p >> 3)) * 8 : (p >> 5) * 32);
    KT_END(3);
    asm volatile("barrier.cluster.arrive.relaxed; barrier.cluster.wait;" ::: "memory");
}

#define WO_RF1 6
constexpr int SM_KV = 0, KV_BYTES = 18432;
constexpr int SM_XT = 2 * KV_BYTES;
constexpr int SM_STG = SM_XT + 65536;
constexpr int SM_Z = SM_STG + 6144;
constexpr int SM_RT = SM_Z + 8192;
constexpr int SM_QKV = SM_RT + 10240;
constexpr int SM_R1 = SM_QKV + 6144;
constexpr int SM_Y = SM_R1;
constexpr int SM_R2 = SM_R1 + 4096;
constexpr int SM_R3 = SM_R2 + 1024;
constexpr int SM_O = SM_R3 + 2048;
constexpr int SM_S = SM_O + 2048;
constexpr int SM_INV = SM_S + 1536;
constexpr int SM_TO = SM_R3;
constexpr int SM_WORK_END = SM_S + 2048;
constexpr int STG_QK = 0, STG_V = 98304;
#define WO_IT 2
__host__ __device__ constexpr int stg_wo(int r) { return r < 9 ? KV_BYTES + r * 2048 : r < 13 ? SM_QKV + (r - 9) * 2048 : SM_S; }
static_assert(WO_RF1 == 6 && SM_QKV % 1024 == 0 && SM_S % 1024 == 0 && SM_QKV + 8192 <= SM_TO, "staging of Wo");
__host__ __device__ constexpr int stg_qk(int t, int r) { return t == 0 ? SM_XT + r * 2048 : r < SM_XT / 2048 ? r * 2048 : (r + 24) * 2048; }
constexpr int SM_WO1 = SM_WORK_END - WO_RF1 * 2048;
constexpr int STG_WO = SM_WO1 - 16384;
constexpr int SM_WQK = (SM_WO1 + 16384 > STG_V + 49152) ? SM_WO1 + 16384 : STG_V + 49152;
constexpr int SM_WV = SM_WQK + 32768;
constexpr int SM_WO2 = SM_WV + 16384;
constexpr int SM_BARS = SM_WO2 + 32768;
enum { MB_W0 = SM_BARS, MB_W1 = SM_BARS + 8, MB_W2 = SM_BARS + 16, MB_W3 = SM_BARS + 24, MB_XT = SM_BARS + 32  , MB_KV = SM_BARS + 48  ,
       MB_R3 = SM_BARS + 64, MB_R1 = SM_BARS + 72, MB_R2 = SM_BARS + 80, MB_RT0 = SM_BARS + 88, MB_RT1 = SM_BARS + 96, MB_FREE = SM_BARS + 104,
       MB_P = SM_BARS + 112, MB_V = SM_BARS + 120, MB_STG = SM_BARS + 128, MB_ROLE = SM_BARS + 136, MB_W4 = SM_BARS + 144, MB_W5 = SM_BARS + 152, SM_ROLE = SM_BARS + 160   };
constexpr int CHAIN_SMEM = SM_ROLE + 8;
static_assert(SM_WORK_END % 1024 == 0 && STG_WO >= STG_V, "work area");
static_assert(SM_Y % 128 == 0, "exchange Y");
static_assert(CHAIN_SMEM <= 232448 && WO_RF1 >= 6, "smem");

#define DLY_X 250
#define DLY_V 0
#define DLY_Y 320
#define DLY_Z 280
#define TS_AT 5
#define ORD0 2
#define ORD1 2
#define ORDV 2
__host__ __device__ constexpr int kstep(int ord, int i) { return ord == 0 ? i : ord == 1 ? (i + 24) % 32 : ord == 2 ? (i % 4 == 3 ? 24 + i / 4 : i / 4 * 3 + i % 4) : ord == 3 ? (i < 16 ? (i % 2 ? 24 + i / 2 : i / 2) : i - 8) : (i < 8 ? i : i < 16 ? i + 16 : i - 8); }

#define GV 1
#define NSV (GV ? 320 : 352)
#define Q3_AT 9
#define NA 7
#define NP2 6
#define P2_FENCE 0
#define SPLIT 5
#define TA0 16
#define Y_CHAIN 1
#define EF_W 1
#define XFLIP 0
#define YFLIP 0
#define ZFLIP 1
#define OFENCE 2
#define REG_A 240
#define REG_B 216
#define REG_C (3 * 168 - REG_A - REG_B)

enum { BAR_Y, BAR_MEM, BAR_PUB, BAR_QK, BAR_S, BAR_O, BAR_SENT, BAR_COMM, BAR_PUBV, BAR_PV, BAR_PDONE, BAR_VP, BAR_ZP, BAR_PRO, BAR_O2, BAR_SV,
       BAR_V = BAR_PV, BAR_SENTC = BAR_PDONE, BAR_Q3 = BAR_PRO, BAR_INV = BAR_PRO, BAR_XT0 = BAR_Y };

__device__ __forceinline__ uint32_t umax4(const uint4& v) { return max(max(v.x, v.y), max(v.z, v.w)); }
__device__ __forceinline__ unsigned gtime() { unsigned t; asm volatile("mov.u32 %0, %%globaltimer_lo;" : "=r"(t)::"memory"); return t; }
__device__ __forceinline__ unsigned clock32() { unsigned t; asm volatile("mov.u32 %0, %%clock;" : "=r"(t)::"memory"); return t; }
__device__ __forceinline__ void spin_cycles(int d) {
    if (d > 0) { const unsigned c0 = clock32(); while (clock32() - c0 < (unsigned)d) {} }
}
__device__ __forceinline__ float ex2_approx(float x) { float y; asm("ex2.approx.ftz.f32 %0, %1;" : "=f"(y) : "f"(x)); return y; }
__device__ __forceinline__ float rcp_approx(float x) { float y; asm("rcp.approx.ftz.f32 %0, %1;" : "=f"(y) : "f"(x)); return y; }
__device__ __forceinline__ void st_sent(const void* p) { asm volatile("st.relaxed.gpu.global.v4.u32 [%0], {%1,%1,%1,%1};" ::"l"(p), "r"(SENT) : "memory"); }
#define POLL_LD(p, a, b, c, d, addr) "@" p " ld.relaxed.gpu.global.v4.u32 {" a "," b "," c "," d "}, [" addr "];\n"
#define POLL_CK(p, a, b, c, d) "max.u32 m, " a "," b "; max.u32 n, " c "," d "; max.u32 m, m, n; setp.eq.u32 " p ", m, 0xFFFFFFFF;\n"
#define POLL_IO(v) "+r"(v.x), "+r"(v.y), "+r"(v.z), "+r"(v.w)
__device__ __forceinline__ void poll_init(uint4& v) { v = make_uint4(SENT, SENT, SENT, SENT); asm volatile("" : POLL_IO(v)); }
__device__ __forceinline__ int poll2(uint4 (&v)[2], const char* a) {
    int c = 0;
    asm volatile("{.reg .pred p0, p1, p; .reg .u32 m, n;\n"
                 "setp.eq.u32 p0, %8, 0; setp.eq.u32 p1, %8, 0;\n"
                 "POLL_LOOP:\n"
                 POLL_LD("p0", "%0", "%1", "%2", "%3", "%9") POLL_LD("p1", "%4", "%5", "%6", "%7", "%9+512")
                 "add.u32 %8, %8, 1;\n"
                 POLL_CK("p0", "%0", "%1", "%2", "%3") POLL_CK("p1", "%4", "%5", "%6", "%7")
                 "or.pred p, p0, p1; setp.lt.and.u32 p, %8, 0x10000, p; vote.sync.any.pred p, p, 0xFFFFFFFF;\n"
                 "@p bra.uni POLL_LOOP;}" : POLL_IO(v[0]), POLL_IO(v[1]), "+r"(c) : "l"(a) : "memory");
    return c;
}
template <int ST> __device__ __forceinline__ int poll4(uint4 (&v)[4], const char* a) {
    int c = 0;
    asm volatile("{.reg .pred p0, p1, p2, p3, p; .reg .u32 m, n;\n"
                 "setp.eq.u32 p0, %16, 0; setp.eq.u32 p1, %16, 0; setp.eq.u32 p2, %16, 0; setp.eq.u32 p3, %16, 0;\n"
                 "POLL_LOOP:\n"
                 POLL_LD("p0", "%0", "%1", "%2", "%3", "%17") POLL_LD("p1", "%4", "%5", "%6", "%7", "%17+%18")
                 POLL_LD("p2", "%8", "%9", "%10", "%11", "%17+%19") POLL_LD("p3", "%12", "%13", "%14", "%15", "%17+%20")
                 "add.u32 %16, %16, 1;\n"
                 POLL_CK("p0", "%0", "%1", "%2", "%3") POLL_CK("p1", "%4", "%5", "%6", "%7") POLL_CK("p2", "%8", "%9", "%10", "%11") POLL_CK("p3", "%12", "%13", "%14", "%15")
                 "or.pred p, p0, p1; or.pred p, p, p2; or.pred p, p, p3; setp.lt.and.u32 p, %16, 0x10000, p; vote.sync.any.pred p, p, 0xFFFFFFFF;\n"
                 "@p bra.uni POLL_LOOP;}" : POLL_IO(v[0]), POLL_IO(v[1]), POLL_IO(v[2]), POLL_IO(v[3]), "+r"(c) : "l"(a), "n"(ST), "n"(2 * ST), "n"(3 * ST) : "memory");
    return c;
}
__device__ __forceinline__ uint32_t add_bf16x2(uint32_t a, uint32_t b) { uint32_t r; asm("add.rn.bf16x2 %0, %1, %2;" : "=r"(r) : "r"(a), "r"(b)); return r; }
__device__ __forceinline__ uint32_t max_bf16x2(uint32_t a, uint32_t b) { uint32_t r; asm("max.bf16x2 %0, %1, %2;" : "=r"(r) : "r"(a), "r"(b)); return r; }
template <class F> __device__ __forceinline__ void softmax40(uint32_t (&pw)[6], uint32_t sa, F mid) {
    const float LOG2E = 1.4426950408889634f;
    uint32_t w[5];
    float e[10];
#pragma unroll
    for (int i = 0; i < 5; i++) w[i] = lds32(sa + i * 128);
    uint32_t m = max_bf16x2(max_bf16x2(max_bf16x2(w[0], w[1]), max_bf16x2(w[2], w[3])), w[4]);
    m = max_bf16x2(m, __shfl_xor_sync(~0u, m, 1));
    m = max_bf16x2(m, __shfl_xor_sync(~0u, m, 2));
    const float mb2 = fmaxf(bf_lo(m), bf_hi(m)) * LOG2E;
#pragma unroll
    for (int i = 0; i < 5; i++) {
        e[2 * i] = ex2_approx(fmaf(bf_lo(w[i]), LOG2E, -mb2));
        e[2 * i + 1] = ex2_approx(fmaf(bf_hi(w[i]), LOG2E, -mb2));
    }
    mid();
#pragma unroll
    for (int i = 0; i < 5; i++) pw[i] = pack_bf16(e[2 * i], e[2 * i + 1]);
    const float sum = (((e[0] + e[1]) + (e[2] + e[3])) + ((e[4] + e[5]) + (e[6] + e[7]))) + (e[8] + e[9]);
    const float hi = bf_hi(__float_as_uint(sum));
    pw[5] = pack_bf16(sum - hi, hi);
}
template <bool NORM, class F> __device__ __forceinline__ void pv32(uint32_t (&w)[4], float (&inv)[2], const uint32_t (&va)[2][2][4], const uint32_t (&vm)[4], const uint32_t (&pw)[6], F mid) {
    float o[2][3][4], t[4] = {0.f, 0.f, 0.f, 0.f};
#pragma unroll
    for (int i = 0; i < 3; i++)
#pragma unroll
        for (int m = 0; m < 2; m++) {
            o[m][i][0] = o[m][i][1] = o[m][i][2] = o[m][i][3] = 0.f;
            if (i < 2) mma16816(o[m][i], va[m][i & 1], pw[2 * i], pw[2 * i + 1]);
            else mma1688(o[m][i], vm[2 * m], vm[2 * m + 1], pw[4]);
        }
    mma1688(t, 0x3F803F80u, 0x3F803F80u, pw[5]);
    mid();
    if (NORM) { inv[0] = rcp_approx(t[0]); inv[1] = rcp_approx(t[1]); }
#pragma unroll
    for (int i = 0; i < 4; i++) {
        const float a = (o[i >> 1][0][2 * (i & 1)] + o[i >> 1][1][2 * (i & 1)]) + o[i >> 1][2][2 * (i & 1)];
        const float b = (o[i >> 1][0][2 * (i & 1) + 1] + o[i >> 1][1][2 * (i & 1) + 1]) + o[i >> 1][2][2 * (i & 1) + 1];
        w[i] = NORM ? pack_bf16(a * inv[0], b * inv[1]) : pack_bf16(a, b);
    }
    if (!NORM) { inv[0] = t[0]; inv[1] = t[1]; }
}
__device__ __forceinline__ uint32_t scale_scores(float a, float b) {
    const float scale = 0.08838834764831845f;
    const uint32_t w = pack_bf16(a, b);
    return pack_bf16(bf_lo(w) * scale, bf_hi(w) * scale);
}

#define TL(i) do {} while (0)
#define TLB(i) do {} while (0)
#define TLC(i) do {} while (0)

#define OPQ_LANE 1
#define CLAIM_T 64
#define PAD_A 0
#define PAD_B 0
#define PAD_C 0
template <int N> __device__ __forceinline__ void code_pad() {
#pragma unroll
    for (int i = 0; i < N; i++) asm volatile("pmevent 0;");
}
__global__ void __cluster_dims__(2, 1, 1) __launch_bounds__(384, 1)
chain_kernel(const __grid_constant__ CUtensorMap mapX, const __grid_constant__ CUtensorMap mapT32, const __grid_constant__ CUtensorMap mapT16,
             const __grid_constant__ CUtensorMap mapTQ, const __grid_constant__ CUtensorMap mapKV,
             const __grid_constant__ CUtensorMap mapWq, const __grid_constant__ CUtensorMap mapWk, const __grid_constant__ CUtensorMap mapWv,
             const __grid_constant__ CUtensorMap mapWo, const bf16* __restrict__ mem0, char* __restrict__ mbox) {
    KT_START(2);
    extern __shared__ __align__(1024) uint8_t smem_chain[];
    constexpr uint32_t SB0 = 1024;
    if (smem_u32(smem_chain) != (SB0 | ((blockIdx.x & 1) << 24))) __trap();
    const int kh = blockIdx.x & 1;
    if (threadIdx.x == 0) {
        const uint32_t sb = smem_u32(smem_chain);
        for (int i = 0; i < 14; i++) mbar_init(sb + SM_BARS + 8 * i, 1);
        mbar_init(sb + MB_P, 4); mbar_init(sb + MB_V, 4); mbar_init(sb + MB_STG, 8); mbar_init(sb + MB_ROLE, 1); mbar_init(sb + MB_W4, 1); mbar_init(sb + MB_W5, 1);
        mbar_expect_tx(sb + MB_ROLE, 4);
        asm volatile("fence.mbarrier_init.release.cluster;" ::: "memory");
    }
    if (threadIdx.x == 32) { prefetch_map(&mapWv); prefetch_map(&mapWq); prefetch_map(&mapWk); prefetch_map(&mapWo); prefetch_map(&mapX); }
    __syncwarp();
    asm volatile("barrier.cluster.arrive.relaxed.aligned;" ::: "memory");
    unsigned claimed = 0;
    if (threadIdx.x == CLAIM_T && kh == 0) claimed = claim_pair(g_reg) & 255;
    __syncwarp();
    asm volatile("barrier.cluster.wait.acquire.aligned;" ::: "memory");
    if (threadIdx.x == CLAIM_T && kh == 0) {
        st_async1((SB0 | (1u << 24)) + SM_ROLE, claimed, (SB0 | (1u << 24)) + MB_ROLE);
        st_async1(SB0 + SM_ROLE, claimed, SB0 + MB_ROLE);
    }
    __syncwarp();
    mbar_wait_w(smem_u32(smem_chain) + MB_ROLE, 0);
    const int pair = uniform(lds32(smem_u32(smem_chain) + SM_ROLE));
#define YFLIP_() (uniform(lds32(sb + SM_ROLE + 4)) ^ YFLIP)
    if (pair >= 64) return;
    if (threadIdx.x == 0) KT_MARK(5);
    const int h = pair >> 1, nh = pair & 1, j = 2 * nh + kh, role = 2 * pair + kh;
#define WG_ORDER 0x210
    const int warp = uniform(((WG_ORDER >> (4 * (threadIdx.x >> 7))) & 3) * 4 + ((threadIdx.x >> 5) & 3));
    const uint32_t g = warp & 3, sb = SB0 | (kh << 24), rsb = sb ^ (1u << 24), cls = pair >> 5, kflip = ZFLIP ^ kh;
    const uint32_t mlo = (uint32_t)(uintptr_t)mbox, mhi = (uint32_t)((uintptr_t)mbox >> 32);
    auto lane16 = [&]() {
        uint32_t t;
        asm volatile("{.reg .u32 l, x; mov.u32 l, %%laneid; xor.b32 x, l, 1; shl.b32 x, x, 4; shfl.sync.bfly.b32 %0, x, 1, 0x1f, 0xffffffff;}" : "=r"(t));
        return t;
    };
#define PHASE(k) uint32_t L; asm volatile("{.reg .u32 t; shr.u32 t, %1, %3; add.u32 %0, %2, t;}" : "=r"(L) : "r"(it), "r"(l16), "n"(8 + (k)))
#define ROWPAT() ((((L << 3) & 0x380) | ((L << 2) & 0x400)) | ((L ^ (L >> 3)) & 0x10) | (L & 0x60))
#define FRAG() (ROWPAT() ^ (g << 5))
#define QFRAG() ((((L >> 1) & 0x80) | (L & 0x70)) + ((L & 0x80) ? SM_KV + 16384 + kvo : SM_QKV))
#define VFRAG() (ROWPAT() ^ ((g & 1) << 6))
#define VBASE() (sb + SM_KV + 8192 + (g >> 1) * 4096 + kvo)
#define XTLO() ((uint32_t)make_desc(SB0 + SM_XT, 16, 1024) + (ui & 1) * 2048)
    if (warp >= 8) {
        asm volatile("setmaxnreg.dec.sync.aligned.u32 %0;" ::"n"(REG_C));
        code_pad<PAD_C>();
        const uint32_t l16 = lane16(), lane = l16 >> 4;
        auto load_xt = [&](int seg, int half) {
            const uint32_t bar = sb + MB_XT + (seg & 1) * 8;
            if (half == 0) mbar_expect_tx(bar, 32768);
            asm volatile("cp.async.bulk.tensor.3d.shared::cluster.global.mbarrier::complete_tx::bytes [%0], [%1, {%3, %4, %5}], [%2];"
                         ::"r"(sb + SM_XT + (seg & 1) * 32768 + half * 16384), "l"(&mapX), "r"(bar), "r"(0), "r"(seg * SEG), "r"(8 * kh + 4 * (half ^ kflip)) : "memory");
        };
        if (warp == 8) {
            const CUtensorMap* ws = kh ? &mapWq : &mapWk;
            const CUtensorMap* wn = kh ? &mapWk : &mapWq;
            const uint64_t pol = EF_W ? policy_evict_first() : policy_evict_normal();
            const int col = h * DH + 64 * nh, row = 512 * kh;
            if (lane == 0) { mbar_expect_tx(sb + MB_W0, 49152); mbar_expect_tx(sb + MB_W1, 49152); mbar_expect_tx(sb + MB_W4, 49152); mbar_expect_tx(sb + MB_W2, 49152); mbar_expect_tx(sb + MB_W3, 65536); }
            __syncwarp();
            if (lane < 24) {
                const int k = lane ^ (16 * kflip);
                tma_load_2d(sb + STG_V + lane * 2048, &mapWv, col, row + 16 * k, sb + MB_W0, pol);
                tma_load_2d(sb + stg_qk(0, lane), ws, col, row + 16 * k, sb + MB_W1, pol);
                tma_load_2d(sb + stg_qk(1, lane), wn, col, row + 16 * k, sb + MB_W4, pol);
            }
            if (lane < 8) {
                const int k = (24 + lane) ^ (16 * kflip);
                tma_load_2d(sb + SM_WQK + lane * 4096, ws, col, row + 16 * k, sb + MB_W2, pol);
                tma_load_2d(sb + SM_WQK + lane * 4096 + 2048, wn, col, row + 16 * k, sb + MB_W2, pol);
                tma_load_2d(sb + SM_WV + lane * 2048, &mapWv, col, row + 16 * k, sb + MB_W2, pol);
            }
            __syncwarp();
        }
        if (warp == 9) {
            bar_sync(BAR_XT0, 160);
            if (lane == 0) { load_xt(0, 0); load_xt(0, 1); }
            __syncwarp();
        }
        if (warp == 10 && lane == 0) {
            wait_prerequisites();
            launch_dependents();
            sts32(sb + SM_ROLE + 4, g_reg[1]);
        }
        __syncwarp();
        bar_sync(BAR_PDONE, 384);
        KT_MARK(9);
        if (warp == 8) {
            const uint32_t dst = lane < 14 ? stg_wo(lane) : lane < 16 ? SM_WO1 + (lane - 8) * 2048 : SM_WO2 + (lane - 16) * 2048;
            tma_load_2d(sb + dst, &mapWo, 256 * j + 64 * (lane >> 3), h * DH + 16 * (lane & 7), sb + MB_W3, EF_W ? policy_evict_first() : policy_evict_normal());
        }
        if ((warp & 1) == 0) for (int c = (warp - 8) * 16 + lane; c < 512; c += 64) {
            uint32_t w[4];
#pragma unroll
            for (int r = 0; r < 4; r++) {
                const uint32_t lo = reinterpret_cast<const uint16_t*>(mem0)[(2 * r) * DM + 512 * kh + c], hi = reinterpret_cast<const uint16_t*>(mem0)[(2 * r + 1) * DM + 512 * kh + c];
                w[r] = lo | (hi << 16);
            }
            sts128(sb + SM_Z + (c ^ (256 * kflip)) * 16, make_uint4(w[0], w[1], w[2], w[3]));
        }
        auto tok_start = [&](int s) {
            if (lane == 0) {
                if (TS_AT == 0) TL(21);
                if (s > -3 && s + 2 < NSEG) {
                    mbar_wait(sb + MB_STG, (s + 2) & 1);
                    if (TS_AT == 1) TL(21);
                    if (TS_AT == 2) TL(21);
                    asm volatile("fence.proxy.async.shared::cta;" ::: "memory");
                    if (TS_AT == 3) TL(21);
                    const int r = ((s + 2) & 3) * NH + h;
                    tma_store_2d(kh ? &mapT32 : &mapTQ, sb + SM_STG, kh ? 64 * nh : 256 * nh, kh ? r * 96 + 32 : r * 12);
                    tma_store_2d(&mapT16, sb + SM_STG + 4096, 64 * nh, r * 96 + 64 + 16 * kh);
                    asm volatile("cp.async.bulk.commit_group;" ::: "memory");
                    if (TS_AT == 4) TL(21);
                }
                if (s + 4 < NSEG) load_xt(s + 4, 0);
                if (s < 0) asm volatile("cp.async.bulk.wait_group.read 0;" ::: "memory");
                if (s < 0) {
                    asm volatile("mbarrier.arrive.shared::cluster.b64 _, [%0];" ::"r"(rsb + MB_FREE) : "memory");
                    mbar_wait(sb + MB_FREE, (s + 3) & 1);
                }
            }
            __syncwarp();
        };
        auto tok_mid = [&](int s) {
            if (lane == 0) {
                if (s + 4 < NSEG) load_xt(s + 4, 1);
                if (s > -3 && s + 2 < NSEG) {
                    asm volatile("cp.async.bulk.wait_group 0;" ::: "memory");
                    if (s == 8 || s == 16) asm volatile("fence.acq_rel.gpu;" ::: "memory");
                    st_relaxed_u32(g_xflag + role, s + 3);
                }
            }
            __syncwarp();
        };
        auto kv_check = [&](int s) {
            if (s + 1 < NSEG) {
                if (lane < 4) {
                    unsigned f; int guard = 0;
                    do {
                        asm volatile("ld.acquire.gpu.global.u32 %0, [%1];" : "=r"(f) : "l"(g_xflag + h * 4 + lane) : "memory");
                        if (++guard > (1 << 20)) __trap();
                    } while (f <= (unsigned)(s + 1));
                }
                __syncwarp();
                asm volatile("fence.proxy.async.global;" ::: "memory");
            }
        };
        auto kv_load = [&](int s) {
            if (lane == 0 && s + 1 < NSEG) {
                const uint32_t bar = sb + MB_KV + ((s + 1) & 1) * 8, dst = sb + SM_KV + ((s + 1) & 1) * KV_BYTES;
                const int row = (((s + 1) & 3) * NH + h) * 96;
                mbar_expect_tx(bar, KV_BYTES);
                asm volatile("cp.async.bulk.tensor.3d.shared::cluster.global.mbarrier::complete_tx::bytes.multicast::cluster [%0], [%1, {%3, %4, %3}], [%2], %5;"
                             ::"r"(dst + kh * 8192), "l"(&mapKV), "r"(bar), "r"(0), "r"(row + 32 + 32 * kh), "h"((uint16_t)3) : "memory");
                bulk_load(dst + 16384, g_tok + row * DH + j * 1024, 2048, bar);
            }
            __syncwarp();
        };
        if (warp == 9) {
#pragma unroll 1
            for (int s = -3; s < 0; s++) { tok_start(s); KT_MARK(13 + s); bar_arrive(BAR_PRO, 288); tok_mid(s); }
        }
        if (warp == 11) { kv_check(-1); kv_load(-1); }
        bar_arrive(BAR_MEM, 384);
        const uint32_t idx = (pair & 31) + 32 * (kh ^ 1);
        const uint32_t ybox = mlo + page_off(idx, cls ^ YFLIP_()), xoth = mlo + WIN + page_off((pair & 31) ^ 1, cls ^ XFLIP);
        const uint32_t zline = mlo + WIN + page_off(32 + (idx >> 5), cls ^ ZFLIP) + (idx & 31) * 128, zbox = mlo + WIN + (page_off(32 + kh, 0) & ~4096u);
        const uint32_t xtype = g == GV ? 2 : g == 2 ? 0 : 1;
        const uint32_t ydst = (lane >> 3) * 128 + ((lane & 7) ^ (lane >> 3)) * 16, ysrc = lane * 128 + ((2 * g) ^ (lane & 7)) * 16;
#pragma unroll 1
        for (int s = 0; s < NSEG; s++) {
            const uint32_t slot = (s & 3) << 14;
            if (g == 3) {
                kv_check(s);
                if (TS_AT == 9) TL(21);
                const uint32_t L = l16, kvo = (s & 1) * KV_BYTES, qa = QFRAG(), sa = sb + SM_S + 512 + (L >> 2);
                float sc[4] = {0.f, 0.f, 0.f, 0.f}, sd[4] = {0.f, 0.f, 0.f, 0.f};
                uint32_t a[4][4], kb[2][4];
                mbar_wait_w(sb + MB_KV + (s & 1) * 8, (s >> 1) & 1);
                mbar_wait_w(sb + MB_P, s & 1);
#pragma unroll
                for (int c = 0; c < 2; c++) {
                    const uint32_t qc = qa + (sb + (nh ^ c) * 1024), kc = L + (sb + SM_QKV + 2048 + (nh ^ c) * 1024);
                    if (TS_AT == 7 && c) TL(21);
                    if (c) bar_sync(BAR_QK, 224);
                    ldsm4t(kb[0], kc); ldsm4t(a[0], qc); ldsm4t(a[1], qc + 256);
                    ldsm4t(kb[1], kc + 512); ldsm4t(a[2], qc + 512); ldsm4t(a[3], qc + 768);
                    mma16816v(sc, a[0], kb[0][0], kb[0][1]);
                    mma16816v(sd, a[1], kb[0][2], kb[0][3]);
                    mma16816v(sc, a[2], kb[1][0], kb[1][1]);
                    mma16816v(sd, a[3], kb[1][2], kb[1][3]);
                }
                sts32(sa, scale_scores(sc[0] + sd[0], sc[1] + sd[1]));
                sts32(sa + 768, scale_scores(sc[2] + sd[2], sc[3] + sd[3]));
                bar_arrive(BAR_S, 160);
                TL(25);
                bar_sync(BAR_SV, NSV);
                kv_load(s);
                if (lane == 0 && s + 3 < NSEG) {
                    asm volatile("fence.proxy.async.shared::cta;" ::: "memory");
                    asm volatile("cp.async.bulk.shared::cluster.shared::cta.mbarrier::complete_tx::bytes [%0], [%1], %2, [%3];" ::"r"(rsb + SM_RT), "r"(sb + SM_Z), "n"(8192), "r"(rsb + MB_RT0) : "memory");
                    if (TS_AT == 10) { mbar_wait(sb + MB_RT0, (s + 3) & 1); TL(21); }
                }
                __syncwarp();
            } else {
                if (g == 1) { tok_start(s); if (TS_AT == 5) TL(21); if (s == 0) KT_MARK(13); }
                const char* p = make_ptr(l16 + (xoth + xtype * 1024 + slot), mhi);
                uint4 v[2];
                const uint32_t dst = l16 + (sb + SM_QKV + xtype * 2048 + (nh ^ 1) * 1024);
                asm volatile("" ::"l"(p));
                poll_init(v[0]); poll_init(v[1]);
                if (g == GV) {
                    bar_sync(BAR_PUBV, 160);
                    mbar_wait_w(sb + MB_V, s & 1);
                    spin_cycles(DLY_V);
                } else {
                    bar_sync(BAR_PUB, 192);
                    spin_cycles(DLY_X);
                }
                const int r = poll2(v, p);
                sts128(dst, v[0]); sts128(dst + 512, v[1]);
                STAT(1, r > 1 && warp == 10);
                if (g != GV) bar_arrive(BAR_QK, 224);
                if (TS_AT == 6 && g == 0) TL(21);
                if (g == GV) { bar_arrive(BAR_V, 160); if (GV == 0) bar_arrive(BAR_SV, NSV); TL(17); }
                if (g == 1) {
                    TL(31);
                    asm volatile("cp.async.bulk.wait_group.read 0;" ::: "memory");
                    bar_sync(BAR_SV, NSV);
                    tok_mid(s);
                    TL(22);
                }
                if (g == 2 && s >= 1) {
                    TL(16);
                    const uint32_t prev = (slot - 0x4000) & 0xC000;
                    const char* y = make_ptr(l16 + (ybox + prev), mhi);
                    const char* x = make_ptr(l16 + (xoth + prev + kh * 1536), mhi);
#pragma unroll
                    for (int i = 0; i < 8; i++) st_sent(y + i * 512);
#pragma unroll
                    for (int i = 0; i < 3; i++) st_sent(x + i * 512);
                    st_relaxed_u32(make_ptr(lane * 4 + (zline + (slot ^ 0x8000)), mhi), SENT);
                    TL(23);
                }
            }
            if (s + 1 == NSEG) break;
            {
                const char* p = make_ptr(l16 + (ybox + g * 1024 + slot), mhi);
                char* zdst = make_ptr(lane * 4 + (zline + g * 32 + slot), mhi);
                const uint32_t dst = ydst + (sb + SM_Y + g * 1024), dst1 = (ydst ^ 64) + (sb + SM_Y + g * 1024 + 512), src = ysrc + (sb + SM_Y), src1 = (ysrc ^ 16) + (sb + SM_Y);
                asm volatile("" ::"l"(p), "l"(zdst));
                uint4 v[2];
                poll_init(v[0]); poll_init(v[1]);
                bar_sync(BAR_SENTC, 384);
                spin_cycles(DLY_Y);
                const int r = poll2(v, p);
                STAT(2, r > 1 && warp == 8);
                sts128(dst, v[0]); sts128(dst1, v[1]);
                bar_sync(BAR_Y, 256);
                TL(18);
                uint32_t b[2][4];
                ldsm4t(b[0], src); ldsm4t(b[1], src1);
                const uint32_t one = 0x3F803F80u;
                float d0[4] = {0.f, 0.f, 0.f, 0.f}, d1[4] = {0.f, 0.f, 0.f, 0.f};
                mma16816(d0, one, one, one, one, b[0][0], b[0][1]);
                mma16816(d1, one, one, one, one, b[1][0], b[1][1]);
                mma16816(d0, one, one, one, one, b[0][2], b[0][3]);
                mma16816(d1, one, one, one, one, b[1][2], b[1][3]);
                const uint32_t w = (lane & 4) ? pack_bf16(d1[0], d1[1]) : pack_bf16(d0[0], d0[1]);
                asm volatile("{.reg .pred p; setp.lt.u32 p, %2, 128; @p st.relaxed.gpu.global.u32 [%0], %1;}" ::"l"(zdst), "r"(w), "r"(l16) : "memory");
                if (s + 3 < NSEG) bar_arrive(BAR_ZP, 256);
                TL(19);
            }
            {
                const char* p = make_ptr(l16 + (zbox + g * 512 + slot), mhi);
                const uint32_t dst = l16 + (sb + SM_Z + g * 512);
                asm volatile("" ::"l"(p));
                uint4 v[4];
                poll_init(v[0]); poll_init(v[1]); poll_init(v[2]); poll_init(v[3]);
                bar_sync(BAR_COMM, 128);
                spin_cycles(DLY_Z);
                const int r = poll4<2048>(v, p);
                STAT(0, r > 1 && warp == 8);
#pragma unroll
                for (int i = 0; i < 4; i++) sts128(dst + i * 2048, v[i]);
                bar_arrive(BAR_MEM, 384);
                TL(20);
            }
        }
    } else if (warp < 4) {
        asm volatile("setmaxnreg.inc.sync.aligned.u32 %0;" ::"n"(REG_A));
        code_pad<PAD_A>();
        const uint32_t l16 = lane16();
        uint32_t wa[2][24][4];
        {
            const uint32_t L = l16, fa = sb + FRAG();
            mbar_wait_w(sb + MB_W1, 0);
            KT_MARK(7);
#pragma unroll
            for (int t = 0; t < 2; t++) {
#pragma unroll
                for (int r = 0; r < 24; r++) ldsm4t(wa[t][r], fa + stg_qk(t, r));
                if (t == 0) { bar_arrive(BAR_XT0, 160); mbar_wait_w(sb + MB_W4, 0); }
            }
            mbar_wait_w(sb + MB_W2, 0);
            bar_sync(BAR_PDONE, 384);
        }
        auto batch1 = [&](float (&d)[16], uint32_t lo, auto tc, auto k0c, auto k1c) {
            constexpr int t = decltype(tc)::value;
            const uint64_t da = make_desc(SB0 + SM_WQK, 16, 1024);
            wg_fence();
            static_for<decltype(k0c)::value, decltype(k1c)::value>([&](auto kc) {
                constexpr int i = decltype(kc)::value, k = kstep(t ? ORD1 : ORD0, i), off = (k >> 2) * 256 + (k & 3) * 2;
                if constexpr (k >= 24) wgmma_ss32u<off, i != 0 || t != 0>(d, da + ((k - 24) * 2 + t) * 128, lo);
                else wgmma_rs32u<off, i != 0 || t != 0>(d, wa[t][k], lo);
            });
            wg_commit();
        };
        const uint32_t xbox = mlo + WIN + page_off(pair & 31, cls ^ XFLIP);
        const uint32_t ybox = mlo + page_off(24 + 2 * g + 32 * nh, kh ^ YFLIP_()) + h * 128;
#pragma unroll 1
        for (uint32_t it = 0; it < NSEG + 3; it++) {
            const int s = (int)it - 3;
            const uint32_t ui = uniform(it), slot = ((ui + 1) & 3) << 14, kvo = (~ui & 1) * KV_BYTES, xtlo = XTLO();
            {
                PHASE(5);
                const uint32_t first = L | (g << 9);
                if (s >= 0) mbar_expect_tx_if0(first, sb + MB_R1, 2048);
                if (s + 3 < NSEG) {
                    mbar_expect_tx_if0(first, sb + MB_RT0, 8192);
                    mbar_wait_w(sb + MB_XT + (ui & 1) * 8, (it >> 1) & 1);
                }
            }
            if (s >= 0) {
                PHASE(0);
                const uint32_t mb = L + (sb + SM_Z), ra = L + (sb + g * 512), r1 = L + (rsb + SM_R1 + g * 512), r1b = rsb + MB_R1;
                sched_fence(r1);
                bar_sync(BAR_MEM, 384);
                TLB(0);
                float acc[2][2][4];
#pragma unroll
                for (int t = 0; t < 4; t++) { acc[t >> 1][t & 1][0] = acc[t >> 1][t & 1][1] = acc[t >> 1][t & 1][2] = acc[t >> 1][t & 1][3] = 0.f; }
                uint32_t b[4][4];
                uint4 u0, u1;
#pragma unroll
                for (int p = 0; p < 4; p++) ldsm4t(b[p], mb + p * 512);
#pragma unroll
                for (int p = 0; p < 12; p++) {
#pragma unroll
                    for (int u = 0; u < 2; u++) {
                        mma16816v(acc[0][u], wa[0][2 * p + u], b[p & 3][2 * u], b[p & 3][2 * u + 1]);
                        mma16816v(acc[1][u], wa[1][2 * p + u], b[p & 3][2 * u], b[p & 3][2 * u + 1]);
                    }
                    if (p + 4 < 12) ldsm4t(b[p & 3], mb + (p + 4) * 512);
                    if (p == Q3_AT) {
                        bar_sync(BAR_Q3, 256);
                        u0 = lds128(ra + SM_R3); u1 = lds128(ra + SM_O);
                    }
                }
                st_async4(r1, (acc[0][0][0] + __uint_as_float(u0.x)) + acc[0][1][0], (acc[0][0][1] + __uint_as_float(u0.y)) + acc[0][1][1],
                          (acc[0][0][2] + __uint_as_float(u0.z)) + acc[0][1][2], (acc[0][0][3] + __uint_as_float(u0.w)) + acc[0][1][3], r1b);
                TL(1);
                const float o0 = (acc[1][0][0] + __uint_as_float(u1.x)) + acc[1][1][0], o1 = (acc[1][0][1] + __uint_as_float(u1.y)) + acc[1][1][1];
                const float o2 = (acc[1][0][2] + __uint_as_float(u1.z)) + acc[1][1][2], o3 = (acc[1][0][3] + __uint_as_float(u1.w)) + acc[1][1][3];
                const uint32_t l4 = L >> 2, qo = SM_QKV + kh * 2048 + nh * 1024 + g * 256, qr = l4 + (rsb + qo), ql = l4 + (sb + qo), pb = rsb + MB_P;
                char* xd = make_ptr(l4 + (xbox + kh * 1024 + g * 256 + slot), mhi);
                asm volatile("" ::"l"(xd), "r"(qr), "r"(pb), "r"(qr + 128), "f"(o0), "f"(o1), "f"(o2), "f"(o3));
                mbar_wait_w(sb + MB_R1, s & 1);
                const uint4 v = lds128(ra + SM_R1);
                const uint32_t w0 = pack_bf16(o0 + __uint_as_float(v.x), o1 + __uint_as_float(v.y)), w1 = pack_bf16(o2 + __uint_as_float(v.z), o3 + __uint_as_float(v.w));
                st_relaxed_u32(xd, w0);
                st_relaxed_u32(xd + 128, w1);
                bar_arrive(BAR_PUB, 192);
                st_async1(qr, w0, pb);
                st_async1(qr + 128, w1, pb);
                sts32(ql, w0);
                sts32(ql + 128, w1);
                __syncwarp();
                mbar_expect_tx_if0(L, sb + MB_P, 256);
                TL(2);
                if (s + 3 < NSEG) bar_sync(BAR_VP, 256);
            } else {
                bar_sync(BAR_PRO, 288);
            }
            if (s + 3 < NSEG) {
                float d[16];
                batch1(d, xtlo, std::integral_constant<int, 0>(), std::integral_constant<int, 0>(), std::integral_constant<int, 32>());
                PHASE(1);
                const uint32_t rt = L + (rsb + SM_RT + g * 2048);
                wg_wait<0>();
                TL(7);
                if (s >= 0) {
                    const uint32_t pk = L + (sb + SM_Z + g * 2048);
#pragma unroll
                    for (int i = 0; i < 4; i++) sts128(pk + i * 512, make_uint4(__float_as_uint(d[4 * i]), __float_as_uint(d[4 * i + 1]), __float_as_uint(d[4 * i + 2]), __float_as_uint(d[4 * i + 3])));
                } else {
#pragma unroll
                    for (int i = 0; i < 4; i++) st_async4(rt + i * 512, d[4 * i], d[4 * i + 1], d[4 * i + 2], d[4 * i + 3], rsb + MB_RT0);
                }
            }
            if (s + 1 == NSEG) { bar_arrive(BAR_SV, NSV); break; }
            if (s >= 0) {
                PHASE(2);
                const uint32_t fo = FRAG() + (sb + SM_WO2 + 16384), lo = L + (sb + SM_O), yo = (L >> 2) + (ybox + slot);
                uint32_t a1[8][4];
                bar_sync(BAR_SV, NSV);
#pragma unroll
                for (int k = 0; k < 8; k++) ldsm4t(a1[k], fo + k * 2048);
                sched_fence(yo);
                bar_sync(BAR_O2, 256);
                TLB(14);
                float y0[4] = {0.f, 0.f, 0.f, 0.f}, y1[4] = {0.f, 0.f, 0.f, 0.f};
                uint32_t b[2][4];
                ldsm4t(b[0], lo); ldsm4t(b[1], lo + 512);
                sched_fence(L);
#pragma unroll
                for (int p = 0; p < 4; p++) {
                    mma16816v(y0, a1[2 * p], b[p & 1][0], b[p & 1][1]);
                    mma16816v(y1, a1[2 * p + 1], b[p & 1][2], b[p & 1][3]);
                    if (p < 2) ldsm4t(b[p & 1], lo + (p + 2) * 512);
                }
                bar_sync(BAR_INV, 256);
                float i0, i1;
                asm volatile("ld.shared.v2.f32 {%0, %1}, [%2];" : "=f"(i0), "=f"(i1) : "r"(((L >> 1) & 0x18) + (sb + SM_INV + g * 32)) : "memory");
                st_relaxed_u32(make_ptr(yo, mhi), pack_bf16((y0[0] + y1[0]) * i0, (y0[1] + y1[1]) * i1));
                st_relaxed_u32(make_ptr(yo ^ 4096, mhi) + 0x2000, pack_bf16((y0[2] + y1[2]) * i0, (y0[3] + y1[3]) * i1));
                bar_arrive(BAR_SENTC, 384);
                TL(6);
            }
            if (s + 3 < NSEG) {
                PHASE(4);
                float d[16];
                const uint32_t rt = L + (sb + SM_RT + g * 2048);
                if (s >= 0) bar_sync(BAR_SENT, 256);
                mbar_wait_w(sb + MB_RT0, it & 1);
                if (s >= 0) bar_arrive(BAR_Y, 256);
#pragma unroll
                for (int i = 0; i < 4; i++) {
                    const uint4 v = lds128(rt + i * 512);
                    d[4 * i] = __uint_as_float(v.x); d[4 * i + 1] = __uint_as_float(v.y); d[4 * i + 2] = __uint_as_float(v.z); d[4 * i + 3] = __uint_as_float(v.w);
                }
                if (SPLIT > 0) batch1(d, xtlo, std::integral_constant<int, 1>(), std::integral_constant<int, 0>(), std::integral_constant<int, SPLIT>());
                if (s >= 0) bar_sync(BAR_ZP, 256);
                TLB(30);
                batch1(d, xtlo, std::integral_constant<int, 1>(), std::integral_constant<int, SPLIT>(), std::integral_constant<int, 32>());
                const uint32_t so = (kh ? FRAG() : ((L & 0x100) << 2) + (L & 0xF0) + g * 256) + (sb + SM_STG);
                wg_wait<0>();
                TL(8);
                uint32_t w[8];
#pragma unroll
                for (int i = 0; i < 8; i++) w[i] = pack_bf16(d[2 * i], d[2 * i + 1]);
                if (kh) {
                    stsm4t(so, w[0], w[1], w[2], w[3]);
                    stsm4t(so + 2048, w[4], w[5], w[6], w[7]);
                } else {
                    stsm4(so, w[0], w[1], w[2], w[3]);
                    stsm4(so + 2048, w[4], w[5], w[6], w[7]);
                }
                __syncwarp();
                mbar_arrive_if0(L, sb + MB_STG);
                TL(9);
            } else {
                bar_arrive(BAR_SENT, 256);
                bar_arrive(BAR_Y, 256);
            }
        }
    } else {
        asm volatile("setmaxnreg.inc.sync.aligned.u32 %0;" ::"n"(REG_B));
        code_pad<PAD_B>();
        const uint32_t l16 = lane16();
        uint32_t wv[24][4], wo[8 + WO_RF1][4];
        {
            const uint32_t L = l16, fa = sb + FRAG();
            mbar_wait_w(sb + MB_W0, 0);
            KT_MARK(6);
#pragma unroll
            for (int r = 0; r < 24; r++) ldsm4t(wv[r], fa + STG_V + r * 2048);
#pragma unroll
            for (int r = 0; r < 8 + WO_RF1; r++) asm volatile("" : "=r"(wo[r][0]), "=r"(wo[r][1]), "=r"(wo[r][2]), "=r"(wo[r][3]));
            mbar_wait_w(sb + MB_W2, 0);
            bar_sync(BAR_PDONE, 384);
        }
        const uint32_t xbox = mlo + WIN + page_off(pair & 31, cls ^ XFLIP);
        const uint32_t ybox = mlo + page_off(2 * g + 32 * nh, kh ^ YFLIP_()) + h * 128;
#pragma unroll 1
        for (uint32_t it = 0; it < NSEG + 3; it++) {
            const int s = (int)it - 3;
            const uint32_t ui = uniform(it), slot = ((ui + 1) & 3) << 14, kvo = (~ui & 1) * KV_BYTES, xtlo = XTLO();
            {
                PHASE(5);
                const uint32_t first = L | (g << 9);
                if (s >= 0) mbar_expect_tx_if0(first, sb + MB_R2, 1024);
                if (s + 3 < NSEG) {
                    mbar_expect_tx_if0(first, sb + MB_RT1, 2048);
                    mbar_wait_w(sb + MB_XT + (ui & 1) * 8, (it >> 1) & 1);
                }
            }
            if (s >= 0) {
                PHASE(0);
                const uint32_t fo = FRAG() + sb, l4 = L >> 2;
                {
                    const uint32_t mb = L + (sb + SM_Z), aw = fo + SM_WQK, ra = L + (sb + g * 512), r2 = (L >> 1) + (rsb + SM_R2 + g * 256), r2b = rsb + MB_R2;
                    uint32_t a[NA][4], b[4][4];
#pragma unroll
                    for (int i = 0; i < NA; i++) ldsm4t(a[i], aw + i * 2048);
                    sched_fence(L);
                    TL(24);
                    bar_sync(BAR_MEM, 384);
#pragma unroll
                    for (int p = 0; p < 4; p++) ldsm4t(b[p], mb + (12 + p) * 512);
                    sched_fence(L);
                    float c[2][4] = {{0.f, 0.f, 0.f, 0.f}, {0.f, 0.f, 0.f, 0.f}};
#pragma unroll
                    for (int i = 0; i < 16; i++) {
                        mma16816v(c[i & 1], a[i % NA], b[i >> 2][i & 2], b[i >> 2][(i & 2) + 1]);
                        ldsm4t(a[i % NA], aw + (i + NA) * 2048);
                    }
                    sts128(ra + SM_R3, make_uint4(__float_as_uint(c[0][0]), __float_as_uint(c[0][1]), __float_as_uint(c[0][2]), __float_as_uint(c[0][3])));
                    sts128(ra + SM_O, make_uint4(__float_as_uint(c[1][0]), __float_as_uint(c[1][1]), __float_as_uint(c[1][2]), __float_as_uint(c[1][3])));
                    bar_arrive(BAR_Q3, 256);
                    TL(29);
                    float acc[4][4];
#pragma unroll
                    for (int t = 0; t < 4; t++) { acc[t][0] = acc[t][1] = acc[t][2] = acc[t][3] = 0.f; }
#pragma unroll
                    for (int i = 16; i < 24; i++) {
                        mma16816v(acc[i & 1], a[i % NA], b[(i - 16) >> 1][2 * (i & 1)], b[(i - 16) >> 1][2 * (i & 1) + 1]);
                        if (i + NA < 24) ldsm4t(a[i % NA], aw + (i + NA) * 2048);
                        else ldsm4t(a[i % NA], mb + (i + NA - 24) * 512);
                    }
#pragma unroll
                    for (int p = 0; p < 12; p++) {
                        mma16816v(acc[(2 * p) & 3], wv[2 * p], a[(24 + p) % NA][0], a[(24 + p) % NA][1]);
                        mma16816v(acc[(2 * p + 1) & 3], wv[2 * p + 1], a[(24 + p) % NA][2], a[(24 + p) % NA][3]);
                        if (p + NA < 12) ldsm4t(a[(24 + p) % NA], mb + (p + NA) * 512);
                    }
                    if (s + 3 < NSEG) bar_arrive(BAR_VP, 256);
                    float o[4];
#pragma unroll
                    for (int i = 0; i < 4; i++) o[i] = (acc[0][i] + acc[1][i]) + (acc[2][i] + acc[3][i]);
                    st_async2(r2, kh ? o[0] : o[2], kh ? o[1] : o[3], r2b);
                    TL(10);
                    const float o0 = kh ? o[2] : o[0], o1 = kh ? o[3] : o[1];
                    const uint32_t qo = SM_QKV + 4096 + nh * 1024 + (2 * g + kh) * 128, qr = l4 + (rsb + qo), ql = l4 + (sb + qo), vb = rsb + MB_V, rl = (L >> 1) + (sb + SM_R2 + g * 256);
                    char* xd = make_ptr(l4 + (xbox + 2048 + (2 * g + kh) * 128 + slot), mhi);
                    asm volatile("" ::"l"(xd), "r"(qr), "r"(vb), "f"(o0), "f"(o1));
                    mbar_wait_w(sb + MB_R2, s & 1);
                    uint32_t vx, vy;
                    asm volatile("ld.shared.v2.u32 {%0,%1}, [%2];" : "=r"(vx), "=r"(vy) : "r"(rl) : "memory");
                    const uint32_t w0 = pack_bf16(o0 + __uint_as_float(vx), o1 + __uint_as_float(vy));
                    st_relaxed_u32(xd, w0);
                    bar_arrive(BAR_PUBV, 160);
                    st_async1(qr, w0, vb);
                    sts32(ql, w0);
                    __syncwarp();
                    mbar_expect_tx_if0(L, sb + MB_V, 128);
                    TL(11);
                }
                const uint32_t vma = L + (sb + SM_QKV + 4096 + g * 512), yo = l4 + (ybox + slot);
                uint32_t va[2][2][4];
                {
                    const uint32_t qa = QFRAG(), vf = VFRAG(), va0 = vf + VBASE(), va1 = (vf ^ 32) + VBASE();
                    const uint32_t kf = ((L << 3) & 0x380) | ((L ^ (L >> 3)) & 0x30) | (L & 0x40), kb0 = sb + SM_KV + kvo + g * 1024;
                    const int d = (int)(L >> 6) - (int)((L >> 3) & 6) + 8 * (j - (int)g);
                    const uint32_t keep = (d < 0 ? 0u : 0xFFFFu) | (d < 1 ? 0u : 0xFFFF0000u), sa = l4 + (sb + SM_S + g * 128);
                    const uint32_t q0 = qa + (sb + nh * 1024), q1 = qa + (sb + (nh ^ 1) * 1024);
                    float sc[4] = {0.f, 0.f, 0.f, 0.f}, sd[4] = {0.f, 0.f, 0.f, 0.f};
                    uint32_t a[4][4], kb[2][4];
                    mbar_wait_w(sb + MB_KV + (~ui & 1) * 8, (s >> 1) & 1);
                    ldsm4(kb[0], kf + (kb0 + nh * 4096)); ldsm4(kb[1], (kf ^ 64) + (kb0 + nh * 4096));
                    mbar_wait_w(sb + MB_P, s & 1);
                    TL(12);
#pragma unroll
                    for (int k = 0; k < 4; k++) ldsm4t(a[k], q0 + k * 256);
#pragma unroll
                    for (int k = 0; k < 4; k++) mma16816v((k & 1) ? sd : sc, a[k], kb[k >> 1][2 * (k & 1)], kb[k >> 1][2 * (k & 1) + 1]);
                    ldsm4(kb[0], kf + (kb0 + (nh ^ 1) * 4096)); ldsm4(kb[1], (kf ^ 64) + (kb0 + (nh ^ 1) * 4096));
                    sched_fence(vf | yo);
                    if (TS_AT == 8) TL(21);
                    bar_sync(BAR_QK, 224);
                    TLB(3);
#pragma unroll
                    for (int k = 0; k < 4; k++) ldsm4t(a[k], q1 + k * 256);
                    sched_fence(L);
#pragma unroll
                    for (int k = 0; k < 4; k++) mma16816v((k & 1) ? sd : sc, a[k], kb[k >> 1][2 * (k & 1)], kb[k >> 1][2 * (k & 1) + 1]);
                    ldsm4t(va[0][0], va0); ldsm4t(va[0][1], va0 + 2048);
                    sts32(sa, scale_scores(sc[0] + sd[0], sc[1] + sd[1]));
                    sts32(sa + 768, (scale_scores(sc[2] + sd[2], sc[3] + sd[3]) & keep) | (0xFF80FF80u & ~keep));
                    bar_arrive(BAR_SV, NSV);
                    ldsm4t(va[1][0], va1); ldsm4t(va[1][1], va1 + 2048);
                }
                bar_sync(BAR_S, 160);
                TLB(4);
                uint32_t pw[6], vm[4];
                if (s + 1 < NSEG) {
                softmax40(pw, l4 + (sb + SM_S), [&]() {
                    bar_sync(BAR_V, 160);
                    ldsm4(vm, vma);
                });
                uint32_t a1[NP2][4];
                float inv[2];
                {
                    uint32_t w[4];
                    pv32<false>(w, inv, va, vm, pw, [&]() {
                        sched_fence(L);
#pragma unroll
                        for (int k = 0; k < NP2; k++) ldsm4t(a1[k], fo + SM_WO2 + k * 2048);
                    });
#pragma unroll
                    for (int i = 0; i < 4; i++) sts32(l4 + (sb + SM_O + g * 512) + i * 128, w[i]);
                }
                const uint32_t lo = L + (sb + SM_O);
                bar_arrive(BAR_O2, 256);
                bar_sync(BAR_O, 128);
                TLB(5);
                {
                    float y0[4] = {0.f, 0.f, 0.f, 0.f}, y1[4] = {0.f, 0.f, 0.f, 0.f}, y2[4] = {0.f, 0.f, 0.f, 0.f};
                    uint32_t b[4][4];
#pragma unroll
                    for (int p = 0; p < 4; p++) ldsm4t(b[p], lo + p * 512);
                    inv[0] = rcp_approx(inv[0]); inv[1] = rcp_approx(inv[1]);
                    asm volatile("st.shared.v2.f32 [%0], {%1, %2};" ::"r"(((L >> 1) & 0x18) + (sb + SM_INV + g * 32)), "f"(inv[0]), "f"(inv[1]) : "memory");
                    bar_arrive(BAR_INV, 256);
                    sched_fence(L);
#pragma unroll
                    for (int k = 0; k < 8; k++) {
                        const int p = k >> 1, u = k & 1;
                        mma16816v(y2, a1[k % NP2], b[p][2 * u], b[p][2 * u + 1]);
                        if (k + NP2 < 8) ldsm4t(a1[k % NP2], fo + SM_WO2 + (k + NP2) * 2048);
                        else if (k + NP2 < 16 - WO_RF1) ldsm4t(a1[k % NP2], fo + SM_WO1 + (k + NP2 - 8 + WO_RF1) * 2048);
                        mma16816v(y0, wo[k], b[p][2 * u], b[p][2 * u + 1]);
                        if (k < WO_RF1) mma16816v(y1, wo[8 + (k < WO_RF1 ? k : 0)], b[p][2 * u], b[p][2 * u + 1]);
                        else mma16816v(y1, a1[(k + 8 - WO_RF1) % NP2], b[p][2 * u], b[p][2 * u + 1]);
                        if (k < P2_FENCE) sched_fence(L);
                    }
                    char* yd = make_ptr(yo, mhi);
                    char* yd1 = make_ptr(yo ^ 4096, mhi);
                    st_relaxed_u32(yd1 + 0x80000, pack_bf16(y2[0] * inv[0], y2[1] * inv[1]));
                    st_relaxed_u32(yd + 0x82000, pack_bf16(y2[2] * inv[0], y2[3] * inv[1]));
                    st_relaxed_u32(yd, pack_bf16(y0[0] * inv[0], y0[1] * inv[1]));
                    st_relaxed_u32(yd1 + 0x2000, pack_bf16(y0[2] * inv[0], y0[3] * inv[1]));
                    st_relaxed_u32(yd + 0x40000, pack_bf16(y1[0] * inv[0], y1[1] * inv[1]));
                    st_relaxed_u32(yd1 + 0x42000, pack_bf16(y1[2] * inv[0], y1[3] * inv[1]));
                }
                bar_arrive(BAR_SENTC, 384);
                TL(13);
                bar_sync(BAR_SENT, 256);
                } else {
                    bar_sync(BAR_V, 160);
                }
            } else {
                if (it == WO_IT) {
                    PHASE(2);
                    const uint32_t fa = sb + FRAG();
                    mbar_wait_w(sb + MB_W3, 0);
                    KT_MARK(8);
#pragma unroll
                    for (int r = 0; r < 8 + WO_RF1; r++) ldsm4t(wo[r], fa + stg_wo(r));
                }
                bar_sync(BAR_PRO, 288);
            }
            float o[8];
            {
                PHASE(1);
                float d[16];
                const uint64_t da = make_desc(SB0 + SM_WV, 16, 1024);
                auto batch = [&](auto k0c, auto k1c) {
                    static_for<decltype(k0c)::value, decltype(k1c)::value>([&](auto kc) {
                        constexpr int i = decltype(kc)::value, k = kstep(ORDV, i), off = (k >> 2) * 256 + (k & 3) * 2;
                        if constexpr (k >= 24) wgmma_ss32u<off, i != 0>(d, da + (k - 24) * 128, xtlo);
                        else wgmma_rs32u<off, i != 0>(d, wv[k], xtlo);
                    });
                };
                const uint32_t vf = VFRAG(), va0 = vf + VBASE(), va1 = (vf ^ 32) + VBASE(), vma = L + (sb + SM_QKV + 4096 + g * 512), sa = (L >> 2) + (sb + SM_S + 768);
                const uint32_t rt = L + (rsb + SM_RT + 8192 + g * 512);
                uint32_t va[2][2][4], vm[4], pw[6], w[4];
                wg_fence();
                batch(std::integral_constant<int, 0>(), std::integral_constant<int, TA0>());
                wg_commit();
                batch(std::integral_constant<int, TA0>(), std::integral_constant<int, 32>());
                wg_commit();
                wg_wait<1>();
                softmax40(pw, sa, [&]() {});
                ldsm4t(va[0][0], va0); ldsm4t(va[0][1], va0 + 2048);
                ldsm4t(va[1][0], va1); ldsm4t(va[1][1], va1 + 2048);
                ldsm4(vm, vma);
                wg_wait<0>();
                TL(27);
                float inv[2];
                pv32<true>(w, inv, va, vm, pw, [&]() {
                    uint32_t q[4];
#pragma unroll
                    for (int i = 0; i < 4; i++) q[i] = pack_bf16(kh ? d[2 * i] : d[8 + 2 * i], kh ? d[2 * i + 1] : d[9 + 2 * i]);
                    if (s + 3 < NSEG) st_async4(rt, __uint_as_float(q[0]), __uint_as_float(q[1]), __uint_as_float(q[2]), __uint_as_float(q[3]), rsb + MB_RT1);
#pragma unroll
                    for (int i = 0; i < 8; i++) o[i] = kh ? d[8 + i] : d[i];
                });
                stsm4t((L & 0x70) * 5 + ((L >> 3) & 0x30) + (sb + SM_TO + g * 640), w[0], w[1], w[2], w[3]);
                __syncwarp();
                const uint4 r = lds128(((L >> 2) & 0x70) * 5 + (L & 0x30) + (sb + SM_TO + g * 640));
                if (s >= 0) stg128(reinterpret_cast<char*>(g_ox) + (((L & 0x1C0) << 7) + (L & 0x30) + (((ui - 3) * SEG + 8 * j) * HD + h * DH + 32 * g) * 2), r);
                TL(26);
            }
            if (s + 3 < NSEG) {
                PHASE(3);
                const uint32_t rt = L + (sb + SM_RT + 8192 + g * 512), so = FRAG() + (sb + SM_STG + 4096);
                mbar_wait_w(sb + MB_RT1, it & 1);
                TL(28);
                uint32_t w[4];
                const uint4 v = lds128(rt);
                w[0] = pack_bf16(o[0] + bf_lo(v.x), o[1] + bf_hi(v.x)); w[1] = pack_bf16(o[2] + bf_lo(v.y), o[3] + bf_hi(v.y));
                w[2] = pack_bf16(o[4] + bf_lo(v.z), o[5] + bf_hi(v.z)); w[3] = pack_bf16(o[6] + bf_lo(v.w), o[7] + bf_hi(v.w));
                stsm4t(so, w[0], w[1], w[2], w[3]);
                __syncwarp();
                mbar_arrive_if0(L, sb + MB_STG);
                TL(15);
            }
        }
    }
    KT_END(2);
    asm volatile("barrier.cluster.arrive.relaxed; barrier.cluster.wait;" ::: "memory");
}
constexpr int B_UCH = 73 * 64;
constexpr int B_SCH = 33 * 64;
constexpr int B_KLEN = 2128;
constexpr int B_KCH = 2 * B_KLEN * 2 + 64;
constexpr int B_KBOX = 136 * 32;
constexpr int B_SM_U = 0;
constexpr int B_SM_S = 8 * B_UCH;
constexpr int B_SM_K = B_SM_S + 8 * B_SCH;
constexpr int B_SM_KT = B_SM_K + 8 * B_KCH;
constexpr int B_SM_VT = B_SM_KT + 8 * B_KBOX;
constexpr int B_SM_QT = B_SM_VT + 32768;
constexpr int B_SM_BAR = B_SM_QT + 32768;
constexpr int B_SMEM = B_SM_BAR + 128 + 512;
static_assert(B_SM_KT % 256 == 0 && B_SM_S % 512 == 0 && B_SMEM <= 232448, "tiles");
constexpr int PROBE_N = 4;
#define PROBE_R 2
constexpr int B_C = 2056;

__device__ __forceinline__ uint32_t atomic_round_trip(char* p) {
    uint32_t t0, t1, v;
    asm volatile("{.reg .pred p;\n"
                 "mov.u32 %0, %%clock;\n"
                 "atom.relaxed.gpu.global.add.u32 %2, [%3], 1;\n"
                 "setp.ne.u32 p, %2, 0x7FFFFFFF;\n"
                 "mov.u32 %1, 0;\n"
                 "@p mov.u32 %1, %%clock;}" : "=&r"(t0), "=&r"(t1), "=&r"(v) : "l"(p) : "memory");
    return t1 - t0;
}
__device__ __forceinline__ uint32_t round_trips(char* a, char* b, uint32_t stride, int lane) {
    for (int i = lane >> 3; i < 2 * PROBE_N; i += 4) stg128(((i & 1) ? b : a) + (i >> 1) * stride + (lane & 7) * 16, make_uint4(0, 0, 0, 0));
    __syncwarp();
    uint32_t ta = 0xFFFF, tb = 0xFFFF;
    if (lane == 0) {
        __threadfence();
#pragma unroll 1
        for (int i = 0; i < PROBE_N; i++) { ta = min(ta, atomic_round_trip(a + i * stride)); tb = min(tb, atomic_round_trip(b + i * stride)); }
    }
    __syncwarp();
    return ta | (tb << 16);
}
__device__ __forceinline__ void measure_distance(char* mbox, int lane) {
    const uint32_t b = blockIdx.x;
    unsigned smid;
    asm volatile("mov.u32 %0, %%smid;" : "=r"(smid));
    char* w1 = mbox + WIN + (b & 31) * 128;
    uint32_t r = 0xFFFFFFFF;
#pragma unroll 1
    for (int i = 0; i < PROBE_R; i++) r = __vminu2(r, round_trips(w1 + page_off(50 + 5 * i + (b >> 5), 0), w1 + page_off(50 + 5 * i + (b >> 5), 1), 16384, lane));
    if (lane == 0) g_cls[smid] = r;
    if (b == 128) {
        char *p = mbox + page_off(0, 0), *q = mbox + page_off(0, 1);
        uint32_t r0 = 0xFFFFFFFF;
#pragma unroll 1
        for (int i = 0; i < PROBE_R; i++) r0 = __vminu2(r0, round_trips(p, q, 128, lane));
        if (lane == 0) { g_reg[1] = ((r0 & 0xFFFF) > (r0 >> 16)) != ((r & 0xFFFF) > (r >> 16)); if (!EARLY_ROLE) g_reg[0] = 0; g_reg[2] = 0; }
        const uint4 sent = make_uint4(SENT, SENT, SENT, SENT);
        stg128(p + lane * 16, sent); stg128(q + lane * 16, sent);
    }
    if (b == 129) for (int i = lane; i < 128; i += 32) g_xflag[i] = 0;
}

#define SP(i)
#define SP2(i)
#define OUT_STG 0
#define PF_STOP 1
#define SENT_AT 3
#define Q_LATE 1
#define PF_DEPTH 4
#define PF_STRIDE 256
struct ChainInputs { const char* w[4]; const char *x, *mem0; };
#define EF_MASK 15
#define EF(i) (((EF_MASK >> (i)) & 1) ? policy_evict_first() : policy_evict_normal())
__device__ __forceinline__ void l2_prefetch(const char* p, uint32_t bytes) {
    asm volatile("cp.async.bulk.prefetch.L2.global [%0], %1;" ::"l"(p), "r"(bytes) : "memory");
}
#define WG_CONV(N, LIST, A0, A1, A2, A3, LO, OF, ...) \
    if constexpr (NN == N) asm volatile("{.reg .b32 l; .reg .b64 e; add.u32 l, %" #LO ", %" #OF "; mov.b64 e, {l, 0x80000020};\n" \
        "wgmma.mma_async.sync.aligned.m64n" #N "k16.f32.bf16.bf16 {" LIST "}, {%" #A0 ",%" #A1 ",%" #A2 ",%" #A3 "}, e, 1, 1, 1, 0;}" \
        : __VA_ARGS__ : "r"(a[0]), "r"(a[1]), "r"(a[2]), "r"(a[3]), "r"(lo), "n"(OFF));
#define WL4 "%0,%1,%2,%3"
#define WL8 WL4 ",%4,%5,%6,%7"
#define WL12 WL8 ",%8,%9,%10,%11"
#define WL16 WL12 ",%12,%13,%14,%15"
#define WL20 WL16 ",%16,%17,%18,%19"
#define WL24 WL20 ",%20,%21,%22,%23"
#define WL28 WL24 ",%24,%25,%26,%27"
#define WL32 WL28 ",%28,%29,%30,%31"
template <int NN, int OFF> __device__ __forceinline__ void wgmma_conv(float (&d)[32], const uint32_t (&a)[4], uint32_t lo) {
    WG_CONV(8, WL4, 4, 5, 6, 7, 8, 9, R4(0))
    WG_CONV(16, WL8, 8, 9, 10, 11, 12, 13, R4(0), R4(4))
    WG_CONV(24, WL12, 12, 13, 14, 15, 16, 17, R4(0), R4(4), R4(8))
    WG_CONV(32, WL16, 16, 17, 18, 19, 20, 21, R16(0))
    WG_CONV(40, WL20, 20, 21, 22, 23, 24, 25, R16(0), R4(16))
    WG_CONV(48, WL24, 24, 25, 26, 27, 28, 29, R16(0), R4(16), R4(20))
    WG_CONV(56, WL28, 28, 29, 30, 31, 32, 33, R16(0), R4(16), R4(20), R4(24))
    WG_CONV(64, WL32, 32, 33, 34, 35, 36, 37, R16(0), R16(16))
}
__device__ __forceinline__ void copy_to_peer(uint32_t dst, uint32_t src, uint32_t bytes, uint32_t bar) {
    asm volatile("cp.async.bulk.shared::cluster.shared::cta.mbarrier::complete_tx::bytes [%0], [%1], %2, [%3];" ::"r"(dst), "r"(src), "r"(bytes), "r"(bar) : "memory");
}
__device__ __forceinline__ uint32_t lds_volatile(uint32_t a) {
    uint32_t v;
    asm volatile("ld.volatile.shared.u32 %0, [%1];" : "=r"(v) : "r"(a) : "memory");
    return v;
}
__device__ __forceinline__ uint32_t swz64(uint32_t a) { return a ^ ((a >> 3) & 0x30); }
__device__ __forceinline__ void fence_async() { asm volatile("fence.proxy.async.shared::cta;" ::: "memory"); }

__global__ void __cluster_dims__(2, 1, 1) __launch_bounds__(576, 1)
ssm_kernel(const __grid_constant__ CUtensorMap mapK, const __grid_constant__ CUtensorMap mapV, const __grid_constant__ CUtensorMap mapQ,
           const __grid_constant__ CUtensorMap mapO, const bf16* __restrict__ shiftk, const bf16* __restrict__ ssmk, const bf16* __restrict__ Dv,
           char* __restrict__ mbox, const __grid_constant__ ChainInputs ci, bf16* __restrict__ outp) {
    extern __shared__ __align__(128) uint8_t smem_raw[];
    const uint32_t sb = (smem_u32(smem_raw) + 511) & ~511u;
    const int rank = blockIdx.x & 1, ch0 = blockIdx.x * 8, c16 = ch0 & ~15, t0 = rank * 1024;
    const int t = threadIdx.x, warp = t >> 5, lane = t & 31;
    const uint32_t bar = sb + B_SM_BAR, barQ = bar + 64, barU = bar + 72, barY = bar + 80, flag = bar + 88;
    SP(0);
    if (lane == 0 && warp < 16 && blockIdx.x < 128) {
        const int i = warp >> 1;
        if (warp & 1) {
            if (i < 3) { mbar_init(barQ + i * 8, 1); mbar_expect_tx(barQ + i * 8, i ? 16384 : 32768); }
            if (i == 3) sts32(flag, 0);
        } else {
            mbar_init(bar + i * 8, 1);
            asm volatile("fence.mbarrier_init.release.cluster;" ::: "memory");
            mbar_expect_tx(bar + i * 8, B_KBOX + 4096);
            tma_load_2d(sb + B_SM_KT + i * B_KBOX, &mapK, c16, t0 + i * 128 - 8, bar + i * 8, EF(0));
            tma_load_2d(sb + B_SM_VT + i * 4096, &mapV, c16, t0 + i * 128, bar + i * 8, EF(0));
        }
        asm volatile("fence.mbarrier_init.release.cluster;" ::: "memory");
    }
    __syncwarp();
    if (warp == 14) SP2(14);
    KT_START(1);
    if (warp == 17) {
        launch_dependents();
        asm volatile("barrier.cluster.arrive.relaxed.aligned;" ::: "memory");
        measure_distance(mbox, lane);
        asm volatile("barrier.cluster.wait.aligned;" ::: "memory");
        KT_MARK(14);
        return;
    }
    if (blockIdx.x >= 128) return;
    if (warp == 16) {
        asm volatile("barrier.cluster.arrive.relaxed.aligned; barrier.cluster.wait.aligned;" ::: "memory");
        SP2(8);
        if (Q_LATE) for (int i = 0; i < 8; i++) { mbar_wait_w(bar + i * 8, 0); SP2(i); }
        if (lane < 8) tma_load_2d(sb + B_SM_QT + lane * 4096, &mapQ, c16, t0 + lane * 128, barQ, EF(3));
        if (!Q_LATE) for (int i = 0; i < 8; i++) mbar_wait_w(bar + i * 8, 0);
        if (lane == 0) {
            l2_prefetch(ci.x + blockIdx.x * 2048, 2048);
            if (blockIdx.x < 8) l2_prefetch(ci.mem0 + blockIdx.x * 2048, 2048);
        }
        uint32_t v[PF_DEPTH], acc = 0;
#pragma unroll
        for (int u = 0; u < PF_DEPTH; u++) v[u] = 0;
        constexpr int PER = 32 * PF_STRIDE, NW = 65536 / PER;
#define PF_N (4 * NW)
        int i = 0;
#pragma unroll 1
        for (; i < PF_N && lds_volatile(flag) == 0; i += PF_DEPTH) {
#pragma unroll
            for (int u = 0; u < PF_DEPTH; u++) {
                const char* a = ci.w[(i + u) / NW] + blockIdx.x * 65536 + ((i + u) % NW) * PER + lane * PF_STRIDE;
                acc |= v[u];
                asm volatile("ld.global.cg.L2::256B.u32 %0, [%1];" : "=r"(v[u]) : "l"(a) : "memory");
            }
        }
#pragma unroll
        for (int u = 0; u < PF_DEPTH; u++) acc |= v[u];
        if (acc == 0x7FFF7FFFu && v[0] == 0x7FFEu) g_err = 1;
        SP2(12);
        KT_MARK(15);
        return;
    }
    asm volatile("barrier.cluster.arrive.relaxed.aligned;" ::: "memory");
    const int far = warp & 1, unit = rank ^ far;
    uint32_t w[4];
    uint32_t d2;
    asm volatile("ld.global.nc.u32 %0, [%1];" : "=r"(d2) : "l"(Dv + ch0 + (warp >> 2) * 2));
    {
        const int ch = warp & 7, half = warp >> 3;
        const uint32_t kb = sb + B_SM_K + ch * B_KCH;
        const uint4* src = reinterpret_cast<const uint4*>(ssmk + (size_t)(ch0 + ch) * S_LEN);
        uint4 kr[4];
#pragma unroll
        for (int i = 0; i < 4; i++) kr[i] = ldg128(src + half * 128 + i * 32 + lane, EF(1));
        const uint32_t edge = half ? 0u : __ldg(reinterpret_cast<const uint32_t*>(src + 128));
        const uint2 sw = __ldg(reinterpret_cast<const uint2*>(shiftk + (size_t)(c16 + unit * 8 + (lane >> 2)) * 4));
        w[0] = __byte_perm(sw.x, 0, 0x1010); w[1] = __byte_perm(sw.x, 0, 0x3232); w[2] = __byte_perm(sw.y, 0, 0x1010); w[3] = __byte_perm(sw.y, 0, 0x3232);
        if (half) sts128(sb + B_SM_U + ch * B_UCH + 4096 + lane * 16, make_uint4(0, 0, 0, 0));
#pragma unroll
        for (int i = 0; i < 4; i++) {
            const uint4 lo = kr[i];
            const uint32_t nx = __shfl_down_sync(~0u, lo.x, 1), n0 = (i < 3) ? __shfl_sync(~0u, kr[i < 3 ? i + 1 : 3].x, 0) : edge;
            const uint32_t hix = (lane < 31) ? nx : n0;
            const int c = 256 - (half * 128 + 32 * i + lane);
            sts128(kb + c * 16, make_uint4(__byte_perm(hix, lo.w, 0x7610), __byte_perm(lo.w, lo.z, 0x7610), __byte_perm(lo.z, lo.y, 0x7610), __byte_perm(lo.y, lo.x, 0x7610)));
            sts128(kb + B_KLEN * 2 + 64 + c * 16, make_uint4(__byte_perm(lo.w, lo.w, 0x1032), __byte_perm(lo.z, lo.z, 0x1032), __byte_perm(lo.y, lo.y, 0x1032), __byte_perm(lo.x, lo.x, 0x1032)));
        }
        const uint32_t k0w = __shfl_sync(~0u, kr[0].x, 0);
        if (half == 0 && lane < 8) {
            sts128(kb + (257 + lane) * 16, make_uint4(lane == 0 ? (k0w & 0xFFFFu) : 0u, 0u, 0u, 0u));
            sts128(kb + B_KLEN * 2 + 64 + (257 + lane) * 16, make_uint4(0u, 0u, 0u, 0u));
        }
    }
    auto sentinels = [&]() {
        const uint4 sent = make_uint4(SENT, SENT, SENT, SENT);
        char* p0 = mbox + blockIdx.x * 16384 + t * 16;
        if (blockIdx.x != 0 || (t & 255) >= 32) stg128(p0, sent);
        stg128(p0 + 8192, sent);
        char* p1 = mbox + WIN + blockIdx.x * 12800 + t * 16;
        stg128(p1, sent);
        if (t < 288) stg128(p1 + 8192, sent);
    };
    if (SENT_AT == 1) sentinels();
    asm volatile("barrier.cluster.wait.acquire.aligned;" ::: "memory");
    SP(1);
    {
        const int box = warp >> 1, row0 = 63 - 32 * rank - 4 * box;
        const uint32_t kt = sb + B_SM_KT + box * B_KBOX + 256 + lane * 32, s0 = (unit ^ ((lane >> 2) & 1)) * 16;
        const uint32_t a0 = kt + s0, a2 = kt - 64 + (unit ^ (((lane + 6) >> 2) & 1)) * 16, a4 = kt - 128 + (s0 ^ 16), av = sb + B_SM_VT + box * 4096 + lane * 32 + s0;
        const uint32_t ul = (lane & 7) * B_UCH + row0 * 64 + (lane >> 3) * 16;
        const uint32_t ud = sb + (far ? B_SM_S + (lane & 7) * (B_SCH - B_UCH) - (1 - rank) * 2048 : B_SM_U);
        mbar_wait_w(bar + box * 8, 0);
        SP(2);
#pragma unroll
        for (int i = 0; i < 4; i++) {
            uint32_t k0[4], k2[4], k4[4], vv[4], o[4];
            ldsm4t(k0, a0 + i * 1024); ldsm4t(k2, a2 + i * 1024); ldsm4t(k4, a4 + i * 1024); ldsm4t(vv, av + i * 1024);
#pragma unroll
            for (int j = 0; j < 4; j++) {
                uint32_t a = bf16_mul(__byte_perm(k4[j], k2[j], 0x5432), w[3]);
                a = bf16_add(a, bf16_mul(k2[j], w[2]));
                a = bf16_add(a, bf16_mul(__byte_perm(k2[j], k0[j], 0x5432), w[1]));
                a = bf16_add(a, bf16_mul(k0[j], w[0]));
                o[j] = bf16_mul(a, vv[j]);
            }
            stsm4(ud + swz64(ul - i * 64), o[0], o[1], o[2], o[3]);
        }
        fence_async();
        __syncwarp();
        if (far && lane < 8) {
            const uint32_t o = lane * B_UCH + (row0 - 3) * 64;
            copy_to_peer(peer_addr(sb + B_SM_U + o, rank ^ 1), ud + o, 256, peer_addr(barU, rank ^ 1));
        }
    }
    bar_sync(1, 512);
    mbar_wait_w(barU, 0);
    if (SENT_AT == 2) sentinels();
    SP(3);
    const int wg = warp >> 2, wq = warp & 3, hi = wq >> 1, g = lane >> 2, tq = lane & 3;
    const uint32_t zero = lds32(sb + B_SM_U + 4096);
#pragma unroll 1
    for (int cc = 0; cc < 2; cc++) {
        const int ch = 2 * wg + cc;
        const uint32_t kb = sb + B_SM_K + ch * B_KCH, ub = sb + B_SM_U + ch * B_UCH;
        const uint32_t dw = __byte_perm(d2, 0, cc ? 0x3232 : 0x1010);
        const int e0 = B_C - g + 2 * tq;
        const uint32_t f0 = ((e0 & 1) ? (kb + B_KLEN * 2 + 64 + (e0 - 1) * 2) : (kb + e0 * 2)) - 32 * wq;
        const uint32_t lo = uniform((ub >> 4) | 0x10000);
        float d[32];
#pragma unroll
        for (int i = 0; i < 32; i++) d[i] = 0.f;
        uint32_t A[2][2][4];
        static_for<0, 32>([&](auto jc) {
            constexpr int j = decltype(jc)::value, N = 64 - 8 * (j / 4);
            if (j >= 2) wg_wait<1>();
            uint32_t(&a)[4] = A[j & 1][0];
            uint32_t(&b)[4] = A[j & 1][1];
            a[0] = lds32(f0 - 128 * j); a[1] = lds32(f0 - 128 * j - 16); a[2] = lds32(f0 - 128 * j + 16);
            b[0] = lds32(f0 - 128 * j + 32); b[2] = lds32(f0 - 128 * j + 48);
            a[3] = a[0] ^ zero; b[1] = a[2] ^ zero; b[3] = b[0] ^ zero;
            wg_fence();
            wgmma_conv<N, 8 * j>(d, a, lo);
            wgmma_conv<N, 8 * j + 2>(d, b, lo);
            wg_commit();
        });
        wg_wait<0>();
        if (cc) SP(4);
        if (PF_STOP == 1 && cc && t == 0) sts32(flag, 1);
        bar_sync(2 + wg, 128);
        if (!hi && tq == 3) { float x = d[13]; d[13] = d[29]; d[29] = x; x = d[15]; d[15] = d[31]; d[31] = x; }
        if (hi && tq == 0) { d[0] = 0.f; d[2] = 0.f; }
        {
            const uint32_t xs = kb + (wq ^ 2) * 2048 + lane * 4;
            const uint32_t xn = hi ? xs + (tq ? 124 : 140) : xs + (tq < 3 ? 4 : -12), wrap = hi ? (tq ? 0 : -1) : (tq < 3 ? 0 : 1);
#pragma unroll
            for (int nb = 0; nb < 4; nb++) {
                const uint32_t xw = xn + ((nb + wrap) & 3) * 512;
#pragma unroll
                for (int i = 0; i < 2; i++) {
                    const float e0v = hi ? d[4 * nb + 2 * i] : d[16 + 4 * nb + 2 * i], e1v = hi ? d[4 * nb + 2 * i + 1] : d[16 + 4 * nb + 2 * i + 1];
                    sts32(hi ? xw + i * 256 : xs + nb * 512 + i * 256 + 128, __float_as_uint(e0v));
                    sts32(hi ? xs + nb * 512 + i * 256 : xw + i * 256, __float_as_uint(e1v));
                }
            }
        }
        bar_sync(2 + wg, 128);
#pragma unroll
        for (int p = 0; p < 2; p++) {
            int row = 16 * p + (lane >> 4) * 8 + (lane & 7);
            row = hi ? row + 31 : row == 31 ? 63 : row;
            const uint32_t a = sb + B_SM_U + swz64(ch * B_UCH + row * 64 + ((wq & 1) * 2 + ((lane >> 3) & 1)) * 16);
            uint32_t u[4];
            ldsm4t(u, a);
#pragma unroll
            for (int b = 0; b < 4; b++) {
                const int r = 8 * p + 2 * b;
                const float y0 = (hi ? d[16 + r] : d[r]) + __uint_as_float(lds32(kb + wq * 2048 + r * 128 + lane * 4));
                const float y1 = (hi ? d[17 + r] : d[r + 1]) + __uint_as_float(lds32(kb + wq * 2048 + r * 128 + 128 + lane * 4));
                u[b] = bf16_add(pack_bf16(y0, y1), bf16_mul(u[b], dw));
            }
            stsm4t(a, u[0], u[1], u[2], u[3]);
        }
        fence_async();
        bar_sync(2 + wg, 128);
        if (SENT_AT == 3 && cc == 0) sentinels();
        if (wq == 0 && lane == 0) copy_to_peer(peer_addr(sb + B_SM_S + ch * B_SCH, rank ^ 1), ub + rank * 2048, 2048, peer_addr(barY, rank ^ 1));
    }
    if (PF_STOP == 2 && t == 0) sts32(flag, 1);
    SP(5);
    mbar_wait_w(barQ, 0);
    bar_sync(1, 512);
    mbar_wait_w(barY, 0);
    asm volatile("barrier.cluster.arrive.relaxed.aligned;" ::: "memory");
    SP(6);
#pragma unroll
    for (int i = 0; i < 4; i++) {
        const int fr = i & 1, row = 63 - 32 * rank - 2 * warp - (i >> 1);
        const uint32_t qa = sb + B_SM_QT + warp * 2048 + (i >> 1) * 1024 + lane * 32 + ((rank ^ fr ^ (lane >> 2)) & 1) * 16;
        uint32_t y[4], q[4];
        ldsm4t(y, sb + (fr ? B_SM_S + (lane & 7) * (B_SCH - B_UCH) - (1 - rank) * 2048 : B_SM_U) + swz64((lane & 7) * B_UCH + row * 64 + (lane >> 3) * 16));
        ldsm4(q, qa);
        stsm4(qa, bf16_mul(q[0], y[0]), bf16_mul(q[1], y[1]), bf16_mul(q[2], y[2]), bf16_mul(q[3], y[3]));
    }
    fence_async();
    __syncwarp();
    if (lane == 0) {
        asm volatile("cp.async.bulk.tensor.2d.global.shared::cta.bulk_group.L2::cache_hint [%0, {%2, %3}], [%1], %4;"
                     ::"l"(&mapO), "r"(sb + B_SM_QT + warp * 2048), "r"(DM + c16), "r"(t0 + warp * 64), "l"(EF(4)) : "memory");
        asm volatile("cp.async.bulk.commit_group;" ::: "memory");
    }
    if (SENT_AT == 0) sentinels();
    if (warp == 0) SP2(10);
    if (lane == 0) asm volatile("cp.async.bulk.wait_group.read 0;" ::: "memory");
    __syncwarp();
    if (warp == 0) SP2(11);
    asm volatile("barrier.cluster.wait.aligned;" ::: "memory");
    SP(7);
    KT_END(1);
}

typedef CUresult (*EncodeFn)(CUtensorMap*, CUtensorMapDataType, cuuint32_t, void*, const cuuint64_t*, const cuuint64_t*, const cuuint32_t*,
                             const cuuint32_t*, CUtensorMapInterleave, CUtensorMapSwizzle, CUtensorMapL2promotion, CUtensorMapFloatOOBfill);

static void make_map(EncodeFn fn, CUtensorMap* m, const void* ptr, uint64_t inner, uint64_t outer, uint32_t box_in, uint32_t box_out,
                     CUtensorMapL2promotion promo = CU_TENSOR_MAP_L2_PROMOTION_L2_256B) {
    cuuint64_t dims[2] = {inner, outer};
    cuuint64_t strides[1] = {inner * 2};
    cuuint32_t box[2] = {box_in, box_out};
    cuuint32_t es[2] = {1, 1};
    fn(m, CU_TENSOR_MAP_DATA_TYPE_BFLOAT16, 2, const_cast<void*>(ptr), dims, strides, box, es, CU_TENSOR_MAP_INTERLEAVE_NONE,
       CU_TENSOR_MAP_SWIZZLE_128B, promo, CU_TENSOR_MAP_FLOAT_OOB_FILL_NONE);
}

#define G2_ST 7
#define PROMO_W CU_TENSOR_MAP_L2_PROMOTION_L2_256B
#define PROMO_O CU_TENSOR_MAP_L2_PROMOTION_L2_256B
#define SSM_PROMO CU_TENSOR_MAP_L2_PROMOTION_NONE
extern "C" void kernel_launch(void* const* d_in, const int* in_sizes, int n_in, void* d_out, int out_size) {
    const bf16* x = (const bf16*)d_in[0];
    const bf16* mem0 = (const bf16*)d_in[1];
    const bf16* Wq = (const bf16*)d_in[2];
    const bf16* Wk = (const bf16*)d_in[3];
    const bf16* Wv = (const bf16*)d_in[4];
    const bf16* Wo = (const bf16*)d_in[5];
    const bf16* Bq = (const bf16*)d_in[7];
    const bf16* Bk = (const bf16*)d_in[8];
    const bf16* Bv = (const bf16*)d_in[9];
    const bf16* Bsh = (const bf16*)d_in[10];
    const bf16* Bssm = (const bf16*)d_in[11];
    const bf16* BD = (const bf16*)d_in[12];
    bf16* out = (bf16*)d_out;

    static bool init = false;
    static EncodeFn enc = nullptr;
    static void *p_tok, *p_ox, *p_mbox;
    static int nclusters = 64;
    if (!init) {
        cudaDriverEntryPointQueryResult qr;
        cudaGetDriverEntryPoint("cuTensorMapEncodeTiled", (void**)&enc, cudaEnableDefault, &qr);
        cudaGetSymbolAddress(&p_tok, g_tok);
        cudaGetSymbolAddress(&p_ox, g_ox);
        cudaGetSymbolAddress(&p_mbox, g_mbox);
        cudaFuncSetAttribute(proj_kernel<96, G2_ST>, cudaFuncAttributeMaxDynamicSharedMemorySize, PROJ_SMEM);
        cudaFuncSetAttribute(proj_kernel<128, 7>, cudaFuncAttributeMaxDynamicSharedMemorySize, PROJ_SMEM);
        cudaFuncSetAttribute(chain_kernel, cudaFuncAttributeMaxDynamicSharedMemorySize, CHAIN_SMEM);
        cudaFuncSetAttribute(ssm_kernel, cudaFuncAttributeMaxDynamicSharedMemorySize, B_SMEM);
        cudaLaunchConfig_t cfg = {};
        cfg.gridDim = dim3(132); cfg.blockDim = dim3(384); cfg.dynamicSmemBytes = CHAIN_SMEM;
        cudaLaunchAttribute at[1];
        at[0].id = cudaLaunchAttributeClusterDimension; at[0].val.clusterDim.x = 2; at[0].val.clusterDim.y = 1; at[0].val.clusterDim.z = 1;
        cfg.attrs = at; cfg.numAttrs = 1;
        int n = 0;
        if (cudaOccupancyMaxActiveClusters(&n, chain_kernel, &cfg) == cudaSuccess && n > 64) nclusters = n < 66 ? n : 66;
        (void)cudaGetLastError();
        init = true;
    }
    char* mbox = (char*)(((uintptr_t)p_mbox + 2 * WIN - 1) & ~(uintptr_t)(2 * WIN - 1));
    CUtensorMap mX, mT32, mT16, mTQ, mKV, mWq, mWk, mWv, mWoC, mWo, mOxE, mOutE, mOx, mOut;
    {
        cuuint64_t dims[3] = {64, S_LEN, DM / 64};
        cuuint64_t strides[2] = {DM * 2, 128};
        cuuint32_t box[3] = {64, 32, 4};
        cuuint32_t es[3] = {1, 1, 1};
        enc(&mX, CU_TENSOR_MAP_DATA_TYPE_BFLOAT16, 3, const_cast<bf16*>(x), dims, strides, box, es, CU_TENSOR_MAP_INTERLEAVE_NONE,
            CU_TENSOR_MAP_SWIZZLE_128B, CU_TENSOR_MAP_L2_PROMOTION_L2_256B, CU_TENSOR_MAP_FLOAT_OOB_FILL_NONE);
    }
    make_map(enc, &mT32, p_tok, DH, 4 * NH * 3 * SEG, 64, 32, CU_TENSOR_MAP_L2_PROMOTION_L2_128B);
    make_map(enc, &mT16, p_tok, DH, 4 * NH * 3 * SEG, 64, 16, CU_TENSOR_MAP_L2_PROMOTION_L2_128B);
    {
        cuuint64_t dims[2] = {512, 4 * NH * 12};
        cuuint64_t strides[1] = {2048};
        cuuint32_t box[2] = {256, 4};
        cuuint32_t es[2] = {1, 1};
        enc(&mTQ, CU_TENSOR_MAP_DATA_TYPE_UINT32, 2, p_tok, dims, strides, box, es, CU_TENSOR_MAP_INTERLEAVE_NONE,
            CU_TENSOR_MAP_SWIZZLE_NONE, CU_TENSOR_MAP_L2_PROMOTION_L2_128B, CU_TENSOR_MAP_FLOAT_OOB_FILL_NONE);
    }
    {
        cuuint64_t dims[3] = {64, 4 * NH * 3 * SEG, 2};
        cuuint64_t strides[2] = {DH * 2, 128};
        cuuint32_t box[3] = {64, 32, 2};
        cuuint32_t es[3] = {1, 1, 1};
        enc(&mKV, CU_TENSOR_MAP_DATA_TYPE_BFLOAT16, 3, p_tok, dims, strides, box, es, CU_TENSOR_MAP_INTERLEAVE_NONE,
            CU_TENSOR_MAP_SWIZZLE_128B, CU_TENSOR_MAP_L2_PROMOTION_L2_128B, CU_TENSOR_MAP_FLOAT_OOB_FILL_NONE);
    }
    make_map(enc, &mWq, Wq, HD, DM, 64, 16, CU_TENSOR_MAP_L2_PROMOTION_L2_128B);
    make_map(enc, &mWk, Wk, HD, DM, 64, 16, CU_TENSOR_MAP_L2_PROMOTION_L2_128B);
    make_map(enc, &mWv, Wv, HD, DM, 64, 16, CU_TENSOR_MAP_L2_PROMOTION_L2_128B);
    make_map(enc, &mWoC, Wo, DM, HD, 64, 16, CU_TENSOR_MAP_L2_PROMOTION_L2_128B);
    const bool early = nclusters >= 66;
    make_map(enc, &mWo, Wo, DM, HD, 64, 64, PROMO_W);
    make_map(enc, &mOxE, p_ox, HD, S_LEN, 64, EARLY_NT / 2);
    make_map(enc, &mOutE, out, OUT_LD, S_LEN, 64, EARLY_NT);
    make_map(enc, &mOx, p_ox, HD, S_LEN, 64, (early ? 96 : 128) >> FIN_SO, PROMO_O);
    make_map(enc, &mOut, out, OUT_LD, S_LEN, 64, early ? 96 : 128);

    CUtensorMap mB[4];
    for (int i = 0; i < 4; i++) {
        cuuint64_t dims[2] = {(cuuint64_t)(i < 3 ? DM : OUT_LD), S_LEN};
        cuuint64_t strides[1] = {dims[0] * 2};
        cuuint32_t box[2] = {16, i == 0 ? 136u : i < 3 ? 128u : 64u};
        cuuint32_t es[2] = {1, 1};
        enc(&mB[i], CU_TENSOR_MAP_DATA_TYPE_BFLOAT16, 2, const_cast<bf16*>(i == 0 ? Bk : i == 1 ? Bv : i == 2 ? Bq : out), dims, strides, box, es,
            CU_TENSOR_MAP_INTERLEAVE_NONE, CU_TENSOR_MAP_SWIZZLE_32B, SSM_PROMO, CU_TENSOR_MAP_FLOAT_OOB_FILL_NONE);
    }
    cudaStream_t st = cudaStreamPerThread;
    const ChainInputs ci = {{(const char*)Wv, (const char*)Wk, (const char*)Wq, (const char*)Wo}, (const char*)x, (const char*)mem0};
    ssm_kernel<<<132, 576, B_SMEM, st>>>(mB[0], mB[1], mB[2], mB[3], Bsh, Bssm, BD, mbox, ci, out);
    cudaLaunchAttribute pdl[1];
    pdl[0].id = cudaLaunchAttributeProgrammaticStreamSerialization; pdl[0].val.programmaticStreamSerializationAllowed = 1;
    cudaLaunchConfig_t lc = {};
    lc.stream = st; lc.attrs = pdl;
    lc.gridDim = dim3(2 * nclusters); lc.blockDim = dim3(384); lc.dynamicSmemBytes = CHAIN_SMEM; lc.numAttrs = PDL & 1;
    cudaLaunchKernelEx(&lc, chain_kernel, mX, mT32, mT16, mTQ, mKV, mWq, mWk, mWv, mWoC, mem0, mbox);
    lc.gridDim = dim3(2 * nclusters); lc.blockDim = dim3(PROJ_THREADS); lc.dynamicSmemBytes = PROJ_SMEM; lc.numAttrs = (PDL >> 1) & 1;
    cudaLaunchKernelEx(&lc, early ? proj_kernel<96, G2_ST> : proj_kernel<128, 7>, mWo, mOx, mOut, mOxE, mOutE);
}
```

```cpp
#include <cuda_runtime.h>
#include <cuda_bf16.h>
#include <cuda.h>
#include <stdint.h>
#include <type_traits>

typedef __nv_bfloat16 bf16;

constexpr int S_LEN = 2048, DM = 1024, NH = 32, DH = 128, NSEG = 64, SEG = 32;
constexpr int HD = NH * DH;
constexpr int OUT_LD = 2048;
constexpr unsigned SENT = 0xFFFFFFFFu;

__device__ bf16 g_tok[4 * NH * 3 * SEG * DH];
__device__ bf16 g_ox[(size_t)S_LEN * HD];
__device__ uint4 g_mbox[4 * 131072];
__device__ unsigned g_xflag[128];
__device__ unsigned g_reg[4];
__device__ __align__(16) unsigned g_cls[256];
__device__ unsigned g_err;
constexpr uint32_t WIN = 2u << 20;
__host__ __device__ constexpr uint32_t page_off(uint32_t idx, uint32_t c) {
    return ((idx & 1) << 13) | ((idx >> 1) << 16) | (((c ^ idx ^ (idx >> 1) ^ (idx >> 2) ^ (idx >> 4)) & 1) << 12);
}
#define STAT(i, c) (void)(c)
#define EARLY_ROLE 1
#define PDL 3

__device__ __forceinline__ void launch_dependents() { asm volatile("griddepcontrol.launch_dependents;" ::: "memory"); }
__device__ __forceinline__ void wait_prerequisites() { asm volatile("griddepcontrol.wait;" ::: "memory"); }
__device__ __forceinline__ void prefetch_map(const CUtensorMap* m) { asm volatile("prefetch.tensormap [%0];" ::"l"(m) : "memory"); }
#define KT_MARK(k)
#define KT_START(k)
#define KT_END(k)

__device__ __forceinline__ uint32_t smem_u32(const void* p) { return (uint32_t)__cvta_generic_to_shared(p); }
__device__ __forceinline__ void ldsm4(uint32_t& r0, uint32_t& r1, uint32_t& r2, uint32_t& r3, uint32_t a) {
    asm volatile("ldmatrix.sync.aligned.m8n8.x4.shared.b16 {%0,%1,%2,%3}, [%4];" : "=r"(r0), "=r"(r1), "=r"(r2), "=r"(r3) : "r"(a) : "memory");
}
__device__ __forceinline__ void ldsm4t(uint32_t& r0, uint32_t& r1, uint32_t& r2, uint32_t& r3, uint32_t a) {
    asm volatile("ldmatrix.sync.aligned.m8n8.x4.trans.shared.b16 {%0,%1,%2,%3}, [%4];" : "=r"(r0), "=r"(r1), "=r"(r2), "=r"(r3) : "r"(a) : "memory");
}
__device__ __forceinline__ void ldsm2(uint32_t& r0, uint32_t& r1, uint32_t a) {
    asm volatile("ldmatrix.sync.aligned.m8n8.x2.shared.b16 {%0,%1}, [%2];" : "=r"(r0), "=r"(r1) : "r"(a) : "memory");
}
__device__ __forceinline__ void stg128(void* p, uint4 v) {
    asm volatile("st.global.v4.u32 [%0], {%1,%2,%3,%4};" ::"l"(p), "r"(v.x), "r"(v.y), "r"(v.z), "r"(v.w) : "memory");
}
__device__ __forceinline__ void stsm4(uint32_t a, uint32_t r0, uint32_t r1, uint32_t r2, uint32_t r3) {
    asm volatile("stmatrix.sync.aligned.m8n8.x4.shared.b16 [%0], {%1,%2,%3,%4};" ::"r"(a), "r"(r0), "r"(r1), "r"(r2), "r"(r3) : "memory");
}
__device__ __forceinline__ void mma16816(float (&d)[4], uint32_t a0, uint32_t a1, uint32_t a2, uint32_t a3, uint32_t b0, uint32_t b1) {
    asm("mma.sync.aligned.m16n8k16.row.col.f32.bf16.bf16.f32 {%0,%1,%2,%3},{%4,%5,%6,%7},{%8,%9},{%0,%1,%2,%3};"
                 : "+f"(d[0]), "+f"(d[1]), "+f"(d[2]), "+f"(d[3])
                 : "r"(a0), "r"(a1), "r"(a2), "r"(a3), "r"(b0), "r"(b1));
}
__device__ __forceinline__ void mma1688(float (&d)[4], uint32_t a0, uint32_t a1, uint32_t b0) {
    asm("mma.sync.aligned.m16n8k8.row.col.f32.bf16.bf16.f32 {%0,%1,%2,%3},{%4,%5},{%6},{%0,%1,%2,%3};"
        : "+f"(d[0]), "+f"(d[1]), "+f"(d[2]), "+f"(d[3]) : "r"(a0), "r"(a1), "r"(b0));
}
__device__ __forceinline__ uint32_t movmat(uint32_t a) {
    uint32_t d;
    asm volatile("movmatrix.sync.aligned.m8n8.trans.b16 %0, %1;" : "=r"(d) : "r"(a));
    return d;
}
__device__ __forceinline__ uint32_t pack_bf16(float lo, float hi) {
    uint32_t r;
    asm("cvt.rn.bf16x2.f32 %0, %1, %2;" : "=r"(r) : "f"(hi), "f"(lo));
    return r;
}
__device__ __forceinline__ uint32_t bf16_mul(uint32_t a, uint32_t b) {
    uint32_t d;
    asm("mul.rn.bf16x2 %0, %1, %2;" : "=r"(d) : "r"(a), "r"(b));
    return d;
}
__device__ __forceinline__ uint32_t bf16_add(uint32_t a, uint32_t b) {
    uint32_t d;
    asm("add.rn.bf16x2 %0, %1, %2;" : "=r"(d) : "r"(a), "r"(b));
    return d;
}

__device__ __forceinline__ float bf16_round(float x) { return __bfloat162float(__float2bfloat16_rn(x)); }
__device__ __forceinline__ float bf_lo(uint32_t w) { return __uint_as_float(w << 16); }
__device__ __forceinline__ float bf_hi(uint32_t w) { return __uint_as_float(w & 0xFFFF0000u); }
__device__ __forceinline__ void bar_sync(int id, int n) { asm volatile("bar.sync %0, %1;" ::"r"(id), "r"(n) : "memory"); }
__device__ __forceinline__ void bar_sync_keep(int id, int n, uint32_t a, uint32_t b) {
    asm volatile("bar.sync %0, %1; // %2 %3" ::"r"(id), "r"(n), "r"(a), "r"(b) : "memory");
}
__device__ __forceinline__ bool bar_red_or(int id, int n, bool p) {
    uint32_t r;
    asm volatile("{.reg .pred p, q; setp.ne.u32 p, %3, 0; bar.red.or.pred q, %1, %2, p; selp.u32 %0, 1, 0, q;}" : "=r"(r) : "r"(id), "r"(n), "r"((uint32_t)p) : "memory");
    return r != 0;
}
__device__ __forceinline__ void bar_arrive(int id, int n) { asm volatile("bar.arrive %0, %1;" ::"r"(id), "r"(n) : "memory"); }
__device__ __forceinline__ void cp_async16(uint32_t dst, const void* src) {
    asm volatile("cp.async.cg.shared.global [%0], [%1], 16;" ::"r"(dst), "l"(src) : "memory");
}
__device__ __forceinline__ void cp_commit() { asm volatile("cp.async.commit_group;" ::: "memory"); }
template <int N> __device__ __forceinline__ void cp_wait() { asm volatile("cp.async.wait_group %0;" ::"n"(N) : "memory"); }
__device__ __forceinline__ uint4 ld_relaxed_v4(const void* p) {
    uint4 v;
    asm volatile("ld.relaxed.gpu.global.v4.u32 {%0,%1,%2,%3}, [%4];" : "=r"(v.x), "=r"(v.y), "=r"(v.z), "=r"(v.w) : "l"(p) : "memory");
    return v;
}
__device__ __forceinline__ void st_relaxed_u32(void* p, uint32_t v) { asm volatile("st.relaxed.gpu.global.u32 [%0], %1;" ::"l"(p), "r"(v) : "memory"); }
__device__ __forceinline__ void st_relaxed_v2(void* p, uint32_t a, uint32_t b) {
    asm volatile("st.relaxed.gpu.global.v2.u32 [%0], {%1,%2};" ::"l"(p), "r"(a), "r"(b) : "memory");
}
__device__ __forceinline__ void sts128(uint32_t a, uint4 v) {
    asm volatile("st.shared.v4.u32 [%0], {%1,%2,%3,%4};" ::"r"(a), "r"(v.x), "r"(v.y), "r"(v.z), "r"(v.w) : "memory");
}
__device__ __forceinline__ uint4 lds128(uint32_t a) {
    uint4 v;
    asm volatile("ld.shared.v4.u32 {%0,%1,%2,%3}, [%4];" : "=r"(v.x), "=r"(v.y), "=r"(v.z), "=r"(v.w) : "r"(a) : "memory");
    return v;
}
__device__ __forceinline__ void sts32(uint32_t a, uint32_t v) { asm volatile("st.shared.u32 [%0], %1;" ::"r"(a), "r"(v) : "memory"); }
__device__ __forceinline__ uint32_t lds32(uint32_t a) {
    uint32_t v;
    asm volatile("ld.shared.u32 %0, [%1];" : "=r"(v) : "r"(a) : "memory");
    return v;
}
__device__ __forceinline__ void mbar_init(uint32_t a, uint32_t c) { asm volatile("mbarrier.init.shared::cta.b64 [%0], %1;" ::"r"(a), "r"(c) : "memory"); }
__device__ __forceinline__ void mbar_expect_tx(uint32_t a, uint32_t bytes) {
    asm volatile("mbarrier.arrive.expect_tx.shared::cta.b64 _, [%0], %1;" ::"r"(a), "r"(bytes) : "memory");
}
__device__ __forceinline__ void mbar_arrive(uint32_t a) { asm volatile("mbarrier.arrive.shared::cta.b64 _, [%0];" ::"r"(a) : "memory"); }
__device__ __forceinline__ void mbar_wait(uint32_t a, uint32_t parity) {
    asm volatile("{.reg .pred p; .reg .u32 c;\n"
                 "mov.u32 c, 0;\n"
                 "MBW_LOOP:\n"
                 "add.u32 c, c, 1;\n"
                 "setp.gt.u32 p, c, 0x10000;\n"
                 "@!p mbarrier.try_wait.parity.shared::cta.b64 p, [%0], %1;\n"
                 "@!p bra.uni MBW_LOOP;}" ::"r"(a), "r"(parity) : "memory");
}
__device__ __forceinline__ void mbar_wait_w(uint32_t a, uint32_t parity) {
    asm volatile("{.reg .pred p; .reg .u32 c;\n"
                 "mov.u32 c, 0;\n"
                 "MBW_LOOP:\n"
                 "add.u32 c, c, 1;\n"
                 "setp.gt.u32 p, c, 0x10000;\n"
                 "@!p mbarrier.try_wait.parity.shared::cta.b64 p, [%0], %1;\n"
                 "vote.sync.all.pred p, p, 0xFFFFFFFF;\n"
                 "@!p bra.uni MBW_LOOP;}" ::"r"(a), "r"(parity) : "memory");
}
__device__ __forceinline__ void mbar_expect_tx_if0(uint32_t sel, uint32_t a, uint32_t bytes) {
    asm volatile("{.reg .pred p; setp.eq.u32 p, %2, 0; @p mbarrier.arrive.expect_tx.shared::cta.b64 _, [%0], %1;}" ::"r"(a), "r"(bytes), "r"(sel) : "memory");
}
__device__ __forceinline__ void mbar_arrive_if0(uint32_t sel, uint32_t a) {
    asm volatile("{.reg .pred p; setp.eq.u32 p, %1, 0; @p mbarrier.arrive.shared::cta.b64 _, [%0];}" ::"r"(a), "r"(sel) : "memory");
}
__device__ __forceinline__ void bulk_load(uint32_t dst, const void* src, uint32_t bytes, uint32_t bar) {
    asm volatile("cp.async.bulk.shared::cluster.global.mbarrier::complete_tx::bytes [%0], [%1], %2, [%3];" ::"r"(dst), "l"(src), "r"(bytes), "r"(bar) : "memory");
}
__device__ __forceinline__ void tma_load_2d(uint32_t dst, const CUtensorMap* map, int c0, int c1, uint32_t bar) {
    asm volatile("cp.async.bulk.tensor.2d.shared::cluster.global.mbarrier::complete_tx::bytes [%0], [%1, {%3, %4}], [%2];"
                 ::"r"(dst), "l"(map), "r"(bar), "r"(c0), "r"(c1) : "memory");
}
__device__ __forceinline__ void tma_load_2d_both(uint32_t dst, const CUtensorMap* map, int c0, int c1, uint32_t bar) {
    asm volatile("cp.async.bulk.tensor.2d.shared::cluster.global.mbarrier::complete_tx::bytes.multicast::cluster [%0], [%1, {%3, %4}], [%2], %5;"
                 ::"r"(dst), "l"(map), "r"(bar), "r"(c0), "r"(c1), "h"((uint16_t)3) : "memory");
}
__device__ __forceinline__ uint64_t policy_evict_first() {
    uint64_t p;
    asm("createpolicy.fractional.L2::evict_first.b64 %0, 1.0;" : "=l"(p));
    return p;
}
__device__ __forceinline__ uint64_t policy_evict_normal() {
    uint64_t p;
    asm("createpolicy.fractional.L2::evict_normal.b64 %0, 1.0;" : "=l"(p));
    return p;
}
__device__ __forceinline__ void tma_load_2d(uint32_t dst, const CUtensorMap* map, int c0, int c1, uint32_t bar, uint64_t pol) {
    asm volatile("cp.async.bulk.tensor.2d.shared::cluster.global.mbarrier::complete_tx::bytes.L2::cache_hint [%0], [%1, {%3, %4}], [%2], %5;"
                 ::"r"(dst), "l"(map), "r"(bar), "r"(c0), "r"(c1), "l"(pol) : "memory");
}
__device__ __forceinline__ uint4 ldg128(const void* p, uint64_t pol) {
    uint4 v;
    asm("ld.global.nc.L2::cache_hint.v4.u32 {%0,%1,%2,%3}, [%4], %5;" : "=r"(v.x), "=r"(v.y), "=r"(v.z), "=r"(v.w) : "l"(p), "l"(pol));
    return v;
}
__device__ __forceinline__ void stg128(void* p, uint4 v, uint64_t pol) {
    asm volatile("st.global.L2::cache_hint.v4.u32 [%0], {%1,%2,%3,%4}, %5;" ::"l"(p), "r"(v.x), "r"(v.y), "r"(v.z), "r"(v.w), "l"(pol) : "memory");
}
__device__ __forceinline__ void tma_store_2d(const CUtensorMap* map, uint32_t src, int c0, int c1) {
    asm volatile("cp.async.bulk.tensor.2d.global.shared::cta.bulk_group [%0, {%2, %3}], [%1];" ::"l"(map), "r"(src), "r"(c0), "r"(c1) : "memory");
}
__device__ __forceinline__ void tma_store_3d(const CUtensorMap* map, uint32_t src, int c0, int c1, int c2) {
    asm volatile("cp.async.bulk.tensor.3d.global.shared::cta.bulk_group [%0, {%2, %3, %4}], [%1];" ::"l"(map), "r"(src), "r"(c0), "r"(c1), "r"(c2) : "memory");
}
__device__ __forceinline__ char* make_ptr(uint32_t lo, uint32_t hi) {
    uint64_t p;
    asm("mov.b64 %0, {%1, %2};" : "=l"(p) : "r"(lo), "r"(hi));
    return reinterpret_cast<char*>(p);
}
__device__ __forceinline__ uint64_t make_desc(uint32_t saddr, uint32_t lbo, uint32_t sbo) {
    return (uint64_t)((saddr & 0x3FFFF) >> 4) | ((uint64_t)((lbo >> 4) & 0x3FFF) << 16) | ((uint64_t)((sbo >> 4) & 0x3FFF) << 32) | ((uint64_t)1 << 62);
}
__device__ __forceinline__ void wg_fence() { asm volatile("wgmma.fence.sync.aligned;" ::: "memory"); }
__device__ __forceinline__ void wg_commit() { asm volatile("wgmma.commit_group.sync.aligned;" ::: "memory"); }
template <int N> __device__ __forceinline__ void wg_wait() { asm volatile("wgmma.wait_group.sync.aligned %0;" ::"n"(N) : "memory"); }

#define R4(b) "+f"(d[b + 0]), "+f"(d[b + 1]), "+f"(d[b + 2]), "+f"(d[b + 3])
#define R16(b) R4(b), R4(b + 4), R4(b + 8), R4(b + 12)
template <int N> __device__ __forceinline__ void wgmma_proj(float (&d)[N / 2], uint64_t da, uint64_t db) {
    if constexpr (N == 96)
        asm volatile("wgmma.mma_async.sync.aligned.m64n96k16.f32.bf16.bf16 {"
            "%0,%1,%2,%3,%4,%5,%6,%7,%8,%9,%10,%11,%12,%13,%14,%15,%16,%17,%18,%19,%20,%21,%22,%23,%24,%25,%26,%27,%28,%29,%30,%31,%32,%33,%34,%35,%36,%37,%38,%39,"
            "%40,%41,%42,%43,%44,%45,%46,%47"
            "}, %48, %49, 1, 1, 1, 1, 0;" : R16(0), R16(16), R16(32) : "l"(da), "l"(db));
    if constexpr (N == 128)
        asm volatile("wgmma.mma_async.sync.aligned.m64n128k16.f32.bf16.bf16 {"
            "%0,%1,%2,%3,%4,%5,%6,%7,%8,%9,%10,%11,%12,%13,%14,%15,%16,%17,%18,%19,%20,%21,%22,%23,%24,%25,%26,%27,%28,%29,%30,%31,%32,%33,%34,%35,%36,%37,%38,%39,"
            "%40,%41,%42,%43,%44,%45,%46,%47,%48,%49,%50,%51,%52,%53,%54,%55,%56,%57,%58,%59,%60,%61,%62,%63"
            "}, %64, %65, 1, 1, 1, 1, 0;" : R16(0), R16(16), R16(32), R16(48) : "l"(da), "l"(db));
    if constexpr (N == 192)
        asm volatile("wgmma.mma_async.sync.aligned.m64n192k16.f32.bf16.bf16 {"
            "%0,%1,%2,%3,%4,%5,%6,%7,%8,%9,%10,%11,%12,%13,%14,%15,%16,%17,%18,%19,%20,%21,%22,%23,%24,%25,%26,%27,%28,%29,%30,%31,%32,%33,%34,%35,%36,%37,%38,%39,"
            "%40,%41,%42,%43,%44,%45,%46,%47,%48,%49,%50,%51,%52,%53,%54,%55,%56,%57,%58,%59,%60,%61,%62,%63,%64,%65,%66,%67,%68,%69,%70,%71,%72,%73,%74,%75,%76,%7"
            "7,%78,%79,%80,%81,%82,%83,%84,%85,%86,%87,%88,%89,%90,%91,%92,%93,%94,%95"
            "}, %96, %97, 1, 1, 1, 1, 0;" : R16(0), R16(16), R16(32), R16(48), R16(64), R16(80) : "l"(da), "l"(db));
    if constexpr (N == 256)
        asm volatile("wgmma.mma_async.sync.aligned.m64n256k16.f32.bf16.bf16 {"
            "%0,%1,%2,%3,%4,%5,%6,%7,%8,%9,%10,%11,%12,%13,%14,%15,%16,%17,%18,%19,%20,%21,%22,%23,%24,%25,%26,%27,%28,%29,%30,%31,%32,%33,%34,%35,%36,%37,%38,%39,"
            "%40,%41,%42,%43,%44,%45,%46,%47,%48,%49,%50,%51,%52,%53,%54,%55,%56,%57,%58,%59,%60,%61,%62,%63,%64,%65,%66,%67,%68,%69,%70,%71,%72,%73,%74,%75,%76,%7"
            "7,%78,%79,%80,%81,%82,%83,%84,%85,%86,%87,%88,%89,%90,%91,%92,%93,%94,%95,%96,%97,%98,%99,%100,%101,%102,%103,%104,%105,%106,%107,%108,%109,%110,%111,"
            "%112,%113,%114,%115,%116,%117,%118,%119,%120,%121,%122,%123,%124,%125,%126,%127"
            "}, %128, %129, 1, 1, 1, 1, 0;" : R16(0), R16(16), R16(32), R16(48), R16(64), R16(80), R16(96), R16(112) : "l"(da), "l"(db));
}

__device__ __forceinline__ void wgmma_rs32(float (&d)[16], const uint32_t (&a)[4], uint64_t db, bool acc) {
    asm volatile(
        "{.reg .pred p; setp.ne.b32 p, %21, 0;\n"
        "wgmma.mma_async.sync.aligned.m64n32k16.f32.bf16.bf16 {%0,%1,%2,%3,%4,%5,%6,%7,%8,%9,%10,%11,%12,%13,%14,%15}, {%16,%17,%18,%19}, %20, p, 1, 1, 0;}"
        : R16(0) : "r"(a[0]), "r"(a[1]), "r"(a[2]), "r"(a[3]), "l"(db), "n"(1) );
}
__device__ __forceinline__ void wgmma_rs32_first(float (&d)[16], const uint32_t (&a)[4], uint64_t db) {
    asm volatile(
        "{.reg .pred p; setp.ne.b32 p, %21, 0;\n"
        "wgmma.mma_async.sync.aligned.m64n32k16.f32.bf16.bf16 {%0,%1,%2,%3,%4,%5,%6,%7,%8,%9,%10,%11,%12,%13,%14,%15}, {%16,%17,%18,%19}, %20, p, 1, 1, 0;}"
        : R16(0) : "r"(a[0]), "r"(a[1]), "r"(a[2]), "r"(a[3]), "l"(db), "n"(0) );
}
__device__ __forceinline__ void wgmma_ss32(float (&d)[16], uint64_t da, uint64_t db) {
    asm volatile(
        "wgmma.mma_async.sync.aligned.m64n32k16.f32.bf16.bf16 {%0,%1,%2,%3,%4,%5,%6,%7,%8,%9,%10,%11,%12,%13,%14,%15}, %16, %17, 1, 1, 1, 1, 0;"
        : R16(0) : "l"(da), "l"(db));
}
template <int OFF, int ACC> __device__ __forceinline__ void wgmma_rs32u(float (&d)[16], const uint32_t (&a)[4], uint32_t lo) {
    asm volatile(
        "{.reg .pred p; .reg .b32 l; .reg .b64 e; setp.ne.b32 p, %22, 0; add.u32 l, %20, %21; mov.b64 e, {l, 0x40000040};\n"
        "wgmma.mma_async.sync.aligned.m64n32k16.f32.bf16.bf16 {%0,%1,%2,%3,%4,%5,%6,%7,%8,%9,%10,%11,%12,%13,%14,%15}, {%16,%17,%18,%19}, e, p, 1, 1, 0;}"
        : R16(0) : "r"(a[0]), "r"(a[1]), "r"(a[2]), "r"(a[3]), "r"(lo), "n"(OFF), "n"(ACC));
}
template <int OFF, int ACC> __device__ __forceinline__ void wgmma_ss32u(float (&d)[16], uint64_t da, uint32_t lo) {
    asm volatile(
        "{.reg .pred p; .reg .b32 l; .reg .b64 e; setp.ne.b32 p, %19, 0; add.u32 l, %17, %18; mov.b64 e, {l, 0x40000040};\n"
        "wgmma.mma_async.sync.aligned.m64n32k16.f32.bf16.bf16 {%0,%1,%2,%3,%4,%5,%6,%7,%8,%9,%10,%11,%12,%13,%14,%15}, %16, e, p, 1, 1, 1, 0;}"
        : R16(0) : "l"(da), "r"(lo), "n"(OFF), "n"(ACC));
}
template <int K0, int K1, class F> __device__ __forceinline__ void static_for(F f) {
    if constexpr (K0 < K1) { f(std::integral_constant<int, K0>()); static_for<K0 + 1, K1>(f); }
}
__device__ __forceinline__ void st_async4(uint32_t a, float x, float y, float z, float w, uint32_t bar) {
    asm volatile("st.async.weak.shared::cluster.mbarrier::complete_tx::bytes.v4.f32 [%0], {%1,%2,%3,%4}, [%5];" ::"r"(a), "f"(x), "f"(y), "f"(z), "f"(w), "r"(bar) : "memory");
}
__device__ __forceinline__ void st_async2(uint32_t a, float x, float y, uint32_t bar) {
    asm volatile("st.async.weak.shared::cluster.mbarrier::complete_tx::bytes.v2.f32 [%0], {%1,%2}, [%3];" ::"r"(a), "f"(x), "f"(y), "r"(bar) : "memory");
}
__device__ __forceinline__ void st_async1(uint32_t a, uint32_t x, uint32_t bar) {
    asm volatile("st.async.weak.shared::cluster.mbarrier::complete_tx::bytes.b32 [%0], %1, [%2];" ::"r"(a), "r"(x), "r"(bar) : "memory");
}
__device__ __forceinline__ uint32_t peer_addr(uint32_t a, uint32_t rank) {
    uint32_t r;
    asm("mapa.shared::cluster.u32 %0, %1, %2;" : "=r"(r) : "r"(a), "r"(rank));
    return r;
}
__device__ __forceinline__ void stsm4t(uint32_t a, uint32_t r0, uint32_t r1, uint32_t r2, uint32_t r3) {
    asm volatile("stmatrix.sync.aligned.m8n8.x4.trans.shared.b16 [%0], {%1,%2,%3,%4};" ::"r"(a), "r"(r0), "r"(r1), "r"(r2), "r"(r3) : "memory");
}
__device__ __forceinline__ void ldsm4t(uint32_t (&r)[4], uint32_t a) { ldsm4t(r[0], r[1], r[2], r[3], a); }
__device__ __forceinline__ void ldsm4(uint32_t (&r)[4], uint32_t a) { ldsm4(r[0], r[1], r[2], r[3], a); }
__device__ __forceinline__ void mma16816(float (&d)[4], const uint32_t (&a)[4], uint32_t b0, uint32_t b1) { mma16816(d, a[0], a[1], a[2], a[3], b0, b1); }
__device__ __forceinline__ void sched_fence(uint32_t v) {
    asm volatile("{.reg .pred p; setp.ne.u32 p, %0, 0xFFFFFFFF; vote.sync.all.pred p, p, 0xFFFFFFFF; @p bra.uni SF_OK; exit; SF_OK:}" ::"r"(v) : "memory");
}
__device__ __forceinline__ void mma16816v(float (&d)[4], const uint32_t (&a)[4], uint32_t b0, uint32_t b1) {
    asm volatile("mma.sync.aligned.m16n8k16.row.col.f32.bf16.bf16.f32 {%0,%1,%2,%3},{%4,%5,%6,%7},{%8,%9},{%0,%1,%2,%3};"
                 : "+f"(d[0]), "+f"(d[1]), "+f"(d[2]), "+f"(d[3]) : "r"(a[0]), "r"(a[1]), "r"(a[2]), "r"(a[3]), "r"(b0), "r"(b1));
}
__device__ __forceinline__ uint32_t uniform(uint32_t v) { return __reduce_max_sync(~0u, v); }

#define WPRE 0
#define G2_X 0
#define G2_K 4
#define FIN_SO 0
#define PROJ_FAST 1
#define KROT 0
#define WFIRST 0
template <int NT, int STAGES> struct ProjCfg {
    static constexpr int STAGE_BYTES = 16384 + NT * 128;
    static constexpr int EPI = NT == 256 ? STAGES * STAGE_BYTES : 0;
    static constexpr int BARS = 229376 + (NT == 256 ? 192 : 0);
    static_assert(STAGES * STAGE_BYTES <= 229376 && EPI + NT * 256 <= 229376 && STAGES <= 12, "smem");
};
constexpr int PROJ_ROLE = 229376 + 384, PROJ_SMEM = PROJ_ROLE + 16;
__device__ __forceinline__ unsigned claim_pair(unsigned* reg) {
    unsigned smid, ncl = gridDim.x >> 1;
    asm volatile("mov.u32 %0, %%smid;" : "=r"(smid));
    uint2 m;
    for (int guard = 0; guard < 1024; guard++) {
        asm volatile("ld.relaxed.gpu.global.v2.u32 {%0, %1}, [%2];" : "=r"(m.x), "=r"(m.y) : "l"(g_cls + (smid & ~1u)) : "memory");
        if (m.x && m.y) break;
    }
    const unsigned r = __vminu2(m.x, m.y), c = (r & 0xFFFF) > (r >> 16);
    unsigned n = atomicAdd(reg, c ? 0x10000u : 1u);
    const unsigned i = c ? n >> 16 : n & 0xFFFF, order = ((n >> 16) + (n & 0xFFFF)) << 8;
    if (i < 32) return c * 32 + i + order;
    for (int guard = 0; guard < (1 << 20); guard++) {
        asm volatile("ld.relaxed.gpu.global.u32 %0, [%1];" : "=r"(n) : "l"(reg) : "memory");
        if ((n >> 16) + (n & 0xFFFF) >= ncl) break;
    }
    const unsigned other = c ? n & 0xFFFF : n >> 16, k = other + i - 32;
    return (k < 32 ? (c ^ 1) * 32 + k : other > 32 ? 64 + c : 32 + k) + order;
}
template <int NT, int STAGES> __device__ __forceinline__ void proj_init(uint32_t sb) {
    for (int i = 0; i < STAGES; i++) { mbar_init(sb + ProjCfg<NT, STAGES>::BARS + 8 * i, 1); mbar_init(sb + ProjCfg<NT, STAGES>::BARS + 8 * (STAGES + i), 16); }
    asm volatile("fence.mbarrier_init.release.cluster;" ::: "memory");
}
template <int NT, int STAGES, bool SHARE_O, class T, class R>
__device__ __forceinline__ void proj_tiles(uint32_t sb, int warp, uint32_t rank, int ntiles, const CUtensorMap* mapW, const CUtensorMap* mapO,
                                           const CUtensorMap* mapOut, T tile, R ready, int rot = 0) {
    using Cfg = ProjCfg<NT, STAGES>;
    const uint32_t bars = sb + Cfg::BARS;
    const int lane = threadIdx.x & 31;
    if (warp == 8) {
        int st = 0; uint32_t ph = 1;
        for (int i = 0; i < ntiles; i++) {
            int col, tok;
            tile(i, col, tok);
            constexpr bool PRE = WPRE && !SHARE_O;
            if (PRE && lane == 0)
                for (int kb = 0; kb < STAGES; kb++) {
                    mbar_expect_tx(bars + 8 * kb, Cfg::STAGE_BYTES);
                    tma_load_2d_both(sb + kb * Cfg::STAGE_BYTES + rank * 8192, mapW, col + rank * 64, kb * 64, bars + 8 * kb);
                }
            ready(i);
            if (lane == 0) {
                if (PRE) {
                    for (int kb = 0; kb < STAGES; kb++) tma_load_2d(sb + kb * Cfg::STAGE_BYTES + 16384, mapO, kb * 64, tok, bars + 8 * kb);
                    ph = 0;
                }
                for (int kb = PRE ? STAGES : 0; kb < HD / 64; kb++) {
                    mbar_wait(bars + 8 * (STAGES + st), ph);
                    const uint32_t full = bars + 8 * st, sa = sb + st * Cfg::STAGE_BYTES;
                    mbar_expect_tx(full, SHARE_O ? Cfg::STAGE_BYTES : G2_X == 1 ? 16384 : G2_X == 2 ? NT * 128 : Cfg::STAGE_BYTES);
                    if (SHARE_O) {
                        tma_load_2d(sa, mapW, col, kb * 64, full);
                        tma_load_2d(sa + 8192, mapW, col + 64, kb * 64, full);
                        tma_load_2d_both(sa + 16384 + rank * (NT * 64), mapO, kb * 64, tok + rank * (NT / 2), full);
                    } else {
                        const int k0 = ((kb + rot) & 63) * 64;
                        if (WFIRST) tma_load_2d_both(sa + rank * 8192, mapW, col + rank * 64, k0, full);
                        if (G2_X != 1) tma_load_2d(sa + 16384, mapO, k0, G2_X == 3 ? tok & 511 : tok, full);
                        if (G2_X == 4) { tma_load_2d(sa, mapW, col, k0, full); tma_load_2d(sa + 8192, mapW, col + 64, k0, full); }
                        else if (!WFIRST && G2_X != 2) tma_load_2d_both(sa + rank * 8192, mapW, col + rank * 64, k0, full);
                    }
                    if (++st == STAGES) { st = 0; ph ^= 1; }
                }
            }
            __syncwarp();
        }
    } else if (warp < 8) {
        const int wg = warp >> 2;
        uint32_t peer_empty;
        asm volatile("mapa.shared::cluster.u32 %0, %1, %2;" : "=r"(peer_empty) : "r"(bars + 8 * STAGES), "r"(rank ^ 1));
        auto release = [&](int stg) {
            if (lane == 0) {
                mbar_arrive(bars + 8 * (STAGES + stg));
                asm volatile("mbarrier.arrive.shared::cluster.b64 _, [%0];" ::"r"(peer_empty + 8 * stg) : "memory");
            }
        };
        const uint32_t ew = sb + Cfg::EPI + wg * (NT * 128);
        int st = 0; uint32_t ph = 0;
        for (int i = 0; i < ntiles; i++) {
            int col, tok;
            tile(i, col, tok);
            float d[NT / 2];
#pragma unroll
            for (int r = 0; r < NT / 2; r++) d[r] = 0.f;
            int prev = -1;
            for (int kb = 0; kb < HD / 64; kb++) {
                mbar_wait(bars + 8 * st, ph);
                const uint32_t sa = sb + st * Cfg::STAGE_BYTES;
                const uint64_t da = make_desc(sa + wg * 8192, 16, 1024), db = make_desc(sa + 16384, 16, 1024);
                wg_fence();
#pragma unroll
                for (int k = 0; k < (NT == 256 ? 4 : G2_K); k++) wgmma_proj<NT>(d, da + k * 128, db + k * 2);
                wg_commit();
                if (prev >= 0) { wg_wait<1>(); release(prev); }
                prev = st;
                if (++st == STAGES) { st = 0; ph ^= 1; }
            }
            wg_wait<0>();
            release(prev);
            if ((warp & 3) == 0 && lane == 0) asm volatile("cp.async.bulk.wait_group.read 0;" ::: "memory");
            if (Cfg::EPI) bar_sync(1 + wg, 128); else bar_sync(3, 256);
            const uint32_t ea = ew + ((lane >> 4) * 8 + (lane & 7)) * 128 + ((((warp & 3) * 2 + ((lane >> 3) & 1)) ^ (lane & 7)) * 16);
#pragma unroll
            for (int r = 0; r < NT / 16; r++)
                stsm4t(ea + r * 2048, pack_bf16(d[8 * r], d[8 * r + 1]), pack_bf16(d[8 * r + 2], d[8 * r + 3]), pack_bf16(d[8 * r + 4], d[8 * r + 5]), pack_bf16(d[8 * r + 6], d[8 * r + 7]));
            asm volatile("fence.proxy.async.shared::cta;" ::: "memory");
            bar_sync(1 + wg, 128);
            if ((warp & 3) == 0 && lane == 0) {
                tma_store_2d(mapOut, ew, col + wg * 64, tok);
                asm volatile("cp.async.bulk.commit_group;" ::: "memory");
            }
        }
        if ((warp & 3) == 0 && lane == 0) asm volatile("cp.async.bulk.wait_group 0;" ::: "memory");
    }
    __syncwarp();
}
constexpr int PROJ_THREADS = 288;

template <int NT, int STAGES>
__global__ void __cluster_dims__(2, 1, 1) __launch_bounds__(PROJ_THREADS, 1)
proj_kernel(const __grid_constant__ CUtensorMap mapW, const __grid_constant__ CUtensorMap mapO, const __grid_constant__ CUtensorMap mapOut) {
    KT_START(3);
    extern __shared__ __align__(1024) uint8_t smem_proj[];
    const uint32_t sb = smem_u32(smem_proj), role = sb + PROJ_ROLE;
    if (sb & 1023) __trap();
    const uint32_t rank = blockIdx.x & 1;
    const int warp = threadIdx.x >> 5;
    if (threadIdx.x == 0) {
        mbar_init(role + 8, 1);
        mbar_expect_tx(role + 8, 4);
        proj_init<NT, STAGES>(sb);
    }
    if (threadIdx.x == 32) { prefetch_map(&mapO); prefetch_map(&mapW); prefetch_map(&mapOut); }
    __syncwarp();
    asm volatile("barrier.cluster.arrive.relaxed.aligned;" ::: "memory");
    unsigned claimed = 0;
    if (threadIdx.x == 256 && rank == 0) claimed = claim_pair(g_reg + 2);
    __syncwarp();
    asm volatile("barrier.cluster.wait.acquire.aligned;" ::: "memory");
    if (threadIdx.x == 256 && rank == 0) {
        st_async1(peer_addr(role, 1), claimed, peer_addr(role + 8, 1));
        st_async1(peer_addr(role, 0), claimed, peer_addr(role + 8, 0));
        if ((claimed >> 8) + 1 == gridDim.x >> 1) {
            g_reg[0] = 0;
            for (int i = 0; i < 64; i++) reinterpret_cast<uint4*>(g_cls)[i] = make_uint4(0, 0, 0, 0);
        }
    }
    __syncwarp();
    mbar_wait_w(role + 8, 0);
    const int p = lds32(role) & 255, order = lds32(role) >> 8;
    if (p >= 64) return;
    proj_tiles<NT, STAGES, false>(sb, warp, rank, 1, &mapW, &mapO, &mapOut,
                                  [&](int, int& col, int& tok) { col = (p & 7) * 128; tok = S_LEN - 16 * NT + ((p >> 3) * 2 + rank) * NT; },
                                  [&](int) { wait_prerequisites();
                                  }, KROT == 0 ? 0 : KROT == 1 ? (p & 7) * 8 : KROT == 2 ? (p >> 3) * 8 : KROT == 3 ? ((p & 7) + (p >> 3)) * 8 : (p >> 5) * 32);
    KT_END(3);
    asm volatile("barrier.cluster.arrive.relaxed; barrier.cluster.wait;" ::: "memory");
}

#define WO_RF1 6
constexpr int SM_KV = 0, KV_BYTES = 18432;
constexpr int SM_XT = 2 * KV_BYTES;
constexpr int SM_STG = SM_XT + 65536;
constexpr int SM_Z = SM_STG + 6144;
constexpr int SM_RT = SM_Z + 8192;
constexpr int SM_OT = SM_RT + 8192;
constexpr int SM_QKV = SM_RT + 10240;
constexpr int SM_R1 = SM_QKV + 6144;
constexpr int SM_Y = SM_R1;
constexpr int SM_R2 = SM_R1 + 4096;
constexpr int SM_R3 = SM_R2 + 1024;
constexpr int SM_O = SM_R3 + 2048;
constexpr int SM_S = SM_O + 2048;
constexpr int SM_INV = SM_S + 1536;
constexpr int SM_TO = SM_R3;
constexpr int SM_WORK_END = SM_S + 2048;
constexpr int STG_QK = 0, STG_V = 98304;
#define WO_IT 2
__host__ __device__ constexpr int stg_wo(int r) { return r < 9 ? KV_BYTES + r * 2048 : r < 13 ? SM_QKV + (r - 9) * 2048 : SM_S; }
static_assert(WO_RF1 == 6 && SM_QKV % 1024 == 0 && SM_S % 1024 == 0 && SM_QKV + 8192 <= SM_TO, "staging of Wo");
__host__ __device__ constexpr int stg_qk(int t, int r) { return t == 0 ? SM_XT + r * 2048 : r < SM_XT / 2048 ? r * 2048 : (r + 24) * 2048; }
constexpr int SM_WO1 = SM_WORK_END - WO_RF1 * 2048;
constexpr int STG_WO = SM_WO1 - 16384;
constexpr int SM_WQK = (SM_WO1 + 16384 > STG_V + 49152) ? SM_WO1 + 16384 : STG_V + 49152;
constexpr int SM_WV = SM_WQK + 32768;
constexpr int SM_WO2 = SM_WV + 16384;
constexpr int SM_BARS = SM_WO2 + 32768;
enum { MB_W0 = SM_BARS, MB_W1 = SM_BARS + 8, MB_W2 = SM_BARS + 16, MB_W3 = SM_BARS + 24, MB_XT = SM_BARS + 32  , MB_KV = SM_BARS + 48  ,
       MB_R3 = SM_BARS + 64, MB_R1 = SM_BARS + 72, MB_R2 = SM_BARS + 80, MB_RT0 = SM_BARS + 88, MB_RT1 = SM_BARS + 96, MB_FREE = SM_BARS + 104,
       MB_P = SM_BARS + 112, MB_V = SM_BARS + 120, MB_STG = SM_BARS + 128, MB_ROLE = SM_BARS + 136, MB_W4 = SM_BARS + 144, MB_W5 = SM_BARS + 152, SM_ROLE = SM_BARS + 160  ,
       MB_FULL = SM_BARS + 176  , MB_EMPTY = SM_BARS + 208  , MB_SUM = SM_BARS + 240 };
constexpr int CHAIN_SMEM = MB_SUM + 8;
static_assert(SM_WORK_END % 1024 == 0 && STG_WO >= STG_V, "work area");
static_assert(SM_Y % 128 == 0, "exchange Y");
static_assert(CHAIN_SMEM <= 232448 && WO_RF1 >= 6, "smem");

#define DLY_X 250
#define DLY_V 0
#define DLY_Y 320
#define DLY_Z 280
#define TS_AT 5
#define EARLY_T 6
#define PH2 0
#define VF1 1
#define COLDV 0
#define COLD() true
#define RT0_B 1
#define OTMA 1
#define TM 7
#define ORD0 2
#define ORD1 2
#define ORDV 2
__host__ __device__ constexpr int kstep(int ord, int i) { return ord == 0 ? i : ord == 1 ? (i + 24) % 32 : ord == 2 ? (i % 4 == 3 ? 24 + i / 4 : i / 4 * 3 + i % 4) : ord == 3 ? (i < 16 ? (i % 2 ? 24 + i / 2 : i / 2) : i - 8) : (i < 8 ? i : i < 16 ? i + 16 : i - 8); }

#define GV 1
#define NSV (GV ? 320 : 352)
#define Q3_AT 9
#define NA 7
#define NP2 6
#define P2_FENCE 0
#define SPLIT 5
#define TA0 16
#define Y_CHAIN 1
#define EF_W 1
#define XFLIP 0
#define YFLIP 0
#define ZFLIP 1
#define OFENCE 2
#define REG_A 240
#define REG_B 216
#define REG_C (3 * 168 - REG_A - REG_B)

enum { BAR_Y, BAR_MEM, BAR_PUB, BAR_QK, BAR_S, BAR_O, BAR_SENT, BAR_COMM, BAR_PUBV, BAR_PV, BAR_PDONE, BAR_VP, BAR_ZP, BAR_PRO, BAR_O2, BAR_SV,
       BAR_V = BAR_PV, BAR_SENTC = BAR_PDONE, BAR_Q3 = BAR_PRO, BAR_INV = BAR_PRO, BAR_XT0 = BAR_Y };

__device__ __forceinline__ uint32_t umax4(const uint4& v) { return max(max(v.x, v.y), max(v.z, v.w)); }
__device__ __forceinline__ unsigned gtime() { unsigned t; asm volatile("mov.u32 %0, %%globaltimer_lo;" : "=r"(t)::"memory"); return t; }
__device__ __forceinline__ unsigned clock32() { unsigned t; asm volatile("mov.u32 %0, %%clock;" : "=r"(t)::"memory"); return t; }
__device__ __forceinline__ void spin_cycles(int d) {
    if (d > 0) { const unsigned c0 = clock32(); while (clock32() - c0 < (unsigned)d) {} }
}
__device__ __forceinline__ float ex2_approx(float x) { float y; asm("ex2.approx.ftz.f32 %0, %1;" : "=f"(y) : "f"(x)); return y; }
__device__ __forceinline__ float rcp_approx(float x) { float y; asm("rcp.approx.ftz.f32 %0, %1;" : "=f"(y) : "f"(x)); return y; }
__device__ __forceinline__ void st_sent(const void* p) { asm volatile("st.relaxed.gpu.global.v4.u32 [%0], {%1,%1,%1,%1};" ::"l"(p), "r"(SENT) : "memory"); }
#define POLL_LD(p, a, b, c, d, addr) "@" p " ld.relaxed.gpu.global.v4.u32 {" a "," b "," c "," d "}, [" addr "];\n"
#define POLL_CK(p, a, b, c, d) "max.u32 m, " a "," b "; max.u32 n, " c "," d "; max.u32 m, m, n; setp.eq.u32 " p ", m, 0xFFFFFFFF;\n"
#define POLL_IO(v) "+r"(v.x), "+r"(v.y), "+r"(v.z), "+r"(v.w)
__device__ __forceinline__ void poll_init(uint4& v) { v = make_uint4(SENT, SENT, SENT, SENT); asm volatile("" : POLL_IO(v)); }
__device__ __forceinline__ int poll2(uint4 (&v)[2], const char* a) {
    int c = 0;
    asm volatile("{.reg .pred p0, p1, p; .reg .u32 m, n;\n"
                 "setp.eq.u32 p0, %8, 0; setp.eq.u32 p1, %8, 0;\n"
                 "POLL_LOOP:\n"
                 POLL_LD("p0", "%0", "%1", "%2", "%3", "%9") POLL_LD("p1", "%4", "%5", "%6", "%7", "%9+512")
                 "add.u32 %8, %8, 1;\n"
                 POLL_CK("p0", "%0", "%1", "%2", "%3") POLL_CK("p1", "%4", "%5", "%6", "%7")
                 "or.pred p, p0, p1; setp.lt.and.u32 p, %8, 0x10000, p; vote.sync.any.pred p, p, 0xFFFFFFFF;\n"
                 "@p bra.uni POLL_LOOP;}" : POLL_IO(v[0]), POLL_IO(v[1]), "+r"(c) : "l"(a) : "memory");
    return c;
}
template <int ST> __device__ __forceinline__ int poll4(uint4 (&v)[4], const char* a) {
    int c = 0;
    asm volatile("{.reg .pred p0, p1, p2, p3, p; .reg .u32 m, n;\n"
                 "setp.eq.u32 p0, %16, 0; setp.eq.u32 p1, %16, 0; setp.eq.u32 p2, %16, 0; setp.eq.u32 p3, %16, 0;\n"
                 "POLL_LOOP:\n"
                 POLL_LD("p0", "%0", "%1", "%2", "%3", "%17") POLL_LD("p1", "%4", "%5", "%6", "%7", "%17+%18")
                 POLL_LD("p2", "%8", "%9", "%10", "%11", "%17+%19") POLL_LD("p3", "%12", "%13", "%14", "%15", "%17+%20")
                 "add.u32 %16, %16, 1;\n"
                 POLL_CK("p0", "%0", "%1", "%2", "%3") POLL_CK("p1", "%4", "%5", "%6", "%7") POLL_CK("p2", "%8", "%9", "%10", "%11") POLL_CK("p3", "%12", "%13", "%14", "%15")
                 "or.pred p, p0, p1; or.pred p, p, p2; or.pred p, p, p3; setp.lt.and.u32 p, %16, 0x10000, p; vote.sync.any.pred p, p, 0xFFFFFFFF;\n"
                 "@p bra.uni POLL_LOOP;}" : POLL_IO(v[0]), POLL_IO(v[1]), POLL_IO(v[2]), POLL_IO(v[3]), "+r"(c) : "l"(a), "n"(ST), "n"(2 * ST), "n"(3 * ST) : "memory");
    return c;
}
__device__ __forceinline__ uint32_t add_bf16x2(uint32_t a, uint32_t b) { uint32_t r; asm("add.rn.bf16x2 %0, %1, %2;" : "=r"(r) : "r"(a), "r"(b)); return r; }
__device__ __forceinline__ uint32_t max_bf16x2(uint32_t a, uint32_t b) { uint32_t r; asm("max.bf16x2 %0, %1, %2;" : "=r"(r) : "r"(a), "r"(b)); return r; }
template <class F> __device__ __forceinline__ void softmax40(uint32_t (&pw)[6], uint32_t sa, F mid) {
    const float LOG2E = 1.4426950408889634f;
    uint32_t w[5];
    float e[10];
#pragma unroll
    for (int i = 0; i < 5; i++) w[i] = lds32(sa + i * 128);
    uint32_t m = max_bf16x2(max_bf16x2(max_bf16x2(w[0], w[1]), max_bf16x2(w[2], w[3])), w[4]);
    m = max_bf16x2(m, __shfl_xor_sync(~0u, m, 1));
    m = max_bf16x2(m, __shfl_xor_sync(~0u, m, 2));
    const float mb2 = fmaxf(bf_lo(m), bf_hi(m)) * LOG2E;
#pragma unroll
    for (int i = 0; i < 5; i++) {
        e[2 * i] = ex2_approx(fmaf(bf_lo(w[i]), LOG2E, -mb2));
        e[2 * i + 1] = ex2_approx(fmaf(bf_hi(w[i]), LOG2E, -mb2));
    }
    mid();
#pragma unroll
    for (int i = 0; i < 5; i++) pw[i] = pack_bf16(e[2 * i], e[2 * i + 1]);
    const float sum = (((e[0] + e[1]) + (e[2] + e[3])) + ((e[4] + e[5]) + (e[6] + e[7]))) + (e[8] + e[9]);
    const float hi = bf_hi(__float_as_uint(sum));
    pw[5] = pack_bf16(sum - hi, hi);
}
template <bool NORM, class F> __device__ __forceinline__ void pv32(uint32_t (&w)[4], float (&inv)[2], const uint32_t (&va)[2][2][4], const uint32_t (&vm)[4], const uint32_t (&pw)[6], F mid) {
    float o[2][3][4], t[4] = {0.f, 0.f, 0.f, 0.f};
#pragma unroll
    for (int i = 0; i < 3; i++)
#pragma unroll
        for (int m = 0; m < 2; m++) {
            o[m][i][0] = o[m][i][1] = o[m][i][2] = o[m][i][3] = 0.f;
            if (i < 2) mma16816(o[m][i], va[m][i & 1], pw[2 * i], pw[2 * i + 1]);
            else mma1688(o[m][i], vm[2 * m], vm[2 * m + 1], pw[4]);
        }
    mma1688(t, 0x3F803F80u, 0x3F803F80u, pw[5]);
    mid();
    if (NORM) { inv[0] = rcp_approx(t[0]); inv[1] = rcp_approx(t[1]); }
#pragma unroll
    for (int i = 0; i < 4; i++) {
        const float a = (o[i >> 1][0][2 * (i & 1)] + o[i >> 1][1][2 * (i & 1)]) + o[i >> 1][2][2 * (i & 1)];
        const float b = (o[i >> 1][0][2 * (i & 1) + 1] + o[i >> 1][1][2 * (i & 1) + 1]) + o[i >> 1][2][2 * (i & 1) + 1];
        w[i] = NORM ? pack_bf16(a * inv[0], b * inv[1]) : pack_bf16(a, b);
    }
    if (!NORM) { inv[0] = t[0]; inv[1] = t[1]; }
}
__device__ __forceinline__ uint32_t scale_scores(float a, float b) {
    const float scale = 0.08838834764831845f;
    const uint32_t w = pack_bf16(a, b);
    return pack_bf16(bf_lo(w) * scale, bf_hi(w) * scale);
}

#define TL(i) do {} while (0)
#define TLB(i) do {} while (0)
#define TLC(i) do {} while (0)

#define OPQ_LANE 1
#define CLAIM_T 64
#define PAD_A 0
#define PAD_B 0
#define PAD_C 0
template <int N> __device__ __forceinline__ void code_pad() {
#pragma unroll
    for (int i = 0; i < N; i++) asm volatile("pmevent 0;");
}

constexpr int TILE_N = 192, EARLY_TOK = 3 * TILE_N, LAST_N = S_LEN - EARLY_TOK - 7 * TILE_N, FLAG_END = NSEG + 3;
constexpr int PJ_STAGE = 16384 + TILE_N * 128, PJ_LOW = 0, PJ_MID = SM_XT + 2 * PJ_STAGE;
__device__ __forceinline__ uint32_t pj_stage(uint32_t i) { return SM_XT + (i & 1) * PJ_STAGE + (i >> 1 & 1) * (SM_WORK_END - SM_XT); }
static_assert(PJ_MID <= SM_QKV && PJ_MID + TILE_N * 128 <= SM_WORK_END && SM_WORK_END + 2 * PJ_STAGE <= SM_BARS && PJ_MID <= SM_OT && SM_OT % 512 == 0 && TILE_N * 128 <= SM_XT && LAST_N == 128, "projection");
template <class R>
__device__ __forceinline__ void pj_fetch(uint32_t sb, uint32_t lane, uint32_t it, int nkb, int n, const CUtensorMap* mapW, const CUtensorMap* mapO, int col0, int col1, int k0, int tok, R ready) {
    auto weights = [&](int kb) {
        const uint32_t i = it + kb, sa = sb + pj_stage(i), full = sb + MB_FULL + (i & 3) * 8;
        mbar_wait(sb + MB_EMPTY + (i & 3) * 8, (~i >> 2) & 1);
        mbar_expect_tx(full, 16384 + n * 128);
        tma_load_2d(sa, mapW, col0, k0 + kb * 64, full);
        tma_load_2d(sa + 8192, mapW, col1, k0 + kb * 64, full);
    };
    auto rows = [&](int kb) {
        const uint32_t i = it + kb, sa = sb + pj_stage(i) + 16384, full = sb + MB_FULL + (i & 3) * 8;
        for (int t = 0; t < n; t += 64) tma_load_2d(sa + t * 128, mapO, k0 + kb * 64, tok + t, full);
    };
    if (lane == 0) for (int kb = 0; kb < 4; kb++) weights(kb);
    __syncwarp();
    ready();
    if (lane == 0) {
        for (int kb = 0; kb < 4; kb++) rows(kb);
#pragma unroll 1
        for (int kb = 4; kb < nkb; kb++) { weights(kb); rows(kb); }
    }
    __syncwarp();
}
template <int N>
__device__ __forceinline__ void pj_sum(float (&d)[N / 2], uint32_t sb, uint32_t lane, uint32_t wg, uint32_t it, int nkb) {
#pragma unroll
    for (int r = 0; r < N / 2; r++) d[r] = 0.f;
#pragma unroll 1
    for (int kb = 0; kb < nkb; kb++) {
        const uint32_t i = it + kb, sa = sb + pj_stage(i);
        mbar_wait_w(sb + MB_FULL + (i & 3) * 8, (i >> 2) & 1);
        const uint64_t da = make_desc(sa + wg * 8192, 16, 1024), db = make_desc(sa + 16384, 16, 1024);
        wg_fence();
#pragma unroll
        for (int k = 0; k < 4; k++) wgmma_proj<N>(d, da + k * 128, db + k * 2);
        wg_commit();
        if (kb > 0) { wg_wait<1>(); mbar_arrive_if0(lane, sb + MB_EMPTY + ((i - 1) & 3) * 8); }
    }
    wg_wait<0>();
    mbar_arrive_if0(lane, sb + MB_EMPTY + ((it + nkb - 1) & 3) * 8);
}
template <int N>
__device__ __forceinline__ void pj_store(const float (&d)[N / 2], uint32_t box, uint32_t t, int bar, const CUtensorMap* mapOut, int col, int tok) {
    const uint32_t ea = box + (((t >> 4) & 1) * 8 + (t & 7)) * 128 + ((((t >> 5) * 2 + ((t >> 3) & 1)) ^ (t & 7)) * 16);
#pragma unroll
    for (int r = 0; r < N / 16; r++)
        stsm4t(ea + r * 2048, pack_bf16(d[8 * r], d[8 * r + 1]), pack_bf16(d[8 * r + 2], d[8 * r + 3]), pack_bf16(d[8 * r + 4], d[8 * r + 5]), pack_bf16(d[8 * r + 6], d[8 * r + 7]));
    asm volatile("fence.proxy.async.shared::cta;" ::: "memory");
    bar_sync(bar, 128);
    if (t == 0) {
        for (int r = 0; r < N; r += 64) tma_store_2d(mapOut, box + r * 128, col, tok + r);
        asm volatile("cp.async.bulk.commit_group;" ::: "memory");
    }
}
template <int N>
__device__ __forceinline__ void pj_last(uint32_t sb, uint32_t wg, uint32_t t, int bar, const CUtensorMap* mapOut, int col, int tok) {
    float d[N / 2];
    mbar_expect_tx_if0(t | (wg ^ 1), sb + MB_SUM, N * 128);
    pj_sum<N>(d, sb, t & 31, wg, 0, 32);
    if (wg == 0) {
        const uint32_t rsb = sb ^ (1u << 24), dst = rsb + PJ_LOW + t * 16;
        mbar_wait_w(sb + MB_FREE, 1);
#pragma unroll
        for (int r = 0; r < N / 16; r++)
            st_async4(dst + r * 2048, __uint_as_float(pack_bf16(d[8 * r], d[8 * r + 1])), __uint_as_float(pack_bf16(d[8 * r + 2], d[8 * r + 3])),
                      __uint_as_float(pack_bf16(d[8 * r + 4], d[8 * r + 5])), __uint_as_float(pack_bf16(d[8 * r + 6], d[8 * r + 7])), rsb + MB_SUM);
    } else {
        mbar_wait_w(sb + MB_SUM, 0);
#pragma unroll
        for (int r = 0; r < N / 16; r++) {
            const uint4 v = lds128(sb + PJ_LOW + t * 16 + r * 2048);
            d[8 * r] += bf_lo(v.x); d[8 * r + 1] += bf_hi(v.x); d[8 * r + 2] += bf_lo(v.y); d[8 * r + 3] += bf_hi(v.y);
            d[8 * r + 4] += bf_lo(v.z); d[8 * r + 5] += bf_hi(v.z); d[8 * r + 6] += bf_lo(v.w); d[8 * r + 7] += bf_hi(v.w);
        }
        pj_store<N>(d, sb + PJ_MID, t, bar, mapOut, col, tok);
        if (t == 0) asm volatile("cp.async.bulk.wait_group 0;" ::: "memory");
        __syncwarp();
    }
}
#define NOINL 0
__device__ __forceinline__
void pj_tile(uint32_t wg, const CUtensorMap* mapOut) {
    uint32_t t, rank;
    asm volatile("mov.u32 %0, %%tid.x; and.b32 %0, %0, 127; mov.u32 %1, %%ctaid.x; and.b32 %1, %1, 1;" : "=r"(t), "=r"(rank));
    const uint32_t base = 1024 | (rank << 24), pr = lds32(base + SM_ROLE);
    const int col = (pr & 7) * 128 + 64 * rank, tok = EARLY_TOK + (pr >> 3) * TILE_N;
    if (pr >> 3 == 7) pj_last<LAST_N>(base, wg, t, BAR_O, mapOut, col, tok); else pj_last<TILE_N>(base, wg, t, BAR_O, mapOut, col, tok);
}
__device__ __forceinline__ void pj_early(uint32_t sb, uint32_t e, uint32_t rank, const CUtensorMap* mapW, const CUtensorMap* mapO, const CUtensorMap* mapOut) {
    const uint32_t warp = threadIdx.x >> 5, lane = threadIdx.x & 31;
    if (warp == 8) {
        wait_prerequisites();
#pragma unroll 1
        for (int i = 0; i < EARLY_T; i++) {
            const int col = ((i & 1) * 4 + e * 2 + rank) * 128;
            pj_fetch(sb, lane, i * 64, 64, TILE_N, mapW, mapO, col, col + 64, 0, (i >> 1) * TILE_N, [&]() {
                if (i & 1) return;
                const unsigned need = TILE_N / SEG * (i / 2 + 1) + 3;
                for (int guard = 0; guard < (1 << 16); guard++) {
                    const uint4 f = ld_relaxed_v4(g_xflag + lane * 4);
                    if (__all_sync(~0u, min(min(f.x, f.y), min(f.z, f.w)) >= need)) break;
                    __nanosleep(500);
                }
                asm volatile("fence.acq_rel.gpu; fence.proxy.async.global;" ::: "memory");
                if (i == 0 && rank == 0 && lane == 0 && atomicAdd(g_reg + 2, 1) == 1) {
                    g_reg[0] = 0;
                    for (int k = 0; k < 64; k++) reinterpret_cast<uint4*>(g_cls)[k] = make_uint4(0, 0, 0, 0);
                }
                __syncwarp();
            });
        }
    } else if (warp < 8) {
        const uint32_t wg = warp >> 2, t = threadIdx.x & 127;
#pragma unroll 1
        for (int i = 0; i < EARLY_T; i++) {
            float d[TILE_N / 2];
            pj_sum<TILE_N>(d, sb, lane, wg, i * 64, 64);
            if (t == 0) asm volatile("cp.async.bulk.wait_group.read 0;" ::: "memory");
            bar_sync(1 + wg, 128);
            pj_store<TILE_N>(d, sb + (wg ? PJ_MID : PJ_LOW), t, 1 + wg, mapOut, ((i & 1) * 4 + e * 2 + rank) * 128 + wg * 64, (i >> 1) * TILE_N);
        }
        if (t == 0) asm volatile("cp.async.bulk.wait_group 0;" ::: "memory");
    }
    __syncwarp();
}
template <bool TAIL>
__global__ void __cluster_dims__(2, 1, 1) __launch_bounds__(384, 1)
chain_kernel(char* __restrict__ mbox, const bf16* __restrict__ mem0,
             const __grid_constant__ CUtensorMap mapX, const __grid_constant__ CUtensorMap mapT32, const __grid_constant__ CUtensorMap mapT16,
             const __grid_constant__ CUtensorMap mapTQ, const __grid_constant__ CUtensorMap mapKV,
             const __grid_constant__ CUtensorMap mapWq, const __grid_constant__ CUtensorMap mapWk, const __grid_constant__ CUtensorMap mapWv,
             const __grid_constant__ CUtensorMap mapWo, const __grid_constant__ CUtensorMap mapPW, const __grid_constant__ CUtensorMap mapPO,
             const __grid_constant__ CUtensorMap mapOut, const __grid_constant__ CUtensorMap mapO8) {
    KT_START(2);
    extern __shared__ __align__(1024) uint8_t smem_chain[];
    constexpr uint32_t SB0 = 1024;
    if (smem_u32(smem_chain) != (SB0 | ((blockIdx.x & 1) << 24))) __trap();
    const int kh = blockIdx.x & 1;
    if (threadIdx.x == 0) {
        const uint32_t sb = smem_u32(smem_chain);
        for (int i = 0; i < 14; i++) mbar_init(sb + SM_BARS + 8 * i, 1);
        mbar_init(sb + MB_P, 4); mbar_init(sb + MB_V, 4); mbar_init(sb + MB_STG, 8); mbar_init(sb + MB_ROLE, 1); mbar_init(sb + MB_W4, 1); mbar_init(sb + MB_W5, 1);
        mbar_expect_tx(sb + MB_ROLE, 4);
        asm volatile("fence.mbarrier_init.release.cluster;" ::: "memory");
    }
    if (TAIL && threadIdx.x == 96) {
        const uint32_t sb = smem_u32(smem_chain);
        for (int i = 0; i < 4; i++) { mbar_init(sb + MB_FULL + 8 * i, 1); mbar_init(sb + MB_EMPTY + 8 * i, 8); }
        mbar_init(sb + MB_SUM, 1);
        asm volatile("fence.mbarrier_init.release.cluster;" ::: "memory");
    }
    if (threadIdx.x == 32) { prefetch_map(&mapWv); prefetch_map(&mapWq); prefetch_map(&mapWk); prefetch_map(&mapWo); prefetch_map(&mapX); }
    __syncwarp();
    asm volatile("barrier.cluster.arrive.relaxed.aligned;" ::: "memory");
    unsigned claimed = 0;
    if (threadIdx.x == CLAIM_T && kh == 0) claimed = claim_pair(g_reg) & 255;
    __syncwarp();
    asm volatile("barrier.cluster.wait.acquire.aligned;" ::: "memory");
    if (threadIdx.x == CLAIM_T && kh == 0) {
        st_async1((SB0 | (1u << 24)) + SM_ROLE, claimed, (SB0 | (1u << 24)) + MB_ROLE);
        st_async1(SB0 + SM_ROLE, claimed, SB0 + MB_ROLE);
    }
    __syncwarp();
    mbar_wait_w(smem_u32(smem_chain) + MB_ROLE, 0);
    const int pair = uniform(lds32(smem_u32(smem_chain) + SM_ROLE));
#define YFLIP_() (uniform(lds32(sb + SM_ROLE + 4)) ^ YFLIP)
    if (pair >= 64) {
        if (TAIL) pj_early(smem_u32(smem_chain), pair - 64, kh, &mapPW, &mapPO, &mapOut);
        if (TAIL) KT_END(3);
        return;
    }
    if (threadIdx.x == 0) KT_MARK(5);
    const int h = pair >> 1, nh = pair & 1, j = 2 * nh + kh, role = 2 * pair + kh;
#define WG_ORDER 0x210
    const int warp = uniform(((WG_ORDER >> (4 * (threadIdx.x >> 7))) & 3) * 4 + ((threadIdx.x >> 5) & 3));
    const uint32_t g = warp & 3, sb = SB0 | (kh << 24), rsb = sb ^ (1u << 24), cls = pair >> 5, kflip = ZFLIP ^ kh;
    const uint32_t mlo = (uint32_t)(uintptr_t)mbox, mhi = (uint32_t)((uintptr_t)mbox >> 32);
    auto lane16 = [&]() {
        uint32_t t;
        asm volatile("{.reg .u32 l, x; mov.u32 l, %%laneid; xor.b32 x, l, 1; shl.b32 x, x, 4; shfl.sync.bfly.b32 %0, x, 1, 0x1f, 0xffffffff;}" : "=r"(t));
        return t;
    };
#define PHASE(k) uint32_t L; asm volatile("{.reg .u32 t; shr.u32 t, %1, %3; add.u32 %0, %2, t;}" : "=r"(L) : "r"(it), "r"(l16), "n"(8 + (k)))
#define ROWPAT() ((((L << 3) & 0x380) | ((L << 2) & 0x400)) | ((L ^ (L >> 3)) & 0x10) | (L & 0x60))
#define FRAG() (ROWPAT() ^ (g << 5))
#define QFRAG() ((((L >> 1) & 0x80) | (L & 0x70)) + ((L & 0x80) ? SM_KV + 16384 + kvo : SM_QKV))
#define VFRAG() (ROWPAT() ^ ((g & 1) << 6))
#define VBASE() (sb + SM_KV + 8192 + (g >> 1) * 4096 + kvo)
#define XTLO() ((uint32_t)make_desc(SB0 + SM_XT, 16, 1024) + (ui & 1) * 2048)
    auto last_tile = [&](uint32_t wg) {
        KT_END(2);
        pj_tile(wg, &mapOut);
    };
    if (warp >= 8) {
        asm volatile("setmaxnreg.dec.sync.aligned.u32 %0;" ::"n"(REG_C));
        code_pad<PAD_C>();
        const uint32_t l16 = lane16(), lane = l16 >> 4;
        auto load_xt = [&](int seg, int half) {
            const uint32_t bar = sb + MB_XT + (seg & 1) * 8;
            if (half == 0) mbar_expect_tx(bar, 32768);
            asm volatile("cp.async.bulk.tensor.3d.shared::cluster.global.mbarrier::complete_tx::bytes [%0], [%1, {%3, %4, %5}], [%2];"
                         ::"r"(sb + SM_XT + (seg & 1) * 32768 + half * 16384), "l"(&mapX), "r"(bar), "r"(0), "r"(seg * SEG), "r"(8 * kh + 4 * (half ^ kflip)) : "memory");
        };
        if (warp == 8) {
            const CUtensorMap* ws = kh ? &mapWq : &mapWk;
            const CUtensorMap* wn = kh ? &mapWk : &mapWq;
            const uint64_t pol = EF_W ? policy_evict_first() : policy_evict_normal();
            const int col = h * DH + 64 * nh, row = 512 * kh;
            if (lane == 0) { mbar_expect_tx(sb + MB_W0, 49152); mbar_expect_tx(sb + MB_W1, 49152); mbar_expect_tx(sb + MB_W4, 49152); mbar_expect_tx(sb + MB_W2, 49152); mbar_expect_tx(sb + MB_W3, 65536); }
            __syncwarp();
            if (lane < 24) {
                const int k = lane ^ (16 * kflip);
                tma_load_2d(sb + STG_V + lane * 2048, &mapWv, col, row + 16 * k, sb + MB_W0, pol);
                tma_load_2d(sb + stg_qk(0, lane), ws, col, row + 16 * k, sb + MB_W1, pol);
                tma_load_2d(sb + stg_qk(1, lane), wn, col, row + 16 * k, sb + MB_W4, pol);
            }
            if (lane < 8) {
                const int k = (24 + lane) ^ (16 * kflip);
                tma_load_2d(sb + SM_WQK + lane * 4096, ws, col, row + 16 * k, sb + MB_W2, pol);
                tma_load_2d(sb + SM_WQK + lane * 4096 + 2048, wn, col, row + 16 * k, sb + MB_W2, pol);
                tma_load_2d(sb + SM_WV + lane * 2048, &mapWv, col, row + 16 * k, sb + MB_W2, pol);
            }
            __syncwarp();
        }
        if (warp == 9) {
            bar_sync(BAR_XT0, 160);
            if (lane == 0) { load_xt(0, 0); load_xt(0, 1); }
            __syncwarp();
        }
        if (warp == 10 && lane == 0) {
            wait_prerequisites();
            launch_dependents();
            sts32(sb + SM_ROLE + 4, g_reg[1]);
        }
        __syncwarp();
        bar_sync(BAR_PDONE, 384);
        KT_MARK(9);
        if (warp == 8) {
            const uint32_t dst = lane < 14 ? stg_wo(lane) : lane < 16 ? SM_WO1 + (lane - 8) * 2048 : SM_WO2 + (lane - 16) * 2048;
            tma_load_2d(sb + dst, &mapWo, 256 * j + 64 * (lane >> 3), h * DH + 16 * (lane & 7), sb + MB_W3, EF_W ? policy_evict_first() : policy_evict_normal());
        }
        if ((warp & 1) == 0) for (int c = (warp - 8) * 16 + lane; c < 512; c += 64) {
            uint32_t w[4];
#pragma unroll
            for (int r = 0; r < 4; r++) {
                const uint32_t lo = reinterpret_cast<const uint16_t*>(mem0)[(2 * r) * DM + 512 * kh + c], hi = reinterpret_cast<const uint16_t*>(mem0)[(2 * r + 1) * DM + 512 * kh + c];
                w[r] = lo | (hi << 16);
            }
            sts128(sb + SM_Z + (c ^ (256 * kflip)) * 16, make_uint4(w[0], w[1], w[2], w[3]));
        }
        auto tok_start = [&](int s) {
            if (lane == 0) {
                if (TS_AT == 0) TL(21);
                if (s > -3 && (OTMA || s + 2 < NSEG)) {
                    mbar_wait(sb + MB_STG, (s + 2) & 1);
                    if (TS_AT == 1) TL(21);
                    if (TS_AT == 2) TL(21);
                    asm volatile("fence.proxy.async.shared::cta;" ::: "memory");
                    if (TS_AT == 3) TL(21);
                    const int r = ((s + 2) & 3) * NH + h;
                    if (s + 2 < NSEG) {
                        tma_store_2d(kh ? &mapT32 : &mapTQ, sb + SM_STG, kh ? 64 * nh : 256 * nh, kh ? r * 96 + 32 : r * 12);
                        tma_store_2d(&mapT16, sb + SM_STG + 4096, 64 * nh, r * 96 + 64 + 16 * kh);
                    }
                    if (OTMA && s > 0) tma_store_3d(&mapO8, sb + SM_OT, 0, (s - 1) * SEG + 8 * j, 4 * h);
                    asm volatile("cp.async.bulk.commit_group;" ::: "memory");
                    if (TS_AT == 4) TL(21);
                }
                if (s + 4 < NSEG) load_xt(s + 4, 0);
                if (s < 0) asm volatile("cp.async.bulk.wait_group.read 0;" ::: "memory");
                if (s < 0) {
                    asm volatile("mbarrier.arrive.shared::cluster.b64 _, [%0];" ::"r"(rsb + MB_FREE) : "memory");
                    mbar_wait(sb + MB_FREE, (s + 3) & 1);
                }
            }
            __syncwarp();
        };
        auto tok_mid = [&](int s) {
            if (lane == 0) {
                if (s + 4 < NSEG) load_xt(s + 4, 1);
                if (s > -3 && s + 2 < NSEG) {
                    asm volatile("cp.async.bulk.wait_group 0;" ::: "memory");
                    st_relaxed_u32(g_xflag + role, s + 3);
                }
            }
            __syncwarp();
        };
        auto kv_check = [&](int s) {
            if (s + 1 < NSEG) {
                if (lane < 4) {
                    unsigned f; int guard = 0;
                    do {
                        asm volatile("ld.acquire.gpu.global.u32 %0, [%1];" : "=r"(f) : "l"(g_xflag + h * 4 + lane) : "memory");
                        if (++guard > (1 << 20)) __trap();
                    } while (f <= (unsigned)(s + 1));
                }
                __syncwarp();
                asm volatile("fence.proxy.async.global;" ::: "memory");
            }
        };
        auto kv_load = [&](int s) {
            if (lane == 0 && s + 1 < NSEG) {
                const uint32_t bar = sb + MB_KV + ((s + 1) & 1) * 8, dst = sb + SM_KV + ((s + 1) & 1) * KV_BYTES;
                const int row = (((s + 1) & 3) * NH + h) * 96;
                mbar_expect_tx(bar, KV_BYTES);
                asm volatile("cp.async.bulk.tensor.3d.shared::cluster.global.mbarrier::complete_tx::bytes.multicast::cluster [%0], [%1, {%3, %4, %3}], [%2], %5;"
                             ::"r"(dst + kh * 8192), "l"(&mapKV), "r"(bar), "r"(0), "r"(row + 32 + 32 * kh), "h"((uint16_t)3) : "memory");
                bulk_load(dst + 16384, g_tok + row * DH + j * 1024, 2048, bar);
            }
            __syncwarp();
        };
        if (warp == 9) {
#pragma unroll 1
            for (int s = -3; s < 0; s++) { tok_start(s); KT_MARK(13 + s); bar_arrive(BAR_PRO, 288); tok_mid(s); }
        }
        if (warp == 11) { kv_check(-1); kv_load(-1); }
        bar_arrive(BAR_MEM, 384);
        const uint32_t idx = (pair & 31) + 32 * (kh ^ 1);
        const uint32_t ybox = mlo + page_off(idx, cls ^ YFLIP_()), xoth = mlo + WIN + page_off((pair & 31) ^ 1, cls ^ XFLIP);
        const uint32_t zline = mlo + WIN + page_off(32 + (idx >> 5), cls ^ ZFLIP) + (idx & 31) * 128, zbox = mlo + WIN + (page_off(32 + kh, 0) & ~4096u);
        const uint32_t xtype = g == GV ? 2 : g == 2 ? 0 : 1;
        const uint32_t ydst = (lane >> 3) * 128 + ((lane & 7) ^ (lane >> 3)) * 16, ysrc = lane * 128 + ((2 * g) ^ (lane & 7)) * 16;
#pragma unroll 1
        for (int s = 0; s < NSEG; s++) {
            const uint32_t slot = (s & 3) << 14;
            if (g == 3) {
                kv_check(s);
                if (TS_AT == 9) TL(21);
                const uint32_t L = l16, kvo = (s & 1) * KV_BYTES, qa = QFRAG(), sa = sb + SM_S + 512 + (L >> 2);
                float sc[4] = {0.f, 0.f, 0.f, 0.f}, sd[4] = {0.f, 0.f, 0.f, 0.f};
                uint32_t a[4][4], kb[2][4];
                mbar_wait_w(sb + MB_KV + (s & 1) * 8, (s >> 1) & 1);
                mbar_wait_w(sb + MB_P, s & 1);
#pragma unroll
                for (int c = 0; c < 2; c++) {
                    const uint32_t qc = qa + (sb + (nh ^ c) * 1024), kc = L + (sb + SM_QKV + 2048 + (nh ^ c) * 1024);
                    if (TS_AT == 7 && c) TL(21);
                    if (c) bar_sync(BAR_QK, 224);
                    ldsm4t(kb[0], kc); ldsm4t(a[0], qc); ldsm4t(a[1], qc + 256);
                    ldsm4t(kb[1], kc + 512); ldsm4t(a[2], qc + 512); ldsm4t(a[3], qc + 768);
                    mma16816v(sc, a[0], kb[0][0], kb[0][1]);
                    mma16816v(sd, a[1], kb[0][2], kb[0][3]);
                    mma16816v(sc, a[2], kb[1][0], kb[1][1]);
                    mma16816v(sd, a[3], kb[1][2], kb[1][3]);
                }
                sts32(sa, scale_scores(sc[0] + sd[0], sc[1] + sd[1]));
                sts32(sa + 768, scale_scores(sc[2] + sd[2], sc[3] + sd[3]));
                bar_arrive(BAR_S, 160);
                TL(25);
                bar_sync(BAR_SV, NSV);
                kv_load(s);
                if (lane == 0 && s + 3 < NSEG) {
                    asm volatile("fence.proxy.async.shared::cta;" ::: "memory");
                    asm volatile("cp.async.bulk.shared::cluster.shared::cta.mbarrier::complete_tx::bytes [%0], [%1], %2, [%3];" ::"r"(rsb + SM_RT), "r"(sb + SM_Z), "n"(8192), "r"(rsb + MB_RT0) : "memory");
                    if (TS_AT == 10) { mbar_wait(sb + MB_RT0, (s + 3) & 1); TL(21); }
                }
                __syncwarp();
            } else {
                if (g == 1) { tok_start(s); if (TS_AT == 5) TL(21); if (s == 0) KT_MARK(13); }
                const char* p = make_ptr(l16 + (xoth + xtype * 1024 + slot), mhi);
                uint4 v[2];
                const uint32_t dst = l16 + (sb + SM_QKV + xtype * 2048 + (nh ^ 1) * 1024);
                asm volatile("" ::"l"(p));
                poll_init(v[0]); poll_init(v[1]);
                if (g == GV) {
                    bar_sync(BAR_PUBV, 160);
                    mbar_wait_w(sb + MB_V, s & 1);
                    spin_cycles(DLY_V);
                } else {
                    bar_sync(BAR_PUB, 192);
                    spin_cycles(DLY_X);
                }
                const int r = poll2(v, p);
                sts128(dst, v[0]); sts128(dst + 512, v[1]);
                STAT(1, r > 1 && warp == 10);
                if (g != GV) bar_arrive(BAR_QK, 224);
                if (TS_AT == 6 && g == 0) TL(21);
                if (OTMA && g == 1) asm volatile("cp.async.bulk.wait_group.read 0;" ::: "memory");
                if (g == GV) { bar_arrive(BAR_V, 160); if (GV == 0) bar_arrive(BAR_SV, NSV); TL(17); }
                if (g == 1) {
                    TL(31);
                    if (!OTMA) asm volatile("cp.async.bulk.wait_group.read 0;" ::: "memory");
                    bar_sync(BAR_SV, NSV);
                    tok_mid(s);
                    TL(22);
                }
                if (g == 2 && s >= 1) {
                    TL(16);
                    const uint32_t prev = (slot - 0x4000) & 0xC000;
                    const char* y = make_ptr(l16 + (ybox + prev), mhi);
                    const char* x = make_ptr(l16 + (xoth + prev + kh * 1536), mhi);
#pragma unroll
                    for (int i = 0; i < 8; i++) st_sent(y + i * 512);
#pragma unroll
                    for (int i = 0; i < 3; i++) st_sent(x + i * 512);
                    st_relaxed_u32(make_ptr(lane * 4 + (zline + (slot ^ 0x8000)), mhi), SENT);
                    TL(23);
                }
            }
            if (s + 1 == NSEG) break;
            {
                const char* p = make_ptr(l16 + (ybox + g * 1024 + slot), mhi);
                char* zdst = make_ptr(lane * 4 + (zline + g * 32 + slot), mhi);
                const uint32_t dst = ydst + (sb + SM_Y + g * 1024), dst1 = (ydst ^ 64) + (sb + SM_Y + g * 1024 + 512), src = ysrc + (sb + SM_Y), src1 = (ysrc ^ 16) + (sb + SM_Y);
                asm volatile("" ::"l"(p), "l"(zdst));
                uint4 v[2];
                poll_init(v[0]); poll_init(v[1]);
                bar_sync(BAR_SENTC, 384);
                spin_cycles(DLY_Y);
                const int r = poll2(v, p);
                STAT(2, r > 1 && warp == 8);
                sts128(dst, v[0]); sts128(dst1, v[1]);
                bar_sync(BAR_Y, 256);
                TL(18);
                uint32_t b[2][4];
                ldsm4t(b[0], src); ldsm4t(b[1], src1);
                const uint32_t one = 0x3F803F80u;
                float d0[4] = {0.f, 0.f, 0.f, 0.f}, d1[4] = {0.f, 0.f, 0.f, 0.f};
                mma16816(d0, one, one, one, one, b[0][0], b[0][1]);
                mma16816(d1, one, one, one, one, b[1][0], b[1][1]);
                mma16816(d0, one, one, one, one, b[0][2], b[0][3]);
                mma16816(d1, one, one, one, one, b[1][2], b[1][3]);
                const uint32_t w = (lane & 4) ? pack_bf16(d1[0], d1[1]) : pack_bf16(d0[0], d0[1]);
                asm volatile("{.reg .pred p; setp.lt.u32 p, %2, 128; @p st.relaxed.gpu.global.u32 [%0], %1;}" ::"l"(zdst), "r"(w), "r"(l16) : "memory");
                if (s + 3 < NSEG) bar_arrive(BAR_ZP, 256);
                TL(19);
            }
            {
                const char* p = make_ptr(l16 + (zbox + g * 512 + slot), mhi);
                const uint32_t dst = l16 + (sb + SM_Z + g * 512);
                asm volatile("" ::"l"(p));
                uint4 v[4];
                poll_init(v[0]); poll_init(v[1]); poll_init(v[2]); poll_init(v[3]);
                bar_sync(BAR_COMM, 128);
                spin_cycles(DLY_Z);
                const int r = poll4<2048>(v, p);
                STAT(0, r > 1 && warp == 8);
#pragma unroll
                for (int i = 0; i < 4; i++) sts128(dst + i * 2048, v[i]);
                bar_arrive(BAR_MEM, 384);
                TL(20);
            }
        }
        if ((OTMA || TAIL) && (TM & 4) && COLD()) {
            uint32_t t, rank;
            asm volatile("mov.u32 %0, %%tid.x; mov.u32 %1, %%ctaid.x; and.b32 %1, %1, 1;" : "=r"(t), "=r"(rank));
            const uint32_t base = SB0 | (rank << 24), ln = t & 31, pr = lds32(base + SM_ROLE), col = (pr & 7) * 128, tg = pr >> 3;
            if (t < 288) {
                if (TAIL) {
                mbar_wait_w(base + MB_V, (NSEG - 1) & 1);
                pj_fetch(base, ln, 0, 32, tg == 7 ? LAST_N : TILE_N, &mapPW, &mapPO, col + 64 * (rank ^ 1), col + 64 * rank, HD / 2 * rank, EARLY_TOK + tg * TILE_N, [&]() {
                    const unsigned need = tg == 7 ? FLAG_END : (S_LEN - LAST_N) / SEG + 3;
                    for (int guard = 0; guard < (1 << 20); guard++) {
                        uint32_t f0, f1;
                        asm volatile("{.reg .b64 t; ld.acquire.gpu.global.b64 t, [%2]; mov.b64 {%0, %1}, t;}" : "=r"(f0), "=r"(f1) : "l"(g_xflag + 64 * rank + 2 * ln) : "memory");
                        if (__all_sync(~0u, min(f0, f1) >= need)) break;
                    }
                    asm volatile("fence.proxy.async.global;" ::: "memory");
                });
                }
            } else if (t < 320) {
                bar_sync(BAR_ZP, 160);
                if (ln == 0) {
                    if (OTMA) {
                        asm volatile("fence.proxy.async.shared::cta;" ::: "memory");
                        tma_store_3d(&mapO8, base + SM_OT, 0, S_LEN - SEG + 16 * (pr & 1) + 8 * rank, 2 * (pr & ~1u));
                        asm volatile("cp.async.bulk.commit_group;" ::: "memory");
                    }
                    if (OTMA) asm volatile("cp.async.bulk.wait_group 0;" ::: "memory");
                    if (TAIL) asm volatile("mbarrier.arrive.shared::cluster.b64 _, [%0];" ::"r"((base ^ (1u << 24)) + MB_FREE) : "memory");
                    if (!OTMA) asm volatile("fence.acq_rel.gpu;" ::: "memory");
                    if (TAIL) st_relaxed_u32(g_xflag + 2 * pr + rank, FLAG_END);
                }
                __syncwarp();
            }
        }
    } else if (warp < 4) {
        asm volatile("setmaxnreg.inc.sync.aligned.u32 %0;" ::"n"(REG_A));
        code_pad<PAD_A>();
        const uint32_t l16 = lane16();
        uint32_t wa[2][24][4];
        {
            const uint32_t L = l16, fa = sb + FRAG();
            mbar_wait_w(sb + MB_W1, 0);
            KT_MARK(7);
#pragma unroll
            for (int t = 0; t < 2; t++) {
#pragma unroll
                for (int r = 0; r < 24; r++) ldsm4t(wa[t][r], fa + stg_qk(t, r));
                if (t == 0) { bar_arrive(BAR_XT0, 160); mbar_wait_w(sb + MB_W4, 0); }
            }
            mbar_wait_w(sb + MB_W2, 0);
            bar_sync(BAR_PDONE, 384);
        }
        auto batch1 = [&](float (&d)[16], uint32_t lo, auto tc, auto k0c, auto k1c) {
            constexpr int t = decltype(tc)::value;
            const uint64_t da = make_desc(SB0 + SM_WQK, 16, 1024);
            wg_fence();
            static_for<decltype(k0c)::value, decltype(k1c)::value>([&](auto kc) {
                constexpr int i = decltype(kc)::value, k = kstep(t ? ORD1 : ORD0, i), off = (k >> 2) * 256 + (k & 3) * 2;
                if constexpr (k >= 24) wgmma_ss32u<off, i != 0 || t != 0>(d, da + ((k - 24) * 2 + t) * 128, lo);
                else wgmma_rs32u<off, i != 0 || t != 0>(d, wa[t][k], lo);
            });
            wg_commit();
        };
        const uint32_t xbox = mlo + WIN + page_off(pair & 31, cls ^ XFLIP);
        const uint32_t ybox = mlo + page_off(24 + 2 * g + 32 * nh, kh ^ YFLIP_()) + h * 128;
#pragma unroll 1
        for (uint32_t it = 0; it < NSEG + 3; it++) {
            const int s = (int)it - 3;
            const uint32_t ui = uniform(it), slot = ((ui + 1) & 3) << 14, kvo = (~ui & 1) * KV_BYTES, xtlo = XTLO();
            {
                PHASE(5);
                const uint32_t first = L | (g << 9);
                if (s >= 0) mbar_expect_tx_if0(first, sb + MB_R1, 2048);
                if (s + 3 < NSEG) {
                    mbar_expect_tx_if0(first, sb + MB_RT0, 8192);
                    mbar_wait_w(sb + MB_XT + (ui & 1) * 8, (it >> 1) & 1);
                }
            }
            if (s >= 0) {
                PHASE(0);
                const uint32_t mb = L + (sb + SM_Z), ra = L + (sb + g * 512), r1 = L + (rsb + SM_R1 + g * 512), r1b = rsb + MB_R1;
                sched_fence(r1);
                bar_sync(BAR_MEM, 384);
                TLB(0);
                float acc[2][2][4];
#pragma unroll
                for (int t = 0; t < 4; t++) { acc[t >> 1][t & 1][0] = acc[t >> 1][t & 1][1] = acc[t >> 1][t & 1][2] = acc[t >> 1][t & 1][3] = 0.f; }
                uint32_t b[4][4];
                uint4 u0, u1;
#pragma unroll
                for (int p = 0; p < 4; p++) ldsm4t(b[p], mb + p * 512);
#pragma unroll
                for (int p = 0; p < 12; p++) {
#pragma unroll
                    for (int u = 0; u < 2; u++) {
                        mma16816v(acc[0][u], wa[0][2 * p + u], b[p & 3][2 * u], b[p & 3][2 * u + 1]);
                        mma16816v(acc[1][u], wa[1][2 * p + u], b[p & 3][2 * u], b[p & 3][2 * u + 1]);
                    }
                    if (p + 4 < 12) ldsm4t(b[p & 3], mb + (p + 4) * 512);
                    if (p == Q3_AT) {
                        bar_sync(BAR_Q3, 256);
                        u0 = lds128(ra + SM_R3); u1 = lds128(ra + SM_O);
                    }
                }
                st_async4(r1, (acc[0][0][0] + __uint_as_float(u0.x)) + acc[0][1][0], (acc[0][0][1] + __uint_as_float(u0.y)) + acc[0][1][1],
                          (acc[0][0][2] + __uint_as_float(u0.z)) + acc[0][1][2], (acc[0][0][3] + __uint_as_float(u0.w)) + acc[0][1][3], r1b);
                TL(1);
                const float o0 = (acc[1][0][0] + __uint_as_float(u1.x)) + acc[1][1][0], o1 = (acc[1][0][1] + __uint_as_float(u1.y)) + acc[1][1][1];
                const float o2 = (acc[1][0][2] + __uint_as_float(u1.z)) + acc[1][1][2], o3 = (acc[1][0][3] + __uint_as_float(u1.w)) + acc[1][1][3];
                const uint32_t l4 = L >> 2, qo = SM_QKV + kh * 2048 + nh * 1024 + g * 256, qr = l4 + (rsb + qo), ql = l4 + (sb + qo), pb = rsb + MB_P;
                char* xd = make_ptr(l4 + (xbox + kh * 1024 + g * 256 + slot), mhi);
                asm volatile("" ::"l"(xd), "r"(qr), "r"(pb), "r"(qr + 128), "f"(o0), "f"(o1), "f"(o2), "f"(o3));
                mbar_wait_w(sb + MB_R1, s & 1);
                const uint4 v = lds128(ra + SM_R1);
                const uint32_t w0 = pack_bf16(o0 + __uint_as_float(v.x), o1 + __uint_as_float(v.y)), w1 = pack_bf16(o2 + __uint_as_float(v.z), o3 + __uint_as_float(v.w));
                st_relaxed_u32(xd, w0);
                st_relaxed_u32(xd + 128, w1);
                bar_arrive(BAR_PUB, 192);
                st_async1(qr, w0, pb);
                st_async1(qr + 128, w1, pb);
                sts32(ql, w0);
                sts32(ql + 128, w1);
                __syncwarp();
                mbar_expect_tx_if0(L, sb + MB_P, 256);
                TL(2);
                if (s + 3 < NSEG) bar_sync(BAR_VP, 256);
            } else {
                bar_sync(BAR_PRO, 288);
            }
            if (s + 3 < NSEG) {
                float d[16];
                batch1(d, xtlo, std::integral_constant<int, 0>(), std::integral_constant<int, 0>(), std::integral_constant<int, 32>());
                PHASE(1);
                const uint32_t rt = L + (rsb + SM_RT + g * 2048);
                wg_wait<0>();
                TL(7);
                if (s >= 0) {
                    const uint32_t pk = L + (sb + SM_Z + g * 2048);
#pragma unroll
                    for (int i = 0; i < 4; i++) sts128(pk + i * 512, make_uint4(__float_as_uint(d[4 * i]), __float_as_uint(d[4 * i + 1]), __float_as_uint(d[4 * i + 2]), __float_as_uint(d[4 * i + 3])));
                } else {
#pragma unroll
                    for (int i = 0; i < 4; i++) st_async4(rt + i * 512, d[4 * i], d[4 * i + 1], d[4 * i + 2], d[4 * i + 3], rsb + MB_RT0);
                }
            }
            if (s + 1 == NSEG) { bar_arrive(BAR_SV, NSV); break; }
            if (s >= 0) {
                PHASE(2);
                const uint32_t fo = FRAG() + (sb + SM_WO2 + 16384), lo = L + (sb + SM_O), yo = (L >> 2) + (ybox + slot);
                uint32_t a1[8][4];
                bar_sync(BAR_SV, NSV);
#pragma unroll
                for (int k = 0; k < 8; k++) ldsm4t(a1[k], fo + k * 2048);
                sched_fence(yo);
                bar_sync(BAR_O2, 256);
                TLB(14);
                float y0[4] = {0.f, 0.f, 0.f, 0.f}, y1[4] = {0.f, 0.f, 0.f, 0.f};
                uint32_t b[2][4];
                ldsm4t(b[0], lo); ldsm4t(b[1], lo + 512);
                sched_fence(L);
#pragma unroll
                for (int p = 0; p < 4; p++) {
                    mma16816v(y0, a1[2 * p], b[p & 1][0], b[p & 1][1]);
                    mma16816v(y1, a1[2 * p + 1], b[p & 1][2], b[p & 1][3]);
                    if (p < 2) ldsm4t(b[p & 1], lo + (p + 2) * 512);
                }
                bar_sync(BAR_INV, 256);
                float i0, i1;
                asm volatile("ld.shared.v2.f32 {%0, %1}, [%2];" : "=f"(i0), "=f"(i1) : "r"(((L >> 1) & 0x18) + (sb + SM_INV + g * 32)) : "memory");
                st_relaxed_u32(make_ptr(yo, mhi), pack_bf16((y0[0] + y1[0]) * i0, (y0[1] + y1[1]) * i1));
                st_relaxed_u32(make_ptr(yo ^ 4096, mhi) + 0x2000, pack_bf16((y0[2] + y1[2]) * i0, (y0[3] + y1[3]) * i1));
                bar_arrive(BAR_SENTC, 384);
                TL(6);
            }
            if (s + 3 < NSEG) {
                PHASE(4);
                float d[16];
                const uint32_t rt = L + (sb + SM_RT + g * 2048);
                if (s >= 0) bar_sync(BAR_SENT, 256);
                mbar_wait_w(sb + MB_RT0, it & 1);
                if (s >= 0) bar_arrive(BAR_Y, 256);
                if (RT0_B && s >= 0) bar_arrive(BAR_VP, 256);
#pragma unroll
                for (int i = 0; i < 4; i++) {
                    const uint4 v = lds128(rt + i * 512);
                    d[4 * i] = __uint_as_float(v.x); d[4 * i + 1] = __uint_as_float(v.y); d[4 * i + 2] = __uint_as_float(v.z); d[4 * i + 3] = __uint_as_float(v.w);
                }
                if (SPLIT > 0) batch1(d, xtlo, std::integral_constant<int, 1>(), std::integral_constant<int, 0>(), std::integral_constant<int, SPLIT>());
                if (s >= 0) bar_sync(BAR_ZP, 256);
                TLB(30);
                batch1(d, xtlo, std::integral_constant<int, 1>(), std::integral_constant<int, SPLIT>(), std::integral_constant<int, 32>());
                const uint32_t so = (kh ? FRAG() : ((L & 0x100) << 2) + (L & 0xF0) + g * 256) + (sb + SM_STG);
                wg_wait<0>();
                TL(8);
                uint32_t w[8];
#pragma unroll
                for (int i = 0; i < 8; i++) w[i] = pack_bf16(d[2 * i], d[2 * i + 1]);
                if (kh) {
                    stsm4t(so, w[0], w[1], w[2], w[3]);
                    stsm4t(so + 2048, w[4], w[5], w[6], w[7]);
                } else {
                    stsm4(so, w[0], w[1], w[2], w[3]);
                    stsm4(so + 2048, w[4], w[5], w[6], w[7]);
                }
                __syncwarp();
                mbar_arrive_if0(L, sb + MB_STG);
                TL(9);
            } else {
                bar_arrive(BAR_SENT, 256);
                bar_arrive(BAR_Y, 256);
                if (OTMA) mbar_arrive_if0(l16, sb + MB_STG);
            }
        }
        if (TAIL && (TM & 1) && COLD()) last_tile(0);
    } else {
        asm volatile("setmaxnreg.inc.sync.aligned.u32 %0;" ::"n"(REG_B));
        code_pad<PAD_B>();
        const uint32_t l16 = lane16();
        uint32_t wv[24][4], wo[8 + WO_RF1][4];
        {
            const uint32_t L = l16, fa = sb + FRAG();
            mbar_wait_w(sb + MB_W0, 0);
            KT_MARK(6);
#pragma unroll
            for (int r = 0; r < 24; r++) ldsm4t(wv[r], fa + STG_V + r * 2048);
#pragma unroll
            for (int r = 0; r < 8 + WO_RF1; r++) asm volatile("" : "=r"(wo[r][0]), "=r"(wo[r][1]), "=r"(wo[r][2]), "=r"(wo[r][3]));
            mbar_wait_w(sb + MB_W2, 0);
            bar_sync(BAR_PDONE, 384);
        }
        const uint32_t xbox = mlo + WIN + page_off(pair & 31, cls ^ XFLIP);
        const uint32_t ybox = mlo + page_off(2 * g + 32 * nh, kh ^ YFLIP_()) + h * 128;
#pragma unroll 1
        for (uint32_t it = 0; it < NSEG + 3; it++) {
            const int s = (int)it - 3;
            const uint32_t ui = uniform(it), slot = ((ui + 1) & 3) << 14, kvo = (~ui & 1) * KV_BYTES, xtlo = XTLO();
            {
                PHASE(5);
                const uint32_t first = L | (g << 9);
                if (s >= 0) mbar_expect_tx_if0(first, sb + MB_R2, 1024);
                if (s + 3 < NSEG) {
                    mbar_expect_tx_if0(first, sb + MB_RT1, 2048);
                    mbar_wait_w(sb + MB_XT + (ui & 1) * 8, (it >> 1) & 1);
                }
            }
            if (s >= 0) {
                PHASE(0);
                uint32_t fr = FRAG();
                asm("" : "+r"(fr));
                const uint32_t fo = fr + sb, l4 = L >> 2;
                {
                    const uint32_t mb = L + (sb + SM_Z), aw = fo + SM_WQK, ra = L + (sb + g * 512), r2 = (L >> 1) + (rsb + SM_R2 + g * 256), r2b = rsb + MB_R2;
                    uint32_t a[NA][4], b[4][4];
#pragma unroll
                    for (int i = 0; i < NA; i++) ldsm4t(a[i], aw + i * 2048);
                    sched_fence(L);
                    TL(24);
                    bar_sync(BAR_MEM, 384);
#pragma unroll
                    for (int p = 0; p < 4; p++) ldsm4t(b[p], mb + (12 + p) * 512);
                    sched_fence(L);
                    float c[2][4] = {{0.f, 0.f, 0.f, 0.f}, {0.f, 0.f, 0.f, 0.f}};
#pragma unroll
                    for (int i = 0; i < 16; i++) {
                        mma16816v(c[i & 1], a[i % NA], b[i >> 2][i & 2], b[i >> 2][(i & 2) + 1]);
                        ldsm4t(a[i % NA], aw + (i + NA) * 2048);
                    }
                    sts128(ra + SM_R3, make_uint4(__float_as_uint(c[0][0]), __float_as_uint(c[0][1]), __float_as_uint(c[0][2]), __float_as_uint(c[0][3])));
                    sts128(ra + SM_O, make_uint4(__float_as_uint(c[1][0]), __float_as_uint(c[1][1]), __float_as_uint(c[1][2]), __float_as_uint(c[1][3])));
                    bar_arrive(BAR_Q3, 256);
                    TL(29);
                    float acc[4][4];
#pragma unroll
                    for (int t = 0; t < 4; t++) { acc[t][0] = acc[t][1] = acc[t][2] = acc[t][3] = 0.f; }
#pragma unroll
                    for (int i = 16; i < 24; i++) {
                        mma16816v(acc[i & 1], a[i % NA], b[(i - 16) >> 1][2 * (i & 1)], b[(i - 16) >> 1][2 * (i & 1) + 1]);
                        if (i + NA < 24) ldsm4t(a[i % NA], aw + (i + NA) * 2048);
                        else ldsm4t(a[i % NA], mb + (i + NA - 24) * 512);
                    }
#pragma unroll
                    for (int p = 0; p < 12; p++) {
                        mma16816v(acc[(2 * p) & 3], wv[2 * p], a[(24 + p) % NA][0], a[(24 + p) % NA][1]);
                        mma16816v(acc[(2 * p + 1) & 3], wv[2 * p + 1], a[(24 + p) % NA][2], a[(24 + p) % NA][3]);
                        if (p + NA < 12) ldsm4t(a[(24 + p) % NA], mb + (p + NA) * 512);
                    }
                    if (s + 3 < NSEG) bar_arrive(BAR_VP, 256);
                    float o[4];
#pragma unroll
                    for (int i = 0; i < 4; i++) o[i] = (acc[0][i] + acc[1][i]) + (acc[2][i] + acc[3][i]);
                    st_async2(r2, kh ? o[0] : o[2], kh ? o[1] : o[3], r2b);
                    TL(10);
                    const float o0 = kh ? o[2] : o[0], o1 = kh ? o[3] : o[1];
                    const uint32_t qo = SM_QKV + 4096 + nh * 1024 + (2 * g + kh) * 128, qr = l4 + (rsb + qo), ql = l4 + (sb + qo), vb = rsb + MB_V, rl = (L >> 1) + (sb + SM_R2 + g * 256);
                    char* xd = make_ptr(l4 + (xbox + 2048 + (2 * g + kh) * 128 + slot), mhi);
                    asm volatile("" ::"l"(xd), "r"(qr), "r"(vb), "f"(o0), "f"(o1));
                    mbar_wait_w(sb + MB_R2, s & 1);
                    uint32_t vx, vy;
                    asm volatile("ld.shared.v2.u32 {%0,%1}, [%2];" : "=r"(vx), "=r"(vy) : "r"(rl) : "memory");
                    const uint32_t w0 = pack_bf16(o0 + __uint_as_float(vx), o1 + __uint_as_float(vy));
                    st_relaxed_u32(xd, w0);
                    bar_arrive(BAR_PUBV, 160);
                    st_async1(qr, w0, vb);
                    sts32(ql, w0);
                    __syncwarp();
                    mbar_expect_tx_if0(L, sb + MB_V, 128);
                    TL(11);
                }
                const uint32_t vma = L + (sb + SM_QKV + 4096 + g * 512), yo = l4 + (ybox + slot);
                uint32_t va[2][2][4];
                {
                    const uint32_t qa = QFRAG(), vf = fr ^ ((g << 5) ^ ((g & 1) << 6)), va0 = vf + VBASE(), va1 = (vf ^ 32) + VBASE();
                    const uint32_t kf = ((L << 3) & 0x380) | ((L ^ (L >> 3)) & 0x30) | (L & 0x40), kb0 = sb + SM_KV + kvo + g * 1024;
                    const int d = (int)(L >> 6) - (int)((L >> 3) & 6) + 8 * (j - (int)g);
                    const uint32_t keep = (d < 0 ? 0u : 0xFFFFu) | (d < 1 ? 0u : 0xFFFF0000u), sa = l4 + (sb + SM_S + g * 128);
                    const uint32_t q0 = qa + (sb + nh * 1024), q1 = qa + (sb + (nh ^ 1) * 1024);
                    float sc[4] = {0.f, 0.f, 0.f, 0.f}, sd[4] = {0.f, 0.f, 0.f, 0.f};
                    uint32_t a[4][4], kb[2][4];
                    mbar_wait_w(sb + MB_KV + (~ui & 1) * 8, (s >> 1) & 1);
                    ldsm4(kb[0], kf + (kb0 + nh * 4096)); ldsm4(kb[1], (kf ^ 64) + (kb0 + nh * 4096));
                    mbar_wait_w(sb + MB_P, s & 1);
                    TL(12);
#pragma unroll
                    for (int k = 0; k < 4; k++) ldsm4t(a[k], q0 + k * 256);
#pragma unroll
                    for (int k = 0; k < 4; k++) mma16816v((k & 1) ? sd : sc, a[k], kb[k >> 1][2 * (k & 1)], kb[k >> 1][2 * (k & 1) + 1]);
                    ldsm4(kb[0], kf + (kb0 + (nh ^ 1) * 4096)); ldsm4(kb[1], (kf ^ 64) + (kb0 + (nh ^ 1) * 4096));
                    sched_fence(vf | yo);
                    if (TS_AT == 8) TL(21);
                    bar_sync(BAR_QK, 224);
                    TLB(3);
#pragma unroll
                    for (int k = 0; k < 4; k++) ldsm4t(a[k], q1 + k * 256);
                    sched_fence(L);
#pragma unroll
                    for (int k = 0; k < 4; k++) mma16816v((k & 1) ? sd : sc, a[k], kb[k >> 1][2 * (k & 1)], kb[k >> 1][2 * (k & 1) + 1]);
                    ldsm4t(va[0][0], va0); ldsm4t(va[0][1], va0 + 2048);
                    sts32(sa, scale_scores(sc[0] + sd[0], sc[1] + sd[1]));
                    sts32(sa + 768, (scale_scores(sc[2] + sd[2], sc[3] + sd[3]) & keep) | (0xFF80FF80u & ~keep));
                    bar_arrive(BAR_SV, NSV);
                    ldsm4t(va[1][0], va1); ldsm4t(va[1][1], va1 + 2048);
                }
                bar_sync(BAR_S, 160);
                TLB(4);
                uint32_t pw[6], vm[4];
                if (s + 1 < NSEG) {
                softmax40(pw, l4 + (sb + SM_S), [&]() {
                    bar_sync(BAR_V, 160);
                    ldsm4(vm, vma);
                });
                uint32_t a1[NP2][4];
                float inv[2];
                {
                    uint32_t w[4];
                    pv32<false>(w, inv, va, vm, pw, [&]() {
                        sched_fence(L);
#pragma unroll
                        for (int k = 0; k < NP2; k++) ldsm4t(a1[k], fo + SM_WO2 + k * 2048);
                    });
#pragma unroll
                    for (int i = 0; i < 4; i++) sts32(l4 + (sb + SM_O + g * 512) + i * 128, w[i]);
                }
                const uint32_t lo = L + (sb + SM_O);
                bar_arrive(BAR_O2, 256);
                bar_sync(BAR_O, 128);
                TLB(5);
                {
                    float y0[4] = {0.f, 0.f, 0.f, 0.f}, y1[4] = {0.f, 0.f, 0.f, 0.f}, y2[4] = {0.f, 0.f, 0.f, 0.f};
                    uint32_t b[4][4];
#pragma unroll
                    for (int p = 0; p < 4; p++) ldsm4t(b[p], lo + p * 512);
                    inv[0] = rcp_approx(inv[0]); inv[1] = rcp_approx(inv[1]);
                    asm volatile("st.shared.v2.f32 [%0], {%1, %2};" ::"r"(((L >> 1) & 0x18) + (sb + SM_INV + g * 32)), "f"(inv[0]), "f"(inv[1]) : "memory");
                    bar_arrive(BAR_INV, 256);
                    sched_fence(L);
#pragma unroll
                    for (int k = 0; k < 8; k++) {
                        const int p = k >> 1, u = k & 1;
                        mma16816v(y2, a1[k % NP2], b[p][2 * u], b[p][2 * u + 1]);
                        if (k + NP2 < 8) ldsm4t(a1[k % NP2], fo + SM_WO2 + (k + NP2) * 2048);
                        else if (k + NP2 < 16 - WO_RF1) ldsm4t(a1[k % NP2], fo + SM_WO1 + (k + NP2 - 8 + WO_RF1) * 2048);
                        mma16816v(y0, wo[k], b[p][2 * u], b[p][2 * u + 1]);
                        if (k < WO_RF1) mma16816v(y1, wo[8 + (k < WO_RF1 ? k : 0)], b[p][2 * u], b[p][2 * u + 1]);
                        else mma16816v(y1, a1[(k + 8 - WO_RF1) % NP2], b[p][2 * u], b[p][2 * u + 1]);
                        if (k < P2_FENCE) sched_fence(L);
                    }
                    char* yd = make_ptr(yo, mhi);
                    char* yd1 = make_ptr(yo ^ 4096, mhi);
                    st_relaxed_u32(yd1 + 0x80000, pack_bf16(y2[0] * inv[0], y2[1] * inv[1]));
                    st_relaxed_u32(yd + 0x82000, pack_bf16(y2[2] * inv[0], y2[3] * inv[1]));
                    st_relaxed_u32(yd, pack_bf16(y0[0] * inv[0], y0[1] * inv[1]));
                    st_relaxed_u32(yd1 + 0x2000, pack_bf16(y0[2] * inv[0], y0[3] * inv[1]));
                    st_relaxed_u32(yd + 0x40000, pack_bf16(y1[0] * inv[0], y1[1] * inv[1]));
                    st_relaxed_u32(yd1 + 0x42000, pack_bf16(y1[2] * inv[0], y1[3] * inv[1]));
                }
                bar_arrive(BAR_SENTC, 384);
                TL(13);
                bar_sync(BAR_SENT, 256);
                } else {
                    bar_sync(BAR_V, 160);
                }
            } else {
                if (it == WO_IT) {
                    PHASE(2);
                    const uint32_t fa = sb + FRAG();
                    mbar_wait_w(sb + MB_W3, 0);
                    KT_MARK(8);
#pragma unroll
                    for (int r = 0; r < 8 + WO_RF1; r++) ldsm4t(wo[r], fa + stg_wo(r));
                }
                bar_sync(BAR_PRO, 288);
            }
            float o[8];
            uint32_t w[4];
            {
                PHASE(1);
                float d[16];
                const uint64_t da = make_desc(SB0 + SM_WV, 16, 1024);
                auto batch = [&](auto k0c, auto k1c) {
                    static_for<decltype(k0c)::value, decltype(k1c)::value>([&](auto kc) {
                        constexpr int i = decltype(kc)::value, k = kstep(ORDV, i), off = (k >> 2) * 256 + (k & 3) * 2;
                        if constexpr (k >= 24) wgmma_ss32u<off, i != 0>(d, da + (k - 24) * 128, xtlo);
                        else wgmma_rs32u<off, i != 0>(d, wv[k], xtlo);
                    });
                };
                const uint32_t vf = VFRAG(), va0 = vf + VBASE(), va1 = (vf ^ 32) + VBASE(), vma = L + (sb + SM_QKV + 4096 + g * 512), sa = (L >> 2) + (sb + SM_S + 768);
                const uint32_t rt = L + (rsb + SM_RT + 8192 + g * 512);
                uint32_t va[2][2][4], vm[4], pw[6];
                wg_fence();
                batch(std::integral_constant<int, 0>(), std::integral_constant<int, TA0>());
                wg_commit();
                batch(std::integral_constant<int, TA0>(), std::integral_constant<int, 32>());
                wg_commit();
                wg_wait<1>();
                if (RT0_B == 3 && (unsigned)s < NSEG - 3) bar_sync(BAR_VP, 256);
                softmax40(pw, sa, [&]() {});
                ldsm4t(va[0][0], va0); ldsm4t(va[0][1], va0 + 2048);
                ldsm4t(va[1][0], va1); ldsm4t(va[1][1], va1 + 2048);
                ldsm4(vm, vma);
                if (RT0_B == 1 && (unsigned)s < NSEG - 3) bar_sync(BAR_VP, 256);
                wg_wait<0>();
                if (RT0_B == 2 && (unsigned)s < NSEG - 3) bar_sync(BAR_VP, 256);
                TL(27);
                float inv[2];
                pv32<true>(w, inv, va, vm, pw, [&]() {
                    uint32_t q[4];
#pragma unroll
                    for (int i = 0; i < 4; i++) q[i] = pack_bf16(kh ? d[2 * i] : d[8 + 2 * i], kh ? d[2 * i + 1] : d[9 + 2 * i]);
                    if (RT0_B == 4 && (unsigned)s < NSEG - 3) bar_sync(BAR_VP, 256);
                    if (s + 3 < NSEG) st_async4(rt, __uint_as_float(q[0]), __uint_as_float(q[1]), __uint_as_float(q[2]), __uint_as_float(q[3]), rsb + MB_RT1);
#pragma unroll
                    for (int i = 0; i < 8; i++) o[i] = kh ? d[8 + i] : d[i];
                });
                TL(26);
            }
            if (s + 3 < NSEG) {
                PHASE(3);
                const uint32_t rt = L + (sb + SM_RT + 8192 + g * 512), so = FRAG() + (sb + SM_STG + 4096);
                mbar_wait_w(sb + MB_RT1, it & 1);
                TL(28);
                const uint4 v = lds128(rt);
                stsm4t(so, pack_bf16(o[0] + bf_lo(v.x), o[1] + bf_hi(v.x)), pack_bf16(o[2] + bf_lo(v.y), o[3] + bf_hi(v.y)),
                       pack_bf16(o[4] + bf_lo(v.z), o[5] + bf_hi(v.z)), pack_bf16(o[6] + bf_lo(v.w), o[7] + bf_hi(v.w)));
                if (!OTMA) { __syncwarp(); mbar_arrive_if0(L, sb + MB_STG); }
                TL(15);
            }
            if (OTMA) {
                PHASE(7);
                __syncwarp();
                stsm4t((((L << 2) & 0x1C0) | (((L >> 3) ^ (L >> 1)) & 0x30)) + (sb + SM_OT + g * 512), w[0], w[1], w[2], w[3]);
                __syncwarp();
                mbar_arrive_if0(L, sb + MB_STG);
            }
        }
        if ((OTMA || TAIL) && (TM & 2) && COLD()) bar_arrive(BAR_ZP, 160);
        if (TAIL && (TM & 2) && COLD()) last_tile(1);
    }
    KT_END(TAIL ? 3 : 2);
    asm volatile("barrier.cluster.arrive.relaxed; barrier.cluster.wait;" ::: "memory");
}
constexpr int B_UCH = 73 * 64;
constexpr int B_SCH = 33 * 64;
constexpr int B_KLEN = 2128;
constexpr int B_KCH = 2 * B_KLEN * 2 + 64;
constexpr int B_KBOX = 136 * 32;
constexpr int B_SM_U = 0;
constexpr int B_SM_S = 8 * B_UCH;
constexpr int B_SM_K = B_SM_S + 8 * B_SCH;
constexpr int B_SM_KT = B_SM_K + 8 * B_KCH;
constexpr int B_SM_VT = B_SM_KT + 8 * B_KBOX;
constexpr int B_SM_QT = B_SM_VT + 32768;
constexpr int B_SM_BAR = B_SM_QT + 32768;
constexpr int B_SMEM = B_SM_BAR + 128 + 512;
static_assert(B_SM_KT % 256 == 0 && B_SM_S % 512 == 0 && B_SMEM <= 232448, "tiles");
constexpr int PROBE_N = 4;
#define PROBE_R 2
constexpr int B_C = 2056;

__device__ __forceinline__ uint32_t atomic_round_trip(char* p) {
    uint32_t t0, t1, v;
    asm volatile("{.reg .pred p;\n"
                 "mov.u32 %0, %%clock;\n"
                 "atom.relaxed.gpu.global.add.u32 %2, [%3], 1;\n"
                 "setp.ne.u32 p, %2, 0x7FFFFFFF;\n"
                 "mov.u32 %1, 0;\n"
                 "@p mov.u32 %1, %%clock;}" : "=&r"(t0), "=&r"(t1), "=&r"(v) : "l"(p) : "memory");
    return t1 - t0;
}
__device__ __forceinline__ uint32_t round_trips(char* a, char* b, uint32_t stride, int lane) {
    for (int i = lane >> 3; i < 2 * PROBE_N; i += 4) stg128(((i & 1) ? b : a) + (i >> 1) * stride + (lane & 7) * 16, make_uint4(0, 0, 0, 0));
    __syncwarp();
    uint32_t ta = 0xFFFF, tb = 0xFFFF;
    if (lane == 0) {
        __threadfence();
#pragma unroll 1
        for (int i = 0; i < PROBE_N; i++) { ta = min(ta, atomic_round_trip(a + i * stride)); tb = min(tb, atomic_round_trip(b + i * stride)); }
    }
    __syncwarp();
    return ta | (tb << 16);
}
__device__ __forceinline__ void measure_distance(char* mbox, int lane) {
    const uint32_t b = blockIdx.x;
    unsigned smid;
    asm volatile("mov.u32 %0, %%smid;" : "=r"(smid));
    char* w1 = mbox + WIN + (b & 31) * 128;
    uint32_t r = 0xFFFFFFFF;
#pragma unroll 1
    for (int i = 0; i < PROBE_R; i++) r = __vminu2(r, round_trips(w1 + page_off(50 + 5 * i + (b >> 5), 0), w1 + page_off(50 + 5 * i + (b >> 5), 1), 16384, lane));
    if (lane == 0) g_cls[smid] = r;
    if (b == 128) {
        char *p = mbox + page_off(0, 0), *q = mbox + page_off(0, 1);
        uint32_t r0 = 0xFFFFFFFF;
#pragma unroll 1
        for (int i = 0; i < PROBE_R; i++) r0 = __vminu2(r0, round_trips(p, q, 128, lane));
        if (lane == 0) { g_reg[1] = ((r0 & 0xFFFF) > (r0 >> 16)) != ((r & 0xFFFF) > (r >> 16)); if (!EARLY_ROLE) g_reg[0] = 0; g_reg[2] = 0; }
        const uint4 sent = make_uint4(SENT, SENT, SENT, SENT);
        stg128(p + lane * 16, sent); stg128(q + lane * 16, sent);
    }
    if (b == 129) for (int i = lane; i < 128; i += 32) g_xflag[i] = 0;
}

#define SP(i)
#define SP2(i)
#define OUT_STG 0
#define PF_STOP 1
#define SENT_AT 3
#define Q_LATE 1
#define PF_DEPTH 4
#define PF_STRIDE 256
struct ChainInputs { const char* w[4]; const char *x, *mem0; };
#define EF_MASK 15
#define EF(i) (((EF_MASK >> (i)) & 1) ? policy_evict_first() : policy_evict_normal())
__device__ __forceinline__ void l2_prefetch(const char* p, uint32_t bytes) {
    asm volatile("cp.async.bulk.prefetch.L2.global [%0], %1;" ::"l"(p), "r"(bytes) : "memory");
}
#define WG_CONV(N, LIST, A0, A1, A2, A3, LO, OF, ...) \
    if constexpr (NN == N) asm volatile("{.reg .b32 l; .reg .b64 e; add.u32 l, %" #LO ", %" #OF "; mov.b64 e, {l, 0x80000020};\n" \
        "wgmma.mma_async.sync.aligned.m64n" #N "k16.f32.bf16.bf16 {" LIST "}, {%" #A0 ",%" #A1 ",%" #A2 ",%" #A3 "}, e, 1, 1, 1, 0;}" \
        : __VA_ARGS__ : "r"(a[0]), "r"(a[1]), "r"(a[2]), "r"(a[3]), "r"(lo), "n"(OFF));
#define WL4 "%0,%1,%2,%3"
#define WL8 WL4 ",%4,%5,%6,%7"
#define WL12 WL8 ",%8,%9,%10,%11"
#define WL16 WL12 ",%12,%13,%14,%15"
#define WL20 WL16 ",%16,%17,%18,%19"
#define WL24 WL20 ",%20,%21,%22,%23"
#define WL28 WL24 ",%24,%25,%26,%27"
#define WL32 WL28 ",%28,%29,%30,%31"
template <int NN, int OFF> __device__ __forceinline__ void wgmma_conv(float (&d)[32], const uint32_t (&a)[4], uint32_t lo) {
    WG_CONV(8, WL4, 4, 5, 6, 7, 8, 9, R4(0))
    WG_CONV(16, WL8, 8, 9, 10, 11, 12, 13, R4(0), R4(4))
    WG_CONV(24, WL12, 12, 13, 14, 15, 16, 17, R4(0), R4(4), R4(8))
    WG_CONV(32, WL16, 16, 17, 18, 19, 20, 21, R16(0))
    WG_CONV(40, WL20, 20, 21, 22, 23, 24, 25, R16(0), R4(16))
    WG_CONV(48, WL24, 24, 25, 26, 27, 28, 29, R16(0), R4(16), R4(20))
    WG_CONV(56, WL28, 28, 29, 30, 31, 32, 33, R16(0), R4(16), R4(20), R4(24))
    WG_CONV(64, WL32, 32, 33, 34, 35, 36, 37, R16(0), R16(16))
}
__device__ __forceinline__ void copy_to_peer(uint32_t dst, uint32_t src, uint32_t bytes, uint32_t bar) {
    asm volatile("cp.async.bulk.shared::cluster.shared::cta.mbarrier::complete_tx::bytes [%0], [%1], %2, [%3];" ::"r"(dst), "r"(src), "r"(bytes), "r"(bar) : "memory");
}
__device__ __forceinline__ uint32_t lds_volatile(uint32_t a) {
    uint32_t v;
    asm volatile("ld.volatile.shared.u32 %0, [%1];" : "=r"(v) : "r"(a) : "memory");
    return v;
}
__device__ __forceinline__ uint32_t swz64(uint32_t a) { return a ^ ((a >> 3) & 0x30); }
__device__ __forceinline__ void fence_async() { asm volatile("fence.proxy.async.shared::cta;" ::: "memory"); }

__global__ void __cluster_dims__(2, 1, 1) __launch_bounds__(576, 1)
ssm_kernel(const __grid_constant__ CUtensorMap mapK, const __grid_constant__ CUtensorMap mapV, const __grid_constant__ CUtensorMap mapQ,
           const __grid_constant__ CUtensorMap mapO, const bf16* __restrict__ shiftk, const bf16* __restrict__ ssmk, const bf16* __restrict__ Dv,
           char* __restrict__ mbox, const __grid_constant__ ChainInputs ci, bf16* __restrict__ outp) {
    extern __shared__ __align__(128) uint8_t smem_raw[];
    const uint32_t sb = (smem_u32(smem_raw) + 511) & ~511u;
    const int rank = blockIdx.x & 1, ch0 = blockIdx.x * 8, c16 = ch0 & ~15, t0 = rank * 1024;
    const int t = threadIdx.x, warp = t >> 5, lane = t & 31;
    const uint32_t bar = sb + B_SM_BAR, barQ = bar + 64, barU = bar + 72, barY = bar + 80, flag = bar + 88;
    SP(0);
    if (lane == 0 && warp < 16 && blockIdx.x < 128) {
        const int i = warp >> 1;
        if (warp & 1) {
            if (i < 3) { mbar_init(barQ + i * 8, 1); mbar_expect_tx(barQ + i * 8, i ? 16384 : 32768); }
            if (i == 3) sts32(flag, 0);
        } else {
            mbar_init(bar + i * 8, 1);
            asm volatile("fence.mbarrier_init.release.cluster;" ::: "memory");
            mbar_expect_tx(bar + i * 8, B_KBOX + 4096);
            tma_load_2d(sb + B_SM_KT + i * B_KBOX, &mapK, c16, t0 + i * 128 - 8, bar + i * 8, EF(0));
            tma_load_2d(sb + B_SM_VT + i * 4096, &mapV, c16, t0 + i * 128, bar + i * 8, EF(0));
        }
        asm volatile("fence.mbarrier_init.release.cluster;" ::: "memory");
    }
    __syncwarp();
    if (warp == 14) SP2(14);
    KT_START(1);
    if (warp == 17) {
        launch_dependents();
        asm volatile("barrier.cluster.arrive.relaxed.aligned;" ::: "memory");
        measure_distance(mbox, lane);
        asm volatile("barrier.cluster.wait.aligned;" ::: "memory");
        KT_MARK(14);
        return;
    }
    if (blockIdx.x >= 128) return;
    if (warp == 16) {
        asm volatile("barrier.cluster.arrive.relaxed.aligned; barrier.cluster.wait.aligned;" ::: "memory");
        SP2(8);
        if (Q_LATE) for (int i = 0; i < 8; i++) { mbar_wait_w(bar + i * 8, 0); SP2(i); }
        if (lane < 8) tma_load_2d(sb + B_SM_QT + lane * 4096, &mapQ, c16, t0 + lane * 128, barQ, EF(3));
        if (!Q_LATE) for (int i = 0; i < 8; i++) mbar_wait_w(bar + i * 8, 0);
        if (lane == 0) {
            l2_prefetch(ci.x + blockIdx.x * 2048, 2048);
            if (blockIdx.x < 8) l2_prefetch(ci.mem0 + blockIdx.x * 2048, 2048);
        }
        uint32_t v[PF_DEPTH], acc = 0;
#pragma unroll
        for (int u = 0; u < PF_DEPTH; u++) v[u] = 0;
        constexpr int PER = 32 * PF_STRIDE, NW = 65536 / PER;
#define PF_N (4 * NW)
        int i = 0;
#pragma unroll 1
        for (; i < PF_N && lds_volatile(flag) == 0; i += PF_DEPTH) {
#pragma unroll
            for (int u = 0; u < PF_DEPTH; u++) {
                const char* a = ci.w[(i + u) / NW] + blockIdx.x * 65536 + ((i + u) % NW) * PER + lane * PF_STRIDE;
                acc |= v[u];
                asm volatile("ld.global.cg.L2::256B.u32 %0, [%1];" : "=r"(v[u]) : "l"(a) : "memory");
            }
        }
#pragma unroll
        for (int u = 0; u < PF_DEPTH; u++) acc |= v[u];
        if (acc == 0x7FFF7FFFu && v[0] == 0x7FFEu) g_err = 1;
        SP2(12);
        KT_MARK(15);
        return;
    }
    asm volatile("barrier.cluster.arrive.relaxed.aligned;" ::: "memory");
    const int far = warp & 1, unit = rank ^ far;
    uint32_t w[4];
    uint32_t d2;
    asm volatile("ld.global.nc.u32 %0, [%1];" : "=r"(d2) : "l"(Dv + ch0 + (warp >> 2) * 2));
    {
        const int ch = warp & 7, half = warp >> 3;
        const uint32_t kb = sb + B_SM_K + ch * B_KCH;
        const uint4* src = reinterpret_cast<const uint4*>(ssmk + (size_t)(ch0 + ch) * S_LEN);
        uint4 kr[4];
#pragma unroll
        for (int i = 0; i < 4; i++) kr[i] = ldg128(src + half * 128 + i * 32 + lane, EF(1));
        const uint32_t edge = half ? 0u : __ldg(reinterpret_cast<const uint32_t*>(src + 128));
        const uint2 sw = __ldg(reinterpret_cast<const uint2*>(shiftk + (size_t)(c16 + unit * 8 + (lane >> 2)) * 4));
        w[0] = __byte_perm(sw.x, 0, 0x1010); w[1] = __byte_perm(sw.x, 0, 0x3232); w[2] = __byte_perm(sw.y, 0, 0x1010); w[3] = __byte_perm(sw.y, 0, 0x3232);
        if (half) sts128(sb + B_SM_U + ch * B_UCH + 4096 + lane * 16, make_uint4(0, 0, 0, 0));
#pragma unroll
        for (int i = 0; i < 4; i++) {
            const uint4 lo = kr[i];
            const uint32_t nx = __shfl_down_sync(~0u, lo.x, 1), n0 = (i < 3) ? __shfl_sync(~0u, kr[i < 3 ? i + 1 : 3].x, 0) : edge;
            const uint32_t hix = (lane < 31) ? nx : n0;
            const int c = 256 - (half * 128 + 32 * i + lane);
            sts128(kb + c * 16, make_uint4(__byte_perm(hix, lo.w, 0x7610), __byte_perm(lo.w, lo.z, 0x7610), __byte_perm(lo.z, lo.y, 0x7610), __byte_perm(lo.y, lo.x, 0x7610)));
            sts128(kb + B_KLEN * 2 + 64 + c * 16, make_uint4(__byte_perm(lo.w, lo.w, 0x1032), __byte_perm(lo.z, lo.z, 0x1032), __byte_perm(lo.y, lo.y, 0x1032), __byte_perm(lo.x, lo.x, 0x1032)));
        }
        const uint32_t k0w = __shfl_sync(~0u, kr[0].x, 0);
        if (half == 0 && lane < 8) {
            sts128(kb + (257 + lane) * 16, make_uint4(lane == 0 ? (k0w & 0xFFFFu) : 0u, 0u, 0u, 0u));
            sts128(kb + B_KLEN * 2 + 64 + (257 + lane) * 16, make_uint4(0u, 0u, 0u, 0u));
        }
    }
    auto sentinels = [&]() {
        const uint4 sent = make_uint4(SENT, SENT, SENT, SENT);
        char* p0 = mbox + blockIdx.x * 16384 + t * 16;
        if (blockIdx.x != 0 || (t & 255) >= 32) stg128(p0, sent);
        stg128(p0 + 8192, sent);
        char* p1 = mbox + WIN + blockIdx.x * 12800 + t * 16;
        stg128(p1, sent);
        if (t < 288) stg128(p1 + 8192, sent);
    };
    if (SENT_AT == 1) sentinels();
    asm volatile("barrier.cluster.wait.acquire.aligned;" ::: "memory");
    SP(1);
    {
        const int box = warp >> 1, row0 = 63 - 32 * rank - 4 * box;
        const uint32_t kt = sb + B_SM_KT + box * B_KBOX + 256 + lane * 32, s0 = (unit ^ ((lane >> 2) & 1)) * 16;
        const uint32_t a0 = kt + s0, a2 = kt - 64 + (unit ^ (((lane + 6) >> 2) & 1)) * 16, a4 = kt - 128 + (s0 ^ 16), av = sb + B_SM_VT + box * 4096 + lane * 32 + s0;
        const uint32_t ul = (lane & 7) * B_UCH + row0 * 64 + (lane >> 3) * 16;
        const uint32_t ud = sb + (far ? B_SM_S + (lane & 7) * (B_SCH - B_UCH) - (1 - rank) * 2048 : B_SM_U);
        mbar_wait_w(bar + box * 8, 0);
        SP(2);
#pragma unroll
        for (int i = 0; i < 4; i++) {
            uint32_t k0[4], k2[4], k4[4], vv[4], o[4];
            ldsm4t(k0, a0 + i * 1024); ldsm4t(k2, a2 + i * 1024); ldsm4t(k4, a4 + i * 1024); ldsm4t(vv, av + i * 1024);
#pragma unroll
            for (int j = 0; j < 4; j++) {
                uint32_t a = bf16_mul(__byte_perm(k4[j], k2[j], 0x5432), w[3]);
                a = bf16_add(a, bf16_mul(k2[j], w[2]));
                a = bf16_add(a, bf16_mul(__byte_perm(k2[j], k0[j], 0x5432), w[1]));
                a = bf16_add(a, bf16_mul(k0[j], w[0]));
                o[j] = bf16_mul(a, vv[j]);
            }
            stsm4(ud + swz64(ul - i * 64), o[0], o[1], o[2], o[3]);
        }
        fence_async();
        __syncwarp();
        if (far && lane < 8) {
            const uint32_t o = lane * B_UCH + (row0 - 3) * 64;
            copy_to_peer(peer_addr(sb + B_SM_U + o, rank ^ 1), ud + o, 256, peer_addr(barU, rank ^ 1));
        }
    }
    bar_sync(1, 512);
    mbar_wait_w(barU, 0);
    if (SENT_AT == 2) sentinels();
    SP(3);
    const int wg = warp >> 2, wq = warp & 3, hi = wq >> 1, g = lane >> 2, tq = lane & 3;
    const uint32_t zero = lds32(sb + B_SM_U + 4096);
#pragma unroll 1
    for (int cc = 0; cc < 2; cc++) {
        const int ch = 2 * wg + cc;
        const uint32_t kb = sb + B_SM_K + ch * B_KCH, ub = sb + B_SM_U + ch * B_UCH;
        const uint32_t dw = __byte_perm(d2, 0, cc ? 0x3232 : 0x1010);
        const int e0 = B_C - g + 2 * tq;
        const uint32_t f0 = ((e0 & 1) ? (kb + B_KLEN * 2 + 64 + (e0 - 1) * 2) : (kb + e0 * 2)) - 32 * wq;
        const uint32_t lo = uniform((ub >> 4) | 0x10000);
        float d[32];
#pragma unroll
        for (int i = 0; i < 32; i++) d[i] = 0.f;
        uint32_t A[2][2][4];
        static_for<0, 32>([&](auto jc) {
            constexpr int j = decltype(jc)::value, N = 64 - 8 * (j / 4);
            if (j >= 2) wg_wait<1>();
            uint32_t(&a)[4] = A[j & 1][0];
            uint32_t(&b)[4] = A[j & 1][1];
            a[0] = lds32(f0 - 128 * j); a[1] = lds32(f0 - 128 * j - 16); a[2] = lds32(f0 - 128 * j + 16);
            b[0] = lds32(f0 - 128 * j + 32); b[2] = lds32(f0 - 128 * j + 48);
            a[3] = a[0] ^ zero; b[1] = a[2] ^ zero; b[3] = b[0] ^ zero;
            wg_fence();
            wgmma_conv<N, 8 * j>(d, a, lo);
            wgmma_conv<N, 8 * j + 2>(d, b, lo);
            wg_commit();
        });
        wg_wait<0>();
        if (cc) SP(4);
        if (PF_STOP == 1 && cc && t == 0) sts32(flag, 1);
        bar_sync(2 + wg, 128);
        if (!hi && tq == 3) { float x = d[13]; d[13] = d[29]; d[29] = x; x = d[15]; d[15] = d[31]; d[31] = x; }
        if (hi && tq == 0) { d[0] = 0.f; d[2] = 0.f; }
        {
            const uint32_t xs = kb + (wq ^ 2) * 2048 + lane * 4;
            const uint32_t xn = hi ? xs + (tq ? 124 : 140) : xs + (tq < 3 ? 4 : -12), wrap = hi ? (tq ? 0 : -1) : (tq < 3 ? 0 : 1);
#pragma unroll
            for (int nb = 0; nb < 4; nb++) {
                const uint32_t xw = xn + ((nb + wrap) & 3) * 512;
#pragma unroll
                for (int i = 0; i < 2; i++) {
                    const float e0v = hi ? d[4 * nb + 2 * i] : d[16 + 4 * nb + 2 * i], e1v = hi ? d[4 * nb + 2 * i + 1] : d[16 + 4 * nb + 2 * i + 1];
                    sts32(hi ? xw + i * 256 : xs + nb * 512 + i * 256 + 128, __float_as_uint(e0v));
                    sts32(hi ? xs + nb * 512 + i * 256 : xw + i * 256, __float_as_uint(e1v));
                }
            }
        }
        bar_sync(2 + wg, 128);
#pragma unroll
        for (int p = 0; p < 2; p++) {
            int row = 16 * p + (lane >> 4) * 8 + (lane & 7);
            row = hi ? row + 31 : row == 31 ? 63 : row;
            const uint32_t a = sb + B_SM_U + swz64(ch * B_UCH + row * 64 + ((wq & 1) * 2 + ((lane >> 3) & 1)) * 16);
            uint32_t u[4];
            ldsm4t(u, a);
#pragma unroll
            for (int b = 0; b < 4; b++) {
                const int r = 8 * p + 2 * b;
                const float y0 = (hi ? d[16 + r] : d[r]) + __uint_as_float(lds32(kb + wq * 2048 + r * 128 + lane * 4));
                const float y1 = (hi ? d[17 + r] : d[r + 1]) + __uint_as_float(lds32(kb + wq * 2048 + r * 128 + 128 + lane * 4));
                u[b] = bf16_add(pack_bf16(y0, y1), bf16_mul(u[b], dw));
            }
            stsm4t(a, u[0], u[1], u[2], u[3]);
        }
        fence_async();
        bar_sync(2 + wg, 128);
        if (SENT_AT == 3 && cc == 0) sentinels();
        if (wq == 0 && lane == 0) copy_to_peer(peer_addr(sb + B_SM_S + ch * B_SCH, rank ^ 1), ub + rank * 2048, 2048, peer_addr(barY, rank ^ 1));
    }
    if (PF_STOP == 2 && t == 0) sts32(flag, 1);
    SP(5);
    mbar_wait_w(barQ, 0);
    bar_sync(1, 512);
    mbar_wait_w(barY, 0);
    asm volatile("barrier.cluster.arrive.relaxed.aligned;" ::: "memory");
    SP(6);
#pragma unroll
    for (int i = 0; i < 4; i++) {
        const int fr = i & 1, row = 63 - 32 * rank - 2 * warp - (i >> 1);
        const uint32_t qa = sb + B_SM_QT + warp * 2048 + (i >> 1) * 1024 + lane * 32 + ((rank ^ fr ^ (lane >> 2)) & 1) * 16;
        uint32_t y[4], q[4];
        ldsm4t(y, sb + (fr ? B_SM_S + (lane & 7) * (B_SCH - B_UCH) - (1 - rank) * 2048 : B_SM_U) + swz64((lane & 7) * B_UCH + row * 64 + (lane >> 3) * 16));
        ldsm4(q, qa);
        stsm4(qa, bf16_mul(q[0], y[0]), bf16_mul(q[1], y[1]), bf16_mul(q[2], y[2]), bf16_mul(q[3], y[3]));
    }
    fence_async();
    __syncwarp();
    if (lane == 0) {
        asm volatile("cp.async.bulk.tensor.2d.global.shared::cta.bulk_group.L2::cache_hint [%0, {%2, %3}], [%1], %4;"
                     ::"l"(&mapO), "r"(sb + B_SM_QT + warp * 2048), "r"(DM + c16), "r"(t0 + warp * 64), "l"(EF(4)) : "memory");
        asm volatile("cp.async.bulk.commit_group;" ::: "memory");
    }
    if (SENT_AT == 0) sentinels();
    if (warp == 0) SP2(10);
    if (lane == 0) asm volatile("cp.async.bulk.wait_group.read 0;" ::: "memory");
    __syncwarp();
    if (warp == 0) SP2(11);
    asm volatile("barrier.cluster.wait.aligned;" ::: "memory");
    SP(7);
    KT_END(1);
}

typedef CUresult (*EncodeFn)(CUtensorMap*, CUtensorMapDataType, cuuint32_t, void*, const cuuint64_t*, const cuuint64_t*, const cuuint32_t*,
                             const cuuint32_t*, CUtensorMapInterleave, CUtensorMapSwizzle, CUtensorMapL2promotion, CUtensorMapFloatOOBfill);

static void make_map(EncodeFn fn, CUtensorMap* m, const void* ptr, uint64_t inner, uint64_t outer, uint32_t box_in, uint32_t box_out,
                     CUtensorMapL2promotion promo = CU_TENSOR_MAP_L2_PROMOTION_L2_256B) {
    cuuint64_t dims[2] = {inner, outer};
    cuuint64_t strides[1] = {inner * 2};
    cuuint32_t box[2] = {box_in, box_out};
    cuuint32_t es[2] = {1, 1};
    fn(m, CU_TENSOR_MAP_DATA_TYPE_BFLOAT16, 2, const_cast<void*>(ptr), dims, strides, box, es, CU_TENSOR_MAP_INTERLEAVE_NONE,
       CU_TENSOR_MAP_SWIZZLE_128B, promo, CU_TENSOR_MAP_FLOAT_OOB_FILL_NONE);
}

#define G2_ST 7
#define PROMO_W CU_TENSOR_MAP_L2_PROMOTION_L2_256B
#define PROMO_O CU_TENSOR_MAP_L2_PROMOTION_L2_256B
#define SSM_PROMO CU_TENSOR_MAP_L2_PROMOTION_NONE
extern "C" void kernel_launch(void* const* d_in, const int* in_sizes, int n_in, void* d_out, int out_size) {
    const bf16* x = (const bf16*)d_in[0];
    const bf16* mem0 = (const bf16*)d_in[1];
    const bf16* Wq = (const bf16*)d_in[2];
    const bf16* Wk = (const bf16*)d_in[3];
    const bf16* Wv = (const bf16*)d_in[4];
    const bf16* Wo = (const bf16*)d_in[5];
    const bf16* Bq = (const bf16*)d_in[7];
    const bf16* Bk = (const bf16*)d_in[8];
    const bf16* Bv = (const bf16*)d_in[9];
    const bf16* Bsh = (const bf16*)d_in[10];
    const bf16* Bssm = (const bf16*)d_in[11];
    const bf16* BD = (const bf16*)d_in[12];
    bf16* out = (bf16*)d_out;

    static bool init = false;
    static EncodeFn enc = nullptr;
    static void *p_tok, *p_ox, *p_mbox;
    static int nclusters = 64;
    if (!init) {
        cudaDriverEntryPointQueryResult qr;
        cudaGetDriverEntryPoint("cuTensorMapEncodeTiled", (void**)&enc, cudaEnableDefault, &qr);
        cudaGetSymbolAddress(&p_tok, g_tok);
        cudaGetSymbolAddress(&p_ox, g_ox);
        cudaGetSymbolAddress(&p_mbox, g_mbox);
        cudaFuncSetAttribute(proj_kernel<128, 7>, cudaFuncAttributeMaxDynamicSharedMemorySize, PROJ_SMEM);
        cudaFuncSetAttribute(chain_kernel<false>, cudaFuncAttributeMaxDynamicSharedMemorySize, CHAIN_SMEM);
        cudaFuncSetAttribute(chain_kernel<true>, cudaFuncAttributeMaxDynamicSharedMemorySize, CHAIN_SMEM);
        cudaFuncSetAttribute(ssm_kernel, cudaFuncAttributeMaxDynamicSharedMemorySize, B_SMEM);
        cudaLaunchConfig_t cfg = {};
        cfg.gridDim = dim3(132); cfg.blockDim = dim3(384); cfg.dynamicSmemBytes = CHAIN_SMEM;
        cudaLaunchAttribute at[1];
        at[0].id = cudaLaunchAttributeClusterDimension; at[0].val.clusterDim.x = 2; at[0].val.clusterDim.y = 1; at[0].val.clusterDim.z = 1;
        cfg.attrs = at; cfg.numAttrs = 1;
        int n = 0;
        if (cudaOccupancyMaxActiveClusters(&n, chain_kernel<true>, &cfg) == cudaSuccess && n > 64) nclusters = n < 66 ? n : 66;
        (void)cudaGetLastError();
        init = true;
    }
    char* mbox = (char*)(((uintptr_t)p_mbox + 2 * WIN - 1) & ~(uintptr_t)(2 * WIN - 1));
    CUtensorMap mX, mT32, mT16, mTQ, mKV, mWq, mWk, mWv, mWoC, mWo, mOx, mOut, mO8;
    {
        cuuint64_t dims[3] = {64, S_LEN, DM / 64};
        cuuint64_t strides[2] = {DM * 2, 128};
        cuuint32_t box[3] = {64, 32, 4};
        cuuint32_t es[3] = {1, 1, 1};
        enc(&mX, CU_TENSOR_MAP_DATA_TYPE_BFLOAT16, 3, const_cast<bf16*>(x), dims, strides, box, es, CU_TENSOR_MAP_INTERLEAVE_NONE,
            CU_TENSOR_MAP_SWIZZLE_128B, CU_TENSOR_MAP_L2_PROMOTION_L2_256B, CU_TENSOR_MAP_FLOAT_OOB_FILL_NONE);
    }
    make_map(enc, &mT32, p_tok, DH, 4 * NH * 3 * SEG, 64, 32, CU_TENSOR_MAP_L2_PROMOTION_L2_128B);
    make_map(enc, &mT16, p_tok, DH, 4 * NH * 3 * SEG, 64, 16, CU_TENSOR_MAP_L2_PROMOTION_L2_128B);
    {
        cuuint64_t dims[2] = {512, 4 * NH * 12};
        cuuint64_t strides[1] = {2048};
        cuuint32_t box[2] = {256, 4};
        cuuint32_t es[2] = {1, 1};
        enc(&mTQ, CU_TENSOR_MAP_DATA_TYPE_UINT32, 2, p_tok, dims, strides, box, es, CU_TENSOR_MAP_INTERLEAVE_NONE,
            CU_TENSOR_MAP_SWIZZLE_NONE, CU_TENSOR_MAP_L2_PROMOTION_L2_128B, CU_TENSOR_MAP_FLOAT_OOB_FILL_NONE);
    }
    {
        cuuint64_t dims[3] = {64, 4 * NH * 3 * SEG, 2};
        cuuint64_t strides[2] = {DH * 2, 128};
        cuuint32_t box[3] = {64, 32, 2};
        cuuint32_t es[3] = {1, 1, 1};
        enc(&mKV, CU_TENSOR_MAP_DATA_TYPE_BFLOAT16, 3, p_tok, dims, strides, box, es, CU_TENSOR_MAP_INTERLEAVE_NONE,
            CU_TENSOR_MAP_SWIZZLE_128B, CU_TENSOR_MAP_L2_PROMOTION_L2_128B, CU_TENSOR_MAP_FLOAT_OOB_FILL_NONE);
    }
    {
        cuuint64_t dims[3] = {32, S_LEN, HD / 32};
        cuuint64_t strides[2] = {HD * 2, 64};
        cuuint32_t box[3] = {32, 8, 4};
        cuuint32_t es[3] = {1, 1, 1};
        enc(&mO8, CU_TENSOR_MAP_DATA_TYPE_BFLOAT16, 3, p_ox, dims, strides, box, es, CU_TENSOR_MAP_INTERLEAVE_NONE,
            CU_TENSOR_MAP_SWIZZLE_64B, CU_TENSOR_MAP_L2_PROMOTION_L2_128B, CU_TENSOR_MAP_FLOAT_OOB_FILL_NONE);
    }
    make_map(enc, &mWq, Wq, HD, DM, 64, 16, CU_TENSOR_MAP_L2_PROMOTION_L2_128B);
    make_map(enc, &mWk, Wk, HD, DM, 64, 16, CU_TENSOR_MAP_L2_PROMOTION_L2_128B);
    make_map(enc, &mWv, Wv, HD, DM, 64, 16, CU_TENSOR_MAP_L2_PROMOTION_L2_128B);
    make_map(enc, &mWoC, Wo, DM, HD, 64, 16, CU_TENSOR_MAP_L2_PROMOTION_L2_128B);
    const bool early = nclusters >= 66;
    make_map(enc, &mWo, Wo, DM, HD, 64, 64, PROMO_W);
    make_map(enc, &mOx, p_ox, HD, S_LEN, 64, early ? 64 : 128, PROMO_O);
    make_map(enc, &mOut, out, OUT_LD, S_LEN, 64, early ? 64 : 128);

    CUtensorMap mB[4];
    for (int i = 0; i < 4; i++) {
        cuuint64_t dims[2] = {(cuuint64_t)(i < 3 ? DM : OUT_LD), S_LEN};
        cuuint64_t strides[1] = {dims[0] * 2};
        cuuint32_t box[2] = {16, i == 0 ? 136u : i < 3 ? 128u : 64u};
        cuuint32_t es[2] = {1, 1};
        enc(&mB[i], CU_TENSOR_MAP_DATA_TYPE_BFLOAT16, 2, const_cast<bf16*>(i == 0 ? Bk : i == 1 ? Bv : i == 2 ? Bq : out), dims, strides, box, es,
            CU_TENSOR_MAP_INTERLEAVE_NONE, CU_TENSOR_MAP_SWIZZLE_32B, SSM_PROMO, CU_TENSOR_MAP_FLOAT_OOB_FILL_NONE);
    }
    cudaStream_t st = cudaStreamPerThread;
    const ChainInputs ci = {{(const char*)Wv, (const char*)Wk, (const char*)Wq, (const char*)Wo}, (const char*)x, (const char*)mem0};
    ssm_kernel<<<132, 576, B_SMEM, st>>>(mB[0], mB[1], mB[2], mB[3], Bsh, Bssm, BD, mbox, ci, out);
    cudaLaunchAttribute pdl[1];
    pdl[0].id = cudaLaunchAttributeProgrammaticStreamSerialization; pdl[0].val.programmaticStreamSerializationAllowed = 1;
    cudaLaunchConfig_t lc = {};
    lc.stream = st; lc.attrs = pdl;
    lc.gridDim = dim3(2 * nclusters); lc.blockDim = dim3(384); lc.dynamicSmemBytes = CHAIN_SMEM; lc.numAttrs = PDL & 1;
    cudaLaunchKernelEx(&lc, early ? chain_kernel<true> : chain_kernel<false>, mbox, mem0, mX, mT32, mT16, mTQ, mKV, mWq, mWk, mWv, mWoC, mWo, mOx, mOut, mO8);
    if (early) return;
    lc.gridDim = dim3(2 * nclusters); lc.blockDim = dim3(PROJ_THREADS); lc.dynamicSmemBytes = PROJ_SMEM; lc.numAttrs = (PDL >> 1) & 1;
    cudaLaunchKernelEx(&lc, proj_kernel<128, 7>, mWo, mOx, mOut);
}
```

```cpp
#include <cuda_runtime.h>
#include <cuda_bf16.h>
#include <cuda.h>
#include <stdint.h>
#include <type_traits>

typedef __nv_bfloat16 bf16;

constexpr int S_LEN = 2048, DM = 1024, NH = 32, DH = 128, NSEG = 64, SEG = 32;
constexpr int HD = NH * DH;
constexpr int OUT_LD = 2048;
constexpr unsigned SENT = 0xFFFFFFFFu;

__device__ bf16 g_tok[4 * NH * 3 * SEG * DH];
__device__ bf16 g_ox[(size_t)S_LEN * HD];
__device__ uint4 g_mbox[4 * 131072];
__device__ unsigned g_xflag[128];
__device__ unsigned g_reg[4];
__device__ __align__(16) unsigned g_cls[256];
__device__ unsigned g_err;
constexpr uint32_t WIN = 2u << 20;
__host__ __device__ constexpr uint32_t page_off(uint32_t idx, uint32_t c) {
    return ((idx & 1) << 13) | ((idx >> 1) << 16) | (((c ^ idx ^ (idx >> 1) ^ (idx >> 2) ^ (idx >> 4)) & 1) << 12);
}
#define STAT(i, c) (void)(c)
#define EARLY_ROLE 1
#define PDL 3

__device__ __forceinline__ void launch_dependents() { asm volatile("griddepcontrol.launch_dependents;" ::: "memory"); }
__device__ __forceinline__ void wait_prerequisites() { asm volatile("griddepcontrol.wait;" ::: "memory"); }
__device__ __forceinline__ void prefetch_map(const CUtensorMap* m) { asm volatile("prefetch.tensormap [%0];" ::"l"(m) : "memory"); }
#define KT_MARK(k)
#define KT_START(k)
#define KT_END(k)

__device__ __forceinline__ uint32_t smem_u32(const void* p) { return (uint32_t)__cvta_generic_to_shared(p); }
__device__ __forceinline__ void ldsm4(uint32_t& r0, uint32_t& r1, uint32_t& r2, uint32_t& r3, uint32_t a) {
    asm volatile("ldmatrix.sync.aligned.m8n8.x4.shared.b16 {%0,%1,%2,%3}, [%4];" : "=r"(r0), "=r"(r1), "=r"(r2), "=r"(r3) : "r"(a) : "memory");
}
__device__ __forceinline__ void ldsm4t(uint32_t& r0, uint32_t& r1, uint32_t& r2, uint32_t& r3, uint32_t a) {
    asm volatile("ldmatrix.sync.aligned.m8n8.x4.trans.shared.b16 {%0,%1,%2,%3}, [%4];" : "=r"(r0), "=r"(r1), "=r"(r2), "=r"(r3) : "r"(a) : "memory");
}
__device__ __forceinline__ void ldsm2(uint32_t& r0, uint32_t& r1, uint32_t a) {
    asm volatile("ldmatrix.sync.aligned.m8n8.x2.shared.b16 {%0,%1}, [%2];" : "=r"(r0), "=r"(r1) : "r"(a) : "memory");
}
__device__ __forceinline__ void stg128(void* p, uint4 v) {
    asm volatile("st.global.v4.u32 [%0], {%1,%2,%3,%4};" ::"l"(p), "r"(v.x), "r"(v.y), "r"(v.z), "r"(v.w) : "memory");
}
__device__ __forceinline__ void stsm4(uint32_t a, uint32_t r0, uint32_t r1, uint32_t r2, uint32_t r3) {
    asm volatile("stmatrix.sync.aligned.m8n8.x4.shared.b16 [%0], {%1,%2,%3,%4};" ::"r"(a), "r"(r0), "r"(r1), "r"(r2), "r"(r3) : "memory");
}
__device__ __forceinline__ void mma16816(float (&d)[4], uint32_t a0, uint32_t a1, uint32_t a2, uint32_t a3, uint32_t b0, uint32_t b1) {
    asm("mma.sync.aligned.m16n8k16.row.col.f32.bf16.bf16.f32 {%0,%1,%2,%3},{%4,%5,%6,%7},{%8,%9},{%0,%1,%2,%3};"
                 : "+f"(d[0]), "+f"(d[1]), "+f"(d[2]), "+f"(d[3])
                 : "r"(a0), "r"(a1), "r"(a2), "r"(a3), "r"(b0), "r"(b1));
}
__device__ __forceinline__ void mma1688(float (&d)[4], uint32_t a0, uint32_t a1, uint32_t b0) {
    asm("mma.sync.aligned.m16n8k8.row.col.f32.bf16.bf16.f32 {%0,%1,%2,%3},{%4,%5},{%6},{%0,%1,%2,%3};"
        : "+f"(d[0]), "+f"(d[1]), "+f"(d[2]), "+f"(d[3]) : "r"(a0), "r"(a1), "r"(b0));
}
__device__ __forceinline__ uint32_t movmat(uint32_t a) {
    uint32_t d;
    asm volatile("movmatrix.sync.aligned.m8n8.trans.b16 %0, %1;" : "=r"(d) : "r"(a));
    return d;
}
__device__ __forceinline__ uint32_t pack_bf16(float lo, float hi) {
    uint32_t r;
    asm("cvt.rn.bf16x2.f32 %0, %1, %2;" : "=r"(r) : "f"(hi), "f"(lo));
    return r;
}
__device__ __forceinline__ uint32_t bf16_mul(uint32_t a, uint32_t b) {
    uint32_t d;
    asm("mul.rn.bf16x2 %0, %1, %2;" : "=r"(d) : "r"(a), "r"(b));
    return d;
}
__device__ __forceinline__ uint32_t bf16_add(uint32_t a, uint32_t b) {
    uint32_t d;
    asm("add.rn.bf16x2 %0, %1, %2;" : "=r"(d) : "r"(a), "r"(b));
    return d;
}

__device__ __forceinline__ float bf16_round(float x) { return __bfloat162float(__float2bfloat16_rn(x)); }
__device__ __forceinline__ float bf_lo(uint32_t w) { return __uint_as_float(w << 16); }
__device__ __forceinline__ float bf_hi(uint32_t w) { return __uint_as_float(w & 0xFFFF0000u); }
__device__ __forceinline__ void bar_sync(int id, int n) { asm volatile("bar.sync %0, %1;" ::"r"(id), "r"(n) : "memory"); }
__device__ __forceinline__ void bar_sync_keep(int id, int n, uint32_t a, uint32_t b) {
    asm volatile("bar.sync %0, %1; // %2 %3" ::"r"(id), "r"(n), "r"(a), "r"(b) : "memory");
}
__device__ __forceinline__ bool bar_red_or(int id, int n, bool p) {
    uint32_t r;
    asm volatile("{.reg .pred p, q; setp.ne.u32 p, %3, 0; bar.red.or.pred q, %1, %2, p; selp.u32 %0, 1, 0, q;}" : "=r"(r) : "r"(id), "r"(n), "r"((uint32_t)p) : "memory");
    return r != 0;
}
__device__ __forceinline__ void bar_arrive(int id, int n) { asm volatile("bar.arrive %0, %1;" ::"r"(id), "r"(n) : "memory"); }
__device__ __forceinline__ void cp_async16(uint32_t dst, const void* src) {
    asm volatile("cp.async.cg.shared.global [%0], [%1], 16;" ::"r"(dst), "l"(src) : "memory");
}
__device__ __forceinline__ void cp_commit() { asm volatile("cp.async.commit_group;" ::: "memory"); }
template <int N> __device__ __forceinline__ void cp_wait() { asm volatile("cp.async.wait_group %0;" ::"n"(N) : "memory"); }
__device__ __forceinline__ uint4 ld_relaxed_v4(const void* p) {
    uint4 v;
    asm volatile("ld.relaxed.gpu.global.v4.u32 {%0,%1,%2,%3}, [%4];" : "=r"(v.x), "=r"(v.y), "=r"(v.z), "=r"(v.w) : "l"(p) : "memory");
    return v;
}
__device__ __forceinline__ void st_relaxed_u32(void* p, uint32_t v) { asm volatile("st.relaxed.gpu.global.u32 [%0], %1;" ::"l"(p), "r"(v) : "memory"); }
__device__ __forceinline__ void st_relaxed_v2(void* p, uint32_t a, uint32_t b) {
    asm volatile("st.relaxed.gpu.global.v2.u32 [%0], {%1,%2};" ::"l"(p), "r"(a), "r"(b) : "memory");
}
__device__ __forceinline__ void sts128(uint32_t a, uint4 v) {
    asm volatile("st.shared.v4.u32 [%0], {%1,%2,%3,%4};" ::"r"(a), "r"(v.x), "r"(v.y), "r"(v.z), "r"(v.w) : "memory");
}
__device__ __forceinline__ uint4 lds128(uint32_t a) {
    uint4 v;
    asm volatile("ld.shared.v4.u32 {%0,%1,%2,%3}, [%4];" : "=r"(v.x), "=r"(v.y), "=r"(v.z), "=r"(v.w) : "r"(a) : "memory");
    return v;
}
__device__ __forceinline__ void sts32(uint32_t a, uint32_t v) { asm volatile("st.shared.u32 [%0], %1;" ::"r"(a), "r"(v) : "memory"); }
__device__ __forceinline__ uint32_t lds32(uint32_t a) {
    uint32_t v;
    asm volatile("ld.shared.u32 %0, [%1];" : "=r"(v) : "r"(a) : "memory");
    return v;
}
__device__ __forceinline__ void mbar_init(uint32_t a, uint32_t c) { asm volatile("mbarrier.init.shared::cta.b64 [%0], %1;" ::"r"(a), "r"(c) : "memory"); }
__device__ __forceinline__ void mbar_expect_tx(uint32_t a, uint32_t bytes) {
    asm volatile("mbarrier.arrive.expect_tx.shared::cta.b64 _, [%0], %1;" ::"r"(a), "r"(bytes) : "memory");
}
__device__ __forceinline__ void mbar_arrive(uint32_t a) { asm volatile("mbarrier.arrive.shared::cta.b64 _, [%0];" ::"r"(a) : "memory"); }
__device__ __forceinline__ void mbar_wait(uint32_t a, uint32_t parity) {
    asm volatile("{.reg .pred p; .reg .u32 c;\n"
                 "mov.u32 c, 0;\n"
                 "MBW_LOOP:\n"
                 "add.u32 c, c, 1;\n"
                 "setp.gt.u32 p, c, 0x10000;\n"
                 "@!p mbarrier.try_wait.parity.shared::cta.b64 p, [%0], %1;\n"
                 "@!p bra.uni MBW_LOOP;}" ::"r"(a), "r"(parity) : "memory");
}
__device__ __forceinline__ void mbar_wait_w(uint32_t a, uint32_t parity) {
    asm volatile("{.reg .pred p; .reg .u32 c;\n"
                 "mov.u32 c, 0;\n"
                 "MBW_LOOP:\n"
                 "add.u32 c, c, 1;\n"
                 "setp.gt.u32 p, c, 0x10000;\n"
                 "@!p mbarrier.try_wait.parity.shared::cta.b64 p, [%0], %1;\n"
                 "vote.sync.all.pred p, p, 0xFFFFFFFF;\n"
                 "@!p bra.uni MBW_LOOP;}" ::"r"(a), "r"(parity) : "memory");
}
__device__ __forceinline__ void mbar_expect_tx_if0(uint32_t sel, uint32_t a, uint32_t bytes) {
    asm volatile("{.reg .pred p; setp.eq.u32 p, %2, 0; @p mbarrier.arrive.expect_tx.shared::cta.b64 _, [%0], %1;}" ::"r"(a), "r"(bytes), "r"(sel) : "memory");
}
__device__ __forceinline__ void mbar_arrive_if0(uint32_t sel, uint32_t a) {
    asm volatile("{.reg .pred p; setp.eq.u32 p, %1, 0; @p mbarrier.arrive.shared::cta.b64 _, [%0];}" ::"r"(a), "r"(sel) : "memory");
}
__device__ __forceinline__ void bulk_load(uint32_t dst, const void* src, uint32_t bytes, uint32_t bar) {
    asm volatile("cp.async.bulk.shared::cluster.global.mbarrier::complete_tx::bytes [%0], [%1], %2, [%3];" ::"r"(dst), "l"(src), "r"(bytes), "r"(bar) : "memory");
}
__device__ __forceinline__ void tma_load_2d(uint32_t dst, const CUtensorMap* map, int c0, int c1, uint32_t bar) {
    asm volatile("cp.async.bulk.tensor.2d.shared::cluster.global.mbarrier::complete_tx::bytes [%0], [%1, {%3, %4}], [%2];"
                 ::"r"(dst), "l"(map), "r"(bar), "r"(c0), "r"(c1) : "memory");
}
__device__ __forceinline__ void tma_load_2d_both(uint32_t dst, const CUtensorMap* map, int c0, int c1, uint32_t bar) {
    asm volatile("cp.async.bulk.tensor.2d.shared::cluster.global.mbarrier::complete_tx::bytes.multicast::cluster [%0], [%1, {%3, %4}], [%2], %5;"
                 ::"r"(dst), "l"(map), "r"(bar), "r"(c0), "r"(c1), "h"((uint16_t)3) : "memory");
}
__device__ __forceinline__ uint64_t policy_evict_first() {
    uint64_t p;
    asm("createpolicy.fractional.L2::evict_first.b64 %0, 1.0;" : "=l"(p));
    return p;
}
__device__ __forceinline__ uint64_t policy_evict_normal() {
    uint64_t p;
    asm("createpolicy.fractional.L2::evict_normal.b64 %0, 1.0;" : "=l"(p));
    return p;
}
__device__ __forceinline__ void tma_load_2d(uint32_t dst, const CUtensorMap* map, int c0, int c1, uint32_t bar, uint64_t pol) {
    asm volatile("cp.async.bulk.tensor.2d.shared::cluster.global.mbarrier::complete_tx::bytes.L2::cache_hint [%0], [%1, {%3, %4}], [%2], %5;"
                 ::"r"(dst), "l"(map), "r"(bar), "r"(c0), "r"(c1), "l"(pol) : "memory");
}
__device__ __forceinline__ uint4 ldg128(const void* p, uint64_t pol) {
    uint4 v;
    asm("ld.global.nc.L2::cache_hint.v4.u32 {%0,%1,%2,%3}, [%4], %5;" : "=r"(v.x), "=r"(v.y), "=r"(v.z), "=r"(v.w) : "l"(p), "l"(pol));
    return v;
}
__device__ __forceinline__ void stg128(void* p, uint4 v, uint64_t pol) {
    asm volatile("st.global.L2::cache_hint.v4.u32 [%0], {%1,%2,%3,%4}, %5;" ::"l"(p), "r"(v.x), "r"(v.y), "r"(v.z), "r"(v.w), "l"(pol) : "memory");
}
__device__ __forceinline__ void tma_store_2d(const CUtensorMap* map, uint32_t src, int c0, int c1) {
    asm volatile("cp.async.bulk.tensor.2d.global.shared::cta.bulk_group [%0, {%2, %3}], [%1];" ::"l"(map), "r"(src), "r"(c0), "r"(c1) : "memory");
}
__device__ __forceinline__ void tma_store_3d(const CUtensorMap* map, uint32_t src, int c0, int c1, int c2) {
    asm volatile("cp.async.bulk.tensor.3d.global.shared::cta.bulk_group [%0, {%2, %3, %4}], [%1];" ::"l"(map), "r"(src), "r"(c0), "r"(c1), "r"(c2) : "memory");
}
__device__ __forceinline__ char* make_ptr(uint32_t lo, uint32_t hi) {
    uint64_t p;
    asm("mov.b64 %0, {%1, %2};" : "=l"(p) : "r"(lo), "r"(hi));
    return reinterpret_cast<char*>(p);
}
__device__ __forceinline__ uint64_t make_desc(uint32_t saddr, uint32_t lbo, uint32_t sbo) {
    return (uint64_t)((saddr & 0x3FFFF) >> 4) | ((uint64_t)((lbo >> 4) & 0x3FFF) << 16) | ((uint64_t)((sbo >> 4) & 0x3FFF) << 32) | ((uint64_t)1 << 62);
}
__device__ __forceinline__ void wg_fence() { asm volatile("wgmma.fence.sync.aligned;" ::: "memory"); }
__device__ __forceinline__ void wg_commit() { asm volatile("wgmma.commit_group.sync.aligned;" ::: "memory"); }
template <int N> __device__ __forceinline__ void wg_wait() { asm volatile("wgmma.wait_group.sync.aligned %0;" ::"n"(N) : "memory"); }

#define R4(b) "+f"(d[b + 0]), "+f"(d[b + 1]), "+f"(d[b + 2]), "+f"(d[b + 3])
#define R16(b) R4(b), R4(b + 4), R4(b + 8), R4(b + 12)
template <int N> __device__ __forceinline__ void wgmma_proj(float (&d)[N / 2], uint64_t da, uint64_t db) {
    if constexpr (N == 96)
        asm volatile("wgmma.mma_async.sync.aligned.m64n96k16.f32.bf16.bf16 {"
            "%0,%1,%2,%3,%4,%5,%6,%7,%8,%9,%10,%11,%12,%13,%14,%15,%16,%17,%18,%19,%20,%21,%22,%23,%24,%25,%26,%27,%28,%29,%30,%31,%32,%33,%34,%35,%36,%37,%38,%39,"
            "%40,%41,%42,%43,%44,%45,%46,%47"
            "}, %48, %49, 1, 1, 1, 1, 0;" : R16(0), R16(16), R16(32) : "l"(da), "l"(db));
    if constexpr (N == 128)
        asm volatile("wgmma.mma_async.sync.aligned.m64n128k16.f32.bf16.bf16 {"
            "%0,%1,%2,%3,%4,%5,%6,%7,%8,%9,%10,%11,%12,%13,%14,%15,%16,%17,%18,%19,%20,%21,%22,%23,%24,%25,%26,%27,%28,%29,%30,%31,%32,%33,%34,%35,%36,%37,%38,%39,"
            "%40,%41,%42,%43,%44,%45,%46,%47,%48,%49,%50,%51,%52,%53,%54,%55,%56,%57,%58,%59,%60,%61,%62,%63"
            "}, %64, %65, 1, 1, 1, 1, 0;" : R16(0), R16(16), R16(32), R16(48) : "l"(da), "l"(db));
    if constexpr (N == 192)
        asm volatile("wgmma.mma_async.sync.aligned.m64n192k16.f32.bf16.bf16 {"
            "%0,%1,%2,%3,%4,%5,%6,%7,%8,%9,%10,%11,%12,%13,%14,%15,%16,%17,%18,%19,%20,%21,%22,%23,%24,%25,%26,%27,%28,%29,%30,%31,%32,%33,%34,%35,%36,%37,%38,%39,"
            "%40,%41,%42,%43,%44,%45,%46,%47,%48,%49,%50,%51,%52,%53,%54,%55,%56,%57,%58,%59,%60,%61,%62,%63,%64,%65,%66,%67,%68,%69,%70,%71,%72,%73,%74,%75,%76,%7"
            "7,%78,%79,%80,%81,%82,%83,%84,%85,%86,%87,%88,%89,%90,%91,%92,%93,%94,%95"
            "}, %96, %97, 1, 1, 1, 1, 0;" : R16(0), R16(16), R16(32), R16(48), R16(64), R16(80) : "l"(da), "l"(db));
    if constexpr (N == 256)
        asm volatile("wgmma.mma_async.sync.aligned.m64n256k16.f32.bf16.bf16 {"
            "%0,%1,%2,%3,%4,%5,%6,%7,%8,%9,%10,%11,%12,%13,%14,%15,%16,%17,%18,%19,%20,%21,%22,%23,%24,%25,%26,%27,%28,%29,%30,%31,%32,%33,%34,%35,%36,%37,%38,%39,"
            "%40,%41,%42,%43,%44,%45,%46,%47,%48,%49,%50,%51,%52,%53,%54,%55,%56,%57,%58,%59,%60,%61,%62,%63,%64,%65,%66,%67,%68,%69,%70,%71,%72,%73,%74,%75,%76,%7"
            "7,%78,%79,%80,%81,%82,%83,%84,%85,%86,%87,%88,%89,%90,%91,%92,%93,%94,%95,%96,%97,%98,%99,%100,%101,%102,%103,%104,%105,%106,%107,%108,%109,%110,%111,"
            "%112,%113,%114,%115,%116,%117,%118,%119,%120,%121,%122,%123,%124,%125,%126,%127"
            "}, %128, %129, 1, 1, 1, 1, 0;" : R16(0), R16(16), R16(32), R16(48), R16(64), R16(80), R16(96), R16(112) : "l"(da), "l"(db));
}

__device__ __forceinline__ void wgmma_rs32(float (&d)[16], const uint32_t (&a)[4], uint64_t db, bool acc) {
    asm volatile(
        "{.reg .pred p; setp.ne.b32 p, %21, 0;\n"
        "wgmma.mma_async.sync.aligned.m64n32k16.f32.bf16.bf16 {%0,%1,%2,%3,%4,%5,%6,%7,%8,%9,%10,%11,%12,%13,%14,%15}, {%16,%17,%18,%19}, %20, p, 1, 1, 0;}"
        : R16(0) : "r"(a[0]), "r"(a[1]), "r"(a[2]), "r"(a[3]), "l"(db), "n"(1) );
}
__device__ __forceinline__ void wgmma_rs32_first(float (&d)[16], const uint32_t (&a)[4], uint64_t db) {
    asm volatile(
        "{.reg .pred p; setp.ne.b32 p, %21, 0;\n"
        "wgmma.mma_async.sync.aligned.m64n32k16.f32.bf16.bf16 {%0,%1,%2,%3,%4,%5,%6,%7,%8,%9,%10,%11,%12,%13,%14,%15}, {%16,%17,%18,%19}, %20, p, 1, 1, 0;}"
        : R16(0) : "r"(a[0]), "r"(a[1]), "r"(a[2]), "r"(a[3]), "l"(db), "n"(0) );
}
__device__ __forceinline__ void wgmma_ss32(float (&d)[16], uint64_t da, uint64_t db) {
    asm volatile(
        "wgmma.mma_async.sync.aligned.m64n32k16.f32.bf16.bf16 {%0,%1,%2,%3,%4,%5,%6,%7,%8,%9,%10,%11,%12,%13,%14,%15}, %16, %17, 1, 1, 1, 1, 0;"
        : R16(0) : "l"(da), "l"(db));
}
template <int OFF, int ACC> __device__ __forceinline__ void wgmma_rs32u(float (&d)[16], const uint32_t (&a)[4], uint32_t lo) {
    asm volatile(
        "{.reg .pred p; .reg .b32 l; .reg .b64 e; setp.ne.b32 p, %22, 0; add.u32 l, %20, %21; mov.b64 e, {l, 0x40000040};\n"
        "wgmma.mma_async.sync.aligned.m64n32k16.f32.bf16.bf16 {%0,%1,%2,%3,%4,%5,%6,%7,%8,%9,%10,%11,%12,%13,%14,%15}, {%16,%17,%18,%19}, e, p, 1, 1, 0;}"
        : R16(0) : "r"(a[0]), "r"(a[1]), "r"(a[2]), "r"(a[3]), "r"(lo), "n"(OFF), "n"(ACC));
}
template <int OFF, int ACC> __device__ __forceinline__ void wgmma_ss32u(float (&d)[16], uint64_t da, uint32_t lo) {
    asm volatile(
        "{.reg .pred p; .reg .b32 l; .reg .b64 e; setp.ne.b32 p, %19, 0; add.u32 l, %17, %18; mov.b64 e, {l, 0x40000040};\n"
        "wgmma.mma_async.sync.aligned.m64n32k16.f32.bf16.bf16 {%0,%1,%2,%3,%4,%5,%6,%7,%8,%9,%10,%11,%12,%13,%14,%15}, %16, e, p, 1, 1, 1, 0;}"
        : R16(0) : "l"(da), "r"(lo), "n"(OFF), "n"(ACC));
}
template <int K0, int K1, class F> __device__ __forceinline__ void static_for(F f) {
    if constexpr (K0 < K1) { f(std::integral_constant<int, K0>()); static_for<K0 + 1, K1>(f); }
}
__device__ __forceinline__ void st_async4(uint32_t a, float x, float y, float z, float w, uint32_t bar) {
    asm volatile("st.async.weak.shared::cluster.mbarrier::complete_tx::bytes.v4.f32 [%0], {%1,%2,%3,%4}, [%5];" ::"r"(a), "f"(x), "f"(y), "f"(z), "f"(w), "r"(bar) : "memory");
}
__device__ __forceinline__ void st_async2(uint32_t a, float x, float y, uint32_t bar) {
    asm volatile("st.async.weak.shared::cluster.mbarrier::complete_tx::bytes.v2.f32 [%0], {%1,%2}, [%3];" ::"r"(a), "f"(x), "f"(y), "r"(bar) : "memory");
}
__device__ __forceinline__ void st_async1(uint32_t a, uint32_t x, uint32_t bar) {
    asm volatile("st.async.weak.shared::cluster.mbarrier::complete_tx::bytes.b32 [%0], %1, [%2];" ::"r"(a), "r"(x), "r"(bar) : "memory");
}
__device__ __forceinline__ uint32_t peer_addr(uint32_t a, uint32_t rank) {
    uint32_t r;
    asm("mapa.shared::cluster.u32 %0, %1, %2;" : "=r"(r) : "r"(a), "r"(rank));
    return r;
}
__device__ __forceinline__ void stsm4t(uint32_t a, uint32_t r0, uint32_t r1, uint32_t r2, uint32_t r3) {
    asm volatile("stmatrix.sync.aligned.m8n8.x4.trans.shared.b16 [%0], {%1,%2,%3,%4};" ::"r"(a), "r"(r0), "r"(r1), "r"(r2), "r"(r3) : "memory");
}
__device__ __forceinline__ void ldsm4t(uint32_t (&r)[4], uint32_t a) { ldsm4t(r[0], r[1], r[2], r[3], a); }
__device__ __forceinline__ void ldsm4(uint32_t (&r)[4], uint32_t a) { ldsm4(r[0], r[1], r[2], r[3], a); }
__device__ __forceinline__ void mma16816(float (&d)[4], const uint32_t (&a)[4], uint32_t b0, uint32_t b1) { mma16816(d, a[0], a[1], a[2], a[3], b0, b1); }
__device__ __forceinline__ void sched_fence(uint32_t v) {
    asm volatile("{.reg .pred p; setp.ne.u32 p, %0, 0xFFFFFFFF; vote.sync.all.pred p, p, 0xFFFFFFFF; @p bra.uni SF_OK; exit; SF_OK:}" ::"r"(v) : "memory");
}
__device__ __forceinline__ void mma16816v(float (&d)[4], const uint32_t (&a)[4], uint32_t b0, uint32_t b1) {
    asm volatile("mma.sync.aligned.m16n8k16.row.col.f32.bf16.bf16.f32 {%0,%1,%2,%3},{%4,%5,%6,%7},{%8,%9},{%0,%1,%2,%3};"
                 : "+f"(d[0]), "+f"(d[1]), "+f"(d[2]), "+f"(d[3]) : "r"(a[0]), "r"(a[1]), "r"(a[2]), "r"(a[3]), "r"(b0), "r"(b1));
}
__device__ __forceinline__ uint32_t uniform(uint32_t v) { return __reduce_max_sync(~0u, v); }

#define WPRE 0
#define G2_X 0
#define G2_K 4
#define FIN_SO 0
#define PROJ_FAST 1
#define KROT 0
#define WFIRST 0
template <int NT, int STAGES> struct ProjCfg {
    static constexpr int STAGE_BYTES = 16384 + NT * 128;
    static constexpr int EPI = NT == 256 ? STAGES * STAGE_BYTES : 0;
    static constexpr int BARS = 229376 + (NT == 256 ? 192 : 0);
    static_assert(STAGES * STAGE_BYTES <= 229376 && EPI + NT * 256 <= 229376 && STAGES <= 12, "smem");
};
constexpr int PROJ_ROLE = 229376 + 384, PROJ_SMEM = PROJ_ROLE + 16;
__device__ __forceinline__ unsigned claim_pair(unsigned* reg) {
    unsigned smid, ncl = gridDim.x >> 1;
    asm volatile("mov.u32 %0, %%smid;" : "=r"(smid));
    uint2 m;
    for (int guard = 0; guard < 1024; guard++) {
        asm volatile("ld.relaxed.gpu.global.v2.u32 {%0, %1}, [%2];" : "=r"(m.x), "=r"(m.y) : "l"(g_cls + (smid & ~1u)) : "memory");
        if (m.x && m.y) break;
    }
    const unsigned r = __vminu2(m.x, m.y), c = (r & 0xFFFF) > (r >> 16);
    unsigned n = atomicAdd(reg, c ? 0x10000u : 1u);
    const unsigned i = c ? n >> 16 : n & 0xFFFF, order = ((n >> 16) + (n & 0xFFFF)) << 8;
    if (i < 32) return c * 32 + i + order;
    for (int guard = 0; guard < (1 << 20); guard++) {
        asm volatile("ld.relaxed.gpu.global.u32 %0, [%1];" : "=r"(n) : "l"(reg) : "memory");
        if ((n >> 16) + (n & 0xFFFF) >= ncl) break;
    }
    const unsigned other = c ? n & 0xFFFF : n >> 16, k = other + i - 32;
    return (k < 32 ? (c ^ 1) * 32 + k : other > 32 ? 64 + c : 32 + k) + order;
}
template <int NT, int STAGES> __device__ __forceinline__ void proj_init(uint32_t sb) {
    for (int i = 0; i < STAGES; i++) { mbar_init(sb + ProjCfg<NT, STAGES>::BARS + 8 * i, 1); mbar_init(sb + ProjCfg<NT, STAGES>::BARS + 8 * (STAGES + i), 16); }
    asm volatile("fence.mbarrier_init.release.cluster;" ::: "memory");
}
template <int NT, int STAGES, bool SHARE_O, class T, class R>
__device__ __forceinline__ void proj_tiles(uint32_t sb, int warp, uint32_t rank, int ntiles, const CUtensorMap* mapW, const CUtensorMap* mapO,
                                           const CUtensorMap* mapOut, T tile, R ready, int rot = 0) {
    using Cfg = ProjCfg<NT, STAGES>;
    const uint32_t bars = sb + Cfg::BARS;
    const int lane = threadIdx.x & 31;
    if (warp == 8) {
        int st = 0; uint32_t ph = 1;
        for (int i = 0; i < ntiles; i++) {
            int col, tok;
            tile(i, col, tok);
            constexpr bool PRE = WPRE && !SHARE_O;
            if (PRE && lane == 0)
                for (int kb = 0; kb < STAGES; kb++) {
                    mbar_expect_tx(bars + 8 * kb, Cfg::STAGE_BYTES);
                    tma_load_2d_both(sb + kb * Cfg::STAGE_BYTES + rank * 8192, mapW, col + rank * 64, kb * 64, bars + 8 * kb);
                }
            ready(i);
            if (lane == 0) {
                if (PRE) {
                    for (int kb = 0; kb < STAGES; kb++) tma_load_2d(sb + kb * Cfg::STAGE_BYTES + 16384, mapO, kb * 64, tok, bars + 8 * kb);
                    ph = 0;
                }
                for (int kb = PRE ? STAGES : 0; kb < HD / 64; kb++) {
                    mbar_wait(bars + 8 * (STAGES + st), ph);
                    const uint32_t full = bars + 8 * st, sa = sb + st * Cfg::STAGE_BYTES;
                    mbar_expect_tx(full, SHARE_O ? Cfg::STAGE_BYTES : G2_X == 1 ? 16384 : G2_X == 2 ? NT * 128 : Cfg::STAGE_BYTES);
                    if (SHARE_O) {
                        tma_load_2d(sa, mapW, col, kb * 64, full);
                        tma_load_2d(sa + 8192, mapW, col + 64, kb * 64, full);
                        tma_load_2d_both(sa + 16384 + rank * (NT * 64), mapO, kb * 64, tok + rank * (NT / 2), full);
                    } else {
                        const int k0 = ((kb + rot) & 63) * 64;
                        if (WFIRST) tma_load_2d_both(sa + rank * 8192, mapW, col + rank * 64, k0, full);
                        if (G2_X != 1) tma_load_2d(sa + 16384, mapO, k0, G2_X == 3 ? tok & 511 : tok, full);
                        if (G2_X == 4) { tma_load_2d(sa, mapW, col, k0, full); tma_load_2d(sa + 8192, mapW, col + 64, k0, full); }
                        else if (!WFIRST && G2_X != 2) tma_load_2d_both(sa + rank * 8192, mapW, col + rank * 64, k0, full);
                    }
                    if (++st == STAGES) { st = 0; ph ^= 1; }
                }
            }
            __syncwarp();
        }
    } else if (warp < 8) {
        const int wg = warp >> 2;
        uint32_t peer_empty;
        asm volatile("mapa.shared::cluster.u32 %0, %1, %2;" : "=r"(peer_empty) : "r"(bars + 8 * STAGES), "r"(rank ^ 1));
        auto release = [&](int stg) {
            if (lane == 0) {
                mbar_arrive(bars + 8 * (STAGES + stg));
                asm volatile("mbarrier.arrive.shared::cluster.b64 _, [%0];" ::"r"(peer_empty + 8 * stg) : "memory");
            }
        };
        const uint32_t ew = sb + Cfg::EPI + wg * (NT * 128);
        int st = 0; uint32_t ph = 0;
        for (int i = 0; i < ntiles; i++) {
            int col, tok;
            tile(i, col, tok);
            float d[NT / 2];
#pragma unroll
            for (int r = 0; r < NT / 2; r++) d[r] = 0.f;
            int prev = -1;
            for (int kb = 0; kb < HD / 64; kb++) {
                mbar_wait(bars + 8 * st, ph);
                const uint32_t sa = sb + st * Cfg::STAGE_BYTES;
                const uint64_t da = make_desc(sa + wg * 8192, 16, 1024), db = make_desc(sa + 16384, 16, 1024);
                wg_fence();
#pragma unroll
                for (int k = 0; k < (NT == 256 ? 4 : G2_K); k++) wgmma_proj<NT>(d, da + k * 128, db + k * 2);
                wg_commit();
                if (prev >= 0) { wg_wait<1>(); release(prev); }
                prev = st;
                if (++st == STAGES) { st = 0; ph ^= 1; }
            }
            wg_wait<0>();
            release(prev);
            if ((warp & 3) == 0 && lane == 0) asm volatile("cp.async.bulk.wait_group.read 0;" ::: "memory");
            if (Cfg::EPI) bar_sync(1 + wg, 128); else bar_sync(3, 256);
            const uint32_t ea = ew + ((lane >> 4) * 8 + (lane & 7)) * 128 + ((((warp & 3) * 2 + ((lane >> 3) & 1)) ^ (lane & 7)) * 16);
#pragma unroll
            for (int r = 0; r < NT / 16; r++)
                stsm4t(ea + r * 2048, pack_bf16(d[8 * r], d[8 * r + 1]), pack_bf16(d[8 * r + 2], d[8 * r + 3]), pack_bf16(d[8 * r + 4], d[8 * r + 5]), pack_bf16(d[8 * r + 6], d[8 * r + 7]));
            asm volatile("fence.proxy.async.shared::cta;" ::: "memory");
            bar_sync(1 + wg, 128);
            if ((warp & 3) == 0 && lane == 0) {
                tma_store_2d(mapOut, ew, col + wg * 64, tok);
                asm volatile("cp.async.bulk.commit_group;" ::: "memory");
            }
        }
        if ((warp & 3) == 0 && lane == 0) asm volatile("cp.async.bulk.wait_group 0;" ::: "memory");
    }
    __syncwarp();
}
constexpr int PROJ_THREADS = 288;

template <int NT, int STAGES>
__global__ void __cluster_dims__(2, 1, 1) __launch_bounds__(PROJ_THREADS, 1)
proj_kernel(const __grid_constant__ CUtensorMap mapW, const __grid_constant__ CUtensorMap mapO, const __grid_constant__ CUtensorMap mapOut) {
    KT_START(3);
    extern __shared__ __align__(1024) uint8_t smem_proj[];
    const uint32_t sb = smem_u32(smem_proj), role = sb + PROJ_ROLE;
    if (sb & 1023) __trap();
    const uint32_t rank = blockIdx.x & 1;
    const int warp = threadIdx.x >> 5;
    if (threadIdx.x == 0) {
        mbar_init(role + 8, 1);
        mbar_expect_tx(role + 8, 4);
        proj_init<NT, STAGES>(sb);
    }
    if (threadIdx.x == 32) { prefetch_map(&mapO); prefetch_map(&mapW); prefetch_map(&mapOut); }
    __syncwarp();
    asm volatile("barrier.cluster.arrive.relaxed.aligned;" ::: "memory");
    unsigned claimed = 0;
    if (threadIdx.x == 256 && rank == 0) claimed = claim_pair(g_reg + 2);
    __syncwarp();
    asm volatile("barrier.cluster.wait.acquire.aligned;" ::: "memory");
    if (threadIdx.x == 256 && rank == 0) {
        st_async1(peer_addr(role, 1), claimed, peer_addr(role + 8, 1));
        st_async1(peer_addr(role, 0), claimed, peer_addr(role + 8, 0));
        if ((claimed >> 8) + 1 == gridDim.x >> 1) {
            g_reg[0] = 0;
            for (int i = 0; i < 64; i++) reinterpret_cast<uint4*>(g_cls)[i] = make_uint4(0, 0, 0, 0);
        }
    }
    __syncwarp();
    mbar_wait_w(role + 8, 0);
    const int p = lds32(role) & 255, order = lds32(role) >> 8;
    if (p >= 64) return;
    proj_tiles<NT, STAGES, false>(sb, warp, rank, 1, &mapW, &mapO, &mapOut,
                                  [&](int, int& col, int& tok) { col = (p & 7) * 128; tok = S_LEN - 16 * NT + ((p >> 3) * 2 + rank) * NT; },
                                  [&](int) { wait_prerequisites();
                                  }, KROT == 0 ? 0 : KROT == 1 ? (p & 7) * 8 : KROT == 2 ? (p >> 3) * 8 : KROT == 3 ? ((p & 7) + (p >> 3)) * 8 : (p >> 5) * 32);
    KT_END(3);
    asm volatile("barrier.cluster.arrive.relaxed; barrier.cluster.wait;" ::: "memory");
}

#define WO_RF1 6
constexpr int SM_KV = 0, KV_BYTES = 18432;
constexpr int SM_XT = 2 * KV_BYTES;
constexpr int SM_STG = SM_XT + 65536;
constexpr int SM_Z = SM_STG + 6144;
constexpr int SM_RT = SM_Z + 8192;
constexpr int SM_OT = SM_RT + 8192;
constexpr int SM_QKV = SM_RT + 10240;
constexpr int SM_R1 = SM_QKV + 6144;
constexpr int SM_Y = SM_R1;
constexpr int SM_R2 = SM_R1 + 4096;
constexpr int SM_R3 = SM_R2 + 1024;
constexpr int SM_O = SM_R3 + 2048;
constexpr int SM_S = SM_O + 2048;
constexpr int SM_INV = SM_S + 1536;
constexpr int SM_TO = SM_R3;
constexpr int SM_WORK_END = SM_S + 2048;
constexpr int STG_QK = 0, STG_V = 98304;
#define WO_IT 2
__host__ __device__ constexpr int stg_wo(int r) { return r < 9 ? KV_BYTES + r * 2048 : r < 13 ? SM_QKV + (r - 9) * 2048 : SM_S; }
static_assert(WO_RF1 == 6 && SM_QKV % 1024 == 0 && SM_S % 1024 == 0 && SM_QKV + 8192 <= SM_TO, "staging of Wo");
__host__ __device__ constexpr int stg_qk(int t, int r) { return t == 0 ? SM_XT + r * 2048 : r < SM_XT / 2048 ? r * 2048 : (r + 24) * 2048; }
constexpr int SM_WO1 = SM_WORK_END - WO_RF1 * 2048;
constexpr int STG_WO = SM_WO1 - 16384;
constexpr int SM_WQK = (SM_WO1 + 16384 > STG_V + 49152) ? SM_WO1 + 16384 : STG_V + 49152;
constexpr int SM_WV = SM_WQK + 32768;
constexpr int SM_WO2 = SM_WV + 16384;
constexpr int SM_BARS = SM_WO2 + 32768;
enum { MB_W0 = SM_BARS, MB_W1 = SM_BARS + 8, MB_W2 = SM_BARS + 16, MB_W3 = SM_BARS + 24, MB_XT = SM_BARS + 32  , MB_KV = SM_BARS + 48  ,
       MB_R3 = SM_BARS + 64, MB_R1 = SM_BARS + 72, MB_R2 = SM_BARS + 80, MB_RT0 = SM_BARS + 88, MB_RT1 = SM_BARS + 96, MB_FREE = SM_BARS + 104,
       MB_P = SM_BARS + 112, MB_V = SM_BARS + 120, MB_STG = SM_BARS + 128, MB_ROLE = SM_BARS + 136, MB_W4 = SM_BARS + 144, MB_W5 = SM_BARS + 152, SM_ROLE = SM_BARS + 160  ,
       MB_FULL = SM_BARS + 176  , MB_EMPTY = SM_BARS + 208  , MB_SUM = SM_BARS + 240 };
constexpr int CHAIN_SMEM = MB_SUM + 8;
static_assert(SM_WORK_END % 1024 == 0 && STG_WO >= STG_V, "work area");
static_assert(SM_Y % 128 == 0, "exchange Y");
static_assert(CHAIN_SMEM <= 232448 && WO_RF1 >= 6, "smem");

#define DLY_X 250
#define DLY_V 0
#define DLY_Y 320
#define DLY_Z 280
#define TS_AT 5
#define EARLY_T 6
#define PH2 0
#define VF1 1
#define COLDV 0
#define COLD() true
#define RT0_B 1
#define PJ_FREE 1
#define PROD10 1
#define QF 0
#define AF 0
#define PRO_LATE 1
#define OTMA 1
#define TM 7
#define ORD0 2
#define ORD1 2
#define ORDV 2
__host__ __device__ constexpr int kstep(int ord, int i) { return ord == 0 ? i : ord == 1 ? (i + 24) % 32 : ord == 2 ? (i % 4 == 3 ? 24 + i / 4 : i / 4 * 3 + i % 4) : ord == 3 ? (i < 16 ? (i % 2 ? 24 + i / 2 : i / 2) : i - 8) : (i < 8 ? i : i < 16 ? i + 16 : i - 8); }

#define GV 1
#define NSV (GV ? 320 : 352)
#define Q3_AT 9
#define NA 7
#define NP2 6
#define P2_FENCE 0
#define SPLIT 5
#define TA0 16
#define Y_CHAIN 1
#define EF_W 1
#define XFLIP 0
#define YFLIP 0
#define ZFLIP 1
#define OFENCE 2
#define REG_A 240
#define REG_B 216
#define REG_C (3 * 168 - REG_A - REG_B)

enum { BAR_Y, BAR_MEM, BAR_PUB, BAR_QK, BAR_S, BAR_O, BAR_SENT, BAR_COMM, BAR_PUBV, BAR_PV, BAR_PDONE, BAR_VP, BAR_ZP, BAR_PRO, BAR_O2, BAR_SV,
       BAR_V = BAR_PV, BAR_SENTC = BAR_PDONE, BAR_Q3 = BAR_PRO, BAR_INV = BAR_PRO, BAR_XT0 = BAR_Y };

__device__ __forceinline__ uint32_t umax4(const uint4& v) { return max(max(v.x, v.y), max(v.z, v.w)); }
__device__ __forceinline__ unsigned gtime() { unsigned t; asm volatile("mov.u32 %0, %%globaltimer_lo;" : "=r"(t)::"memory"); return t; }
__device__ __forceinline__ unsigned clock32() { unsigned t; asm volatile("mov.u32 %0, %%clock;" : "=r"(t)::"memory"); return t; }
__device__ __forceinline__ void spin_cycles(int d) {
    if (d > 0) { const unsigned c0 = clock32(); while (clock32() - c0 < (unsigned)d) {} }
}
__device__ __forceinline__ float ex2_approx(float x) { float y; asm("ex2.approx.ftz.f32 %0, %1;" : "=f"(y) : "f"(x)); return y; }
__device__ __forceinline__ float rcp_approx(float x) { float y; asm("rcp.approx.ftz.f32 %0, %1;" : "=f"(y) : "f"(x)); return y; }
__device__ __forceinline__ void st_sent(const void* p) { asm volatile("st.relaxed.gpu.global.v4.u32 [%0], {%1,%1,%1,%1};" ::"l"(p), "r"(SENT) : "memory"); }
#define POLL_LD(p, a, b, c, d, addr) "@" p " ld.relaxed.gpu.global.v4.u32 {" a "," b "," c "," d "}, [" addr "];\n"
#define POLL_CK(p, a, b, c, d) "max.u32 m, " a "," b "; max.u32 n, " c "," d "; max.u32 m, m, n; setp.eq.u32 " p ", m, 0xFFFFFFFF;\n"
#define POLL_IO(v) "+r"(v.x), "+r"(v.y), "+r"(v.z), "+r"(v.w)
__device__ __forceinline__ void poll_init(uint4& v) { v = make_uint4(SENT, SENT, SENT, SENT); asm volatile("" : POLL_IO(v)); }
__device__ __forceinline__ int poll2(uint4 (&v)[2], const char* a) {
    int c = 0;
    asm volatile("{.reg .pred p0, p1, p; .reg .u32 m, n;\n"
                 "setp.eq.u32 p0, %8, 0; setp.eq.u32 p1, %8, 0;\n"
                 "POLL_LOOP:\n"
                 POLL_LD("p0", "%0", "%1", "%2", "%3", "%9") POLL_LD("p1", "%4", "%5", "%6", "%7", "%9+512")
                 "add.u32 %8, %8, 1;\n"
                 POLL_CK("p0", "%0", "%1", "%2", "%3") POLL_CK("p1", "%4", "%5", "%6", "%7")
                 "or.pred p, p0, p1; setp.lt.and.u32 p, %8, 0x10000, p; vote.sync.any.pred p, p, 0xFFFFFFFF;\n"
                 "@p bra.uni POLL_LOOP;}" : POLL_IO(v[0]), POLL_IO(v[1]), "+r"(c) : "l"(a) : "memory");
    return c;
}
template <int ST> __device__ __forceinline__ int poll4(uint4 (&v)[4], const char* a) {
    int c = 0;
    asm volatile("{.reg .pred p0, p1, p2, p3, p; .reg .u32 m, n;\n"
                 "setp.eq.u32 p0, %16, 0; setp.eq.u32 p1, %16, 0; setp.eq.u32 p2, %16, 0; setp.eq.u32 p3, %16, 0;\n"
                 "POLL_LOOP:\n"
                 POLL_LD("p0", "%0", "%1", "%2", "%3", "%17") POLL_LD("p1", "%4", "%5", "%6", "%7", "%17+%18")
                 POLL_LD("p2", "%8", "%9", "%10", "%11", "%17+%19") POLL_LD("p3", "%12", "%13", "%14", "%15", "%17+%20")
                 "add.u32 %16, %16, 1;\n"
                 POLL_CK("p0", "%0", "%1", "%2", "%3") POLL_CK("p1", "%4", "%5", "%6", "%7") POLL_CK("p2", "%8", "%9", "%10", "%11") POLL_CK("p3", "%12", "%13", "%14", "%15")
                 "or.pred p, p0, p1; or.pred p, p, p2; or.pred p, p, p3; setp.lt.and.u32 p, %16, 0x10000, p; vote.sync.any.pred p, p, 0xFFFFFFFF;\n"
                 "@p bra.uni POLL_LOOP;}" : POLL_IO(v[0]), POLL_IO(v[1]), POLL_IO(v[2]), POLL_IO(v[3]), "+r"(c) : "l"(a), "n"(ST), "n"(2 * ST), "n"(3 * ST) : "memory");
    return c;
}
__device__ __forceinline__ uint32_t add_bf16x2(uint32_t a, uint32_t b) { uint32_t r; asm("add.rn.bf16x2 %0, %1, %2;" : "=r"(r) : "r"(a), "r"(b)); return r; }
__device__ __forceinline__ uint32_t max_bf16x2(uint32_t a, uint32_t b) { uint32_t r; asm("max.bf16x2 %0, %1, %2;" : "=r"(r) : "r"(a), "r"(b)); return r; }
template <class F> __device__ __forceinline__ void softmax40(uint32_t (&pw)[6], uint32_t sa, F mid) {
    const float LOG2E = 1.4426950408889634f;
    uint32_t w[5];
    float e[10];
#pragma unroll
    for (int i = 0; i < 5; i++) w[i] = lds32(sa + i * 128);
    uint32_t m = max_bf16x2(max_bf16x2(max_bf16x2(w[0], w[1]), max_bf16x2(w[2], w[3])), w[4]);
    m = max_bf16x2(m, __shfl_xor_sync(~0u, m, 1));
    m = max_bf16x2(m, __shfl_xor_sync(~0u, m, 2));
    const float mb2 = fmaxf(bf_lo(m), bf_hi(m)) * LOG2E;
#pragma unroll
    for (int i = 0; i < 5; i++) {
        e[2 * i] = ex2_approx(fmaf(bf_lo(w[i]), LOG2E, -mb2));
        e[2 * i + 1] = ex2_approx(fmaf(bf_hi(w[i]), LOG2E, -mb2));
    }
    mid();
#pragma unroll
    for (int i = 0; i < 5; i++) pw[i] = pack_bf16(e[2 * i], e[2 * i + 1]);
    const float sum = (((e[0] + e[1]) + (e[2] + e[3])) + ((e[4] + e[5]) + (e[6] + e[7]))) + (e[8] + e[9]);
    const float hi = bf_hi(__float_as_uint(sum));
    pw[5] = pack_bf16(sum - hi, hi);
}
template <bool NORM, class F> __device__ __forceinline__ void pv32(uint32_t (&w)[4], float (&inv)[2], const uint32_t (&va)[2][2][4], const uint32_t (&vm)[4], const uint32_t (&pw)[6], F mid) {
    float o[2][3][4], t[4] = {0.f, 0.f, 0.f, 0.f};
#pragma unroll
    for (int i = 0; i < 3; i++)
#pragma unroll
        for (int m = 0; m < 2; m++) {
            o[m][i][0] = o[m][i][1] = o[m][i][2] = o[m][i][3] = 0.f;
            if (i < 2) mma16816(o[m][i], va[m][i & 1], pw[2 * i], pw[2 * i + 1]);
            else mma1688(o[m][i], vm[2 * m], vm[2 * m + 1], pw[4]);
        }
    mma1688(t, 0x3F803F80u, 0x3F803F80u, pw[5]);
    mid();
    if (NORM) { inv[0] = rcp_approx(t[0]); inv[1] = rcp_approx(t[1]); }
#pragma unroll
    for (int i = 0; i < 4; i++) {
        const float a = (o[i >> 1][0][2 * (i & 1)] + o[i >> 1][1][2 * (i & 1)]) + o[i >> 1][2][2 * (i & 1)];
        const float b = (o[i >> 1][0][2 * (i & 1) + 1] + o[i >> 1][1][2 * (i & 1) + 1]) + o[i >> 1][2][2 * (i & 1) + 1];
        w[i] = NORM ? pack_bf16(a * inv[0], b * inv[1]) : pack_bf16(a, b);
    }
    if (!NORM) { inv[0] = t[0]; inv[1] = t[1]; }
}
__device__ __forceinline__ uint32_t scale_scores(float a, float b) {
    const float scale = 0.08838834764831845f;
    const uint32_t w = pack_bf16(a, b);
    return pack_bf16(bf_lo(w) * scale, bf_hi(w) * scale);
}

#define TL(i) do {} while (0)
#define TLB(i) do {} while (0)
#define TLC(i) do {} while (0)

#define OPQ_LANE 1
#define CLAIM_T 64
#define PAD_A 0
#define PAD_B 0
#define PAD_C 0
template <int N> __device__ __forceinline__ void code_pad() {
#pragma unroll
    for (int i = 0; i < N; i++) asm volatile("pmevent 0;");
}

constexpr int TILE_N = 192, EARLY_TOK = 3 * TILE_N, LAST_N = S_LEN - EARLY_TOK - 7 * TILE_N, FLAG_END = NSEG + 3;
constexpr int PJ_STAGE = 16384 + TILE_N * 128, PJ_LOW = 0, PJ_MID = SM_XT + 2 * PJ_STAGE;
__device__ __forceinline__ uint32_t pj_stage(uint32_t i) { return SM_XT + (i & 1) * PJ_STAGE + (i >> 1 & 1) * (SM_WORK_END - SM_XT); }
static_assert(PJ_MID <= SM_QKV && PJ_MID + TILE_N * 128 <= SM_WORK_END && SM_WORK_END + 2 * PJ_STAGE <= SM_BARS && PJ_MID <= SM_OT && SM_OT % 512 == 0 && TILE_N * 128 <= SM_XT && LAST_N == 128, "projection");
template <class R, class F>
__device__ __forceinline__ void pj_fetch(uint32_t sb, uint32_t lane, uint32_t it, int nkb, int n, const CUtensorMap* mapW, const CUtensorMap* mapO, int col0, int col1, int k0, int tok, bool soon, R ready, F room) {
    auto weights = [&](int kb) {
        const uint32_t i = it + kb, sa = sb + pj_stage(i), full = sb + MB_FULL + (i & 3) * 8;
        mbar_wait(sb + MB_EMPTY + (i & 3) * 8, (~i >> 2) & 1);
        mbar_expect_tx(full, 16384 + n * 128);
        tma_load_2d(sa, mapW, col0, k0 + kb * 64, full);
        tma_load_2d(sa + 8192, mapW, col1, k0 + kb * 64, full);
    };
    auto rows = [&](int kb) {
        const uint32_t i = it + kb, sa = sb + pj_stage(i) + 16384, full = sb + MB_FULL + (i & 3) * 8;
        for (int t = 0; t < n; t += 64) tma_load_2d(sa + t * 128, mapO, k0 + kb * 64, tok + t, full);
    };
    if (soon) ready();
#pragma unroll 1
    for (int kb = 0; kb < 4; kb++) {
        if (kb == PJ_FREE) room();
        if (lane == 0) { weights(kb); if (soon) rows(kb); }
        __syncwarp();
    }
    if (!soon) ready();
    if (lane == 0) {
#pragma unroll 1
        for (int kb = 0; kb < 4; kb++) if (!soon) rows(kb);
#pragma unroll 1
        for (int kb = 4; kb < nkb; kb++) { weights(kb); rows(kb); }
    }
    __syncwarp();
}
template <int N>
__device__ __forceinline__ void pj_sum(float (&d)[N / 2], uint32_t sb, uint32_t lane, uint32_t wg, uint32_t it, int nkb) {
#pragma unroll
    for (int r = 0; r < N / 2; r++) d[r] = 0.f;
#pragma unroll 1
    for (int kb = 0; kb < nkb; kb++) {
        const uint32_t i = it + kb, sa = sb + pj_stage(i);
        mbar_wait_w(sb + MB_FULL + (i & 3) * 8, (i >> 2) & 1);
        const uint64_t da = make_desc(sa + wg * 8192, 16, 1024), db = make_desc(sa + 16384, 16, 1024);
        wg_fence();
#pragma unroll
        for (int k = 0; k < 4; k++) wgmma_proj<N>(d, da + k * 128, db + k * 2);
        wg_commit();
        if (kb > 0) { wg_wait<1>(); mbar_arrive_if0(lane, sb + MB_EMPTY + ((i - 1) & 3) * 8); }
    }
    wg_wait<0>();
    mbar_arrive_if0(lane, sb + MB_EMPTY + ((it + nkb - 1) & 3) * 8);
}
template <int N>
__device__ __forceinline__ void pj_store(const float (&d)[N / 2], uint32_t box, uint32_t t, int bar, const CUtensorMap* mapOut, int col, int tok) {
    const uint32_t ea = box + (((t >> 4) & 1) * 8 + (t & 7)) * 128 + ((((t >> 5) * 2 + ((t >> 3) & 1)) ^ (t & 7)) * 16);
#pragma unroll
    for (int r = 0; r < N / 16; r++)
        stsm4t(ea + r * 2048, pack_bf16(d[8 * r], d[8 * r + 1]), pack_bf16(d[8 * r + 2], d[8 * r + 3]), pack_bf16(d[8 * r + 4], d[8 * r + 5]), pack_bf16(d[8 * r + 6], d[8 * r + 7]));
    asm volatile("fence.proxy.async.shared::cta;" ::: "memory");
    bar_sync(bar, 128);
    if (t == 0) {
        for (int r = 0; r < N; r += 64) tma_store_2d(mapOut, box + r * 128, col, tok + r);
        asm volatile("cp.async.bulk.commit_group;" ::: "memory");
    }
}
template <int N>
__device__ __forceinline__ void pj_last(uint32_t sb, uint32_t wg, uint32_t t, int bar, const CUtensorMap* mapOut, int col, int tok) {
    float d[N / 2];
    mbar_expect_tx_if0(t | (wg ^ 1), sb + MB_SUM, N * 128);
    pj_sum<N>(d, sb, t & 31, wg, 0, 32);
    if (wg == 0) {
        const uint32_t rsb = sb ^ (1u << 24), dst = rsb + PJ_LOW + t * 16;
        mbar_wait_w(sb + MB_FREE, 1);
#pragma unroll
        for (int r = 0; r < N / 16; r++)
            st_async4(dst + r * 2048, __uint_as_float(pack_bf16(d[8 * r], d[8 * r + 1])), __uint_as_float(pack_bf16(d[8 * r + 2], d[8 * r + 3])),
                      __uint_as_float(pack_bf16(d[8 * r + 4], d[8 * r + 5])), __uint_as_float(pack_bf16(d[8 * r + 6], d[8 * r + 7])), rsb + MB_SUM);
    } else {
        mbar_wait_w(sb + MB_SUM, 0);
#pragma unroll
        for (int r = 0; r < N / 16; r++) {
            const uint4 v = lds128(sb + PJ_LOW + t * 16 + r * 2048);
            d[8 * r] += bf_lo(v.x); d[8 * r + 1] += bf_hi(v.x); d[8 * r + 2] += bf_lo(v.y); d[8 * r + 3] += bf_hi(v.y);
            d[8 * r + 4] += bf_lo(v.z); d[8 * r + 5] += bf_hi(v.z); d[8 * r + 6] += bf_lo(v.w); d[8 * r + 7] += bf_hi(v.w);
        }
        pj_store<N>(d, sb + PJ_MID, t, bar, mapOut, col, tok);
        if (t == 0) asm volatile("cp.async.bulk.wait_group.read 0;" ::: "memory");
        __syncwarp();
    }
}
#define NOINL 0
__device__ __forceinline__
void pj_tile(uint32_t wg, const CUtensorMap* mapOut) {
    uint32_t t, rank;
    asm volatile("mov.u32 %0, %%tid.x; and.b32 %0, %0, 127; mov.u32 %1, %%ctaid.x; and.b32 %1, %1, 1;" : "=r"(t), "=r"(rank));
    const uint32_t base = 1024 | (rank << 24), pr = lds32(base + SM_ROLE);
    const int col = (pr & 7) * 128 + 64 * rank, tok = EARLY_TOK + (pr >> 3) * TILE_N;
    if (pr >> 3 == 7) pj_last<LAST_N>(base, wg, t, BAR_O, mapOut, col, tok); else pj_last<TILE_N>(base, wg, t, BAR_O, mapOut, col, tok);
}
__device__ __forceinline__ void pj_early(uint32_t sb, uint32_t e, uint32_t rank, const CUtensorMap* mapW, const CUtensorMap* mapO, const CUtensorMap* mapOut) {
    const uint32_t warp = threadIdx.x >> 5, lane = threadIdx.x & 31;
    if (warp == 8) {
        wait_prerequisites();
#pragma unroll 1
        for (int i = 0; i < EARLY_T; i++) {
            const int col = ((i & 1) * 4 + e * 2 + rank) * 128;
            pj_fetch(sb, lane, i * 64, 64, TILE_N, mapW, mapO, col, col + 64, 0, (i >> 1) * TILE_N, false, [&]() {
                if (i & 1) return;
                const unsigned need = TILE_N / SEG * (i / 2 + 1) + 3;
                for (int guard = 0; guard < (1 << 16); guard++) {
                    const uint4 f = ld_relaxed_v4(g_xflag + lane * 4);
                    if (__all_sync(~0u, min(min(f.x, f.y), min(f.z, f.w)) >= need)) break;
                    __nanosleep(500);
                }
                asm volatile("fence.acq_rel.gpu; fence.proxy.async.global;" ::: "memory");
                if (i == 0 && rank == 0 && lane == 0 && atomicAdd(g_reg + 2, 1) == 1) {
                    g_reg[0] = 0;
                    for (int k = 0; k < 64; k++) reinterpret_cast<uint4*>(g_cls)[k] = make_uint4(0, 0, 0, 0);
                }
                __syncwarp();
            }, []() {});
        }
    } else if (warp < 8) {
        const uint32_t wg = warp >> 2, t = threadIdx.x & 127;
#pragma unroll 1
        for (int i = 0; i < EARLY_T; i++) {
            float d[TILE_N / 2];
            pj_sum<TILE_N>(d, sb, lane, wg, i * 64, 64);
            if (t == 0) asm volatile("cp.async.bulk.wait_group.read 0;" ::: "memory");
            bar_sync(1 + wg, 128);
            pj_store<TILE_N>(d, sb + (wg ? PJ_MID : PJ_LOW), t, 1 + wg, mapOut, ((i & 1) * 4 + e * 2 + rank) * 128 + wg * 64, (i >> 1) * TILE_N);
        }
        if (t == 0) asm volatile("cp.async.bulk.wait_group 0;" ::: "memory");
    }
    __syncwarp();
}
template <bool TAIL>
__global__ void __cluster_dims__(2, 1, 1) __launch_bounds__(384, 1)
chain_kernel(char* __restrict__ mbox, const bf16* __restrict__ mem0,
             const __grid_constant__ CUtensorMap mapX, const __grid_constant__ CUtensorMap mapT32, const __grid_constant__ CUtensorMap mapT16,
             const __grid_constant__ CUtensorMap mapTQ, const __grid_constant__ CUtensorMap mapKV,
             const __grid_constant__ CUtensorMap mapWq, const __grid_constant__ CUtensorMap mapWk, const __grid_constant__ CUtensorMap mapWv,
             const __grid_constant__ CUtensorMap mapWo, const __grid_constant__ CUtensorMap mapPW, const __grid_constant__ CUtensorMap mapPO,
             const __grid_constant__ CUtensorMap mapOut, const __grid_constant__ CUtensorMap mapO8) {
    KT_START(2);
    extern __shared__ __align__(1024) uint8_t smem_chain[];
    constexpr uint32_t SB0 = 1024;
    if (smem_u32(smem_chain) != (SB0 | ((blockIdx.x & 1) << 24))) __trap();
    const int kh = blockIdx.x & 1;
    if (threadIdx.x == 0) {
        const uint32_t sb = smem_u32(smem_chain);
        for (int i = 0; i < 14; i++) mbar_init(sb + SM_BARS + 8 * i, 1);
        mbar_init(sb + MB_P, 4); mbar_init(sb + MB_V, 4); mbar_init(sb + MB_STG, 8); mbar_init(sb + MB_ROLE, 1); mbar_init(sb + MB_W4, 1); mbar_init(sb + MB_W5, 1);
        mbar_expect_tx(sb + MB_ROLE, 4);
        asm volatile("fence.mbarrier_init.release.cluster;" ::: "memory");
    }
    if (TAIL && threadIdx.x == 96) {
        const uint32_t sb = smem_u32(smem_chain);
        for (int i = 0; i < 4; i++) { mbar_init(sb + MB_FULL + 8 * i, 1); mbar_init(sb + MB_EMPTY + 8 * i, 8); }
        mbar_init(sb + MB_SUM, 1);
        asm volatile("fence.mbarrier_init.release.cluster;" ::: "memory");
    }
    if (threadIdx.x == 32) { prefetch_map(&mapWv); prefetch_map(&mapWq); prefetch_map(&mapWk); prefetch_map(&mapWo); prefetch_map(&mapX); }
    __syncwarp();
    asm volatile("barrier.cluster.arrive.relaxed.aligned;" ::: "memory");
    unsigned claimed = 0;
    if (threadIdx.x == CLAIM_T && kh == 0) claimed = claim_pair(g_reg) & 255;
    __syncwarp();
    asm volatile("barrier.cluster.wait.acquire.aligned;" ::: "memory");
    if (threadIdx.x == CLAIM_T && kh == 0) {
        st_async1((SB0 | (1u << 24)) + SM_ROLE, claimed, (SB0 | (1u << 24)) + MB_ROLE);
        st_async1(SB0 + SM_ROLE, claimed, SB0 + MB_ROLE);
    }
    __syncwarp();
    mbar_wait_w(smem_u32(smem_chain) + MB_ROLE, 0);
    const int pair = uniform(lds32(smem_u32(smem_chain) + SM_ROLE));
#define YFLIP_() (uniform(lds32(sb + SM_ROLE + 4)) ^ YFLIP)
    if (pair >= 64) {
        if (TAIL) pj_early(smem_u32(smem_chain), pair - 64, kh, &mapPW, &mapPO, &mapOut);
        if (TAIL) KT_END(3);
        return;
    }
    if (threadIdx.x == 0) KT_MARK(5);
    const int h = pair >> 1, nh = pair & 1, j = 2 * nh + kh, role = 2 * pair + kh;
#define WG_ORDER 0x210
    const int warp = uniform(((WG_ORDER >> (4 * (threadIdx.x >> 7))) & 3) * 4 + ((threadIdx.x >> 5) & 3));
    const uint32_t g = warp & 3, sb = SB0 | (kh << 24), rsb = sb ^ (1u << 24), cls = pair >> 5, kflip = ZFLIP ^ kh;
    const uint32_t mlo = (uint32_t)(uintptr_t)mbox, mhi = (uint32_t)((uintptr_t)mbox >> 32);
    auto lane16 = [&]() {
        uint32_t t;
        asm volatile("{.reg .u32 l, x; mov.u32 l, %%laneid; xor.b32 x, l, 1; shl.b32 x, x, 4; shfl.sync.bfly.b32 %0, x, 1, 0x1f, 0xffffffff;}" : "=r"(t));
        return t;
    };
#define PHASE(k) uint32_t L; asm volatile("{.reg .u32 t; shr.u32 t, %1, %3; add.u32 %0, %2, t;}" : "=r"(L) : "r"(it), "r"(l16), "n"(8 + (k)))
#define ROWPAT() ((((L << 3) & 0x380) | ((L << 2) & 0x400)) | ((L ^ (L >> 3)) & 0x10) | (L & 0x60))
#define FRAG() (ROWPAT() ^ (g << 5))
#define QFRAG() ((((L >> 1) & 0x80) | (L & 0x70)) + ((L & 0x80) ? SM_KV + 16384 + kvo : SM_QKV))
#define VFRAG() (ROWPAT() ^ ((g & 1) << 6))
#define VBASE() (sb + SM_KV + 8192 + (g >> 1) * 4096 + kvo)
#define XTLO() ((uint32_t)make_desc(SB0 + SM_XT, 16, 1024) + (ui & 1) * 2048)
    auto last_tile = [&](uint32_t wg) {
        KT_END(2);
        pj_tile(wg, &mapOut);
    };
    if (warp >= 8) {
        asm volatile("setmaxnreg.dec.sync.aligned.u32 %0;" ::"n"(REG_C));
        code_pad<PAD_C>();
        const uint32_t l16 = lane16(), lane = l16 >> 4;
        auto load_xt = [&](int seg, int half) {
            const uint32_t bar = sb + MB_XT + (seg & 1) * 8;
            if (half == 0) mbar_expect_tx(bar, 32768);
            asm volatile("cp.async.bulk.tensor.3d.shared::cluster.global.mbarrier::complete_tx::bytes [%0], [%1, {%3, %4, %5}], [%2];"
                         ::"r"(sb + SM_XT + (seg & 1) * 32768 + half * 16384), "l"(&mapX), "r"(bar), "r"(0), "r"(seg * SEG), "r"(8 * kh + 4 * (half ^ kflip)) : "memory");
        };
        if (warp == 8) {
            const CUtensorMap* ws = kh ? &mapWq : &mapWk;
            const CUtensorMap* wn = kh ? &mapWk : &mapWq;
            const uint64_t pol = EF_W ? policy_evict_first() : policy_evict_normal();
            const int col = h * DH + 64 * nh, row = 512 * kh;
            if (lane == 0) { mbar_expect_tx(sb + MB_W0, 49152); mbar_expect_tx(sb + MB_W1, 49152); mbar_expect_tx(sb + MB_W4, 49152); mbar_expect_tx(sb + MB_W2, 49152); mbar_expect_tx(sb + MB_W3, 65536); }
            __syncwarp();
            if (lane < 24) {
                const int k = lane ^ (16 * kflip);
                tma_load_2d(sb + STG_V + lane * 2048, &mapWv, col, row + 16 * k, sb + MB_W0, pol);
                tma_load_2d(sb + stg_qk(0, lane), ws, col, row + 16 * k, sb + MB_W1, pol);
                tma_load_2d(sb + stg_qk(1, lane), wn, col, row + 16 * k, sb + MB_W4, pol);
            }
            if (lane < 8) {
                const int k = (24 + lane) ^ (16 * kflip);
                tma_load_2d(sb + SM_WQK + lane * 4096, ws, col, row + 16 * k, sb + MB_W2, pol);
                tma_load_2d(sb + SM_WQK + lane * 4096 + 2048, wn, col, row + 16 * k, sb + MB_W2, pol);
                tma_load_2d(sb + SM_WV + lane * 2048, &mapWv, col, row + 16 * k, sb + MB_W2, pol);
            }
            __syncwarp();
        }
        if (warp == 9) {
            bar_sync(BAR_XT0, 160);
            if (lane == 0) { load_xt(0, 0); load_xt(0, 1); }
            __syncwarp();
        }
        if (warp == 10 && lane == 0) {
            wait_prerequisites();
            launch_dependents();
            sts32(sb + SM_ROLE + 4, g_reg[1]);
        }
        __syncwarp();
        bar_sync(BAR_PDONE, 384);
        KT_MARK(9);
        if (warp == 8) {
            const uint32_t dst = lane < 14 ? stg_wo(lane) : lane < 16 ? SM_WO1 + (lane - 8) * 2048 : SM_WO2 + (lane - 16) * 2048;
            tma_load_2d(sb + dst, &mapWo, 256 * j + 64 * (lane >> 3), h * DH + 16 * (lane & 7), sb + MB_W3, EF_W ? policy_evict_first() : policy_evict_normal());
        }
        if ((warp & 1) == 0) for (int c = (warp - 8) * 16 + lane; c < 512; c += 64) {
            uint32_t w[4];
#pragma unroll
            for (int r = 0; r < 4; r++) {
                const uint32_t lo = reinterpret_cast<const uint16_t*>(mem0)[(2 * r) * DM + 512 * kh + c], hi = reinterpret_cast<const uint16_t*>(mem0)[(2 * r + 1) * DM + 512 * kh + c];
                w[r] = lo | (hi << 16);
            }
            sts128(sb + SM_Z + (c ^ (256 * kflip)) * 16, make_uint4(w[0], w[1], w[2], w[3]));
        }
        auto tok_start = [&](int s) {
            if (lane == 0) {
                if (TS_AT == 0) TL(21);
                if (s > -3 && (OTMA || s + 2 < NSEG)) {
                    mbar_wait(sb + MB_STG, (s + 2) & 1);
                    if (TS_AT == 1) TL(21);
                    if (TS_AT == 2) TL(21);
                    asm volatile("fence.proxy.async.shared::cta;" ::: "memory");
                    if (TS_AT == 3) TL(21);
                    const int r = ((s + 2) & 3) * NH + h;
                    if (s + 2 < NSEG) {
                        tma_store_2d(kh ? &mapT32 : &mapTQ, sb + SM_STG, kh ? 64 * nh : 256 * nh, kh ? r * 96 + 32 : r * 12);
                        tma_store_2d(&mapT16, sb + SM_STG + 4096, 64 * nh, r * 96 + 64 + 16 * kh);
                    }
                    if (OTMA && s > 0) tma_store_3d(&mapO8, sb + SM_OT, 0, (s - 1) * SEG + 8 * j, 4 * h);
                    asm volatile("cp.async.bulk.commit_group;" ::: "memory");
                    if (TS_AT == 4) TL(21);
                }
                if (s + 4 < NSEG) load_xt(s + 4, 0);
                if (s < 0) asm volatile("cp.async.bulk.wait_group.read 0;" ::: "memory");
                if (s < 0) {
                    asm volatile("mbarrier.arrive.shared::cluster.b64 _, [%0];" ::"r"(rsb + MB_FREE) : "memory");
                    mbar_wait(sb + MB_FREE, (s + 3) & 1);
                }
            }
            __syncwarp();
        };
        auto tok_mid = [&](int s) {
            if (lane == 0) {
                if (s + 4 < NSEG) load_xt(s + 4, 1);
                if (s > -3 && s + 2 < NSEG) {
                    asm volatile("cp.async.bulk.wait_group 0;" ::: "memory");
                    st_relaxed_u32(g_xflag + role, s + 3);
                }
            }
            __syncwarp();
        };
        auto kv_check = [&](int s) {
            if (s + 1 < NSEG) {
                if (lane < 4) {
                    unsigned f; int guard = 0;
                    do {
                        asm volatile("ld.acquire.gpu.global.u32 %0, [%1];" : "=r"(f) : "l"(g_xflag + h * 4 + lane) : "memory");
                        if (++guard > (1 << 20)) __trap();
                    } while (f <= (unsigned)(s + 1));
                }
                __syncwarp();
                asm volatile("fence.proxy.async.global;" ::: "memory");
            }
        };
        auto kv_load = [&](int s) {
            if (lane == 0 && s + 1 < NSEG) {
                const uint32_t bar = sb + MB_KV + ((s + 1) & 1) * 8, dst = sb + SM_KV + ((s + 1) & 1) * KV_BYTES;
                const int row = (((s + 1) & 3) * NH + h) * 96;
                mbar_expect_tx(bar, KV_BYTES);
                asm volatile("cp.async.bulk.tensor.3d.shared::cluster.global.mbarrier::complete_tx::bytes.multicast::cluster [%0], [%1, {%3, %4, %3}], [%2], %5;"
                             ::"r"(dst + kh * 8192), "l"(&mapKV), "r"(bar), "r"(0), "r"(row + 32 + 32 * kh), "h"((uint16_t)3) : "memory");
                bulk_load(dst + 16384, g_tok + row * DH + j * 1024, 2048, bar);
            }
            __syncwarp();
        };
        if (warp == 9) {
#pragma unroll 1
            for (int s = -3; s < 0; s++) { tok_start(s); KT_MARK(13 + s); bar_arrive(BAR_PRO, 288); tok_mid(s); }
        }
        if (warp == 11) { kv_check(-1); kv_load(-1); }
        bar_arrive(BAR_MEM, 384);
        const uint32_t idx = (pair & 31) + 32 * (kh ^ 1);
        const uint32_t ybox = mlo + page_off(idx, cls ^ YFLIP_()), xoth = mlo + WIN + page_off((pair & 31) ^ 1, cls ^ XFLIP);
        const uint32_t zline = mlo + WIN + page_off(32 + (idx >> 5), cls ^ ZFLIP) + (idx & 31) * 128, zbox = mlo + WIN + (page_off(32 + kh, 0) & ~4096u);
        const uint32_t xtype = g == GV ? 2 : g == 2 ? 0 : 1;
        const int send = TAIL && PROD10 && g == 2 ? NSEG - 1 : NSEG;
        const uint32_t ydst = (lane >> 3) * 128 + ((lane & 7) ^ (lane >> 3)) * 16, ysrc = lane * 128 + ((2 * g) ^ (lane & 7)) * 16;
#pragma unroll 1
        for (int s = 0; s < send; s++) {
            const uint32_t slot = (s & 3) << 14;
            if (g == 3) {
                kv_check(s);
                if (TS_AT == 9) TL(21);
                const uint32_t L = l16, kvo = (s & 1) * KV_BYTES, qa = QFRAG(), sa = sb + SM_S + 512 + (L >> 2);
                float sc[4] = {0.f, 0.f, 0.f, 0.f}, sd[4] = {0.f, 0.f, 0.f, 0.f};
                uint32_t a[4][4], kb[2][4];
                mbar_wait_w(sb + MB_KV + (s & 1) * 8, (s >> 1) & 1);
                mbar_wait_w(sb + MB_P, s & 1);
#pragma unroll
                for (int c = 0; c < 2; c++) {
                    const uint32_t qc = qa + (sb + (nh ^ c) * 1024), kc = L + (sb + SM_QKV + 2048 + (nh ^ c) * 1024);
                    if (TS_AT == 7 && c) TL(21);
                    if (c) bar_sync(BAR_QK, 224);
                    ldsm4t(kb[0], kc); ldsm4t(a[0], qc); ldsm4t(a[1], qc + 256);
                    ldsm4t(kb[1], kc + 512); ldsm4t(a[2], qc + 512); ldsm4t(a[3], qc + 768);
                    mma16816v(sc, a[0], kb[0][0], kb[0][1]);
                    mma16816v(sd, a[1], kb[0][2], kb[0][3]);
                    mma16816v(sc, a[2], kb[1][0], kb[1][1]);
                    mma16816v(sd, a[3], kb[1][2], kb[1][3]);
                }
                sts32(sa, scale_scores(sc[0] + sd[0], sc[1] + sd[1]));
                sts32(sa + 768, scale_scores(sc[2] + sd[2], sc[3] + sd[3]));
                bar_arrive(BAR_S, 160);
                TL(25);
                bar_sync(BAR_SV, NSV);
                kv_load(s);
                if (lane == 0 && s + 3 < NSEG) {
                    asm volatile("fence.proxy.async.shared::cta;" ::: "memory");
                    asm volatile("cp.async.bulk.shared::cluster.shared::cta.mbarrier::complete_tx::bytes [%0], [%1], %2, [%3];" ::"r"(rsb + SM_RT), "r"(sb + SM_Z), "n"(8192), "r"(rsb + MB_RT0) : "memory");
                    if (TS_AT == 10) { mbar_wait(sb + MB_RT0, (s + 3) & 1); TL(21); }
                }
                __syncwarp();
            } else {
                if (g == 1) { tok_start(s); if (TS_AT == 5) TL(21); if (s == 0) KT_MARK(13); }
                const char* p = make_ptr(l16 + (xoth + xtype * 1024 + slot), mhi);
                uint4 v[2];
                const uint32_t dst = l16 + (sb + SM_QKV + xtype * 2048 + (nh ^ 1) * 1024);
                asm volatile("" ::"l"(p));
                poll_init(v[0]); poll_init(v[1]);
                if (g == GV) {
                    bar_sync(BAR_PUBV, 160);
                    mbar_wait_w(sb + MB_V, s & 1);
                    spin_cycles(DLY_V);
                } else {
                    bar_sync(BAR_PUB, 192);
                    spin_cycles(DLY_X);
                }
                const int r = poll2(v, p);
                sts128(dst, v[0]); sts128(dst + 512, v[1]);
                STAT(1, r > 1 && warp == 10);
                if (g != GV) bar_arrive(BAR_QK, 224);
                if (TS_AT == 6 && g == 0) TL(21);
                if (OTMA && g == 1) asm volatile("cp.async.bulk.wait_group.read 0;" ::: "memory");
                if (g == GV) { bar_arrive(BAR_V, 160); if (GV == 0) bar_arrive(BAR_SV, NSV); TL(17); }
                if (g == 1) {
                    TL(31);
                    if (!OTMA) asm volatile("cp.async.bulk.wait_group.read 0;" ::: "memory");
                    bar_sync(BAR_SV, NSV);
                    tok_mid(s);
                    TL(22);
                }
                if (g == 2 && s >= 1) {
                    TL(16);
                    const uint32_t prev = (slot - 0x4000) & 0xC000;
                    const char* y = make_ptr(l16 + (ybox + prev), mhi);
                    const char* x = make_ptr(l16 + (xoth + prev + kh * 1536), mhi);
#pragma unroll
                    for (int i = 0; i < 8; i++) st_sent(y + i * 512);
#pragma unroll
                    for (int i = 0; i < 3; i++) st_sent(x + i * 512);
                    st_relaxed_u32(make_ptr(lane * 4 + (zline + (slot ^ 0x8000)), mhi), SENT);
                    TL(23);
                }
            }
            if (s + 1 == NSEG) break;
            {
                const char* p = make_ptr(l16 + (ybox + g * 1024 + slot), mhi);
                char* zdst = make_ptr(lane * 4 + (zline + g * 32 + slot), mhi);
                const uint32_t dst = ydst + (sb + SM_Y + g * 1024), dst1 = (ydst ^ 64) + (sb + SM_Y + g * 1024 + 512), src = ysrc + (sb + SM_Y), src1 = (ysrc ^ 16) + (sb + SM_Y);
                asm volatile("" ::"l"(p), "l"(zdst));
                uint4 v[2];
                poll_init(v[0]); poll_init(v[1]);
                bar_sync(BAR_SENTC, 384);
                spin_cycles(DLY_Y);
                const int r = poll2(v, p);
                STAT(2, r > 1 && warp == 8);
                sts128(dst, v[0]); sts128(dst1, v[1]);
                bar_sync(BAR_Y, 256);
                TL(18);
                uint32_t b[2][4];
                ldsm4t(b[0], src); ldsm4t(b[1], src1);
                const uint32_t one = 0x3F803F80u;
                float d0[4] = {0.f, 0.f, 0.f, 0.f}, d1[4] = {0.f, 0.f, 0.f, 0.f};
                mma16816(d0, one, one, one, one, b[0][0], b[0][1]);
                mma16816(d1, one, one, one, one, b[1][0], b[1][1]);
                mma16816(d0, one, one, one, one, b[0][2], b[0][3]);
                mma16816(d1, one, one, one, one, b[1][2], b[1][3]);
                const uint32_t w = (lane & 4) ? pack_bf16(d1[0], d1[1]) : pack_bf16(d0[0], d0[1]);
                asm volatile("{.reg .pred p; setp.lt.u32 p, %2, 128; @p st.relaxed.gpu.global.u32 [%0], %1;}" ::"l"(zdst), "r"(w), "r"(l16) : "memory");
                if (s + 3 < NSEG) bar_arrive(BAR_ZP, 256);
                TL(19);
            }
            {
                const char* p = make_ptr(l16 + (zbox + g * 512 + slot), mhi);
                const uint32_t dst = l16 + (sb + SM_Z + g * 512);
                asm volatile("" ::"l"(p));
                uint4 v[4];
                poll_init(v[0]); poll_init(v[1]); poll_init(v[2]); poll_init(v[3]);
                bar_sync(BAR_COMM, 128);
                spin_cycles(DLY_Z);
                const int r = poll4<2048>(v, p);
                STAT(0, r > 1 && warp == 8);
#pragma unroll
                for (int i = 0; i < 4; i++) sts128(dst + i * 2048, v[i]);
                bar_arrive(BAR_MEM, 384);
                TL(20);
            }
        }
        if ((OTMA || TAIL) && (TM & 4) && COLD()) {
            uint32_t t, rank;
            asm volatile("mov.u32 %0, %%tid.x; mov.u32 %1, %%ctaid.x; and.b32 %1, %1, 1;" : "=r"(t), "=r"(rank));
            const uint32_t base = SB0 | (rank << 24), ln = t & 31, pr = lds32(base + SM_ROLE), col = (pr & 7) * 128, tg = pr >> 3;
            if (t >> 5 == (PROD10 ? 10 : 8)) {
                if (TAIL) {
                if (PROD10) {
                    bar_arrive(BAR_PUB, 192); bar_arrive(BAR_QK, 224);
                    if (ln == 0) { prefetch_map(&mapPW); prefetch_map(&mapPO); prefetch_map(&mapOut); }
                    __syncwarp();
                }
                pj_fetch(base, ln, 0, 32, tg == 7 ? LAST_N : TILE_N, &mapPW, &mapPO, col + 64 * (rank ^ 1), col + 64 * rank, HD / 2 * rank, EARLY_TOK + tg * TILE_N, PROD10 && tg < 7, [&]() {
                    const unsigned need = tg == 7 ? FLAG_END : (S_LEN - LAST_N) / SEG + 3;
                    for (int guard = 0; guard < (1 << 20); guard++) {
                        uint32_t f0, f1;
                        asm volatile("{.reg .b64 t; ld.acquire.gpu.global.b64 t, [%2]; mov.b64 {%0, %1}, t;}" : "=r"(f0), "=r"(f1) : "l"(g_xflag + 64 * rank + 2 * ln) : "memory");
                        if (__all_sync(~0u, min(f0, f1) >= need)) break;
                    }
                    asm volatile("fence.proxy.async.global;" ::: "memory");
                }, [&]() {
                    mbar_wait_w(base + MB_P, (NSEG - 1) & 1);
                    mbar_wait_w(base + MB_V, (NSEG - 1) & 1);
                });
                }
            } else if (t >> 5 == 9) {
                bar_sync(BAR_ZP, 160);
                if (ln == 0) {
                    if (OTMA) {
                        asm volatile("fence.proxy.async.shared::cta;" ::: "memory");
                        tma_store_3d(&mapO8, base + SM_OT, 0, S_LEN - SEG + 16 * (pr & 1) + 8 * rank, 2 * (pr & ~1u));
                        asm volatile("cp.async.bulk.commit_group;" ::: "memory");
                    }
                    if (OTMA) asm volatile("cp.async.bulk.wait_group 0;" ::: "memory");
                    if (TAIL) asm volatile("mbarrier.arrive.shared::cluster.b64 _, [%0];" ::"r"((base ^ (1u << 24)) + MB_FREE) : "memory");
                    if (!OTMA) asm volatile("fence.acq_rel.gpu;" ::: "memory");
                    if (TAIL) st_relaxed_u32(g_xflag + 2 * pr + rank, FLAG_END);
                }
                __syncwarp();
            }
        }
    } else if (warp < 4) {
        asm volatile("setmaxnreg.inc.sync.aligned.u32 %0;" ::"n"(REG_A));
        code_pad<PAD_A>();
        const uint32_t l16 = lane16();
        uint32_t wa[2][24][4];
        {
            const uint32_t L = l16, fa = sb + FRAG();
            mbar_wait_w(sb + MB_W1, 0);
            KT_MARK(7);
#pragma unroll
            for (int t = 0; t < 2; t++) {
#pragma unroll
                for (int r = 0; r < 24; r++) ldsm4t(wa[t][r], fa + stg_qk(t, r));
                if (t == 0) { bar_arrive(BAR_XT0, 160); mbar_wait_w(sb + MB_W4, 0); }
            }
            mbar_wait_w(sb + MB_W2, 0);
            bar_sync(BAR_PDONE, 384);
        }
        auto batch1 = [&](float (&d)[16], uint32_t lo, auto tc, auto k0c, auto k1c) {
            constexpr int t = decltype(tc)::value;
            const uint64_t da = make_desc(SB0 + SM_WQK, 16, 1024);
            wg_fence();
            static_for<decltype(k0c)::value, decltype(k1c)::value>([&](auto kc) {
                constexpr int i = decltype(kc)::value, k = kstep(t ? ORD1 : ORD0, i), off = (k >> 2) * 256 + (k & 3) * 2;
                if constexpr (k >= 24) wgmma_ss32u<off, i != 0 || t != 0>(d, da + ((k - 24) * 2 + t) * 128, lo);
                else wgmma_rs32u<off, i != 0 || t != 0>(d, wa[t][k], lo);
            });
            wg_commit();
        };
        const uint32_t xbox = mlo + WIN + page_off(pair & 31, cls ^ XFLIP);
        const uint32_t ybox = mlo + page_off(24 + 2 * g + 32 * nh, kh ^ YFLIP_()) + h * 128;
#pragma unroll 1
        for (uint32_t it = 0; it < NSEG + 3; it++) {
            const int s = (int)it - 3;
            const uint32_t ui = uniform(it), slot = ((ui + 1) & 3) << 14, kvo = (~ui & 1) * KV_BYTES, xtlo = XTLO();
            {
                PHASE(5);
                const uint32_t first = L | (g << 9);
                if (s >= 0) mbar_expect_tx_if0(first, sb + MB_R1, 2048);
                if (s + 3 < NSEG) {
                    mbar_expect_tx_if0(first, sb + MB_RT0, 8192);
                    mbar_wait_w(sb + MB_XT + (ui & 1) * 8, (it >> 1) & 1);
                }
            }
            if (s >= 0) {
                PHASE(0);
                const uint32_t mb = L + (sb + SM_Z), ra = L + (sb + g * 512), r1 = L + (rsb + SM_R1 + g * 512), r1b = rsb + MB_R1;
                sched_fence(r1);
                bar_sync(BAR_MEM, 384);
                TLB(0);
                float acc[2][2][4];
#pragma unroll
                for (int t = 0; t < 4; t++) { acc[t >> 1][t & 1][0] = acc[t >> 1][t & 1][1] = acc[t >> 1][t & 1][2] = acc[t >> 1][t & 1][3] = 0.f; }
                uint32_t b[4][4];
                uint4 u0, u1;
#pragma unroll
                for (int p = 0; p < 4; p++) ldsm4t(b[p], mb + p * 512);
#pragma unroll
                for (int p = 0; p < 12; p++) {
#pragma unroll
                    for (int u = 0; u < 2; u++) {
                        mma16816v(acc[0][u], wa[0][2 * p + u], b[p & 3][2 * u], b[p & 3][2 * u + 1]);
                        mma16816v(acc[1][u], wa[1][2 * p + u], b[p & 3][2 * u], b[p & 3][2 * u + 1]);
                    }
                    if (p + 4 < 12) ldsm4t(b[p & 3], mb + (p + 4) * 512);
                    if (AF >> p & 1) sched_fence(L);
                    if (p == Q3_AT) {
                        bar_sync(BAR_Q3, 256);
                        u0 = lds128(ra + SM_R3); u1 = lds128(ra + SM_O);
                    }
                }
                st_async4(r1, (acc[0][0][0] + __uint_as_float(u0.x)) + acc[0][1][0], (acc[0][0][1] + __uint_as_float(u0.y)) + acc[0][1][1],
                          (acc[0][0][2] + __uint_as_float(u0.z)) + acc[0][1][2], (acc[0][0][3] + __uint_as_float(u0.w)) + acc[0][1][3], r1b);
                TL(1);
                const float o0 = (acc[1][0][0] + __uint_as_float(u1.x)) + acc[1][1][0], o1 = (acc[1][0][1] + __uint_as_float(u1.y)) + acc[1][1][1];
                const float o2 = (acc[1][0][2] + __uint_as_float(u1.z)) + acc[1][1][2], o3 = (acc[1][0][3] + __uint_as_float(u1.w)) + acc[1][1][3];
                const uint32_t l4 = L >> 2, qo = SM_QKV + kh * 2048 + nh * 1024 + g * 256, qr = l4 + (rsb + qo), ql = l4 + (sb + qo), pb = rsb + MB_P;
                char* xd = make_ptr(l4 + (xbox + kh * 1024 + g * 256 + slot), mhi);
                asm volatile("" ::"l"(xd), "r"(qr), "r"(pb), "r"(qr + 128), "f"(o0), "f"(o1), "f"(o2), "f"(o3));
                mbar_wait_w(sb + MB_R1, s & 1);
                const uint4 v = lds128(ra + SM_R1);
                const uint32_t w0 = pack_bf16(o0 + __uint_as_float(v.x), o1 + __uint_as_float(v.y)), w1 = pack_bf16(o2 + __uint_as_float(v.z), o3 + __uint_as_float(v.w));
                st_relaxed_u32(xd, w0);
                st_relaxed_u32(xd + 128, w1);
                bar_arrive(BAR_PUB, 192);
                st_async1(qr, w0, pb);
                st_async1(qr + 128, w1, pb);
                sts32(ql, w0);
                sts32(ql + 128, w1);
                __syncwarp();
                mbar_expect_tx_if0(L, sb + MB_P, 256);
                TL(2);
                if (s + 3 < NSEG) bar_sync(BAR_VP, 256);
            } else if (!PRO_LATE) {
                bar_sync(BAR_PRO, 288);
            }
            if (s + 3 < NSEG) {
                float d[16];
                batch1(d, xtlo, std::integral_constant<int, 0>(), std::integral_constant<int, 0>(), std::integral_constant<int, 32>());
                PHASE(1);
                const uint32_t rt = L + (rsb + SM_RT + g * 2048);
                wg_wait<0>();
                TL(7);
                if (s >= 0) {
                    const uint32_t pk = L + (sb + SM_Z + g * 2048);
#pragma unroll
                    for (int i = 0; i < 4; i++) sts128(pk + i * 512, make_uint4(__float_as_uint(d[4 * i]), __float_as_uint(d[4 * i + 1]), __float_as_uint(d[4 * i + 2]), __float_as_uint(d[4 * i + 3])));
                } else {
                    if (PRO_LATE) bar_sync(BAR_PRO, 288);
#pragma unroll
                    for (int i = 0; i < 4; i++) st_async4(rt + i * 512, d[4 * i], d[4 * i + 1], d[4 * i + 2], d[4 * i + 3], rsb + MB_RT0);
                }
            }
            if (s + 1 == NSEG) { bar_arrive(BAR_SV, NSV); break; }
            if (s >= 0) {
                PHASE(2);
                const uint32_t fo = FRAG() + (sb + SM_WO2 + 16384), lo = L + (sb + SM_O), yo = (L >> 2) + (ybox + slot);
                uint32_t a1[8][4];
                bar_sync(BAR_SV, NSV);
#pragma unroll
                for (int k = 0; k < 8; k++) ldsm4t(a1[k], fo + k * 2048);
                sched_fence(yo);
                bar_sync(BAR_O2, 256);
                TLB(14);
                float y0[4] = {0.f, 0.f, 0.f, 0.f}, y1[4] = {0.f, 0.f, 0.f, 0.f};
                uint32_t b[2][4];
                ldsm4t(b[0], lo); ldsm4t(b[1], lo + 512);
                sched_fence(L);
#pragma unroll
                for (int p = 0; p < 4; p++) {
                    mma16816v(y0, a1[2 * p], b[p & 1][0], b[p & 1][1]);
                    mma16816v(y1, a1[2 * p + 1], b[p & 1][2], b[p & 1][3]);
                    if (p < 2) ldsm4t(b[p & 1], lo + (p + 2) * 512);
                }
                bar_sync(BAR_INV, 256);
                float i0, i1;
                asm volatile("ld.shared.v2.f32 {%0, %1}, [%2];" : "=f"(i0), "=f"(i1) : "r"(((L >> 1) & 0x18) + (sb + SM_INV + g * 32)) : "memory");
                st_relaxed_u32(make_ptr(yo, mhi), pack_bf16((y0[0] + y1[0]) * i0, (y0[1] + y1[1]) * i1));
                st_relaxed_u32(make_ptr(yo ^ 4096, mhi) + 0x2000, pack_bf16((y0[2] + y1[2]) * i0, (y0[3] + y1[3]) * i1));
                bar_arrive(BAR_SENTC, 384);
                TL(6);
            }
            if (s + 3 < NSEG) {
                PHASE(4);
                float d[16];
                const uint32_t rt = L + (sb + SM_RT + g * 2048);
                if (s >= 0) bar_sync(BAR_SENT, 256);
                mbar_wait_w(sb + MB_RT0, it & 1);
                if (s >= 0) bar_arrive(BAR_Y, 256);
                if (RT0_B && s >= 0) bar_arrive(BAR_VP, 256);
#pragma unroll
                for (int i = 0; i < 4; i++) {
                    const uint4 v = lds128(rt + i * 512);
                    d[4 * i] = __uint_as_float(v.x); d[4 * i + 1] = __uint_as_float(v.y); d[4 * i + 2] = __uint_as_float(v.z); d[4 * i + 3] = __uint_as_float(v.w);
                }
                if (SPLIT > 0) batch1(d, xtlo, std::integral_constant<int, 1>(), std::integral_constant<int, 0>(), std::integral_constant<int, SPLIT>());
                if (s >= 0) bar_sync(BAR_ZP, 256);
                TLB(30);
                batch1(d, xtlo, std::integral_constant<int, 1>(), std::integral_constant<int, SPLIT>(), std::integral_constant<int, 32>());
                const uint32_t so = (kh ? FRAG() : ((L & 0x100) << 2) + (L & 0xF0) + g * 256) + (sb + SM_STG);
                wg_wait<0>();
                TL(8);
                uint32_t w[8];
#pragma unroll
                for (int i = 0; i < 8; i++) w[i] = pack_bf16(d[2 * i], d[2 * i + 1]);
                if (kh) {
                    stsm4t(so, w[0], w[1], w[2], w[3]);
                    stsm4t(so + 2048, w[4], w[5], w[6], w[7]);
                } else {
                    stsm4(so, w[0], w[1], w[2], w[3]);
                    stsm4(so + 2048, w[4], w[5], w[6], w[7]);
                }
                __syncwarp();
                mbar_arrive_if0(L, sb + MB_STG);
                TL(9);
            } else {
                bar_arrive(BAR_SENT, 256);
                bar_arrive(BAR_Y, 256);
                if (OTMA) mbar_arrive_if0(l16, sb + MB_STG);
            }
        }
        if (TAIL && (TM & 1) && COLD()) last_tile(0);
    } else {
        asm volatile("setmaxnreg.inc.sync.aligned.u32 %0;" ::"n"(REG_B));
        code_pad<PAD_B>();
        const uint32_t l16 = lane16();
        uint32_t wv[24][4], wo[8 + WO_RF1][4];
        {
            const uint32_t L = l16, fa = sb + FRAG();
            mbar_wait_w(sb + MB_W0, 0);
            KT_MARK(6);
#pragma unroll
            for (int r = 0; r < 24; r++) ldsm4t(wv[r], fa + STG_V + r * 2048);
#pragma unroll
            for (int r = 0; r < 8 + WO_RF1; r++) asm volatile("" : "=r"(wo[r][0]), "=r"(wo[r][1]), "=r"(wo[r][2]), "=r"(wo[r][3]));
            mbar_wait_w(sb + MB_W2, 0);
            bar_sync(BAR_PDONE, 384);
        }
        const uint32_t xbox = mlo + WIN + page_off(pair & 31, cls ^ XFLIP);
        const uint32_t ybox = mlo + page_off(2 * g + 32 * nh, kh ^ YFLIP_()) + h * 128;
#pragma unroll 1
        for (uint32_t it = 0; it < NSEG + 3; it++) {
            const int s = (int)it - 3;
            const uint32_t ui = uniform(it), slot = ((ui + 1) & 3) << 14, kvo = (~ui & 1) * KV_BYTES, xtlo = XTLO();
            {
                PHASE(5);
                const uint32_t first = L | (g << 9);
                if (s >= 0) mbar_expect_tx_if0(first, sb + MB_R2, 1024);
                if (s + 3 < NSEG) {
                    mbar_expect_tx_if0(first, sb + MB_RT1, 2048);
                    mbar_wait_w(sb + MB_XT + (ui & 1) * 8, (it >> 1) & 1);
                }
            }
            if (s >= 0) {
                PHASE(0);
                uint32_t fr = FRAG();
                asm("" : "+r"(fr));
                const uint32_t fo = fr + sb, l4 = L >> 2;
                {
                    const uint32_t mb = L + (sb + SM_Z), aw = fo + SM_WQK, ra = L + (sb + g * 512), r2 = (L >> 1) + (rsb + SM_R2 + g * 256), r2b = rsb + MB_R2;
                    uint32_t a[NA][4], b[4][4];
#pragma unroll
                    for (int i = 0; i < NA; i++) ldsm4t(a[i], aw + i * 2048);
                    sched_fence(L);
                    TL(24);
                    bar_sync(BAR_MEM, 384);
#pragma unroll
                    for (int p = 0; p < 4; p++) ldsm4t(b[p], mb + (12 + p) * 512);
                    sched_fence(L);
                    float c[2][4] = {{0.f, 0.f, 0.f, 0.f}, {0.f, 0.f, 0.f, 0.f}};
#pragma unroll
                    for (int i = 0; i < 16; i++) {
                        mma16816v(c[i & 1], a[i % NA], b[i >> 2][i & 2], b[i >> 2][(i & 2) + 1]);
                        ldsm4t(a[i % NA], aw + (i + NA) * 2048);
                        if (QF >> i & 1) sched_fence(L);
                    }
                    sts128(ra + SM_R3, make_uint4(__float_as_uint(c[0][0]), __float_as_uint(c[0][1]), __float_as_uint(c[0][2]), __float_as_uint(c[0][3])));
                    sts128(ra + SM_O, make_uint4(__float_as_uint(c[1][0]), __float_as_uint(c[1][1]), __float_as_uint(c[1][2]), __float_as_uint(c[1][3])));
                    bar_arrive(BAR_Q3, 256);
                    if (QF >> 16 & 1) sched_fence(L);
                    TL(29);
                    float acc[4][4];
#pragma unroll
                    for (int t = 0; t < 4; t++) { acc[t][0] = acc[t][1] = acc[t][2] = acc[t][3] = 0.f; }
#pragma unroll
                    for (int i = 16; i < 24; i++) {
                        mma16816v(acc[i & 1], a[i % NA], b[(i - 16) >> 1][2 * (i & 1)], b[(i - 16) >> 1][2 * (i & 1) + 1]);
                        if (i + NA < 24) ldsm4t(a[i % NA], aw + (i + NA) * 2048);
                        else ldsm4t(a[i % NA], mb + (i + NA - 24) * 512);
                    }
#pragma unroll
                    for (int p = 0; p < 12; p++) {
                        mma16816v(acc[(2 * p) & 3], wv[2 * p], a[(24 + p) % NA][0], a[(24 + p) % NA][1]);
                        mma16816v(acc[(2 * p + 1) & 3], wv[2 * p + 1], a[(24 + p) % NA][2], a[(24 + p) % NA][3]);
                        if (p + NA < 12) ldsm4t(a[(24 + p) % NA], mb + (p + NA) * 512);
                    }
                    if (s + 3 < NSEG) bar_arrive(BAR_VP, 256);
                    float o[4];
#pragma unroll
                    for (int i = 0; i < 4; i++) o[i] = (acc[0][i] + acc[1][i]) + (acc[2][i] + acc[3][i]);
                    st_async2(r2, kh ? o[0] : o[2], kh ? o[1] : o[3], r2b);
                    TL(10);
                    const float o0 = kh ? o[2] : o[0], o1 = kh ? o[3] : o[1];
                    const uint32_t qo = SM_QKV + 4096 + nh * 1024 + (2 * g + kh) * 128, qr = l4 + (rsb + qo), ql = l4 + (sb + qo), vb = rsb + MB_V, rl = (L >> 1) + (sb + SM_R2 + g * 256);
                    char* xd = make_ptr(l4 + (xbox + 2048 + (2 * g + kh) * 128 + slot), mhi);
                    asm volatile("" ::"l"(xd), "r"(qr), "r"(vb), "f"(o0), "f"(o1));
                    mbar_wait_w(sb + MB_R2, s & 1);
                    uint32_t vx, vy;
                    asm volatile("ld.shared.v2.u32 {%0,%1}, [%2];" : "=r"(vx), "=r"(vy) : "r"(rl) : "memory");
                    const uint32_t w0 = pack_bf16(o0 + __uint_as_float(vx), o1 + __uint_as_float(vy));
                    st_relaxed_u32(xd, w0);
                    bar_arrive(BAR_PUBV, 160);
                    st_async1(qr, w0, vb);
                    sts32(ql, w0);
                    __syncwarp();
                    mbar_expect_tx_if0(L, sb + MB_V, 128);
                    TL(11);
                }
                const uint32_t vma = L + (sb + SM_QKV + 4096 + g * 512), yo = l4 + (ybox + slot);
                uint32_t va[2][2][4];
                {
                    const uint32_t qa = QFRAG(), vf = fr ^ ((g << 5) ^ ((g & 1) << 6)), va0 = vf + VBASE(), va1 = (vf ^ 32) + VBASE();
                    const uint32_t kf = ((L << 3) & 0x380) | ((L ^ (L >> 3)) & 0x30) | (L & 0x40), kb0 = sb + SM_KV + kvo + g * 1024;
                    const int d = (int)(L >> 6) - (int)((L >> 3) & 6) + 8 * (j - (int)g);
                    const uint32_t keep = (d < 0 ? 0u : 0xFFFFu) | (d < 1 ? 0u : 0xFFFF0000u), sa = l4 + (sb + SM_S + g * 128);
                    const uint32_t q0 = qa + (sb + nh * 1024), q1 = qa + (sb + (nh ^ 1) * 1024);
                    float sc[4] = {0.f, 0.f, 0.f, 0.f}, sd[4] = {0.f, 0.f, 0.f, 0.f};
                    uint32_t a[4][4], kb[2][4];
                    mbar_wait_w(sb + MB_KV + (~ui & 1) * 8, (s >> 1) & 1);
                    ldsm4(kb[0], kf + (kb0 + nh * 4096)); ldsm4(kb[1], (kf ^ 64) + (kb0 + nh * 4096));
                    mbar_wait_w(sb + MB_P, s & 1);
                    TL(12);
#pragma unroll
                    for (int k = 0; k < 4; k++) ldsm4t(a[k], q0 + k * 256);
#pragma unroll
                    for (int k = 0; k < 4; k++) mma16816v((k & 1) ? sd : sc, a[k], kb[k >> 1][2 * (k & 1)], kb[k >> 1][2 * (k & 1) + 1]);
                    ldsm4(kb[0], kf + (kb0 + (nh ^ 1) * 4096)); ldsm4(kb[1], (kf ^ 64) + (kb0 + (nh ^ 1) * 4096));
                    sched_fence(vf | yo);
                    if (TS_AT == 8) TL(21);
                    bar_sync(BAR_QK, 224);
                    TLB(3);
#pragma unroll
                    for (int k = 0; k < 4; k++) ldsm4t(a[k], q1 + k * 256);
                    sched_fence(L);
#pragma unroll
                    for (int k = 0; k < 4; k++) mma16816v((k & 1) ? sd : sc, a[k], kb[k >> 1][2 * (k & 1)], kb[k >> 1][2 * (k & 1) + 1]);
                    ldsm4t(va[0][0], va0); ldsm4t(va[0][1], va0 + 2048);
                    sts32(sa, scale_scores(sc[0] + sd[0], sc[1] + sd[1]));
                    sts32(sa + 768, (scale_scores(sc[2] + sd[2], sc[3] + sd[3]) & keep) | (0xFF80FF80u & ~keep));
                    bar_arrive(BAR_SV, NSV);
                    ldsm4t(va[1][0], va1); ldsm4t(va[1][1], va1 + 2048);
                }
                bar_sync(BAR_S, 160);
                TLB(4);
                uint32_t pw[6], vm[4];
                if (s + 1 < NSEG) {
                softmax40(pw, l4 + (sb + SM_S), [&]() {
                    bar_sync(BAR_V, 160);
                    ldsm4(vm, vma);
                });
                uint32_t a1[NP2][4];
                float inv[2];
                {
                    uint32_t w[4];
                    pv32<false>(w, inv, va, vm, pw, [&]() {
                        sched_fence(L);
#pragma unroll
                        for (int k = 0; k < NP2; k++) ldsm4t(a1[k], fo + SM_WO2 + k * 2048);
                    });
#pragma unroll
                    for (int i = 0; i < 4; i++) sts32(l4 + (sb + SM_O + g * 512) + i * 128, w[i]);
                }
                const uint32_t lo = L + (sb + SM_O);
                bar_arrive(BAR_O2, 256);
                bar_sync(BAR_O, 128);
                TLB(5);
                {
                    float y0[4] = {0.f, 0.f, 0.f, 0.f}, y1[4] = {0.f, 0.f, 0.f, 0.f}, y2[4] = {0.f, 0.f, 0.f, 0.f};
                    uint32_t b[4][4];
#pragma unroll
                    for (int p = 0; p < 4; p++) ldsm4t(b[p], lo + p * 512);
                    inv[0] = rcp_approx(inv[0]); inv[1] = rcp_approx(inv[1]);
                    asm volatile("st.shared.v2.f32 [%0], {%1, %2};" ::"r"(((L >> 1) & 0x18) + (sb + SM_INV + g * 32)), "f"(inv[0]), "f"(inv[1]) : "memory");
                    bar_arrive(BAR_INV, 256);
                    sched_fence(L);
#pragma unroll
                    for (int k = 0; k < 8; k++) {
                        const int p = k >> 1, u = k & 1;
                        mma16816v(y2, a1[k % NP2], b[p][2 * u], b[p][2 * u + 1]);
                        if (k + NP2 < 8) ldsm4t(a1[k % NP2], fo + SM_WO2 + (k + NP2) * 2048);
                        else if (k + NP2 < 16 - WO_RF1) ldsm4t(a1[k % NP2], fo + SM_WO1 + (k + NP2 - 8 + WO_RF1) * 2048);
                        mma16816v(y0, wo[k], b[p][2 * u], b[p][2 * u + 1]);
                        if (k < WO_RF1) mma16816v(y1, wo[8 + (k < WO_RF1 ? k : 0)], b[p][2 * u], b[p][2 * u + 1]);
                        else mma16816v(y1, a1[(k + 8 - WO_RF1) % NP2], b[p][2 * u], b[p][2 * u + 1]);
                        if (k < P2_FENCE) sched_fence(L);
                    }
                    char* yd = make_ptr(yo, mhi);
                    char* yd1 = make_ptr(yo ^ 4096, mhi);
                    st_relaxed_u32(yd1 + 0x80000, pack_bf16(y2[0] * inv[0], y2[1] * inv[1]));
                    st_relaxed_u32(yd + 0x82000, pack_bf16(y2[2] * inv[0], y2[3] * inv[1]));
                    st_relaxed_u32(yd, pack_bf16(y0[0] * inv[0], y0[1] * inv[1]));
                    st_relaxed_u32(yd1 + 0x2000, pack_bf16(y0[2] * inv[0], y0[3] * inv[1]));
                    st_relaxed_u32(yd + 0x40000, pack_bf16(y1[0] * inv[0], y1[1] * inv[1]));
                    st_relaxed_u32(yd1 + 0x42000, pack_bf16(y1[2] * inv[0], y1[3] * inv[1]));
                }
                bar_arrive(BAR_SENTC, 384);
                TL(13);
                bar_sync(BAR_SENT, 256);
                } else {
                    bar_sync(BAR_V, 160);
                }
            } else {
                if (it == WO_IT) {
                    PHASE(2);
                    const uint32_t fa = sb + FRAG();
                    mbar_wait_w(sb + MB_W3, 0);
                    KT_MARK(8);
#pragma unroll
                    for (int r = 0; r < 8 + WO_RF1; r++) ldsm4t(wo[r], fa + stg_wo(r));
                }
                bar_sync(BAR_PRO, 288);
            }
            float o[8];
            uint32_t w[4];
            {
                PHASE(1);
                float d[16];
                const uint64_t da = make_desc(SB0 + SM_WV, 16, 1024);
                auto batch = [&](auto k0c, auto k1c) {
                    static_for<decltype(k0c)::value, decltype(k1c)::value>([&](auto kc) {
                        constexpr int i = decltype(kc)::value, k = kstep(ORDV, i), off = (k >> 2) * 256 + (k & 3) * 2;
                        if constexpr (k >= 24) wgmma_ss32u<off, i != 0>(d, da + (k - 24) * 128, xtlo);
                        else wgmma_rs32u<off, i != 0>(d, wv[k], xtlo);
                    });
                };
                const uint32_t vf = VFRAG(), va0 = vf + VBASE(), va1 = (vf ^ 32) + VBASE(), vma = L + (sb + SM_QKV + 4096 + g * 512), sa = (L >> 2) + (sb + SM_S + 768);
                const uint32_t rt = L + (rsb + SM_RT + 8192 + g * 512);
                uint32_t va[2][2][4], vm[4], pw[6];
                wg_fence();
                batch(std::integral_constant<int, 0>(), std::integral_constant<int, TA0>());
                wg_commit();
                batch(std::integral_constant<int, TA0>(), std::integral_constant<int, 32>());
                wg_commit();
                wg_wait<1>();
                if (RT0_B == 3 && (unsigned)s < NSEG - 3) bar_sync(BAR_VP, 256);
                softmax40(pw, sa, [&]() {});
                ldsm4t(va[0][0], va0); ldsm4t(va[0][1], va0 + 2048);
                ldsm4t(va[1][0], va1); ldsm4t(va[1][1], va1 + 2048);
                ldsm4(vm, vma);
                if (RT0_B == 1 && (unsigned)s < NSEG - 3) bar_sync(BAR_VP, 256);
                wg_wait<0>();
                if (RT0_B == 2 && (unsigned)s < NSEG - 3) bar_sync(BAR_VP, 256);
                TL(27);
                float inv[2];
                pv32<true>(w, inv, va, vm, pw, [&]() {
                    uint32_t q[4];
#pragma unroll
                    for (int i = 0; i < 4; i++) q[i] = pack_bf16(kh ? d[2 * i] : d[8 + 2 * i], kh ? d[2 * i + 1] : d[9 + 2 * i]);
                    if (RT0_B == 4 && (unsigned)s < NSEG - 3) bar_sync(BAR_VP, 256);
                    if (s + 3 < NSEG) st_async4(rt, __uint_as_float(q[0]), __uint_as_float(q[1]), __uint_as_float(q[2]), __uint_as_float(q[3]), rsb + MB_RT1);
#pragma unroll
                    for (int i = 0; i < 8; i++) o[i] = kh ? d[8 + i] : d[i];
                });
                TL(26);
            }
            if (s + 3 < NSEG) {
                PHASE(3);
                const uint32_t rt = L + (sb + SM_RT + 8192 + g * 512), so = FRAG() + (sb + SM_STG + 4096);
                mbar_wait_w(sb + MB_RT1, it & 1);
                TL(28);
                const uint4 v = lds128(rt);
                stsm4t(so, pack_bf16(o[0] + bf_lo(v.x), o[1] + bf_hi(v.x)), pack_bf16(o[2] + bf_lo(v.y), o[3] + bf_hi(v.y)),
                       pack_bf16(o[4] + bf_lo(v.z), o[5] + bf_hi(v.z)), pack_bf16(o[6] + bf_lo(v.w), o[7] + bf_hi(v.w)));
                if (!OTMA) { __syncwarp(); mbar_arrive_if0(L, sb + MB_STG); }
                TL(15);
            }
            if (OTMA) {
                PHASE(7);
                __syncwarp();
                stsm4t((((L << 2) & 0x1C0) | (((L >> 3) ^ (L >> 1)) & 0x30)) + (sb + SM_OT + g * 512), w[0], w[1], w[2], w[3]);
                __syncwarp();
                mbar_arrive_if0(L, sb + MB_STG);
            }
        }
        if ((OTMA || TAIL) && (TM & 2) && COLD()) bar_arrive(BAR_ZP, 160);
        if (TAIL && (TM & 2) && COLD()) last_tile(1);
    }
    KT_END(TAIL ? 3 : 2);
    asm volatile("barrier.cluster.arrive.relaxed; barrier.cluster.wait;" ::: "memory");
}
constexpr int B_UCH = 73 * 64;
constexpr int B_SCH = 33 * 64;
constexpr int B_KLEN = 2128;
constexpr int B_KCH = 2 * B_KLEN * 2 + 64;
constexpr int B_KBOX = 136 * 32;
constexpr int B_SM_U = 0;
constexpr int B_SM_S = 8 * B_UCH;
constexpr int B_SM_K = B_SM_S + 8 * B_SCH;
constexpr int B_SM_KT = B_SM_K + 8 * B_KCH;
constexpr int B_SM_VT = B_SM_KT + 8 * B_KBOX;
constexpr int B_SM_QT = B_SM_VT + 32768;
constexpr int B_SM_BAR = B_SM_QT + 32768;
constexpr int B_SMEM = B_SM_BAR + 128 + 512;
static_assert(B_SM_KT % 256 == 0 && B_SM_S % 512 == 0 && B_SMEM <= 232448, "tiles");
constexpr int PROBE_N = 4;
#define PROBE_R 2
constexpr int B_C = 2056;

__device__ __forceinline__ uint32_t atomic_round_trip(char* p) {
    uint32_t t0, t1, v;
    asm volatile("{.reg .pred p;\n"
                 "mov.u32 %0, %%clock;\n"
                 "atom.relaxed.gpu.global.add.u32 %2, [%3], 1;\n"
                 "setp.ne.u32 p, %2, 0x7FFFFFFF;\n"
                 "mov.u32 %1, 0;\n"
                 "@p mov.u32 %1, %%clock;}" : "=&r"(t0), "=&r"(t1), "=&r"(v) : "l"(p) : "memory");
    return t1 - t0;
}
__device__ __forceinline__ uint32_t round_trips(char* a, char* b, uint32_t stride, int lane) {
    for (int i = lane >> 3; i < 2 * PROBE_N; i += 4) stg128(((i & 1) ? b : a) + (i >> 1) * stride + (lane & 7) * 16, make_uint4(0, 0, 0, 0));
    __syncwarp();
    uint32_t ta = 0xFFFF, tb = 0xFFFF;
    if (lane == 0) {
        __threadfence();
#pragma unroll 1
        for (int i = 0; i < PROBE_N; i++) { ta = min(ta, atomic_round_trip(a + i * stride)); tb = min(tb, atomic_round_trip(b + i * stride)); }
    }
    __syncwarp();
    return ta | (tb << 16);
}
__device__ __forceinline__ void measure_distance(char* mbox, int lane) {
    const uint32_t b = blockIdx.x;
    unsigned smid;
    asm volatile("mov.u32 %0, %%smid;" : "=r"(smid));
    char* w1 = mbox + WIN + (b & 31) * 128;
    uint32_t r = 0xFFFFFFFF;
#pragma unroll 1
    for (int i = 0; i < PROBE_R; i++) r = __vminu2(r, round_trips(w1 + page_off(50 + 5 * i + (b >> 5), 0), w1 + page_off(50 + 5 * i + (b >> 5), 1), 16384, lane));
    if (lane == 0) g_cls[smid] = r;
    if (b == 128) {
        char *p = mbox + page_off(0, 0), *q = mbox + page_off(0, 1);
        uint32_t r0 = 0xFFFFFFFF;
#pragma unroll 1
        for (int i = 0; i < PROBE_R; i++) r0 = __vminu2(r0, round_trips(p, q, 128, lane));
        if (lane == 0) { g_reg[1] = ((r0 & 0xFFFF) > (r0 >> 16)) != ((r & 0xFFFF) > (r >> 16)); if (!EARLY_ROLE) g_reg[0] = 0; g_reg[2] = 0; }
        const uint4 sent = make_uint4(SENT, SENT, SENT, SENT);
        stg128(p + lane * 16, sent); stg128(q + lane * 16, sent);
    }
    if (b == 129) for (int i = lane; i < 128; i += 32) g_xflag[i] = 0;
}

#define SP(i)
#define SP2(i)
#define OUT_STG 0
#define PF_STOP 1
#define SENT_AT 3
#define Q_LATE 1
#define PF_DEPTH 4
#define PF_STRIDE 256
struct ChainInputs { const char* w[4]; const char *x, *mem0; };
#define EF_MASK 15
#define EF(i) (((EF_MASK >> (i)) & 1) ? policy_evict_first() : policy_evict_normal())
__device__ __forceinline__ void l2_prefetch(const char* p, uint32_t bytes) {
    asm volatile("cp.async.bulk.prefetch.L2.global [%0], %1;" ::"l"(p), "r"(bytes) : "memory");
}
#define WG_CONV(N, LIST, A0, A1, A2, A3, LO, OF, ...) \
    if constexpr (NN == N) asm volatile("{.reg .b32 l; .reg .b64 e; add.u32 l, %" #LO ", %" #OF "; mov.b64 e, {l, 0x80000020};\n" \
        "wgmma.mma_async.sync.aligned.m64n" #N "k16.f32.bf16.bf16 {" LIST "}, {%" #A0 ",%" #A1 ",%" #A2 ",%" #A3 "}, e, 1, 1, 1, 0;}" \
        : __VA_ARGS__ : "r"(a[0]), "r"(a[1]), "r"(a[2]), "r"(a[3]), "r"(lo), "n"(OFF));
#define WL4 "%0,%1,%2,%3"
#define WL8 WL4 ",%4,%5,%6,%7"
#define WL12 WL8 ",%8,%9,%10,%11"
#define WL16 WL12 ",%12,%13,%14,%15"
#define WL20 WL16 ",%16,%17,%18,%19"
#define WL24 WL20 ",%20,%21,%22,%23"
#define WL28 WL24 ",%24,%25,%26,%27"
#define WL32 WL28 ",%28,%29,%30,%31"
template <int NN, int OFF> __device__ __forceinline__ void wgmma_conv(float (&d)[32], const uint32_t (&a)[4], uint32_t lo) {
    WG_CONV(8, WL4, 4, 5, 6, 7, 8, 9, R4(0))
    WG_CONV(16, WL8, 8, 9, 10, 11, 12, 13, R4(0), R4(4))
    WG_CONV(24, WL12, 12, 13, 14, 15, 16, 17, R4(0), R4(4), R4(8))
    WG_CONV(32, WL16, 16, 17, 18, 19, 20, 21, R16(0))
    WG_CONV(40, WL20, 20, 21, 22, 23, 24, 25, R16(0), R4(16))
    WG_CONV(48, WL24, 24, 25, 26, 27, 28, 29, R16(0), R4(16), R4(20))
    WG_CONV(56, WL28, 28, 29, 30, 31, 32, 33, R16(0), R4(16), R4(20), R4(24))
    WG_CONV(64, WL32, 32, 33, 34, 35, 36, 37, R16(0), R16(16))
}
__device__ __forceinline__ void copy_to_peer(uint32_t dst, uint32_t src, uint32_t bytes, uint32_t bar) {
    asm volatile("cp.async.bulk.shared::cluster.shared::cta.mbarrier::complete_tx::bytes [%0], [%1], %2, [%3];" ::"r"(dst), "r"(src), "r"(bytes), "r"(bar) : "memory");
}
__device__ __forceinline__ uint32_t lds_volatile(uint32_t a) {
    uint32_t v;
    asm volatile("ld.volatile.shared.u32 %0, [%1];" : "=r"(v) : "r"(a) : "memory");
    return v;
}
__device__ __forceinline__ uint32_t swz64(uint32_t a) { return a ^ ((a >> 3) & 0x30); }
__device__ __forceinline__ void fence_async() { asm volatile("fence.proxy.async.shared::cta;" ::: "memory"); }

__global__ void __cluster_dims__(2, 1, 1) __launch_bounds__(576, 1)
ssm_kernel(const __grid_constant__ CUtensorMap mapK, const __grid_constant__ CUtensorMap mapV, const __grid_constant__ CUtensorMap mapQ,
           const __grid_constant__ CUtensorMap mapO, const bf16* __restrict__ shiftk, const bf16* __restrict__ ssmk, const bf16* __restrict__ Dv,
           char* __restrict__ mbox, const __grid_constant__ ChainInputs ci, bf16* __restrict__ outp) {
    extern __shared__ __align__(128) uint8_t smem_raw[];
    const uint32_t sb = (smem_u32(smem_raw) + 511) & ~511u;
    const int rank = blockIdx.x & 1, ch0 = blockIdx.x * 8, c16 = ch0 & ~15, t0 = rank * 1024;
    const int t = threadIdx.x, warp = t >> 5, lane = t & 31;
    const uint32_t bar = sb + B_SM_BAR, barQ = bar + 64, barU = bar + 72, barY = bar + 80, flag = bar + 88;
    SP(0);
    if (lane == 0 && warp < 16 && blockIdx.x < 128) {
        const int i = warp >> 1;
        if (warp & 1) {
            if (i < 3) { mbar_init(barQ + i * 8, 1); mbar_expect_tx(barQ + i * 8, i ? 16384 : 32768); }
            if (i == 3) sts32(flag, 0);
        } else {
            mbar_init(bar + i * 8, 1);
            asm volatile("fence.mbarrier_init.release.cluster;" ::: "memory");
            mbar_expect_tx(bar + i * 8, B_KBOX + 4096);
            tma_load_2d(sb + B_SM_KT + i * B_KBOX, &mapK, c16, t0 + i * 128 - 8, bar + i * 8, EF(0));
            tma_load_2d(sb + B_SM_VT + i * 4096, &mapV, c16, t0 + i * 128, bar + i * 8, EF(0));
        }
        asm volatile("fence.mbarrier_init.release.cluster;" ::: "memory");
    }
    __syncwarp();
    if (warp == 14) SP2(14);
    KT_START(1);
    if (warp == 17) {
        launch_dependents();
        asm volatile("barrier.cluster.arrive.relaxed.aligned;" ::: "memory");
        measure_distance(mbox, lane);
        asm volatile("barrier.cluster.wait.aligned;" ::: "memory");
        KT_MARK(14);
        return;
    }
    if (blockIdx.x >= 128) return;
    if (warp == 16) {
        asm volatile("barrier.cluster.arrive.relaxed.aligned; barrier.cluster.wait.aligned;" ::: "memory");
        SP2(8);
        if (Q_LATE) for (int i = 0; i < 8; i++) { mbar_wait_w(bar + i * 8, 0); SP2(i); }
        if (lane < 8) tma_load_2d(sb + B_SM_QT + lane * 4096, &mapQ, c16, t0 + lane * 128, barQ, EF(3));
        if (!Q_LATE) for (int i = 0; i < 8; i++) mbar_wait_w(bar + i * 8, 0);
        if (lane == 0) {
            l2_prefetch(ci.x + blockIdx.x * 2048, 2048);
            if (blockIdx.x < 8) l2_prefetch(ci.mem0 + blockIdx.x * 2048, 2048);
        }
        uint32_t v[PF_DEPTH], acc = 0;
#pragma unroll
        for (int u = 0; u < PF_DEPTH; u++) v[u] = 0;
        constexpr int PER = 32 * PF_STRIDE, NW = 65536 / PER;
#define PF_N (4 * NW)
        int i = 0;
#pragma unroll 1
        for (; i < PF_N && lds_volatile(flag) == 0; i += PF_DEPTH) {
#pragma unroll
            for (int u = 0; u < PF_DEPTH; u++) {
                const char* a = ci.w[(i + u) / NW] + blockIdx.x * 65536 + ((i + u) % NW) * PER + lane * PF_STRIDE;
                acc |= v[u];
                asm volatile("ld.global.cg.L2::256B.u32 %0, [%1];" : "=r"(v[u]) : "l"(a) : "memory");
            }
        }
#pragma unroll
        for (int u = 0; u < PF_DEPTH; u++) acc |= v[u];
        if (acc == 0x7FFF7FFFu && v[0] == 0x7FFEu) g_err = 1;
        SP2(12);
        KT_MARK(15);
        return;
    }
    asm volatile("barrier.cluster.arrive.relaxed.aligned;" ::: "memory");
    const int far = warp & 1, unit = rank ^ far;
    uint32_t w[4];
    uint32_t d2;
    asm volatile("ld.global.nc.u32 %0, [%1];" : "=r"(d2) : "l"(Dv + ch0 + (warp >> 2) * 2));
    {
        const int ch = warp & 7, half = warp >> 3;
        const uint32_t kb = sb + B_SM_K + ch * B_KCH;
        const uint4* src = reinterpret_cast<const uint4*>(ssmk + (size_t)(ch0 + ch) * S_LEN);
        uint4 kr[4];
#pragma unroll
        for (int i = 0; i < 4; i++) kr[i] = ldg128(src + half * 128 + i * 32 + lane, EF(1));
        const uint32_t edge = half ? 0u : __ldg(reinterpret_cast<const uint32_t*>(src + 128));
        const uint2 sw = __ldg(reinterpret_cast<const uint2*>(shiftk + (size_t)(c16 + unit * 8 + (lane >> 2)) * 4));
        w[0] = __byte_perm(sw.x, 0, 0x1010); w[1] = __byte_perm(sw.x, 0, 0x3232); w[2] = __byte_perm(sw.y, 0, 0x1010); w[3] = __byte_perm(sw.y, 0, 0x3232);
        if (half) sts128(sb + B_SM_U + ch * B_UCH + 4096 + lane * 16, make_uint4(0, 0, 0, 0));
#pragma unroll
        for (int i = 0; i < 4; i++) {
            const uint4 lo = kr[i];
            const uint32_t nx = __shfl_down_sync(~0u, lo.x, 1), n0 = (i < 3) ? __shfl_sync(~0u, kr[i < 3 ? i + 1 : 3].x, 0) : edge;
            const uint32_t hix = (lane < 31) ? nx : n0;
            const int c = 256 - (half * 128 + 32 * i + lane);
            sts128(kb + c * 16, make_uint4(__byte_perm(hix, lo.w, 0x7610), __byte_perm(lo.w, lo.z, 0x7610), __byte_perm(lo.z, lo.y, 0x7610), __byte_perm(lo.y, lo.x, 0x7610)));
            sts128(kb + B_KLEN * 2 + 64 + c * 16, make_uint4(__byte_perm(lo.w, lo.w, 0x1032), __byte_perm(lo.z, lo.z, 0x1032), __byte_perm(lo.y, lo.y, 0x1032), __byte_perm(lo.x, lo.x, 0x1032)));
        }
        const uint32_t k0w = __shfl_sync(~0u, kr[0].x, 0);
        if (half == 0 && lane < 8) {
            sts128(kb + (257 + lane) * 16, make_uint4(lane == 0 ? (k0w & 0xFFFFu) : 0u, 0u, 0u, 0u));
            sts128(kb + B_KLEN * 2 + 64 + (257 + lane) * 16, make_uint4(0u, 0u, 0u, 0u));
        }
    }
    auto sentinels = [&]() {
        const uint4 sent = make_uint4(SENT, SENT, SENT, SENT);
        char* p0 = mbox + blockIdx.x * 16384 + t * 16;
        if (blockIdx.x != 0 || (t & 255) >= 32) stg128(p0, sent);
        stg128(p0 + 8192, sent);
        char* p1 = mbox + WIN + blockIdx.x * 12800 + t * 16;
        stg128(p1, sent);
        if (t < 288) stg128(p1 + 8192, sent);
    };
    if (SENT_AT == 1) sentinels();
    asm volatile("barrier.cluster.wait.acquire.aligned;" ::: "memory");
    SP(1);
    {
        const int box = warp >> 1, row0 = 63 - 32 * rank - 4 * box;
        const uint32_t kt = sb + B_SM_KT + box * B_KBOX + 256 + lane * 32, s0 = (unit ^ ((lane >> 2) & 1)) * 16;
        const uint32_t a0 = kt + s0, a2 = kt - 64 + (unit ^ (((lane + 6) >> 2) & 1)) * 16, a4 = kt - 128 + (s0 ^ 16), av = sb + B_SM_VT + box * 4096 + lane * 32 + s0;
        const uint32_t ul = (lane & 7) * B_UCH + row0 * 64 + (lane >> 3) * 16;
        const uint32_t ud = sb + (far ? B_SM_S + (lane & 7) * (B_SCH - B_UCH) - (1 - rank) * 2048 : B_SM_U);
        mbar_wait_w(bar + box * 8, 0);
        SP(2);
#pragma unroll
        for (int i = 0; i < 4; i++) {
            uint32_t k0[4], k2[4], k4[4], vv[4], o[4];
            ldsm4t(k0, a0 + i * 1024); ldsm4t(k2, a2 + i * 1024); ldsm4t(k4, a4 + i * 1024); ldsm4t(vv, av + i * 1024);
#pragma unroll
            for (int j = 0; j < 4; j++) {
                uint32_t a = bf16_mul(__byte_perm(k4[j], k2[j], 0x5432), w[3]);
                a = bf16_add(a, bf16_mul(k2[j], w[2]));
                a = bf16_add(a, bf16_mul(__byte_perm(k2[j], k0[j], 0x5432), w[1]));
                a = bf16_add(a, bf16_mul(k0[j], w[0]));
                o[j] = bf16_mul(a, vv[j]);
            }
            stsm4(ud + swz64(ul - i * 64), o[0], o[1], o[2], o[3]);
        }
        fence_async();
        __syncwarp();
        if (far && lane < 8) {
            const uint32_t o = lane * B_UCH + (row0 - 3) * 64;
            copy_to_peer(peer_addr(sb + B_SM_U + o, rank ^ 1), ud + o, 256, peer_addr(barU, rank ^ 1));
        }
    }
    bar_sync(1, 512);
    mbar_wait_w(barU, 0);
    if (SENT_AT == 2) sentinels();
    SP(3);
    const int wg = warp >> 2, wq = warp & 3, hi = wq >> 1, g = lane >> 2, tq = lane & 3;
    const uint32_t zero = lds32(sb + B_SM_U + 4096);
#pragma unroll 1
    for (int cc = 0; cc < 2; cc++) {
        const int ch = 2 * wg + cc;
        const uint32_t kb = sb + B_SM_K + ch * B_KCH, ub = sb + B_SM_U + ch * B_UCH;
        const uint32_t dw = __byte_perm(d2, 0, cc ? 0x3232 : 0x1010);
        const int e0 = B_C - g + 2 * tq;
        const uint32_t f0 = ((e0 & 1) ? (kb + B_KLEN * 2 + 64 + (e0 - 1) * 2) : (kb + e0 * 2)) - 32 * wq;
        const uint32_t lo = uniform((ub >> 4) | 0x10000);
        float d[32];
#pragma unroll
        for (int i = 0; i < 32; i++) d[i] = 0.f;
        uint32_t A[2][2][4];
        static_for<0, 32>([&](auto jc) {
            constexpr int j = decltype(jc)::value, N = 64 - 8 * (j / 4);
            if (j >= 2) wg_wait<1>();
            uint32_t(&a)[4] = A[j & 1][0];
            uint32_t(&b)[4] = A[j & 1][1];
            a[0] = lds32(f0 - 128 * j); a[1] = lds32(f0 - 128 * j - 16); a[2] = lds32(f0 - 128 * j + 16);
            b[0] = lds32(f0 - 128 * j + 32); b[2] = lds32(f0 - 128 * j + 48);
            a[3] = a[0] ^ zero; b[1] = a[2] ^ zero; b[3] = b[0] ^ zero;
            wg_fence();
            wgmma_conv<N, 8 * j>(d, a, lo);
            wgmma_conv<N, 8 * j + 2>(d, b, lo);
            wg_commit();
        });
        wg_wait<0>();
        if (cc) SP(4);
        if (PF_STOP == 1 && cc && t == 0) sts32(flag, 1);
        bar_sync(2 + wg, 128);
        if (!hi && tq == 3) { float x = d[13]; d[13] = d[29]; d[29] = x; x = d[15]; d[15] = d[31]; d[31] = x; }
        if (hi && tq == 0) { d[0] = 0.f; d[2] = 0.f; }
        {
            const uint32_t xs = kb + (wq ^ 2) * 2048 + lane * 4;
            const uint32_t xn = hi ? xs + (tq ? 124 : 140) : xs + (tq < 3 ? 4 : -12), wrap = hi ? (tq ? 0 : -1) : (tq < 3 ? 0 : 1);
#pragma unroll
            for (int nb = 0; nb < 4; nb++) {
                const uint32_t xw = xn + ((nb + wrap) & 3) * 512;
#pragma unroll
                for (int i = 0; i < 2; i++) {
                    const float e0v = hi ? d[4 * nb + 2 * i] : d[16 + 4 * nb + 2 * i], e1v = hi ? d[4 * nb + 2 * i + 1] : d[16 + 4 * nb + 2 * i + 1];
                    sts32(hi ? xw + i * 256 : xs + nb * 512 + i * 256 + 128, __float_as_uint(e0v));
                    sts32(hi ? xs + nb * 512 + i * 256 : xw + i * 256, __float_as_uint(e1v));
                }
            }
        }
        bar_sync(2 + wg, 128);
#pragma unroll
        for (int p = 0; p < 2; p++) {
            int row = 16 * p + (lane >> 4) * 8 + (lane & 7);
            row = hi ? row + 31 : row == 31 ? 63 : row;
            const uint32_t a = sb + B_SM_U + swz64(ch * B_UCH + row * 64 + ((wq & 1) * 2 + ((lane >> 3) & 1)) * 16);
            uint32_t u[4];
            ldsm4t(u, a);
#pragma unroll
            for (int b = 0; b < 4; b++) {
                const int r = 8 * p + 2 * b;
                const float y0 = (hi ? d[16 + r] : d[r]) + __uint_as_float(lds32(kb + wq * 2048 + r * 128 + lane * 4));
                const float y1 = (hi ? d[17 + r] : d[r + 1]) + __uint_as_float(lds32(kb + wq * 2048 + r * 128 + 128 + lane * 4));
                u[b] = bf16_add(pack_bf16(y0, y1), bf16_mul(u[b], dw));
            }
            stsm4t(a, u[0], u[1], u[2], u[3]);
        }
        fence_async();
        bar_sync(2 + wg, 128);
        if (SENT_AT == 3 && cc == 0) sentinels();
        if (wq == 0 && lane == 0) copy_to_peer(peer_addr(sb + B_SM_S + ch * B_SCH, rank ^ 1), ub + rank * 2048, 2048, peer_addr(barY, rank ^ 1));
    }
    if (PF_STOP == 2 && t == 0) sts32(flag, 1);
    SP(5);
    mbar_wait_w(barQ, 0);
    bar_sync(1, 512);
    mbar_wait_w(barY, 0);
    asm volatile("barrier.cluster.arrive.relaxed.aligned;" ::: "memory");
    SP(6);
#pragma unroll
    for (int i = 0; i < 4; i++) {
        const int fr = i & 1, row = 63 - 32 * rank - 2 * warp - (i >> 1);
        const uint32_t qa = sb + B_SM_QT + warp * 2048 + (i >> 1) * 1024 + lane * 32 + ((rank ^ fr ^ (lane >> 2)) & 1) * 16;
        uint32_t y[4], q[4];
        ldsm4t(y, sb + (fr ? B_SM_S + (lane & 7) * (B_SCH - B_UCH) - (1 - rank) * 2048 : B_SM_U) + swz64((lane & 7) * B_UCH + row * 64 + (lane >> 3) * 16));
        ldsm4(q, qa);
        stsm4(qa, bf16_mul(q[0], y[0]), bf16_mul(q[1], y[1]), bf16_mul(q[2], y[2]), bf16_mul(q[3], y[3]));
    }
    fence_async();
    __syncwarp();
    if (lane == 0) {
        asm volatile("cp.async.bulk.tensor.2d.global.shared::cta.bulk_group.L2::cache_hint [%0, {%2, %3}], [%1], %4;"
                     ::"l"(&mapO), "r"(sb + B_SM_QT + warp * 2048), "r"(DM + c16), "r"(t0 + warp * 64), "l"(EF(4)) : "memory");
        asm volatile("cp.async.bulk.commit_group;" ::: "memory");
    }
    if (SENT_AT == 0) sentinels();
    if (warp == 0) SP2(10);
    if (lane == 0) asm volatile("cp.async.bulk.wait_group.read 0;" ::: "memory");
    __syncwarp();
    if (warp == 0) SP2(11);
    asm volatile("barrier.cluster.wait.aligned;" ::: "memory");
    SP(7);
    KT_END(1);
}

typedef CUresult (*EncodeFn)(CUtensorMap*, CUtensorMapDataType, cuuint32_t, void*, const cuuint64_t*, const cuuint64_t*, const cuuint32_t*,
                             const cuuint32_t*, CUtensorMapInterleave, CUtensorMapSwizzle, CUtensorMapL2promotion, CUtensorMapFloatOOBfill);

static void make_map(EncodeFn fn, CUtensorMap* m, const void* ptr, uint64_t inner, uint64_t outer, uint32_t box_in, uint32_t box_out,
                     CUtensorMapL2promotion promo = CU_TENSOR_MAP_L2_PROMOTION_L2_256B) {
    cuuint64_t dims[2] = {inner, outer};
    cuuint64_t strides[1] = {inner * 2};
    cuuint32_t box[2] = {box_in, box_out};
    cuuint32_t es[2] = {1, 1};
    fn(m, CU_TENSOR_MAP_DATA_TYPE_BFLOAT16, 2, const_cast<void*>(ptr), dims, strides, box, es, CU_TENSOR_MAP_INTERLEAVE_NONE,
       CU_TENSOR_MAP_SWIZZLE_128B, promo, CU_TENSOR_MAP_FLOAT_OOB_FILL_NONE);
}

#define G2_ST 7
#define PROMO_W CU_TENSOR_MAP_L2_PROMOTION_L2_256B
#define PROMO_O CU_TENSOR_MAP_L2_PROMOTION_L2_256B
#define SSM_PROMO CU_TENSOR_MAP_L2_PROMOTION_NONE
extern "C" void kernel_launch(void* const* d_in, const int* in_sizes, int n_in, void* d_out, int out_size) {
    const bf16* x = (const bf16*)d_in[0];
    const bf16* mem0 = (const bf16*)d_in[1];
    const bf16* Wq = (const bf16*)d_in[2];
    const bf16* Wk = (const bf16*)d_in[3];
    const bf16* Wv = (const bf16*)d_in[4];
    const bf16* Wo = (const bf16*)d_in[5];
    const bf16* Bq = (const bf16*)d_in[7];
    const bf16* Bk = (const bf16*)d_in[8];
    const bf16* Bv = (const bf16*)d_in[9];
    const bf16* Bsh = (const bf16*)d_in[10];
    const bf16* Bssm = (const bf16*)d_in[11];
    const bf16* BD = (const bf16*)d_in[12];
    bf16* out = (bf16*)d_out;

    static bool init = false;
    static EncodeFn enc = nullptr;
    static void *p_tok, *p_ox, *p_mbox;
    static int nclusters = 64;
    if (!init) {
        cudaDriverEntryPointQueryResult qr;
        cudaGetDriverEntryPoint("cuTensorMapEncodeTiled", (void**)&enc, cudaEnableDefault, &qr);
        cudaGetSymbolAddress(&p_tok, g_tok);
        cudaGetSymbolAddress(&p_ox, g_ox);
        cudaGetSymbolAddress(&p_mbox, g_mbox);
        cudaFuncSetAttribute(proj_kernel<128, 7>, cudaFuncAttributeMaxDynamicSharedMemorySize, PROJ_SMEM);
        cudaFuncSetAttribute(chain_kernel<false>, cudaFuncAttributeMaxDynamicSharedMemorySize, CHAIN_SMEM);
        cudaFuncSetAttribute(chain_kernel<true>, cudaFuncAttributeMaxDynamicSharedMemorySize, CHAIN_SMEM);
        cudaFuncSetAttribute(ssm_kernel, cudaFuncAttributeMaxDynamicSharedMemorySize, B_SMEM);
        cudaLaunchConfig_t cfg = {};
        cfg.gridDim = dim3(132); cfg.blockDim = dim3(384); cfg.dynamicSmemBytes = CHAIN_SMEM;
        cudaLaunchAttribute at[1];
        at[0].id = cudaLaunchAttributeClusterDimension; at[0].val.clusterDim.x = 2; at[0].val.clusterDim.y = 1; at[0].val.clusterDim.z = 1;
        cfg.attrs = at; cfg.numAttrs = 1;
        int n = 0;
        if (cudaOccupancyMaxActiveClusters(&n, chain_kernel<true>, &cfg) == cudaSuccess && n > 64) nclusters = n < 66 ? n : 66;
        (void)cudaGetLastError();
        init = true;
    }
    char* mbox = (char*)(((uintptr_t)p_mbox + 2 * WIN - 1) & ~(uintptr_t)(2 * WIN - 1));
    CUtensorMap mX, mT32, mT16, mTQ, mKV, mWq, mWk, mWv, mWoC, mWo, mOx, mOut, mO8;
    {
        cuuint64_t dims[3] = {64, S_LEN, DM / 64};
        cuuint64_t strides[2] = {DM * 2, 128};
        cuuint32_t box[3] = {64, 32, 4};
        cuuint32_t es[3] = {1, 1, 1};
        enc(&mX, CU_TENSOR_MAP_DATA_TYPE_BFLOAT16, 3, const_cast<bf16*>(x), dims, strides, box, es, CU_TENSOR_MAP_INTERLEAVE_NONE,
            CU_TENSOR_MAP_SWIZZLE_128B, CU_TENSOR_MAP_L2_PROMOTION_L2_256B, CU_TENSOR_MAP_FLOAT_OOB_FILL_NONE);
    }
    make_map(enc, &mT32, p_tok, DH, 4 * NH * 3 * SEG, 64, 32, CU_TENSOR_MAP_L2_PROMOTION_L2_128B);
    make_map(enc, &mT16, p_tok, DH, 4 * NH * 3 * SEG, 64, 16, CU_TENSOR_MAP_L2_PROMOTION_L2_128B);
    {
        cuuint64_t dims[2] = {512, 4 * NH * 12};
        cuuint64_t strides[1] = {2048};
        cuuint32_t box[2] = {256, 4};
        cuuint32_t es[2] = {1, 1};
        enc(&mTQ, CU_TENSOR_MAP_DATA_TYPE_UINT32, 2, p_tok, dims, strides, box, es, CU_TENSOR_MAP_INTERLEAVE_NONE,
            CU_TENSOR_MAP_SWIZZLE_NONE, CU_TENSOR_MAP_L2_PROMOTION_L2_128B, CU_TENSOR_MAP_FLOAT_OOB_FILL_NONE);
    }
    {
        cuuint64_t dims[3] = {64, 4 * NH * 3 * SEG, 2};
        cuuint64_t strides[2] = {DH * 2, 128};
        cuuint32_t box[3] = {64, 32, 2};
        cuuint32_t es[3] = {1, 1, 1};
        enc(&mKV, CU_TENSOR_MAP_DATA_TYPE_BFLOAT16, 3, p_tok, dims, strides, box, es, CU_TENSOR_MAP_INTERLEAVE_NONE,
            CU_TENSOR_MAP_SWIZZLE_128B, CU_TENSOR_MAP_L2_PROMOTION_L2_128B, CU_TENSOR_MAP_FLOAT_OOB_FILL_NONE);
    }
    {
        cuuint64_t dims[3] = {32, S_LEN, HD / 32};
        cuuint64_t strides[2] = {HD * 2, 64};
        cuuint32_t box[3] = {32, 8, 4};
        cuuint32_t es[3] = {1, 1, 1};
        enc(&mO8, CU_TENSOR_MAP_DATA_TYPE_BFLOAT16, 3, p_ox, dims, strides, box, es, CU_TENSOR_MAP_INTERLEAVE_NONE,
            CU_TENSOR_MAP_SWIZZLE_64B, CU_TENSOR_MAP_L2_PROMOTION_L2_128B, CU_TENSOR_MAP_FLOAT_OOB_FILL_NONE);
    }
    make_map(enc, &mWq, Wq, HD, DM, 64, 16, CU_TENSOR_MAP_L2_PROMOTION_L2_128B);
    make_map(enc, &mWk, Wk, HD, DM, 64, 16, CU_TENSOR_MAP_L2_PROMOTION_L2_128B);
    make_map(enc, &mWv, Wv, HD, DM, 64, 16, CU_TENSOR_MAP_L2_PROMOTION_L2_128B);
    make_map(enc, &mWoC, Wo, DM, HD, 64, 16, CU_TENSOR_MAP_L2_PROMOTION_L2_128B);
    const bool early = nclusters >= 66;
    make_map(enc, &mWo, Wo, DM, HD, 64, 64, PROMO_W);
    make_map(enc, &mOx, p_ox, HD, S_LEN, 64, early ? 64 : 128, PROMO_O);
    make_map(enc, &mOut, out, OUT_LD, S_LEN, 64, early ? 64 : 128);

    CUtensorMap mB[4];
    for (int i = 0; i < 4; i++) {
        cuuint64_t dims[2] = {(cuuint64_t)(i < 3 ? DM : OUT_LD), S_LEN};
        cuuint64_t strides[1] = {dims[0] * 2};
        cuuint32_t box[2] = {16, i == 0 ? 136u : i < 3 ? 128u : 64u};
        cuuint32_t es[2] = {1, 1};
        enc(&mB[i], CU_TENSOR_MAP_DATA_TYPE_BFLOAT16, 2, const_cast<bf16*>(i == 0 ? Bk : i == 1 ? Bv : i == 2 ? Bq : out), dims, strides, box, es,
            CU_TENSOR_MAP_INTERLEAVE_NONE, CU_TENSOR_MAP_SWIZZLE_32B, SSM_PROMO, CU_TENSOR_MAP_FLOAT_OOB_FILL_NONE);
    }
    cudaStream_t st = cudaStreamPerThread;
    const ChainInputs ci = {{(const char*)Wv, (const char*)Wk, (const char*)Wq, (const char*)Wo}, (const char*)x, (const char*)mem0};
    ssm_kernel<<<132, 576, B_SMEM, st>>>(mB[0], mB[1], mB[2], mB[3], Bsh, Bssm, BD, mbox, ci, out);
    cudaLaunchAttribute pdl[1];
    pdl[0].id = cudaLaunchAttributeProgrammaticStreamSerialization; pdl[0].val.programmaticStreamSerializationAllowed = 1;
    cudaLaunchConfig_t lc = {};
    lc.stream = st; lc.attrs = pdl;
    lc.gridDim = dim3(2 * nclusters); lc.blockDim = dim3(384); lc.dynamicSmemBytes = CHAIN_SMEM; lc.numAttrs = PDL & 1;
    cudaLaunchKernelEx(&lc, early ? chain_kernel<true> : chain_kernel<false>, mbox, mem0, mX, mT32, mT16, mTQ, mKV, mWq, mWk, mWv, mWoC, mWo, mOx, mOut, mO8);
    if (early) return;
    lc.gridDim = dim3(2 * nclusters); lc.blockDim = dim3(PROJ_THREADS); lc.dynamicSmemBytes = PROJ_SMEM; lc.numAttrs = (PDL >> 1) & 1;
    cudaLaunchKernelEx(&lc, proj_kernel<128, 7>, mWo, mOx, mOut);
}
```

```cpp
#include <cuda_runtime.h>
#include <cuda_bf16.h>
#include <cuda.h>
#include <stdint.h>
#include <type_traits>

typedef __nv_bfloat16 bf16;

constexpr int S_LEN = 2048, DM = 1024, NH = 32, DH = 128, NSEG = 64, SEG = 32;
constexpr int HD = NH * DH;
constexpr int OUT_LD = 2048;
constexpr unsigned SENT = 0xFFFFFFFFu;

__device__ bf16 g_tok[4 * NH * 3 * SEG * DH];
__device__ bf16 g_ox[(size_t)S_LEN * HD];
__device__ uint4 g_mbox[4 * 131072];
__device__ unsigned g_xflag[128];
__device__ unsigned g_reg[4];
__device__ __align__(16) unsigned g_cls[256];
__device__ unsigned g_err;
constexpr uint32_t WIN = 2u << 20;
__host__ __device__ constexpr uint32_t page_off(uint32_t idx, uint32_t c) {
    return ((idx & 1) << 13) | ((idx >> 1) << 16) | (((c ^ idx ^ (idx >> 1) ^ (idx >> 2) ^ (idx >> 4)) & 1) << 12);
}
#define STAT(i, c) (void)(c)
#define EARLY_ROLE 1
#define PDL 3

__device__ __forceinline__ void launch_dependents() { asm volatile("griddepcontrol.launch_dependents;" ::: "memory"); }
__device__ __forceinline__ void wait_prerequisites() { asm volatile("griddepcontrol.wait;" ::: "memory"); }
__device__ __forceinline__ void prefetch_map(const CUtensorMap* m) { asm volatile("prefetch.tensormap [%0];" ::"l"(m) : "memory"); }
#define KT_MARK(k)
#define KT_START(k)
#define KT_END(k)

__device__ __forceinline__ uint32_t smem_u32(const void* p) { return (uint32_t)__cvta_generic_to_shared(p); }
__device__ __forceinline__ void ldsm4(uint32_t& r0, uint32_t& r1, uint32_t& r2, uint32_t& r3, uint32_t a) {
    asm volatile("ldmatrix.sync.aligned.m8n8.x4.shared.b16 {%0,%1,%2,%3}, [%4];" : "=r"(r0), "=r"(r1), "=r"(r2), "=r"(r3) : "r"(a) : "memory");
}
__device__ __forceinline__ void ldsm4t(uint32_t& r0, uint32_t& r1, uint32_t& r2, uint32_t& r3, uint32_t a) {
    asm volatile("ldmatrix.sync.aligned.m8n8.x4.trans.shared.b16 {%0,%1,%2,%3}, [%4];" : "=r"(r0), "=r"(r1), "=r"(r2), "=r"(r3) : "r"(a) : "memory");
}
__device__ __forceinline__ void ldsm2(uint32_t& r0, uint32_t& r1, uint32_t a) {
    asm volatile("ldmatrix.sync.aligned.m8n8.x2.shared.b16 {%0,%1}, [%2];" : "=r"(r0), "=r"(r1) : "r"(a) : "memory");
}
__device__ __forceinline__ void stg128(void* p, uint4 v) {
    asm volatile("st.global.v4.u32 [%0], {%1,%2,%3,%4};" ::"l"(p), "r"(v.x), "r"(v.y), "r"(v.z), "r"(v.w) : "memory");
}
__device__ __forceinline__ void stsm4(uint32_t a, uint32_t r0, uint32_t r1, uint32_t r2, uint32_t r3) {
    asm volatile("stmatrix.sync.aligned.m8n8.x4.shared.b16 [%0], {%1,%2,%3,%4};" ::"r"(a), "r"(r0), "r"(r1), "r"(r2), "r"(r3) : "memory");
}
__device__ __forceinline__ void mma16816(float (&d)[4], uint32_t a0, uint32_t a1, uint32_t a2, uint32_t a3, uint32_t b0, uint32_t b1) {
    asm("mma.sync.aligned.m16n8k16.row.col.f32.bf16.bf16.f32 {%0,%1,%2,%3},{%4,%5,%6,%7},{%8,%9},{%0,%1,%2,%3};"
                 : "+f"(d[0]), "+f"(d[1]), "+f"(d[2]), "+f"(d[3])
                 : "r"(a0), "r"(a1), "r"(a2), "r"(a3), "r"(b0), "r"(b1));
}
__device__ __forceinline__ void mma1688(float (&d)[4], uint32_t a0, uint32_t a1, uint32_t b0) {
    asm("mma.sync.aligned.m16n8k8.row.col.f32.bf16.bf16.f32 {%0,%1,%2,%3},{%4,%5},{%6},{%0,%1,%2,%3};"
        : "+f"(d[0]), "+f"(d[1]), "+f"(d[2]), "+f"(d[3]) : "r"(a0), "r"(a1), "r"(b0));
}
__device__ __forceinline__ uint32_t movmat(uint32_t a) {
    uint32_t d;
    asm volatile("movmatrix.sync.aligned.m8n8.trans.b16 %0, %1;" : "=r"(d) : "r"(a));
    return d;
}
__device__ __forceinline__ uint32_t pack_bf16(float lo, float hi) {
    uint32_t r;
    asm("cvt.rn.bf16x2.f32 %0, %1, %2;" : "=r"(r) : "f"(hi), "f"(lo));
    return r;
}
__device__ __forceinline__ uint32_t bf16_mul(uint32_t a, uint32_t b) {
    uint32_t d;
    asm("mul.rn.bf16x2 %0, %1, %2;" : "=r"(d) : "r"(a), "r"(b));
    return d;
}
__device__ __forceinline__ uint32_t bf16_add(uint32_t a, uint32_t b) {
    uint32_t d;
    asm("add.rn.bf16x2 %0, %1, %2;" : "=r"(d) : "r"(a), "r"(b));
    return d;
}

__device__ __forceinline__ float bf16_round(float x) { return __bfloat162float(__float2bfloat16_rn(x)); }
__device__ __forceinline__ float bf_lo(uint32_t w) { return __uint_as_float(w << 16); }
__device__ __forceinline__ float bf_hi(uint32_t w) { return __uint_as_float(w & 0xFFFF0000u); }
__device__ __forceinline__ void bar_sync(int id, int n) { asm volatile("bar.sync %0, %1;" ::"r"(id), "r"(n) : "memory"); }
__device__ __forceinline__ void bar_sync_keep(int id, int n, uint32_t a, uint32_t b) {
    asm volatile("bar.sync %0, %1; // %2 %3" ::"r"(id), "r"(n), "r"(a), "r"(b) : "memory");
}
__device__ __forceinline__ bool bar_red_or(int id, int n, bool p) {
    uint32_t r;
    asm volatile("{.reg .pred p, q; setp.ne.u32 p, %3, 0; bar.red.or.pred q, %1, %2, p; selp.u32 %0, 1, 0, q;}" : "=r"(r) : "r"(id), "r"(n), "r"((uint32_t)p) : "memory");
    return r != 0;
}
__device__ __forceinline__ void bar_arrive(int id, int n) { asm volatile("bar.arrive %0, %1;" ::"r"(id), "r"(n) : "memory"); }
__device__ __forceinline__ void cp_async16(uint32_t dst, const void* src) {
    asm volatile("cp.async.cg.shared.global [%0], [%1], 16;" ::"r"(dst), "l"(src) : "memory");
}
__device__ __forceinline__ void cp_commit() { asm volatile("cp.async.commit_group;" ::: "memory"); }
template <int N> __device__ __forceinline__ void cp_wait() { asm volatile("cp.async.wait_group %0;" ::"n"(N) : "memory"); }
__device__ __forceinline__ uint4 ld_relaxed_v4(const void* p) {
    uint4 v;
    asm volatile("ld.relaxed.gpu.global.v4.u32 {%0,%1,%2,%3}, [%4];" : "=r"(v.x), "=r"(v.y), "=r"(v.z), "=r"(v.w) : "l"(p) : "memory");
    return v;
}
__device__ __forceinline__ void st_relaxed_u32(void* p, uint32_t v) { asm volatile("st.relaxed.gpu.global.u32 [%0], %1;" ::"l"(p), "r"(v) : "memory"); }
__device__ __forceinline__ void st_relaxed_v2(void* p, uint32_t a, uint32_t b) {
    asm volatile("st.relaxed.gpu.global.v2.u32 [%0], {%1,%2};" ::"l"(p), "r"(a), "r"(b) : "memory");
}
__device__ __forceinline__ void sts128(uint32_t a, uint4 v) {
    asm volatile("st.shared.v4.u32 [%0], {%1,%2,%3,%4};" ::"r"(a), "r"(v.x), "r"(v.y), "r"(v.z), "r"(v.w) : "memory");
}
__device__ __forceinline__ uint4 lds128(uint32_t a) {
    uint4 v;
    asm volatile("ld.shared.v4.u32 {%0,%1,%2,%3}, [%4];" : "=r"(v.x), "=r"(v.y), "=r"(v.z), "=r"(v.w) : "r"(a) : "memory");
    return v;
}
__device__ __forceinline__ void sts32(uint32_t a, uint32_t v) { asm volatile("st.shared.u32 [%0], %1;" ::"r"(a), "r"(v) : "memory"); }
__device__ __forceinline__ uint32_t lds32(uint32_t a) {
    uint32_t v;
    asm volatile("ld.shared.u32 %0, [%1];" : "=r"(v) : "r"(a) : "memory");
    return v;
}
__device__ __forceinline__ void mbar_init(uint32_t a, uint32_t c) { asm volatile("mbarrier.init.shared::cta.b64 [%0], %1;" ::"r"(a), "r"(c) : "memory"); }
__device__ __forceinline__ void mbar_expect_tx(uint32_t a, uint32_t bytes) {
    asm volatile("mbarrier.arrive.expect_tx.shared::cta.b64 _, [%0], %1;" ::"r"(a), "r"(bytes) : "memory");
}
__device__ __forceinline__ void mbar_arrive(uint32_t a) { asm volatile("mbarrier.arrive.shared::cta.b64 _, [%0];" ::"r"(a) : "memory"); }
__device__ __forceinline__ void mbar_wait(uint32_t a, uint32_t parity) {
    asm volatile("{.reg .pred p; .reg .u32 c;\n"
                 "mov.u32 c, 0;\n"
                 "MBW_LOOP:\n"
                 "add.u32 c, c, 1;\n"
                 "setp.gt.u32 p, c, 0x10000;\n"
                 "@!p mbarrier.try_wait.parity.shared::cta.b64 p, [%0], %1;\n"
                 "@!p bra.uni MBW_LOOP;}" ::"r"(a), "r"(parity) : "memory");
}
__device__ __forceinline__ void mbar_wait_w(uint32_t a, uint32_t parity) {
    asm volatile("{.reg .pred p; .reg .u32 c;\n"
                 "mov.u32 c, 0;\n"
                 "MBW_LOOP:\n"
                 "add.u32 c, c, 1;\n"
                 "setp.gt.u32 p, c, 0x10000;\n"
                 "@!p mbarrier.try_wait.parity.shared::cta.b64 p, [%0], %1;\n"
                 "vote.sync.all.pred p, p, 0xFFFFFFFF;\n"
                 "@!p bra.uni MBW_LOOP;}" ::"r"(a), "r"(parity) : "memory");
}
__device__ __forceinline__ void mbar_expect_tx_if0(uint32_t sel, uint32_t a, uint32_t bytes) {
    asm volatile("{.reg .pred p; setp.eq.u32 p, %2, 0; @p mbarrier.arrive.expect_tx.shared::cta.b64 _, [%0], %1;}" ::"r"(a), "r"(bytes), "r"(sel) : "memory");
}
__device__ __forceinline__ void mbar_arrive_if0(uint32_t sel, uint32_t a) {
    asm volatile("{.reg .pred p; setp.eq.u32 p, %1, 0; @p mbarrier.arrive.shared::cta.b64 _, [%0];}" ::"r"(a), "r"(sel) : "memory");
}
__device__ __forceinline__ void bulk_load(uint32_t dst, const void* src, uint32_t bytes, uint32_t bar) {
    asm volatile("cp.async.bulk.shared::cluster.global.mbarrier::complete_tx::bytes [%0], [%1], %2, [%3];" ::"r"(dst), "l"(src), "r"(bytes), "r"(bar) : "memory");
}
__device__ __forceinline__ void tma_load_2d(uint32_t dst, const CUtensorMap* map, int c0, int c1, uint32_t bar) {
    asm volatile("cp.async.bulk.tensor.2d.shared::cluster.global.mbarrier::complete_tx::bytes [%0], [%1, {%3, %4}], [%2];"
                 ::"r"(dst), "l"(map), "r"(bar), "r"(c0), "r"(c1) : "memory");
}
__device__ __forceinline__ void tma_load_2d_both(uint32_t dst, const CUtensorMap* map, int c0, int c1, uint32_t bar) {
    asm volatile("cp.async.bulk.tensor.2d.shared::cluster.global.mbarrier::complete_tx::bytes.multicast::cluster [%0], [%1, {%3, %4}], [%2], %5;"
                 ::"r"(dst), "l"(map), "r"(bar), "r"(c0), "r"(c1), "h"((uint16_t)3) : "memory");
}
__device__ __forceinline__ uint64_t policy_evict_first() {
    uint64_t p;
    asm("createpolicy.fractional.L2::evict_first.b64 %0, 1.0;" : "=l"(p));
    return p;
}
__device__ __forceinline__ uint64_t policy_evict_normal() {
    uint64_t p;
    asm("createpolicy.fractional.L2::evict_normal.b64 %0, 1.0;" : "=l"(p));
    return p;
}
__device__ __forceinline__ void tma_load_2d(uint32_t dst, const CUtensorMap* map, int c0, int c1, uint32_t bar, uint64_t pol) {
    asm volatile("cp.async.bulk.tensor.2d.shared::cluster.global.mbarrier::complete_tx::bytes.L2::cache_hint [%0], [%1, {%3, %4}], [%2], %5;"
                 ::"r"(dst), "l"(map), "r"(bar), "r"(c0), "r"(c1), "l"(pol) : "memory");
}
__device__ __forceinline__ uint4 ldg128(const void* p, uint64_t pol) {
    uint4 v;
    asm("ld.global.nc.L2::cache_hint.v4.u32 {%0,%1,%2,%3}, [%4], %5;" : "=r"(v.x), "=r"(v.y), "=r"(v.z), "=r"(v.w) : "l"(p), "l"(pol));
    return v;
}
__device__ __forceinline__ void stg128(void* p, uint4 v, uint64_t pol) {
    asm volatile("st.global.L2::cache_hint.v4.u32 [%0], {%1,%2,%3,%4}, %5;" ::"l"(p), "r"(v.x), "r"(v.y), "r"(v.z), "r"(v.w), "l"(pol) : "memory");
}
__device__ __forceinline__ void tma_store_2d(const CUtensorMap* map, uint32_t src, int c0, int c1) {
    asm volatile("cp.async.bulk.tensor.2d.global.shared::cta.bulk_group [%0, {%2, %3}], [%1];" ::"l"(map), "r"(src), "r"(c0), "r"(c1) : "memory");
}
__device__ __forceinline__ void tma_store_3d(const CUtensorMap* map, uint32_t src, int c0, int c1, int c2) {
    asm volatile("cp.async.bulk.tensor.3d.global.shared::cta.bulk_group [%0, {%2, %3, %4}], [%1];" ::"l"(map), "r"(src), "r"(c0), "r"(c1), "r"(c2) : "memory");
}
__device__ __forceinline__ char* make_ptr(uint32_t lo, uint32_t hi) {
    uint64_t p;
    asm("mov.b64 %0, {%1, %2};" : "=l"(p) : "r"(lo), "r"(hi));
    return reinterpret_cast<char*>(p);
}
__device__ __forceinline__ uint64_t make_desc(uint32_t saddr, uint32_t lbo, uint32_t sbo) {
    return (uint64_t)((saddr & 0x3FFFF) >> 4) | ((uint64_t)((lbo >> 4) & 0x3FFF) << 16) | ((uint64_t)((sbo >> 4) & 0x3FFF) << 32) | ((uint64_t)1 << 62);
}
__device__ __forceinline__ void wg_fence() { asm volatile("wgmma.fence.sync.aligned;" ::: "memory"); }
__device__ __forceinline__ void wg_commit() { asm volatile("wgmma.commit_group.sync.aligned;" ::: "memory"); }
template <int N> __device__ __forceinline__ void wg_wait() { asm volatile("wgmma.wait_group.sync.aligned %0;" ::"n"(N) : "memory"); }

#define R4(b) "+f"(d[b + 0]), "+f"(d[b + 1]), "+f"(d[b + 2]), "+f"(d[b + 3])
#define R16(b) R4(b), R4(b + 4), R4(b + 8), R4(b + 12)
template <int N> __device__ __forceinline__ void wgmma_proj(float (&d)[N / 2], uint64_t da, uint64_t db) {
    if constexpr (N == 96)
        asm volatile("wgmma.mma_async.sync.aligned.m64n96k16.f32.bf16.bf16 {"
            "%0,%1,%2,%3,%4,%5,%6,%7,%8,%9,%10,%11,%12,%13,%14,%15,%16,%17,%18,%19,%20,%21,%22,%23,%24,%25,%26,%27,%28,%29,%30,%31,%32,%33,%34,%35,%36,%37,%38,%39,"
            "%40,%41,%42,%43,%44,%45,%46,%47"
            "}, %48, %49, 1, 1, 1, 1, 0;" : R16(0), R16(16), R16(32) : "l"(da), "l"(db));
    if constexpr (N == 128)
        asm volatile("wgmma.mma_async.sync.aligned.m64n128k16.f32.bf16.bf16 {"
            "%0,%1,%2,%3,%4,%5,%6,%7,%8,%9,%10,%11,%12,%13,%14,%15,%16,%17,%18,%19,%20,%21,%22,%23,%24,%25,%26,%27,%28,%29,%30,%31,%32,%33,%34,%35,%36,%37,%38,%39,"
            "%40,%41,%42,%43,%44,%45,%46,%47,%48,%49,%50,%51,%52,%53,%54,%55,%56,%57,%58,%59,%60,%61,%62,%63"
            "}, %64, %65, 1, 1, 1, 1, 0;" : R16(0), R16(16), R16(32), R16(48) : "l"(da), "l"(db));
    if constexpr (N == 192)
        asm volatile("wgmma.mma_async.sync.aligned.m64n192k16.f32.bf16.bf16 {"
            "%0,%1,%2,%3,%4,%5,%6,%7,%8,%9,%10,%11,%12,%13,%14,%15,%16,%17,%18,%19,%20,%21,%22,%23,%24,%25,%26,%27,%28,%29,%30,%31,%32,%33,%34,%35,%36,%37,%38,%39,"
            "%40,%41,%42,%43,%44,%45,%46,%47,%48,%49,%50,%51,%52,%53,%54,%55,%56,%57,%58,%59,%60,%61,%62,%63,%64,%65,%66,%67,%68,%69,%70,%71,%72,%73,%74,%75,%76,%7"
            "7,%78,%79,%80,%81,%82,%83,%84,%85,%86,%87,%88,%89,%90,%91,%92,%93,%94,%95"
            "}, %96, %97, 1, 1, 1, 1, 0;" : R16(0), R16(16), R16(32), R16(48), R16(64), R16(80) : "l"(da), "l"(db));
    if constexpr (N == 256)
        asm volatile("wgmma.mma_async.sync.aligned.m64n256k16.f32.bf16.bf16 {"
            "%0,%1,%2,%3,%4,%5,%6,%7,%8,%9,%10,%11,%12,%13,%14,%15,%16,%17,%18,%19,%20,%21,%22,%23,%24,%25,%26,%27,%28,%29,%30,%31,%32,%33,%34,%35,%36,%37,%38,%39,"
            "%40,%41,%42,%43,%44,%45,%46,%47,%48,%49,%50,%51,%52,%53,%54,%55,%56,%57,%58,%59,%60,%61,%62,%63,%64,%65,%66,%67,%68,%69,%70,%71,%72,%73,%74,%75,%76,%7"
            "7,%78,%79,%80,%81,%82,%83,%84,%85,%86,%87,%88,%89,%90,%91,%92,%93,%94,%95,%96,%97,%98,%99,%100,%101,%102,%103,%104,%105,%106,%107,%108,%109,%110,%111,"
            "%112,%113,%114,%115,%116,%117,%118,%119,%120,%121,%122,%123,%124,%125,%126,%127"
            "}, %128, %129, 1, 1, 1, 1, 0;" : R16(0), R16(16), R16(32), R16(48), R16(64), R16(80), R16(96), R16(112) : "l"(da), "l"(db));
}

__device__ __forceinline__ void wgmma_rs32(float (&d)[16], const uint32_t (&a)[4], uint64_t db, bool acc) {
    asm volatile(
        "{.reg .pred p; setp.ne.b32 p, %21, 0;\n"
        "wgmma.mma_async.sync.aligned.m64n32k16.f32.bf16.bf16 {%0,%1,%2,%3,%4,%5,%6,%7,%8,%9,%10,%11,%12,%13,%14,%15}, {%16,%17,%18,%19}, %20, p, 1, 1, 0;}"
        : R16(0) : "r"(a[0]), "r"(a[1]), "r"(a[2]), "r"(a[3]), "l"(db), "n"(1) );
}
__device__ __forceinline__ void wgmma_rs32_first(float (&d)[16], const uint32_t (&a)[4], uint64_t db) {
    asm volatile(
        "{.reg .pred p; setp.ne.b32 p, %21, 0;\n"
        "wgmma.mma_async.sync.aligned.m64n32k16.f32.bf16.bf16 {%0,%1,%2,%3,%4,%5,%6,%7,%8,%9,%10,%11,%12,%13,%14,%15}, {%16,%17,%18,%19}, %20, p, 1, 1, 0;}"
        : R16(0) : "r"(a[0]), "r"(a[1]), "r"(a[2]), "r"(a[3]), "l"(db), "n"(0) );
}
__device__ __forceinline__ void wgmma_ss32(float (&d)[16], uint64_t da, uint64_t db) {
    asm volatile(
        "wgmma.mma_async.sync.aligned.m64n32k16.f32.bf16.bf16 {%0,%1,%2,%3,%4,%5,%6,%7,%8,%9,%10,%11,%12,%13,%14,%15}, %16, %17, 1, 1, 1, 1, 0;"
        : R16(0) : "l"(da), "l"(db));
}
template <int OFF, int ACC> __device__ __forceinline__ void wgmma_rs32u(float (&d)[16], const uint32_t (&a)[4], uint32_t lo) {
    asm volatile(
        "{.reg .pred p; .reg .b32 l; .reg .b64 e; setp.ne.b32 p, %22, 0; add.u32 l, %20, %21; mov.b64 e, {l, 0x40000040};\n"
        "wgmma.mma_async.sync.aligned.m64n32k16.f32.bf16.bf16 {%0,%1,%2,%3,%4,%5,%6,%7,%8,%9,%10,%11,%12,%13,%14,%15}, {%16,%17,%18,%19}, e, p, 1, 1, 0;}"
        : R16(0) : "r"(a[0]), "r"(a[1]), "r"(a[2]), "r"(a[3]), "r"(lo), "n"(OFF), "n"(ACC));
}
template <int OFF, int ACC> __device__ __forceinline__ void wgmma_ss32u(float (&d)[16], uint64_t da, uint32_t lo) {
    asm volatile(
        "{.reg .pred p; .reg .b32 l; .reg .b64 e; setp.ne.b32 p, %19, 0; add.u32 l, %17, %18; mov.b64 e, {l, 0x40000040};\n"
        "wgmma.mma_async.sync.aligned.m64n32k16.f32.bf16.bf16 {%0,%1,%2,%3,%4,%5,%6,%7,%8,%9,%10,%11,%12,%13,%14,%15}, %16, e, p, 1, 1, 1, 0;}"
        : R16(0) : "l"(da), "r"(lo), "n"(OFF), "n"(ACC));
}
template <int K0, int K1, class F> __device__ __forceinline__ void static_for(F f) {
    if constexpr (K0 < K1) { f(std::integral_constant<int, K0>()); static_for<K0 + 1, K1>(f); }
}
__device__ __forceinline__ void st_async4(uint32_t a, float x, float y, float z, float w, uint32_t bar) {
    asm volatile("st.async.weak.shared::cluster.mbarrier::complete_tx::bytes.v4.f32 [%0], {%1,%2,%3,%4}, [%5];" ::"r"(a), "f"(x), "f"(y), "f"(z), "f"(w), "r"(bar) : "memory");
}
__device__ __forceinline__ void st_async2(uint32_t a, float x, float y, uint32_t bar) {
    asm volatile("st.async.weak.shared::cluster.mbarrier::complete_tx::bytes.v2.f32 [%0], {%1,%2}, [%3];" ::"r"(a), "f"(x), "f"(y), "r"(bar) : "memory");
}
__device__ __forceinline__ void st_async1(uint32_t a, uint32_t x, uint32_t bar) {
    asm volatile("st.async.weak.shared::cluster.mbarrier::complete_tx::bytes.b32 [%0], %1, [%2];" ::"r"(a), "r"(x), "r"(bar) : "memory");
}
__device__ __forceinline__ uint32_t peer_addr(uint32_t a, uint32_t rank) {
    uint32_t r;
    asm("mapa.shared::cluster.u32 %0, %1, %2;" : "=r"(r) : "r"(a), "r"(rank));
    return r;
}
__device__ __forceinline__ void stsm4t(uint32_t a, uint32_t r0, uint32_t r1, uint32_t r2, uint32_t r3) {
    asm volatile("stmatrix.sync.aligned.m8n8.x4.trans.shared.b16 [%0], {%1,%2,%3,%4};" ::"r"(a), "r"(r0), "r"(r1), "r"(r2), "r"(r3) : "memory");
}
__device__ __forceinline__ void ldsm4t(uint32_t (&r)[4], uint32_t a) { ldsm4t(r[0], r[1], r[2], r[3], a); }
__device__ __forceinline__ void ldsm4(uint32_t (&r)[4], uint32_t a) { ldsm4(r[0], r[1], r[2], r[3], a); }
__device__ __forceinline__ void mma16816(float (&d)[4], const uint32_t (&a)[4], uint32_t b0, uint32_t b1) { mma16816(d, a[0], a[1], a[2], a[3], b0, b1); }
__device__ __forceinline__ void sched_fence(uint32_t v) {
    asm volatile("{.reg .pred p; setp.ne.u32 p, %0, 0xFFFFFFFF; vote.sync.all.pred p, p, 0xFFFFFFFF; @p bra.uni SF_OK; exit; SF_OK:}" ::"r"(v) : "memory");
}
__device__ __forceinline__ void mma16816v(float (&d)[4], const uint32_t (&a)[4], uint32_t b0, uint32_t b1) {
    asm volatile("mma.sync.aligned.m16n8k16.row.col.f32.bf16.bf16.f32 {%0,%1,%2,%3},{%4,%5,%6,%7},{%8,%9},{%0,%1,%2,%3};"
                 : "+f"(d[0]), "+f"(d[1]), "+f"(d[2]), "+f"(d[3]) : "r"(a[0]), "r"(a[1]), "r"(a[2]), "r"(a[3]), "r"(b0), "r"(b1));
}
__device__ __forceinline__ uint32_t uniform(uint32_t v) { return __reduce_max_sync(~0u, v); }

#define WPRE 0
#define G2_X 0
#define G2_K 4
#define FIN_SO 0
#define PROJ_FAST 1
#define KROT 0
#define WFIRST 0
template <int NT, int STAGES> struct ProjCfg {
    static constexpr int STAGE_BYTES = 16384 + NT * 128;
    static constexpr int EPI = NT == 256 ? STAGES * STAGE_BYTES : 0;
    static constexpr int BARS = 229376 + (NT == 256 ? 192 : 0);
    static_assert(STAGES * STAGE_BYTES <= 229376 && EPI + NT * 256 <= 229376 && STAGES <= 12, "smem");
};
constexpr int PROJ_ROLE = 229376 + 384, PROJ_SMEM = PROJ_ROLE + 16;
__device__ __forceinline__ unsigned claim_pair(unsigned* reg) {
    unsigned smid, ncl = gridDim.x >> 1;
    asm volatile("mov.u32 %0, %%smid;" : "=r"(smid));
    uint2 m;
    for (int guard = 0; guard < 1024; guard++) {
        asm volatile("ld.relaxed.gpu.global.v2.u32 {%0, %1}, [%2];" : "=r"(m.x), "=r"(m.y) : "l"(g_cls + (smid & ~1u)) : "memory");
        if (m.x && m.y) break;
    }
    const unsigned r = __vminu2(m.x, m.y), c = (r & 0xFFFF) > (r >> 16);
    unsigned n = atomicAdd(reg, c ? 0x10000u : 1u);
    const unsigned i = c ? n >> 16 : n & 0xFFFF, order = ((n >> 16) + (n & 0xFFFF)) << 8;
    if (i < 32) return c * 32 + i + order;
    for (int guard = 0; guard < (1 << 20); guard++) {
        asm volatile("ld.relaxed.gpu.global.u32 %0, [%1];" : "=r"(n) : "l"(reg) : "memory");
        if ((n >> 16) + (n & 0xFFFF) >= ncl) break;
    }
    const unsigned other = c ? n & 0xFFFF : n >> 16, k = other + i - 32;
    return (k < 32 ? (c ^ 1) * 32 + k : other > 32 ? 64 + c : 32 + k) + order;
}
template <int NT, int STAGES> __device__ __forceinline__ void proj_init(uint32_t sb) {
    for (int i = 0; i < STAGES; i++) { mbar_init(sb + ProjCfg<NT, STAGES>::BARS + 8 * i, 1); mbar_init(sb + ProjCfg<NT, STAGES>::BARS + 8 * (STAGES + i), 16); }
    asm volatile("fence.mbarrier_init.release.cluster;" ::: "memory");
}
template <int NT, int STAGES, bool SHARE_O, class T, class R>
__device__ __forceinline__ void proj_tiles(uint32_t sb, int warp, uint32_t rank, int ntiles, const CUtensorMap* mapW, const CUtensorMap* mapO,
                                           const CUtensorMap* mapOut, T tile, R ready, int rot = 0) {
    using Cfg = ProjCfg<NT, STAGES>;
    const uint32_t bars = sb + Cfg::BARS;
    const int lane = threadIdx.x & 31;
    if (warp == 8) {
        int st = 0; uint32_t ph = 1;
        for (int i = 0; i < ntiles; i++) {
            int col, tok;
            tile(i, col, tok);
            constexpr bool PRE = WPRE && !SHARE_O;
            if (PRE && lane == 0)
                for (int kb = 0; kb < STAGES; kb++) {
                    mbar_expect_tx(bars + 8 * kb, Cfg::STAGE_BYTES);
                    tma_load_2d_both(sb + kb * Cfg::STAGE_BYTES + rank * 8192, mapW, col + rank * 64, kb * 64, bars + 8 * kb);
                }
            ready(i);
            if (lane == 0) {
                if (PRE) {
                    for (int kb = 0; kb < STAGES; kb++) tma_load_2d(sb + kb * Cfg::STAGE_BYTES + 16384, mapO, kb * 64, tok, bars + 8 * kb);
                    ph = 0;
                }
                for (int kb = PRE ? STAGES : 0; kb < HD / 64; kb++) {
                    mbar_wait(bars + 8 * (STAGES + st), ph);
                    const uint32_t full = bars + 8 * st, sa = sb + st * Cfg::STAGE_BYTES;
                    mbar_expect_tx(full, SHARE_O ? Cfg::STAGE_BYTES : G2_X == 1 ? 16384 : G2_X == 2 ? NT * 128 : Cfg::STAGE_BYTES);
                    if (SHARE_O) {
                        tma_load_2d(sa, mapW, col, kb * 64, full);
                        tma_load_2d(sa + 8192, mapW, col + 64, kb * 64, full);
                        tma_load_2d_both(sa + 16384 + rank * (NT * 64), mapO, kb * 64, tok + rank * (NT / 2), full);
                    } else {
                        const int k0 = ((kb + rot) & 63) * 64;
                        if (WFIRST) tma_load_2d_both(sa + rank * 8192, mapW, col + rank * 64, k0, full);
                        if (G2_X != 1) tma_load_2d(sa + 16384, mapO, k0, G2_X == 3 ? tok & 511 : tok, full);
                        if (G2_X == 4) { tma_load_2d(sa, mapW, col, k0, full); tma_load_2d(sa + 8192, mapW, col + 64, k0, full); }
                        else if (!WFIRST && G2_X != 2) tma_load_2d_both(sa + rank * 8192, mapW, col + rank * 64, k0, full);
                    }
                    if (++st == STAGES) { st = 0; ph ^= 1; }
                }
            }
            __syncwarp();
        }
    } else if (warp < 8) {
        const int wg = warp >> 2;
        uint32_t peer_empty;
        asm volatile("mapa.shared::cluster.u32 %0, %1, %2;" : "=r"(peer_empty) : "r"(bars + 8 * STAGES), "r"(rank ^ 1));
        auto release = [&](int stg) {
            if (lane == 0) {
                mbar_arrive(bars + 8 * (STAGES + stg));
                asm volatile("mbarrier.arrive.shared::cluster.b64 _, [%0];" ::"r"(peer_empty + 8 * stg) : "memory");
            }
        };
        const uint32_t ew = sb + Cfg::EPI + wg * (NT * 128);
        int st = 0; uint32_t ph = 0;
        for (int i = 0; i < ntiles; i++) {
            int col, tok;
            tile(i, col, tok);
            float d[NT / 2];
#pragma unroll
            for (int r = 0; r < NT / 2; r++) d[r] = 0.f;
            int prev = -1;
            for (int kb = 0; kb < HD / 64; kb++) {
                mbar_wait(bars + 8 * st, ph);
                const uint32_t sa = sb + st * Cfg::STAGE_BYTES;
                const uint64_t da = make_desc(sa + wg * 8192, 16, 1024), db = make_desc(sa + 16384, 16, 1024);
                wg_fence();
#pragma unroll
                for (int k = 0; k < (NT == 256 ? 4 : G2_K); k++) wgmma_proj<NT>(d, da + k * 128, db + k * 2);
                wg_commit();
                if (prev >= 0) { wg_wait<1>(); release(prev); }
                prev = st;
                if (++st == STAGES) { st = 0; ph ^= 1; }
            }
            wg_wait<0>();
            release(prev);
            if ((warp & 3) == 0 && lane == 0) asm volatile("cp.async.bulk.wait_group.read 0;" ::: "memory");
            if (Cfg::EPI) bar_sync(1 + wg, 128); else bar_sync(3, 256);
            const uint32_t ea = ew + ((lane >> 4) * 8 + (lane & 7)) * 128 + ((((warp & 3) * 2 + ((lane >> 3) & 1)) ^ (lane & 7)) * 16);
#pragma unroll
            for (int r = 0; r < NT / 16; r++)
                stsm4t(ea + r * 2048, pack_bf16(d[8 * r], d[8 * r + 1]), pack_bf16(d[8 * r + 2], d[8 * r + 3]), pack_bf16(d[8 * r + 4], d[8 * r + 5]), pack_bf16(d[8 * r + 6], d[8 * r + 7]));
            asm volatile("fence.proxy.async.shared::cta;" ::: "memory");
            bar_sync(1 + wg, 128);
            if ((warp & 3) == 0 && lane == 0) {
                tma_store_2d(mapOut, ew, col + wg * 64, tok);
                asm volatile("cp.async.bulk.commit_group;" ::: "memory");
            }
        }
        if ((warp & 3) == 0 && lane == 0) asm volatile("cp.async.bulk.wait_group 0;" ::: "memory");
    }
    __syncwarp();
}
constexpr int PROJ_THREADS = 288;

template <int NT, int STAGES>
__global__ void __cluster_dims__(2, 1, 1) __launch_bounds__(PROJ_THREADS, 1)
proj_kernel(const __grid_constant__ CUtensorMap mapW, const __grid_constant__ CUtensorMap mapO, const __grid_constant__ CUtensorMap mapOut) {
    KT_START(3);
    extern __shared__ __align__(1024) uint8_t smem_proj[];
    const uint32_t sb = smem_u32(smem_proj), role = sb + PROJ_ROLE;
    if (sb & 1023) __trap();
    const uint32_t rank = blockIdx.x & 1;
    const int warp = threadIdx.x >> 5;
    if (threadIdx.x == 0) {
        mbar_init(role + 8, 1);
        mbar_expect_tx(role + 8, 4);
        proj_init<NT, STAGES>(sb);
    }
    if (threadIdx.x == 32) { prefetch_map(&mapO); prefetch_map(&mapW); prefetch_map(&mapOut); }
    __syncwarp();
    asm volatile("barrier.cluster.arrive.relaxed.aligned;" ::: "memory");
    unsigned claimed = 0;
    if (threadIdx.x == 256 && rank == 0) claimed = claim_pair(g_reg + 2);
    __syncwarp();
    asm volatile("barrier.cluster.wait.acquire.aligned;" ::: "memory");
    if (threadIdx.x == 256 && rank == 0) {
        st_async1(peer_addr(role, 1), claimed, peer_addr(role + 8, 1));
        st_async1(peer_addr(role, 0), claimed, peer_addr(role + 8, 0));
        if ((claimed >> 8) + 1 == gridDim.x >> 1) {
            g_reg[0] = 0;
            for (int i = 0; i < 64; i++) reinterpret_cast<uint4*>(g_cls)[i] = make_uint4(0, 0, 0, 0);
        }
    }
    __syncwarp();
    mbar_wait_w(role + 8, 0);
    const int p = lds32(role) & 255, order = lds32(role) >> 8;
    if (p >= 64) return;
    proj_tiles<NT, STAGES, false>(sb, warp, rank, 1, &mapW, &mapO, &mapOut,
                                  [&](int, int& col, int& tok) { col = (p & 7) * 128; tok = S_LEN - 16 * NT + ((p >> 3) * 2 + rank) * NT; },
                                  [&](int) { wait_prerequisites();
                                  }, KROT == 0 ? 0 : KROT == 1 ? (p & 7) * 8 : KROT == 2 ? (p >> 3) * 8 : KROT == 3 ? ((p & 7) + (p >> 3)) * 8 : (p >> 5) * 32);
    KT_END(3);
    asm volatile("barrier.cluster.arrive.relaxed; barrier.cluster.wait;" ::: "memory");
}

#define WO_RF1 6
constexpr int SM_KV = 0, KV_BYTES = 18432;
constexpr int SM_XT = 2 * KV_BYTES;
constexpr int SM_STG = SM_XT + 65536;
constexpr int SM_Z = SM_STG + 6144;
constexpr int SM_RT = SM_Z + 8192;
constexpr int SM_OT = SM_RT + 8192;
constexpr int SM_QKV = SM_RT + 10240;
constexpr int SM_R1 = SM_QKV + 6144;
constexpr int SM_Y = SM_R1;
constexpr int SM_R2 = SM_R1 + 4096;
constexpr int SM_R3 = SM_R2 + 1024;
constexpr int SM_O = SM_R3 + 2048;
constexpr int SM_S = SM_O + 2048;
constexpr int SM_INV = SM_S + 1536;
constexpr int SM_TO = SM_R3;
constexpr int SM_WORK_END = SM_S + 2048;
constexpr int STG_QK = 0, STG_V = 98304;
#define LEAD 2
#define FL_AT (LEAD == 3 ? 0 : 4)
#define KC_AT (LEAD == 3 ? 0 : 4)
#define KC_PRE 1
#define RTF 1
#define XT11 0
#define XT_AT 1
#define RTW 0
#define KVMC 1
#define WO_IT (LEAD - 1)
__host__ __device__ constexpr int stg_wo(int r) { return r < 9 ? KV_BYTES + r * 2048 : r < 13 ? SM_QKV + (r - 9) * 2048 : SM_S; }
static_assert(WO_RF1 == 6 && SM_QKV % 1024 == 0 && SM_S % 1024 == 0 && SM_QKV + 8192 <= SM_TO, "staging of Wo");
__host__ __device__ constexpr int stg_qk(int t, int r) { return t == 0 ? SM_XT + r * 2048 : r < SM_XT / 2048 ? r * 2048 : (r + 24) * 2048; }
constexpr int SM_WO1 = SM_WORK_END - WO_RF1 * 2048;
constexpr int STG_WO = SM_WO1 - 16384;
constexpr int SM_WQK = (SM_WO1 + 16384 > STG_V + 49152) ? SM_WO1 + 16384 : STG_V + 49152;
constexpr int SM_WV = SM_WQK + 32768;
constexpr int SM_WO2 = SM_WV + 16384;
constexpr int SM_BARS = SM_WO2 + 32768;
enum { MB_W0 = SM_BARS, MB_W1 = SM_BARS + 8, MB_W2 = SM_BARS + 16, MB_W3 = SM_BARS + 24, MB_XT = SM_BARS + 32  , MB_KV = SM_BARS + 48  ,
       MB_R3 = SM_BARS + 64, MB_R1 = SM_BARS + 72, MB_R2 = SM_BARS + 80, MB_RT0 = SM_BARS + 88, MB_RT1 = SM_BARS + 96, MB_FREE = SM_BARS + 104,
       MB_P = SM_BARS + 112, MB_V = SM_BARS + 120, MB_STG = SM_BARS + 128, MB_ROLE = SM_BARS + 136, MB_W4 = SM_BARS + 144, MB_W5 = SM_BARS + 152, SM_ROLE = SM_BARS + 160  ,
       MB_FULL = SM_BARS + 176  , MB_EMPTY = SM_BARS + 208  , MB_SUM = SM_BARS + 240 };
constexpr int CHAIN_SMEM = MB_SUM + 8;
static_assert(SM_WORK_END % 1024 == 0 && STG_WO >= STG_V, "work area");
static_assert(SM_Y % 128 == 0, "exchange Y");
static_assert(CHAIN_SMEM <= 232448 && WO_RF1 >= 6, "smem");

#define DLY_X 250
#define DLY_V 0
#define DLY_Y 320
#define DLY_Z 280
#define TS_AT 5
#define EARLY_T 6
#define PH2 0
#define VF1 1
#define COLDV 0
#define COLD() true
#define RT0_B 1
#define PJ_FREE 1
#define PROD10 1
#define QF 0
#define AF 0
#define PRO_LATE 1
#define OTMA 1
#define TM 7
#define ORD0 2
#define ORD1 2
#define ORDV 2
__host__ __device__ constexpr int kstep(int ord, int i) { return ord == 0 ? i : ord == 1 ? (i + 24) % 32 : ord == 2 ? (i % 4 == 3 ? 24 + i / 4 : i / 4 * 3 + i % 4) : ord == 3 ? (i < 16 ? (i % 2 ? 24 + i / 2 : i / 2) : i - 8) : (i < 8 ? i : i < 16 ? i + 16 : i - 8); }

#define GV 1
#define NSV (GV ? 320 : 352)
#define Q3_AT 9
#define NA 7
#define NP2 5
#define P2_FENCE 0
#define SPLIT 5
#define TA0 16
#define Y_CHAIN 1
#define EF_W 1
#define XFLIP 0
#define YFLIP 0
#define ZFLIP 1
#define OFENCE 2
#define REG_A 240
#define REG_B 216
#define REG_C (3 * 168 - REG_A - REG_B)

enum { BAR_Y, BAR_MEM, BAR_PUB, BAR_QK, BAR_S, BAR_O, BAR_SENT, BAR_COMM, BAR_PUBV, BAR_PV, BAR_PDONE, BAR_VP, BAR_ZP, BAR_PRO, BAR_O2, BAR_SV,
       BAR_V = BAR_PV, BAR_SENTC = BAR_PDONE, BAR_Q3 = BAR_PRO, BAR_INV = BAR_PRO, BAR_XT0 = BAR_Y };

__device__ __forceinline__ uint32_t umax4(const uint4& v) { return max(max(v.x, v.y), max(v.z, v.w)); }
__device__ __forceinline__ unsigned gtime() { unsigned t; asm volatile("mov.u32 %0, %%globaltimer_lo;" : "=r"(t)::"memory"); return t; }
__device__ __forceinline__ unsigned clock32() { unsigned t; asm volatile("mov.u32 %0, %%clock;" : "=r"(t)::"memory"); return t; }
__device__ __forceinline__ void spin_cycles(int d) {
    if (d > 0) { const unsigned c0 = clock32(); while (clock32() - c0 < (unsigned)d) {} }
}
__device__ __forceinline__ float ex2_approx(float x) { float y; asm("ex2.approx.ftz.f32 %0, %1;" : "=f"(y) : "f"(x)); return y; }
__device__ __forceinline__ float rcp_approx(float x) { float y; asm("rcp.approx.ftz.f32 %0, %1;" : "=f"(y) : "f"(x)); return y; }
__device__ __forceinline__ void st_sent(const void* p) { asm volatile("st.relaxed.gpu.global.v4.u32 [%0], {%1,%1,%1,%1};" ::"l"(p), "r"(SENT) : "memory"); }
#define POLL_LD(p, a, b, c, d, addr) "@" p " ld.relaxed.gpu.global.v4.u32 {" a "," b "," c "," d "}, [" addr "];\n"
#define POLL_CK(p, a, b, c, d) "max.u32 m, " a "," b "; max.u32 n, " c "," d "; max.u32 m, m, n; setp.eq.u32 " p ", m, 0xFFFFFFFF;\n"
#define POLL_IO(v) "+r"(v.x), "+r"(v.y), "+r"(v.z), "+r"(v.w)
__device__ __forceinline__ void poll_init(uint4& v) { v = make_uint4(SENT, SENT, SENT, SENT); asm volatile("" : POLL_IO(v)); }
__device__ __forceinline__ int poll2(uint4 (&v)[2], const char* a) {
    int c = 0;
    asm volatile("{.reg .pred p0, p1, p; .reg .u32 m, n;\n"
                 "setp.eq.u32 p0, %8, 0; setp.eq.u32 p1, %8, 0;\n"
                 "POLL_LOOP:\n"
                 POLL_LD("p0", "%0", "%1", "%2", "%3", "%9") POLL_LD("p1", "%4", "%5", "%6", "%7", "%9+512")
                 "add.u32 %8, %8, 1;\n"
                 POLL_CK("p0", "%0", "%1", "%2", "%3") POLL_CK("p1", "%4", "%5", "%6", "%7")
                 "or.pred p, p0, p1; setp.lt.and.u32 p, %8, 0x10000, p; vote.sync.any.pred p, p, 0xFFFFFFFF;\n"
                 "@p bra.uni POLL_LOOP;}" : POLL_IO(v[0]), POLL_IO(v[1]), "+r"(c) : "l"(a) : "memory");
    return c;
}
template <int ST> __device__ __forceinline__ int poll4(uint4 (&v)[4], const char* a) {
    int c = 0;
    asm volatile("{.reg .pred p0, p1, p2, p3, p; .reg .u32 m, n;\n"
                 "setp.eq.u32 p0, %16, 0; setp.eq.u32 p1, %16, 0; setp.eq.u32 p2, %16, 0; setp.eq.u32 p3, %16, 0;\n"
                 "POLL_LOOP:\n"
                 POLL_LD("p0", "%0", "%1", "%2", "%3", "%17") POLL_LD("p1", "%4", "%5", "%6", "%7", "%17+%18")
                 POLL_LD("p2", "%8", "%9", "%10", "%11", "%17+%19") POLL_LD("p3", "%12", "%13", "%14", "%15", "%17+%20")
                 "add.u32 %16, %16, 1;\n"
                 POLL_CK("p0", "%0", "%1", "%2", "%3") POLL_CK("p1", "%4", "%5", "%6", "%7") POLL_CK("p2", "%8", "%9", "%10", "%11") POLL_CK("p3", "%12", "%13", "%14", "%15")
                 "or.pred p, p0, p1; or.pred p, p, p2; or.pred p, p, p3; setp.lt.and.u32 p, %16, 0x10000, p; vote.sync.any.pred p, p, 0xFFFFFFFF;\n"
                 "@p bra.uni POLL_LOOP;}" : POLL_IO(v[0]), POLL_IO(v[1]), POLL_IO(v[2]), POLL_IO(v[3]), "+r"(c) : "l"(a), "n"(ST), "n"(2 * ST), "n"(3 * ST) : "memory");
    return c;
}
__device__ __forceinline__ uint32_t add_bf16x2(uint32_t a, uint32_t b) { uint32_t r; asm("add.rn.bf16x2 %0, %1, %2;" : "=r"(r) : "r"(a), "r"(b)); return r; }
__device__ __forceinline__ uint32_t max_bf16x2(uint32_t a, uint32_t b) { uint32_t r; asm("max.bf16x2 %0, %1, %2;" : "=r"(r) : "r"(a), "r"(b)); return r; }
template <class F> __device__ __forceinline__ void softmax40(uint32_t (&pw)[6], uint32_t sa, F mid) {
    const float LOG2E = 1.4426950408889634f;
    uint32_t w[5];
    float e[10];
#pragma unroll
    for (int i = 0; i < 5; i++) w[i] = lds32(sa + i * 128);
    uint32_t m = max_bf16x2(max_bf16x2(max_bf16x2(w[0], w[1]), max_bf16x2(w[2], w[3])), w[4]);
    m = max_bf16x2(m, __shfl_xor_sync(~0u, m, 1));
    m = max_bf16x2(m, __shfl_xor_sync(~0u, m, 2));
    const float mb2 = fmaxf(bf_lo(m), bf_hi(m)) * LOG2E;
#pragma unroll
    for (int i = 0; i < 5; i++) {
        e[2 * i] = ex2_approx(fmaf(bf_lo(w[i]), LOG2E, -mb2));
        e[2 * i + 1] = ex2_approx(fmaf(bf_hi(w[i]), LOG2E, -mb2));
    }
    mid();
#pragma unroll
    for (int i = 0; i < 5; i++) pw[i] = pack_bf16(e[2 * i], e[2 * i + 1]);
    const float sum = (((e[0] + e[1]) + (e[2] + e[3])) + ((e[4] + e[5]) + (e[6] + e[7]))) + (e[8] + e[9]);
    const float hi = bf_hi(__float_as_uint(sum));
    pw[5] = pack_bf16(sum - hi, hi);
}
template <bool NORM, class F> __device__ __forceinline__ void pv32(uint32_t (&w)[4], float (&inv)[2], const uint32_t (&va)[2][2][4], const uint32_t (&vm)[4], const uint32_t (&pw)[6], F mid) {
    float o[2][3][4], t[4] = {0.f, 0.f, 0.f, 0.f};
#pragma unroll
    for (int i = 0; i < 3; i++)
#pragma unroll
        for (int m = 0; m < 2; m++) {
            o[m][i][0] = o[m][i][1] = o[m][i][2] = o[m][i][3] = 0.f;
            if (i < 2) mma16816(o[m][i], va[m][i & 1], pw[2 * i], pw[2 * i + 1]);
            else mma1688(o[m][i], vm[2 * m], vm[2 * m + 1], pw[4]);
        }
    mma1688(t, 0x3F803F80u, 0x3F803F80u, pw[5]);
    mid();
    if (NORM) { inv[0] = rcp_approx(t[0]); inv[1] = rcp_approx(t[1]); }
#pragma unroll
    for (int i = 0; i < 4; i++) {
        const float a = (o[i >> 1][0][2 * (i & 1)] + o[i >> 1][1][2 * (i & 1)]) + o[i >> 1][2][2 * (i & 1)];
        const float b = (o[i >> 1][0][2 * (i & 1) + 1] + o[i >> 1][1][2 * (i & 1) + 1]) + o[i >> 1][2][2 * (i & 1) + 1];
        w[i] = NORM ? pack_bf16(a * inv[0], b * inv[1]) : pack_bf16(a, b);
    }
    if (!NORM) { inv[0] = t[0]; inv[1] = t[1]; }
}
__device__ __forceinline__ uint32_t scale_scores(float a, float b) {
    const float scale = 0.08838834764831845f;
    const uint32_t w = pack_bf16(a, b);
    return pack_bf16(bf_lo(w) * scale, bf_hi(w) * scale);
}

#define TL(i) do {} while (0)
#define TLB(i) do {} while (0)
#define TLC(i) do {} while (0)

#define OPQ_LANE 1
#define CLAIM_T 64
#define PAD_A 0
#define PAD_B 0
#define PAD_C 0
template <int N> __device__ __forceinline__ void code_pad() {
#pragma unroll
    for (int i = 0; i < N; i++) asm volatile("pmevent 0;");
}

constexpr int TILE_N = 192, EARLY_TOK = 3 * TILE_N, LAST_N = S_LEN - EARLY_TOK - 7 * TILE_N, FLAG_END = NSEG + 3;
constexpr int PJ_STAGE = 16384 + TILE_N * 128, PJ_LOW = 0, PJ_MID = SM_XT + 2 * PJ_STAGE;
__device__ __forceinline__ uint32_t pj_stage(uint32_t i) { return SM_XT + (i & 1) * PJ_STAGE + (i >> 1 & 1) * (SM_WORK_END - SM_XT); }
static_assert(PJ_MID <= SM_QKV && PJ_MID + TILE_N * 128 <= SM_WORK_END && SM_WORK_END + 2 * PJ_STAGE <= SM_BARS && PJ_MID <= SM_OT && SM_OT % 512 == 0 && TILE_N * 128 <= SM_XT && LAST_N == 128, "projection");
template <class R, class F>
__device__ __forceinline__ void pj_fetch(uint32_t sb, uint32_t lane, uint32_t it, int nkb, int n, const CUtensorMap* mapW, const CUtensorMap* mapO, int col0, int col1, int k0, int tok, bool soon, R ready, F room) {
    auto weights = [&](int kb) {
        const uint32_t i = it + kb, sa = sb + pj_stage(i), full = sb + MB_FULL + (i & 3) * 8;
        mbar_wait(sb + MB_EMPTY + (i & 3) * 8, (~i >> 2) & 1);
        mbar_expect_tx(full, 16384 + n * 128);
        tma_load_2d(sa, mapW, col0, k0 + kb * 64, full);
        tma_load_2d(sa + 8192, mapW, col1, k0 + kb * 64, full);
    };
    auto rows = [&](int kb) {
        const uint32_t i = it + kb, sa = sb + pj_stage(i) + 16384, full = sb + MB_FULL + (i & 3) * 8;
        for (int t = 0; t < n; t += 64) tma_load_2d(sa + t * 128, mapO, k0 + kb * 64, tok + t, full);
    };
    if (soon) ready();
#pragma unroll 1
    for (int kb = 0; kb < 4; kb++) {
        if (kb == PJ_FREE) room();
        if (lane == 0) { weights(kb); if (soon) rows(kb); }
        __syncwarp();
    }
    if (!soon) ready();
    if (lane == 0) {
#pragma unroll 1
        for (int kb = 0; kb < 4; kb++) if (!soon) rows(kb);
#pragma unroll 1
        for (int kb = 4; kb < nkb; kb++) { weights(kb); rows(kb); }
    }
    __syncwarp();
}
template <int N>
__device__ __forceinline__ void pj_sum(float (&d)[N / 2], uint32_t sb, uint32_t lane, uint32_t wg, uint32_t it, int nkb) {
#pragma unroll
    for (int r = 0; r < N / 2; r++) d[r] = 0.f;
#pragma unroll 1
    for (int kb = 0; kb < nkb; kb++) {
        const uint32_t i = it + kb, sa = sb + pj_stage(i);
        mbar_wait_w(sb + MB_FULL + (i & 3) * 8, (i >> 2) & 1);
        const uint64_t da = make_desc(sa + wg * 8192, 16, 1024), db = make_desc(sa + 16384, 16, 1024);
        wg_fence();
#pragma unroll
        for (int k = 0; k < 4; k++) wgmma_proj<N>(d, da + k * 128, db + k * 2);
        wg_commit();
        if (kb > 0) { wg_wait<1>(); mbar_arrive_if0(lane, sb + MB_EMPTY + ((i - 1) & 3) * 8); }
    }
    wg_wait<0>();
    mbar_arrive_if0(lane, sb + MB_EMPTY + ((it + nkb - 1) & 3) * 8);
}
template <int N>
__device__ __forceinline__ void pj_store(const float (&d)[N / 2], uint32_t box, uint32_t t, int bar, const CUtensorMap* mapOut, int col, int tok) {
    const uint32_t ea = box + (((t >> 4) & 1) * 8 + (t & 7)) * 128 + ((((t >> 5) * 2 + ((t >> 3) & 1)) ^ (t & 7)) * 16);
#pragma unroll
    for (int r = 0; r < N / 16; r++)
        stsm4t(ea + r * 2048, pack_bf16(d[8 * r], d[8 * r + 1]), pack_bf16(d[8 * r + 2], d[8 * r + 3]), pack_bf16(d[8 * r + 4], d[8 * r + 5]), pack_bf16(d[8 * r + 6], d[8 * r + 7]));
    asm volatile("fence.proxy.async.shared::cta;" ::: "memory");
    bar_sync(bar, 128);
    if (t == 0) {
        for (int r = 0; r < N; r += 64) tma_store_2d(mapOut, box + r * 128, col, tok + r);
        asm volatile("cp.async.bulk.commit_group;" ::: "memory");
    }
}
template <int N>
__device__ __forceinline__ void pj_last(uint32_t sb, uint32_t wg, uint32_t t, int bar, const CUtensorMap* mapOut, int col, int tok) {
    float d[N / 2];
    mbar_expect_tx_if0(t | (wg ^ 1), sb + MB_SUM, N * 128);
    pj_sum<N>(d, sb, t & 31, wg, 0, 32);
    if (wg == 0) {
        const uint32_t rsb = sb ^ (1u << 24), dst = rsb + PJ_LOW + t * 16;
        mbar_wait_w(sb + MB_FREE, LEAD & 1);
#pragma unroll
        for (int r = 0; r < N / 16; r++)
            st_async4(dst + r * 2048, __uint_as_float(pack_bf16(d[8 * r], d[8 * r + 1])), __uint_as_float(pack_bf16(d[8 * r + 2], d[8 * r + 3])),
                      __uint_as_float(pack_bf16(d[8 * r + 4], d[8 * r + 5])), __uint_as_float(pack_bf16(d[8 * r + 6], d[8 * r + 7])), rsb + MB_SUM);
    } else {
        mbar_wait_w(sb + MB_SUM, 0);
#pragma unroll
        for (int r = 0; r < N / 16; r++) {
            const uint4 v = lds128(sb + PJ_LOW + t * 16 + r * 2048);
            d[8 * r] += bf_lo(v.x); d[8 * r + 1] += bf_hi(v.x); d[8 * r + 2] += bf_lo(v.y); d[8 * r + 3] += bf_hi(v.y);
            d[8 * r + 4] += bf_lo(v.z); d[8 * r + 5] += bf_hi(v.z); d[8 * r + 6] += bf_lo(v.w); d[8 * r + 7] += bf_hi(v.w);
        }
        pj_store<N>(d, sb + PJ_MID, t, bar, mapOut, col, tok);
        if (t == 0) asm volatile("cp.async.bulk.wait_group.read 0;" ::: "memory");
        __syncwarp();
    }
}
#define NOINL 0
__device__ __forceinline__
void pj_tile(uint32_t wg, const CUtensorMap* mapOut) {
    uint32_t t, rank;
    asm volatile("mov.u32 %0, %%tid.x; and.b32 %0, %0, 127; mov.u32 %1, %%ctaid.x; and.b32 %1, %1, 1;" : "=r"(t), "=r"(rank));
    const uint32_t base = 1024 | (rank << 24), pr = lds32(base + SM_ROLE);
    const int col = (pr & 7) * 128 + 64 * rank, tok = EARLY_TOK + (pr >> 3) * TILE_N;
    if (pr >> 3 == 7) pj_last<LAST_N>(base, wg, t, BAR_O, mapOut, col, tok); else pj_last<TILE_N>(base, wg, t, BAR_O, mapOut, col, tok);
}
__device__ __forceinline__ void pj_early(uint32_t sb, uint32_t e, uint32_t rank, const CUtensorMap* mapW, const CUtensorMap* mapO, const CUtensorMap* mapOut) {
    const uint32_t warp = threadIdx.x >> 5, lane = threadIdx.x & 31;
    if (warp == 8) {
        wait_prerequisites();
#pragma unroll 1
        for (int i = 0; i < EARLY_T; i++) {
            const int col = ((i & 1) * 4 + e * 2 + rank) * 128;
            pj_fetch(sb, lane, i * 64, 64, TILE_N, mapW, mapO, col, col + 64, 0, (i >> 1) * TILE_N, false, [&]() {
                if (i & 1) return;
                const unsigned need = TILE_N / SEG * (i / 2 + 1) + LEAD;
                for (int guard = 0; guard < (1 << 16); guard++) {
                    const uint4 f = ld_relaxed_v4(g_xflag + lane * 4);
                    if (__all_sync(~0u, min(min(f.x, f.y), min(f.z, f.w)) >= need)) break;
                    __nanosleep(500);
                }
                asm volatile("fence.acq_rel.gpu; fence.proxy.async.global;" ::: "memory");
                if (i == 0 && rank == 0 && lane == 0 && atomicAdd(g_reg + 2, 1) == 1) {
                    g_reg[0] = 0;
                    for (int k = 0; k < 64; k++) reinterpret_cast<uint4*>(g_cls)[k] = make_uint4(0, 0, 0, 0);
                }
                __syncwarp();
            }, []() {});
        }
    } else if (warp < 8) {
        const uint32_t wg = warp >> 2, t = threadIdx.x & 127;
#pragma unroll 1
        for (int i = 0; i < EARLY_T; i++) {
            float d[TILE_N / 2];
            pj_sum<TILE_N>(d, sb, lane, wg, i * 64, 64);
            if (t == 0) asm volatile("cp.async.bulk.wait_group.read 0;" ::: "memory");
            bar_sync(1 + wg, 128);
            pj_store<TILE_N>(d, sb + (wg ? PJ_MID : PJ_LOW), t, 1 + wg, mapOut, ((i & 1) * 4 + e * 2 + rank) * 128 + wg * 64, (i >> 1) * TILE_N);
        }
        if (t == 0) asm volatile("cp.async.bulk.wait_group 0;" ::: "memory");
    }
    __syncwarp();
}
template <bool TAIL>
__global__ void __cluster_dims__(2, 1, 1) __launch_bounds__(384, 1)
chain_kernel(char* __restrict__ mbox, const bf16* __restrict__ mem0,
             const __grid_constant__ CUtensorMap mapX, const __grid_constant__ CUtensorMap mapT32, const __grid_constant__ CUtensorMap mapT16,
             const __grid_constant__ CUtensorMap mapTQ, const __grid_constant__ CUtensorMap mapKV,
             const __grid_constant__ CUtensorMap mapWq, const __grid_constant__ CUtensorMap mapWk, const __grid_constant__ CUtensorMap mapWv,
             const __grid_constant__ CUtensorMap mapWo, const __grid_constant__ CUtensorMap mapPW, const __grid_constant__ CUtensorMap mapPO,
             const __grid_constant__ CUtensorMap mapOut, const __grid_constant__ CUtensorMap mapO8) {
    KT_START(2);
    extern __shared__ __align__(1024) uint8_t smem_chain[];
    constexpr uint32_t SB0 = 1024;
    if (smem_u32(smem_chain) != (SB0 | ((blockIdx.x & 1) << 24))) __trap();
    const int kh = blockIdx.x & 1;
    if (threadIdx.x == 0) {
        const uint32_t sb = smem_u32(smem_chain);
        for (int i = 0; i < 14; i++) mbar_init(sb + SM_BARS + 8 * i, 1);
        mbar_init(sb + MB_P, 4); mbar_init(sb + MB_V, 4); mbar_init(sb + MB_STG, 8); mbar_init(sb + MB_ROLE, 1); mbar_init(sb + MB_W4, 1); mbar_init(sb + MB_W5, 1);
        mbar_expect_tx(sb + MB_ROLE, 4);
        asm volatile("fence.mbarrier_init.release.cluster;" ::: "memory");
    }
    if (TAIL && threadIdx.x == 96) {
        const uint32_t sb = smem_u32(smem_chain);
        for (int i = 0; i < 4; i++) { mbar_init(sb + MB_FULL + 8 * i, 1); mbar_init(sb + MB_EMPTY + 8 * i, 8); }
        mbar_init(sb + MB_SUM, 1);
        asm volatile("fence.mbarrier_init.release.cluster;" ::: "memory");
    }
    if (threadIdx.x == 32) { prefetch_map(&mapWv); prefetch_map(&mapWq); prefetch_map(&mapWk); prefetch_map(&mapWo); prefetch_map(&mapX); }
    __syncwarp();
    asm volatile("barrier.cluster.arrive.relaxed.aligned;" ::: "memory");
    unsigned claimed = 0;
    if (threadIdx.x == CLAIM_T && kh == 0) claimed = claim_pair(g_reg) & 255;
    __syncwarp();
    asm volatile("barrier.cluster.wait.acquire.aligned;" ::: "memory");
    if (threadIdx.x == CLAIM_T && kh == 0) {
        st_async1((SB0 | (1u << 24)) + SM_ROLE, claimed, (SB0 | (1u << 24)) + MB_ROLE);
        st_async1(SB0 + SM_ROLE, claimed, SB0 + MB_ROLE);
    }
    __syncwarp();
    mbar_wait_w(smem_u32(smem_chain) + MB_ROLE, 0);
    const int pair = uniform(lds32(smem_u32(smem_chain) + SM_ROLE));
#define YFLIP_() (uniform(lds32(sb + SM_ROLE + 4)) ^ YFLIP)
    if (pair >= 64) {
        if (TAIL) pj_early(smem_u32(smem_chain), pair - 64, kh, &mapPW, &mapPO, &mapOut);
        if (TAIL) KT_END(3);
        return;
    }
    if (threadIdx.x == 0) KT_MARK(5);
    const int h = pair >> 1, nh = pair & 1, j = 2 * nh + kh, role = 2 * pair + kh;
#define WG_ORDER 0x210
    const int warp = uniform(((WG_ORDER >> (4 * (threadIdx.x >> 7))) & 3) * 4 + ((threadIdx.x >> 5) & 3));
    const uint32_t g = warp & 3, sb = SB0 | (kh << 24), rsb = sb ^ (1u << 24), cls = pair >> 5, kflip = ZFLIP ^ kh;
    const uint32_t mlo = (uint32_t)(uintptr_t)mbox, mhi = (uint32_t)((uintptr_t)mbox >> 32);
    auto lane16 = [&]() {
        uint32_t t;
        asm volatile("{.reg .u32 l, x; mov.u32 l, %%laneid; xor.b32 x, l, 1; shl.b32 x, x, 4; shfl.sync.bfly.b32 %0, x, 1, 0x1f, 0xffffffff;}" : "=r"(t));
        return t;
    };
#define PHASE(k) uint32_t L; asm volatile("{.reg .u32 t; shr.u32 t, %1, %3; add.u32 %0, %2, t;}" : "=r"(L) : "r"(it), "r"(l16), "n"(8 + (k)))
#define ROWPAT() ((((L << 3) & 0x380) | ((L << 2) & 0x400)) | ((L ^ (L >> 3)) & 0x10) | (L & 0x60))
#define FRAG() (ROWPAT() ^ (g << 5))
#define QFRAG() ((((L >> 1) & 0x80) | (L & 0x70)) + ((L & 0x80) ? SM_KV + 16384 + kvo : SM_QKV))
#define VFRAG() (ROWPAT() ^ ((g & 1) << 6))
#define VBASE() (sb + SM_KV + 8192 + (g >> 1) * 4096 + kvo)
#define XTLO() ((uint32_t)make_desc(SB0 + SM_XT, 16, 1024) + (ui & 1) * 2048)
    auto last_tile = [&](uint32_t wg) {
        KT_END(2);
        pj_tile(wg, &mapOut);
    };
    if (warp >= 8) {
        asm volatile("setmaxnreg.dec.sync.aligned.u32 %0;" ::"n"(REG_C));
        code_pad<PAD_C>();
        const uint32_t l16 = lane16(), lane = l16 >> 4;
        auto load_xt = [&](int seg, int half) {
            const uint32_t bar = sb + MB_XT + (seg & 1) * 8;
            if (half == 0) mbar_expect_tx(bar, 32768);
            asm volatile("cp.async.bulk.tensor.3d.shared::cluster.global.mbarrier::complete_tx::bytes [%0], [%1, {%3, %4, %5}], [%2];"
                         ::"r"(sb + SM_XT + (seg & 1) * 32768 + half * 16384), "l"(&mapX), "r"(bar), "r"(0), "r"(seg * SEG), "r"(8 * kh + 4 * (half ^ kflip)) : "memory");
        };
        if (warp == 8) {
            const CUtensorMap* ws = kh ? &mapWq : &mapWk;
            const CUtensorMap* wn = kh ? &mapWk : &mapWq;
            const uint64_t pol = EF_W ? policy_evict_first() : policy_evict_normal();
            const int col = h * DH + 64 * nh, row = 512 * kh;
            if (lane == 0) { mbar_expect_tx(sb + MB_W0, 49152); mbar_expect_tx(sb + MB_W1, 49152); mbar_expect_tx(sb + MB_W4, 49152); mbar_expect_tx(sb + MB_W2, 49152); mbar_expect_tx(sb + MB_W3, 65536); }
            __syncwarp();
            if (lane < 24) {
                const int k = lane ^ (16 * kflip);
                tma_load_2d(sb + STG_V + lane * 2048, &mapWv, col, row + 16 * k, sb + MB_W0, pol);
                tma_load_2d(sb + stg_qk(0, lane), ws, col, row + 16 * k, sb + MB_W1, pol);
                tma_load_2d(sb + stg_qk(1, lane), wn, col, row + 16 * k, sb + MB_W4, pol);
            }
            if (lane < 8) {
                const int k = (24 + lane) ^ (16 * kflip);
                tma_load_2d(sb + SM_WQK + lane * 4096, ws, col, row + 16 * k, sb + MB_W2, pol);
                tma_load_2d(sb + SM_WQK + lane * 4096 + 2048, wn, col, row + 16 * k, sb + MB_W2, pol);
                tma_load_2d(sb + SM_WV + lane * 2048, &mapWv, col, row + 16 * k, sb + MB_W2, pol);
            }
            __syncwarp();
        }
        if (warp == 9) {
            bar_sync(BAR_XT0, 160);
            if (lane == 0) { load_xt(0, 0); load_xt(0, 1); }
            __syncwarp();
        }
        if (warp == 10 && lane == 0) {
            wait_prerequisites();
            launch_dependents();
            sts32(sb + SM_ROLE + 4, g_reg[1]);
        }
        __syncwarp();
        bar_sync(BAR_PDONE, 384);
        KT_MARK(9);
        if ((warp & 1) == 0) for (int c = (warp - 8) * 16 + lane; c < 512; c += 64) {
            uint32_t w[4];
#pragma unroll
            for (int r = 0; r < 4; r++) {
                const uint32_t lo = reinterpret_cast<const uint16_t*>(mem0)[(2 * r) * DM + 512 * kh + c], hi = reinterpret_cast<const uint16_t*>(mem0)[(2 * r + 1) * DM + 512 * kh + c];
                w[r] = lo | (hi << 16);
            }
            sts128(sb + SM_Z + (c ^ (256 * kflip)) * 16, make_uint4(w[0], w[1], w[2], w[3]));
        }
        if (warp == 11) {
            const uint32_t dst = lane < 14 ? stg_wo(lane) : lane < 16 ? SM_WO1 + (lane - 8) * 2048 : SM_WO2 + (lane - 16) * 2048;
            tma_load_2d(sb + dst, &mapWo, 256 * j + 64 * (lane >> 3), h * DH + 16 * (lane & 7), sb + MB_W3, EF_W ? policy_evict_first() : policy_evict_normal());
        }
        auto tok_start = [&](int s) {
            if (lane == 0) {
                if (TS_AT == 0) TL(21);
                if (s > -LEAD && (OTMA || s + LEAD - 1 < NSEG)) {
                    mbar_wait(sb + MB_STG, (s + LEAD - 1) & 1);
                    if (TS_AT == 1) TL(21);
                    if (TS_AT == 2) TL(21);
                    asm volatile("fence.proxy.async.shared::cta;" ::: "memory");
                    if (TS_AT == 3) TL(21);
                    const int r = ((s + LEAD - 1) & 3) * NH + h;
                    if (s + LEAD - 1 < NSEG) {
                        tma_store_2d(kh ? &mapT32 : &mapTQ, sb + SM_STG, kh ? 64 * nh : 256 * nh, kh ? r * 96 + 32 : r * 12);
                        tma_store_2d(&mapT16, sb + SM_STG + 4096, 64 * nh, r * 96 + 64 + 16 * kh);
                    }
                    if (OTMA && s > 0) tma_store_3d(&mapO8, sb + SM_OT, 0, (s - 1) * SEG + 8 * j, 4 * h);
                    asm volatile("cp.async.bulk.commit_group;" ::: "memory");
                    if (TS_AT == 4) TL(21);
                }
                if (s + LEAD + 1 < NSEG) load_xt(s + LEAD + 1, 0);
                if (s < 0) asm volatile("cp.async.bulk.wait_group.read 0;" ::: "memory");
                if (s < 0) {
                    asm volatile("mbarrier.arrive.shared::cluster.b64 _, [%0];" ::"r"(rsb + MB_FREE) : "memory");
                    mbar_wait(sb + MB_FREE, (s + LEAD) & 1);
                }
            }
            __syncwarp();
        };
        auto tok_mid = [&](int s, bool flag) {
            if (lane == 0) {
                if (s + LEAD + 1 < NSEG) load_xt(s + LEAD + 1, 1);
                if (flag && s > -LEAD && s + LEAD - 1 < NSEG) {
                    asm volatile("cp.async.bulk.wait_group 0;" ::: "memory");
                    st_relaxed_u32(g_xflag + role, s + LEAD);
                }
            }
            __syncwarp();
        };
        auto tok_flag = [&](int s) {
            asm volatile("cp.async.bulk.wait_group 0;" ::: "memory");
            asm volatile("{.reg .pred p; setp.lt.u32 p, %2, %3; @p st.relaxed.gpu.global.u32 [%0], %1;}" ::"l"(g_xflag + role), "r"(s + LEAD), "r"(s + (l16 << 8)), "n"(NSEG + 1 - LEAD) : "memory");
        };
        auto kv_check = [&](int s) {
            if (s + 1 < NSEG) {
                if (lane < 4) {
                    unsigned f; int guard = 0;
                    do {
                        asm volatile("ld.acquire.gpu.global.u32 %0, [%1];" : "=r"(f) : "l"(g_xflag + h * 4 + lane) : "memory");
                        if (++guard > (1 << 20)) __trap();
                    } while (f <= (unsigned)(s + 1));
                }
                __syncwarp();
                asm volatile("fence.proxy.async.global;" ::: "memory");
            }
        };
        auto kv_load = [&](int s) {
            if (lane == 0 && s + 1 < NSEG) {
                const uint32_t bar = sb + MB_KV + ((s + 1) & 1) * 8, dst = sb + SM_KV + ((s + 1) & 1) * KV_BYTES;
                const int row = (((s + 1) & 3) * NH + h) * 96;
                mbar_expect_tx(bar, KV_BYTES);
                if (KVMC) asm volatile("cp.async.bulk.tensor.3d.shared::cluster.global.mbarrier::complete_tx::bytes.multicast::cluster [%0], [%1, {%3, %4, %3}], [%2], %5;"
                             ::"r"(dst + kh * 8192), "l"(&mapKV), "r"(bar), "r"(0), "r"(row + 32 + 32 * kh), "h"((uint16_t)3) : "memory");
                else for (int i = 0; i < 2; i++) asm volatile("cp.async.bulk.tensor.3d.shared::cluster.global.mbarrier::complete_tx::bytes [%0], [%1, {%3, %4, %3}], [%2];"
                             ::"r"(dst + i * 8192), "l"(&mapKV), "r"(bar), "r"(0), "r"(row + 32 + 32 * i) : "memory");
                bulk_load(dst + 16384, g_tok + row * DH + j * 1024, 2048, bar);
            }
            __syncwarp();
        };
        if (warp == 9) {
#pragma unroll 1
            for (int s = -LEAD; s < 0; s++) { tok_start(s); KT_MARK(13 + s); bar_arrive(BAR_PRO, 288); tok_mid(s, true); }
        }
        if (warp == 11) { kv_check(-1); kv_load(-1); }
        bar_arrive(BAR_MEM, 384);
        const uint32_t idx = (pair & 31) + 32 * (kh ^ 1);
        const uint32_t ybox = mlo + page_off(idx, cls ^ YFLIP_()), xoth = mlo + WIN + page_off((pair & 31) ^ 1, cls ^ XFLIP);
        const uint32_t zline = mlo + WIN + page_off(32 + (idx >> 5), cls ^ ZFLIP) + (idx & 31) * 128, zbox = mlo + WIN + (page_off(32 + kh, 0) & ~4096u);
        const uint32_t xtype = g == GV ? 2 : g == 2 ? 0 : 1;
        const int send = TAIL && PROD10 && g == 2 ? NSEG - 1 : NSEG;
        const uint32_t ydst = (lane >> 3) * 128 + ((lane & 7) ^ (lane >> 3)) * 16, ysrc = lane * 128 + ((2 * g) ^ (lane & 7)) * 16;
#pragma unroll 1
        for (int s = 0; s < send; s++) {
            const uint32_t slot = (s & 3) << 14;
            if (g == 3) {
                if (KC_AT == 0) kv_check(s);
                unsigned f = 0;
                const unsigned* fp = g_xflag + h * 4 + (lane & 3);
                auto kv_seen = [&]() {
                    for (int guard = 0; guard < (1 << 20) && s + 1 < NSEG && __any_sync(~0u, f <= (unsigned)(s + 1)); guard++) {
                        asm volatile("ld.relaxed.gpu.global.u32 %0, [%1];" : "=r"(f) : "l"(fp) : "memory");
                    }
                    asm volatile("fence.proxy.async.global;" ::: "memory");
                };
                if (TS_AT == 9) TL(21);
                const uint32_t L = l16, kvo = (s & 1) * KV_BYTES, qa = QFRAG(), sa = sb + SM_S + 512 + (L >> 2);
                float sc[4] = {0.f, 0.f, 0.f, 0.f}, sd[4] = {0.f, 0.f, 0.f, 0.f};
                uint32_t a[4][4], kb[2][4];
                mbar_wait_w(sb + MB_KV + (s & 1) * 8, (s >> 1) & 1);
                mbar_wait_w(sb + MB_P, s & 1);
#pragma unroll
                for (int c = 0; c < 2; c++) {
                    const uint32_t qc = qa + (sb + (nh ^ c) * 1024), kc = L + (sb + SM_QKV + 2048 + (nh ^ c) * 1024);
                    if (TS_AT == 7 && c) TL(21);
                    if (KC_AT == 4 && c) asm volatile("ld.relaxed.gpu.global.u32 %0, [%1];" : "=r"(f) : "l"(fp) : "memory");
                    if (c) bar_sync(BAR_QK, 224);
                    if (KC_AT == 1 && c) asm volatile("ld.relaxed.gpu.global.u32 %0, [%1];" : "=r"(f) : "l"(fp) : "memory");
                    ldsm4t(kb[0], kc); ldsm4t(a[0], qc); ldsm4t(a[1], qc + 256);
                    ldsm4t(kb[1], kc + 512); ldsm4t(a[2], qc + 512); ldsm4t(a[3], qc + 768);
                    mma16816v(sc, a[0], kb[0][0], kb[0][1]);
                    mma16816v(sd, a[1], kb[0][2], kb[0][3]);
                    mma16816v(sc, a[2], kb[1][0], kb[1][1]);
                    mma16816v(sd, a[3], kb[1][2], kb[1][3]);
                }
                sts32(sa, scale_scores(sc[0] + sd[0], sc[1] + sd[1]));
                sts32(sa + 768, scale_scores(sc[2] + sd[2], sc[3] + sd[3]));
                bar_arrive(BAR_S, 160);
                if (KC_AT == 2) asm volatile("ld.relaxed.gpu.global.u32 %0, [%1];" : "=r"(f) : "l"(fp) : "memory");
                TL(25);
                if (KC_AT && KC_PRE) kv_seen();
                if (KC_PRE == 3) kv_load(s);
                bar_sync(BAR_SV, NSV);
                if (KC_AT == 0 || KC_PRE == 2) kv_load(s);
                if (!RTW && lane == 0 && s + LEAD < NSEG) {
                    if (!RTF) asm volatile("fence.proxy.async.shared::cta;" ::: "memory");
                    asm volatile("cp.async.bulk.shared::cluster.shared::cta.mbarrier::complete_tx::bytes [%0], [%1], %2, [%3];" ::"r"(rsb + SM_RT), "r"(sb + SM_Z), "n"(8192), "r"(rsb + MB_RT0) : "memory");
                    if (TS_AT == 10) { mbar_wait(sb + MB_RT0, (s + LEAD) & 1); TL(21); }
                }
                __syncwarp();
                if (KC_AT && KC_PRE == 0) kv_seen();
                if (XT11 == 1) tok_mid(s, false);
                if (KC_AT && KC_PRE < 2) kv_load(s);
                if (XT11 == 2) tok_mid(s, false);
            } else {
                if (g == 1) { tok_start(s); if (XT_AT == 2) tok_mid(s, false); if (FL_AT == 4) tok_flag(s); if (XT_AT == 3) tok_mid(s, false); if (TS_AT == 5) TL(21); if (s == 0) KT_MARK(13); }
                const char* p = make_ptr(l16 + (xoth + xtype * 1024 + slot), mhi);
                uint4 v[2];
                const uint32_t dst = l16 + (sb + SM_QKV + xtype * 2048 + (nh ^ 1) * 1024);
                asm volatile("" ::"l"(p));
                poll_init(v[0]); poll_init(v[1]);
                if (g == GV) {
                    bar_sync(BAR_PUBV, 160);
                    if (FL_AT == 1) tok_flag(s);
                    mbar_wait_w(sb + MB_V, s & 1);
                    if (FL_AT == 2) tok_flag(s);
                    spin_cycles(DLY_V);
                } else {
                    bar_sync(BAR_PUB, 192);
                    spin_cycles(DLY_X);
                }
                const int r = poll2(v, p);
                sts128(dst, v[0]); sts128(dst + 512, v[1]);
                STAT(1, r > 1 && warp == 10);
                if (g != GV) bar_arrive(BAR_QK, 224);
                if (TS_AT == 6 && g == 0) TL(21);
                if (FL_AT == 3 && g == 1) tok_flag(s);
                if (OTMA && FL_AT == 0 && g == 1) asm volatile("cp.async.bulk.wait_group.read 0;" ::: "memory");
                if (g == GV) { bar_arrive(BAR_V, 160); if (GV == 0) bar_arrive(BAR_SV, NSV); TL(17); }
                if (g == 1) {
                    TL(31);
                    if (!OTMA) asm volatile("cp.async.bulk.wait_group.read 0;" ::: "memory");
                    if (XT_AT == 1) tok_mid(s, false);
                    if (XT_AT == 0 && !XT11) bar_sync(BAR_SV, NSV);
                    else bar_arrive(BAR_SV, NSV);
                    if (!XT11 && XT_AT == 0) tok_mid(s, FL_AT == 0);
                    TL(22);
                }
                if (g == 2 && s >= 1) {
                    TL(16);
                    const uint32_t prev = (slot - 0x4000) & 0xC000;
                    const char* y = make_ptr(l16 + (ybox + prev), mhi);
                    const char* x = make_ptr(l16 + (xoth + prev + kh * 1536), mhi);
#pragma unroll
                    for (int i = 0; i < 8; i++) st_sent(y + i * 512);
#pragma unroll
                    for (int i = 0; i < 3; i++) st_sent(x + i * 512);
                    st_relaxed_u32(make_ptr(lane * 4 + (zline + (slot ^ 0x8000)), mhi), SENT);
                    TL(23);
                }
            }
            if (s + 1 == NSEG) break;
            {
                const char* p = make_ptr(l16 + (ybox + g * 1024 + slot), mhi);
                char* zdst = make_ptr(lane * 4 + (zline + g * 32 + slot), mhi);
                const uint32_t dst = ydst + (sb + SM_Y + g * 1024), dst1 = (ydst ^ 64) + (sb + SM_Y + g * 1024 + 512), src = ysrc + (sb + SM_Y), src1 = (ysrc ^ 16) + (sb + SM_Y);
                asm volatile("" ::"l"(p), "l"(zdst));
                uint4 v[2];
                poll_init(v[0]); poll_init(v[1]);
                bar_sync(BAR_SENTC, 384);
                spin_cycles(DLY_Y);
                const int r = poll2(v, p);
                STAT(2, r > 1 && warp == 8);
                sts128(dst, v[0]); sts128(dst1, v[1]);
                bar_sync(BAR_Y, 256);
                TL(18);
                uint32_t b[2][4];
                ldsm4t(b[0], src); ldsm4t(b[1], src1);
                const uint32_t one = 0x3F803F80u;
                float d0[4] = {0.f, 0.f, 0.f, 0.f}, d1[4] = {0.f, 0.f, 0.f, 0.f};
                mma16816(d0, one, one, one, one, b[0][0], b[0][1]);
                mma16816(d1, one, one, one, one, b[1][0], b[1][1]);
                mma16816(d0, one, one, one, one, b[0][2], b[0][3]);
                mma16816(d1, one, one, one, one, b[1][2], b[1][3]);
                const uint32_t w = (lane & 4) ? pack_bf16(d1[0], d1[1]) : pack_bf16(d0[0], d0[1]);
                asm volatile("{.reg .pred p; setp.lt.u32 p, %2, 128; @p st.relaxed.gpu.global.u32 [%0], %1;}" ::"l"(zdst), "r"(w), "r"(l16) : "memory");
                if (s + LEAD < NSEG) bar_arrive(BAR_ZP, 256);
                TL(19);
            }
            {
                const char* p = make_ptr(l16 + (zbox + g * 512 + slot), mhi);
                const uint32_t dst = l16 + (sb + SM_Z + g * 512);
                asm volatile("" ::"l"(p));
                uint4 v[4];
                poll_init(v[0]); poll_init(v[1]); poll_init(v[2]); poll_init(v[3]);
                bar_sync(BAR_COMM, 128);
                spin_cycles(DLY_Z);
                const int r = poll4<2048>(v, p);
                STAT(0, r > 1 && warp == 8);
#pragma unroll
                for (int i = 0; i < 4; i++) sts128(dst + i * 2048, v[i]);
                bar_arrive(BAR_MEM, 384);
                TL(20);
            }
        }
        if ((OTMA || TAIL) && (TM & 4) && COLD()) {
            uint32_t t, rank;
            asm volatile("mov.u32 %0, %%tid.x; mov.u32 %1, %%ctaid.x; and.b32 %1, %1, 1;" : "=r"(t), "=r"(rank));
            const uint32_t base = SB0 | (rank << 24), ln = t & 31, pr = lds32(base + SM_ROLE), col = (pr & 7) * 128, tg = pr >> 3;
            if (t >> 5 == (PROD10 ? 10 : 8)) {
                if (TAIL) {
                if (PROD10) {
                    bar_arrive(BAR_PUB, 192); bar_arrive(BAR_QK, 224);
                    if (ln == 0) { prefetch_map(&mapPW); prefetch_map(&mapPO); prefetch_map(&mapOut); }
                    __syncwarp();
                }
                pj_fetch(base, ln, 0, 32, tg == 7 ? LAST_N : TILE_N, &mapPW, &mapPO, col + 64 * (rank ^ 1), col + 64 * rank, HD / 2 * rank, EARLY_TOK + tg * TILE_N, PROD10 && tg < 7, [&]() {
                    const unsigned need = tg == 7 ? FLAG_END : (S_LEN - LAST_N) / SEG + LEAD;
                    for (int guard = 0; guard < (1 << 20); guard++) {
                        uint32_t f0, f1;
                        asm volatile("{.reg .b64 t; ld.acquire.gpu.global.b64 t, [%2]; mov.b64 {%0, %1}, t;}" : "=r"(f0), "=r"(f1) : "l"(g_xflag + 64 * rank + 2 * ln) : "memory");
                        if (__all_sync(~0u, min(f0, f1) >= need)) break;
                    }
                    asm volatile("fence.proxy.async.global;" ::: "memory");
                }, [&]() {
                    mbar_wait_w(base + MB_P, (NSEG - 1) & 1);
                    mbar_wait_w(base + MB_V, (NSEG - 1) & 1);
                });
                }
            } else if (t >> 5 == 9) {
                bar_sync(BAR_ZP, 160);
                if (ln == 0) {
                    if (OTMA) {
                        asm volatile("fence.proxy.async.shared::cta;" ::: "memory");
                        tma_store_3d(&mapO8, base + SM_OT, 0, S_LEN - SEG + 16 * (pr & 1) + 8 * rank, 2 * (pr & ~1u));
                        asm volatile("cp.async.bulk.commit_group;" ::: "memory");
                    }
                    if (OTMA) asm volatile("cp.async.bulk.wait_group 0;" ::: "memory");
                    if (TAIL) asm volatile("mbarrier.arrive.shared::cluster.b64 _, [%0];" ::"r"((base ^ (1u << 24)) + MB_FREE) : "memory");
                    if (!OTMA) asm volatile("fence.acq_rel.gpu;" ::: "memory");
                    if (TAIL) st_relaxed_u32(g_xflag + 2 * pr + rank, FLAG_END);
                }
                __syncwarp();
            }
        }
    } else if (warp < 4) {
        asm volatile("setmaxnreg.inc.sync.aligned.u32 %0;" ::"n"(REG_A));
        code_pad<PAD_A>();
        const uint32_t l16 = lane16();
        uint32_t wa[2][24][4];
        {
            const uint32_t L = l16, fa = sb + FRAG();
            mbar_wait_w(sb + MB_W1, 0);
            KT_MARK(7);
#pragma unroll
            for (int t = 0; t < 2; t++) {
#pragma unroll
                for (int r = 0; r < 24; r++) ldsm4t(wa[t][r], fa + stg_qk(t, r));
                if (t == 0) { bar_arrive(BAR_XT0, 160); mbar_wait_w(sb + MB_W4, 0); }
            }
            mbar_wait_w(sb + MB_W2, 0);
            bar_sync(BAR_PDONE, 384);
        }
        auto batch1 = [&](float (&d)[16], uint32_t lo, auto tc, auto k0c, auto k1c) {
            constexpr int t = decltype(tc)::value;
            const uint64_t da = make_desc(SB0 + SM_WQK, 16, 1024);
            wg_fence();
            static_for<decltype(k0c)::value, decltype(k1c)::value>([&](auto kc) {
                constexpr int i = decltype(kc)::value, k = kstep(t ? ORD1 : ORD0, i), off = (k >> 2) * 256 + (k & 3) * 2;
                if constexpr (k >= 24) wgmma_ss32u<off, i != 0 || t != 0>(d, da + ((k - 24) * 2 + t) * 128, lo);
                else wgmma_rs32u<off, i != 0 || t != 0>(d, wa[t][k], lo);
            });
            wg_commit();
        };
        const uint32_t xbox = mlo + WIN + page_off(pair & 31, cls ^ XFLIP);
        const uint32_t ybox = mlo + page_off(24 + 2 * g + 32 * nh, kh ^ YFLIP_()) + h * 128;
#pragma unroll 1
        for (uint32_t it = 0; it < NSEG + LEAD; it++) {
            const int s = (int)it - LEAD;
            const uint32_t ui = uniform(it), slot = ((ui + 4 - LEAD) & 3) << 14, kvo = ((LEAD & 1 ? ~ui : ui) & 1) * KV_BYTES, xtlo = XTLO();
            {
                PHASE(5);
                const uint32_t first = L | (g << 9);
                if (s >= 0) mbar_expect_tx_if0(first, sb + MB_R1, 2048);
                if (s + LEAD < NSEG) {
                    mbar_expect_tx_if0(first, sb + MB_RT0, 8192);
                    mbar_wait_w(sb + MB_XT + (ui & 1) * 8, (it >> 1) & 1);
                }
            }
            if (s >= 0) {
                PHASE(0);
                const uint32_t mb = L + (sb + SM_Z), ra = L + (sb + g * 512), r1 = L + (rsb + SM_R1 + g * 512), r1b = rsb + MB_R1;
                sched_fence(r1);
                bar_sync(BAR_MEM, 384);
                TLB(0);
                float acc[2][2][4];
#pragma unroll
                for (int t = 0; t < 4; t++) { acc[t >> 1][t & 1][0] = acc[t >> 1][t & 1][1] = acc[t >> 1][t & 1][2] = acc[t >> 1][t & 1][3] = 0.f; }
                uint32_t b[4][4];
                uint4 u0, u1;
#pragma unroll
                for (int p = 0; p < 4; p++) ldsm4t(b[p], mb + p * 512);
#pragma unroll
                for (int p = 0; p < 12; p++) {
#pragma unroll
                    for (int u = 0; u < 2; u++) {
                        mma16816v(acc[0][u], wa[0][2 * p + u], b[p & 3][2 * u], b[p & 3][2 * u + 1]);
                        mma16816v(acc[1][u], wa[1][2 * p + u], b[p & 3][2 * u], b[p & 3][2 * u + 1]);
                    }
                    if (p + 4 < 12) ldsm4t(b[p & 3], mb + (p + 4) * 512);
                    if (AF >> p & 1) sched_fence(L);
                    if (p == Q3_AT) {
                        bar_sync(BAR_Q3, 256);
                        u0 = lds128(ra + SM_R3); u1 = lds128(ra + SM_O);
                    }
                }
                st_async4(r1, (acc[0][0][0] + __uint_as_float(u0.x)) + acc[0][1][0], (acc[0][0][1] + __uint_as_float(u0.y)) + acc[0][1][1],
                          (acc[0][0][2] + __uint_as_float(u0.z)) + acc[0][1][2], (acc[0][0][3] + __uint_as_float(u0.w)) + acc[0][1][3], r1b);
                TL(1);
                const float o0 = (acc[1][0][0] + __uint_as_float(u1.x)) + acc[1][1][0], o1 = (acc[1][0][1] + __uint_as_float(u1.y)) + acc[1][1][1];
                const float o2 = (acc[1][0][2] + __uint_as_float(u1.z)) + acc[1][1][2], o3 = (acc[1][0][3] + __uint_as_float(u1.w)) + acc[1][1][3];
                const uint32_t l4 = L >> 2, qo = SM_QKV + kh * 2048 + nh * 1024 + g * 256, qr = l4 + (rsb + qo), ql = l4 + (sb + qo), pb = rsb + MB_P;
                char* xd = make_ptr(l4 + (xbox + kh * 1024 + g * 256 + slot), mhi);
                asm volatile("" ::"l"(xd), "r"(qr), "r"(pb), "r"(qr + 128), "f"(o0), "f"(o1), "f"(o2), "f"(o3));
                mbar_wait_w(sb + MB_R1, s & 1);
                const uint4 v = lds128(ra + SM_R1);
                const uint32_t w0 = pack_bf16(o0 + __uint_as_float(v.x), o1 + __uint_as_float(v.y)), w1 = pack_bf16(o2 + __uint_as_float(v.z), o3 + __uint_as_float(v.w));
                st_relaxed_u32(xd, w0);
                st_relaxed_u32(xd + 128, w1);
                bar_arrive(BAR_PUB, 192);
                st_async1(qr, w0, pb);
                st_async1(qr + 128, w1, pb);
                sts32(ql, w0);
                sts32(ql + 128, w1);
                __syncwarp();
                mbar_expect_tx_if0(L, sb + MB_P, 256);
                TL(2);
                if (s + LEAD < NSEG) bar_sync(BAR_VP, 256);
            } else if (!PRO_LATE) {
                bar_sync(BAR_PRO, 288);
            }
            if (s + LEAD < NSEG) {
                float d[16];
                batch1(d, xtlo, std::integral_constant<int, 0>(), std::integral_constant<int, 0>(), std::integral_constant<int, 32>());
                PHASE(1);
                const uint32_t rt = L + (rsb + SM_RT + g * 2048);
                wg_wait<0>();
                TL(7);
                if (s >= 0) {
                    const uint32_t pk = L + (sb + SM_Z + g * 2048);
#pragma unroll
                    for (int i = 0; i < 4; i++) sts128(pk + i * 512, make_uint4(__float_as_uint(d[4 * i]), __float_as_uint(d[4 * i + 1]), __float_as_uint(d[4 * i + 2]), __float_as_uint(d[4 * i + 3])));
                    if (RTF) asm volatile("fence.proxy.async.shared::cta;" ::: "memory");
                    if (RTW) {
                        __syncwarp();
                        asm volatile("{.reg .pred p; setp.eq.u32 p, %3, 0; @p cp.async.bulk.shared::cluster.shared::cta.mbarrier::complete_tx::bytes [%0], [%1], 2048, [%2];}"
                                     ::"r"(rsb + SM_RT + g * 2048), "r"(sb + SM_Z + g * 2048), "r"(rsb + MB_RT0), "r"(L) : "memory");
                    }
                } else {
                    if (PRO_LATE) bar_sync(BAR_PRO, 288);
#pragma unroll
                    for (int i = 0; i < 4; i++) st_async4(rt + i * 512, d[4 * i], d[4 * i + 1], d[4 * i + 2], d[4 * i + 3], rsb + MB_RT0);
                }
            }
            if (s + 1 == NSEG) { bar_arrive(BAR_SV, NSV); break; }
            if (s >= 0) {
                PHASE(2);
                const uint32_t fo = FRAG() + (sb + SM_WO2 + 16384), lo = L + (sb + SM_O), yo = (L >> 2) + (ybox + slot);
                uint32_t a1[8][4];
                bar_sync(BAR_SV, NSV);
                if (TS_AT == 13) TLB(21);
#pragma unroll
                for (int k = 0; k < 8; k++) ldsm4t(a1[k], fo + k * 2048);
                sched_fence(yo);
                bar_sync(BAR_O2, 256);
                TLB(14);
                float y0[4] = {0.f, 0.f, 0.f, 0.f}, y1[4] = {0.f, 0.f, 0.f, 0.f};
                uint32_t b[2][4];
                ldsm4t(b[0], lo); ldsm4t(b[1], lo + 512);
                sched_fence(L);
#pragma unroll
                for (int p = 0; p < 4; p++) {
                    mma16816v(y0, a1[2 * p], b[p & 1][0], b[p & 1][1]);
                    mma16816v(y1, a1[2 * p + 1], b[p & 1][2], b[p & 1][3]);
                    if (p < 2) ldsm4t(b[p & 1], lo + (p + 2) * 512);
                }
                bar_sync(BAR_INV, 256);
                float i0, i1;
                asm volatile("ld.shared.v2.f32 {%0, %1}, [%2];" : "=f"(i0), "=f"(i1) : "r"(((L >> 1) & 0x18) + (sb + SM_INV + g * 32)) : "memory");
                st_relaxed_u32(make_ptr(yo, mhi), pack_bf16((y0[0] + y1[0]) * i0, (y0[1] + y1[1]) * i1));
                st_relaxed_u32(make_ptr(yo ^ 4096, mhi) + 0x2000, pack_bf16((y0[2] + y1[2]) * i0, (y0[3] + y1[3]) * i1));
                bar_arrive(BAR_SENTC, 384);
                TL(6);
            }
            if (s + LEAD < NSEG) {
                PHASE(4);
                float d[16];
                const uint32_t rt = L + (sb + SM_RT + g * 2048);
                if (s >= 0) bar_sync(BAR_SENT, 256);
                if (TS_AT == 12) TLB(21);
                mbar_wait_w(sb + MB_RT0, it & 1);
                if (TS_AT == 11) TL(21);
                if (s >= 0) bar_arrive(BAR_Y, 256);
                if (RT0_B && s >= 0) bar_arrive(BAR_VP, 256);
#pragma unroll
                for (int i = 0; i < 4; i++) {
                    const uint4 v = lds128(rt + i * 512);
                    d[4 * i] = __uint_as_float(v.x); d[4 * i + 1] = __uint_as_float(v.y); d[4 * i + 2] = __uint_as_float(v.z); d[4 * i + 3] = __uint_as_float(v.w);
                }
                if (SPLIT > 0) batch1(d, xtlo, std::integral_constant<int, 1>(), std::integral_constant<int, 0>(), std::integral_constant<int, SPLIT>());
                if (s >= 0) bar_sync(BAR_ZP, 256);
                TLB(30);
                batch1(d, xtlo, std::integral_constant<int, 1>(), std::integral_constant<int, SPLIT>(), std::integral_constant<int, 32>());
                const uint32_t so = (kh ? FRAG() : ((L & 0x100) << 2) + (L & 0xF0) + g * 256) + (sb + SM_STG);
                wg_wait<0>();
                TL(8);
                uint32_t w[8];
#pragma unroll
                for (int i = 0; i < 8; i++) w[i] = pack_bf16(d[2 * i], d[2 * i + 1]);
                if (kh) {
                    stsm4t(so, w[0], w[1], w[2], w[3]);
                    stsm4t(so + 2048, w[4], w[5], w[6], w[7]);
                } else {
                    stsm4(so, w[0], w[1], w[2], w[3]);
                    stsm4(so + 2048, w[4], w[5], w[6], w[7]);
                }
                __syncwarp();
                mbar_arrive_if0(L, sb + MB_STG);
                TL(9);
            } else {
                bar_arrive(BAR_SENT, 256);
                bar_arrive(BAR_Y, 256);
                if (OTMA) mbar_arrive_if0(l16, sb + MB_STG);
            }
        }
        if (TAIL && (TM & 1) && COLD()) last_tile(0);
    } else {
        asm volatile("setmaxnreg.inc.sync.aligned.u32 %0;" ::"n"(REG_B));
        code_pad<PAD_B>();
        const uint32_t l16 = lane16();
        uint32_t wv[24][4], wo[8 + WO_RF1][4];
        {
            const uint32_t L = l16, fa = sb + FRAG();
            mbar_wait_w(sb + MB_W0, 0);
            KT_MARK(6);
#pragma unroll
            for (int r = 0; r < 24; r++) ldsm4t(wv[r], fa + STG_V + r * 2048);
#pragma unroll
            for (int r = 0; r < 8 + WO_RF1; r++) asm volatile("" : "=r"(wo[r][0]), "=r"(wo[r][1]), "=r"(wo[r][2]), "=r"(wo[r][3]));
            mbar_wait_w(sb + MB_W2, 0);
            bar_sync(BAR_PDONE, 384);
        }
        const uint32_t xbox = mlo + WIN + page_off(pair & 31, cls ^ XFLIP);
        const uint32_t ybox = mlo + page_off(2 * g + 32 * nh, kh ^ YFLIP_()) + h * 128;
#pragma unroll 1
        for (uint32_t it = 0; it < NSEG + LEAD; it++) {
            const int s = (int)it - LEAD;
            const uint32_t ui = uniform(it), slot = ((ui + 4 - LEAD) & 3) << 14, kvo = ((LEAD & 1 ? ~ui : ui) & 1) * KV_BYTES, xtlo = XTLO();
            {
                PHASE(5);
                const uint32_t first = L | (g << 9);
                if (s >= 0) mbar_expect_tx_if0(first, sb + MB_R2, 1024);
                if (s + LEAD < NSEG) {
                    mbar_expect_tx_if0(first, sb + MB_RT1, 2048);
                    mbar_wait_w(sb + MB_XT + (ui & 1) * 8, (it >> 1) & 1);
                }
            }
            if (s >= 0) {
                PHASE(0);
                uint32_t fr = FRAG();
                asm("" : "+r"(fr));
                const uint32_t fo = fr + sb, l4 = L >> 2;
                {
                    const uint32_t mb = L + (sb + SM_Z), aw = fo + SM_WQK, ra = L + (sb + g * 512), r2 = (L >> 1) + (rsb + SM_R2 + g * 256), r2b = rsb + MB_R2;
                    uint32_t a[NA][4], b[4][4];
#pragma unroll
                    for (int i = 0; i < NA; i++) ldsm4t(a[i], aw + i * 2048);
                    sched_fence(L);
                    TL(24);
                    bar_sync(BAR_MEM, 384);
#pragma unroll
                    for (int p = 0; p < 4; p++) ldsm4t(b[p], mb + (12 + p) * 512);
                    sched_fence(L);
                    float c[2][4] = {{0.f, 0.f, 0.f, 0.f}, {0.f, 0.f, 0.f, 0.f}};
#pragma unroll
                    for (int i = 0; i < 16; i++) {
                        mma16816v(c[i & 1], a[i % NA], b[i >> 2][i & 2], b[i >> 2][(i & 2) + 1]);
                        ldsm4t(a[i % NA], aw + (i + NA) * 2048);
                        if (QF >> i & 1) sched_fence(L);
                    }
                    sts128(ra + SM_R3, make_uint4(__float_as_uint(c[0][0]), __float_as_uint(c[0][1]), __float_as_uint(c[0][2]), __float_as_uint(c[0][3])));
                    sts128(ra + SM_O, make_uint4(__float_as_uint(c[1][0]), __float_as_uint(c[1][1]), __float_as_uint(c[1][2]), __float_as_uint(c[1][3])));
                    bar_arrive(BAR_Q3, 256);
                    if (QF >> 16 & 1) sched_fence(L);
                    TL(29);
                    float acc[4][4];
#pragma unroll
                    for (int t = 0; t < 4; t++) { acc[t][0] = acc[t][1] = acc[t][2] = acc[t][3] = 0.f; }
#pragma unroll
                    for (int i = 16; i < 24; i++) {
                        mma16816v(acc[i & 1], a[i % NA], b[(i - 16) >> 1][2 * (i & 1)], b[(i - 16) >> 1][2 * (i & 1) + 1]);
                        if (i + NA < 24) ldsm4t(a[i % NA], aw + (i + NA) * 2048);
                        else ldsm4t(a[i % NA], mb + (i + NA - 24) * 512);
                    }
#pragma unroll
                    for (int p = 0; p < 12; p++) {
                        mma16816v(acc[(2 * p) & 3], wv[2 * p], a[(24 + p) % NA][0], a[(24 + p) % NA][1]);
                        mma16816v(acc[(2 * p + 1) & 3], wv[2 * p + 1], a[(24 + p) % NA][2], a[(24 + p) % NA][3]);
                        if (p + NA < 12) ldsm4t(a[(24 + p) % NA], mb + (p + NA) * 512);
                    }
                    if (s + LEAD < NSEG) bar_arrive(BAR_VP, 256);
                    float o[4];
#pragma unroll
                    for (int i = 0; i < 4; i++) o[i] = (acc[0][i] + acc[1][i]) + (acc[2][i] + acc[3][i]);
                    st_async2(r2, kh ? o[0] : o[2], kh ? o[1] : o[3], r2b);
                    TL(10);
                    const float o0 = kh ? o[2] : o[0], o1 = kh ? o[3] : o[1];
                    const uint32_t qo = SM_QKV + 4096 + nh * 1024 + (2 * g + kh) * 128, qr = l4 + (rsb + qo), ql = l4 + (sb + qo), vb = rsb + MB_V, rl = (L >> 1) + (sb + SM_R2 + g * 256);
                    char* xd = make_ptr(l4 + (xbox + 2048 + (2 * g + kh) * 128 + slot), mhi);
                    asm volatile("" ::"l"(xd), "r"(qr), "r"(vb), "f"(o0), "f"(o1));
                    mbar_wait_w(sb + MB_R2, s & 1);
                    uint32_t vx, vy;
                    asm volatile("ld.shared.v2.u32 {%0,%1}, [%2];" : "=r"(vx), "=r"(vy) : "r"(rl) : "memory");
                    const uint32_t w0 = pack_bf16(o0 + __uint_as_float(vx), o1 + __uint_as_float(vy));
                    st_relaxed_u32(xd, w0);
                    bar_arrive(BAR_PUBV, 160);
                    st_async1(qr, w0, vb);
                    sts32(ql, w0);
                    __syncwarp();
                    mbar_expect_tx_if0(L, sb + MB_V, 128);
                    TL(11);
                }
                const uint32_t vma = L + (sb + SM_QKV + 4096 + g * 512), yo = l4 + (ybox + slot);
                uint32_t va[2][2][4];
                {
                    const uint32_t qa = QFRAG(), vf = fr ^ ((g << 5) ^ ((g & 1) << 6)), va0 = vf + VBASE(), va1 = (vf ^ 32) + VBASE();
                    const uint32_t kf = ((L << 3) & 0x380) | ((L ^ (L >> 3)) & 0x30) | (L & 0x40), kb0 = sb + SM_KV + kvo + g * 1024;
                    const int d = (int)(L >> 6) - (int)((L >> 3) & 6) + 8 * (j - (int)g);
                    const uint32_t keep = (d < 0 ? 0u : 0xFFFFu) | (d < 1 ? 0u : 0xFFFF0000u), sa = l4 + (sb + SM_S + g * 128);
                    const uint32_t q0 = qa + (sb + nh * 1024), q1 = qa + (sb + (nh ^ 1) * 1024);
                    float sc[4] = {0.f, 0.f, 0.f, 0.f}, sd[4] = {0.f, 0.f, 0.f, 0.f};
                    uint32_t a[4][4], kb[2][4];
                    mbar_wait_w(sb + MB_KV + ((LEAD & 1 ? ~ui : ui) & 1) * 8, (s >> 1) & 1);
                    ldsm4(kb[0], kf + (kb0 + nh * 4096)); ldsm4(kb[1], (kf ^ 64) + (kb0 + nh * 4096));
                    mbar_wait_w(sb + MB_P, s & 1);
                    TL(12);
#pragma unroll
                    for (int k = 0; k < 4; k++) ldsm4t(a[k], q0 + k * 256);
#pragma unroll
                    for (int k = 0; k < 4; k++) mma16816v((k & 1) ? sd : sc, a[k], kb[k >> 1][2 * (k & 1)], kb[k >> 1][2 * (k & 1) + 1]);
                    ldsm4(kb[0], kf + (kb0 + (nh ^ 1) * 4096)); ldsm4(kb[1], (kf ^ 64) + (kb0 + (nh ^ 1) * 4096));
                    sched_fence(vf | yo);
                    if (TS_AT == 8) TL(21);
                    bar_sync(BAR_QK, 224);
                    TLB(3);
#pragma unroll
                    for (int k = 0; k < 4; k++) ldsm4t(a[k], q1 + k * 256);
                    sched_fence(L);
#pragma unroll
                    for (int k = 0; k < 4; k++) mma16816v((k & 1) ? sd : sc, a[k], kb[k >> 1][2 * (k & 1)], kb[k >> 1][2 * (k & 1) + 1]);
                    ldsm4t(va[0][0], va0); ldsm4t(va[0][1], va0 + 2048);
                    sts32(sa, scale_scores(sc[0] + sd[0], sc[1] + sd[1]));
                    sts32(sa + 768, (scale_scores(sc[2] + sd[2], sc[3] + sd[3]) & keep) | (0xFF80FF80u & ~keep));
                    bar_arrive(BAR_SV, NSV);
                    ldsm4t(va[1][0], va1); ldsm4t(va[1][1], va1 + 2048);
                }
                bar_sync(BAR_S, 160);
                TLB(4);
                uint32_t pw[6], vm[4];
                if (s + 1 < NSEG) {
                softmax40(pw, l4 + (sb + SM_S), [&]() {
                    bar_sync(BAR_V, 160);
                    ldsm4(vm, vma);
                });
                uint32_t a1[NP2][4];
                float inv[2];
                {
                    uint32_t w[4];
                    pv32<false>(w, inv, va, vm, pw, [&]() {
                        sched_fence(L);
#pragma unroll
                        for (int k = 0; k < NP2; k++) ldsm4t(a1[k], fo + SM_WO2 + k * 2048);
                    });
#pragma unroll
                    for (int i = 0; i < 4; i++) sts32(l4 + (sb + SM_O + g * 512) + i * 128, w[i]);
                }
                const uint32_t lo = L + (sb + SM_O);
                bar_arrive(BAR_O2, 256);
                bar_sync(BAR_O, 128);
                TLB(5);
                {
                    float y0[4] = {0.f, 0.f, 0.f, 0.f}, y1[4] = {0.f, 0.f, 0.f, 0.f}, y2[4] = {0.f, 0.f, 0.f, 0.f};
                    uint32_t b[4][4];
#pragma unroll
                    for (int p = 0; p < 4; p++) ldsm4t(b[p], lo + p * 512);
                    inv[0] = rcp_approx(inv[0]); inv[1] = rcp_approx(inv[1]);
                    asm volatile("st.shared.v2.f32 [%0], {%1, %2};" ::"r"(((L >> 1) & 0x18) + (sb + SM_INV + g * 32)), "f"(inv[0]), "f"(inv[1]) : "memory");
                    bar_arrive(BAR_INV, 256);
                    sched_fence(L);
#pragma unroll
                    for (int k = 0; k < 8; k++) {
                        const int p = k >> 1, u = k & 1;
                        mma16816v(y2, a1[k % NP2], b[p][2 * u], b[p][2 * u + 1]);
                        if (k + NP2 < 8) ldsm4t(a1[k % NP2], fo + SM_WO2 + (k + NP2) * 2048);
                        else if (k + NP2 < 16 - WO_RF1) ldsm4t(a1[k % NP2], fo + SM_WO1 + (k + NP2 - 8 + WO_RF1) * 2048);
                        mma16816v(y0, wo[k], b[p][2 * u], b[p][2 * u + 1]);
                        if (k < WO_RF1) mma16816v(y1, wo[8 + (k < WO_RF1 ? k : 0)], b[p][2 * u], b[p][2 * u + 1]);
                        else mma16816v(y1, a1[(k + 8 - WO_RF1) % NP2], b[p][2 * u], b[p][2 * u + 1]);
                        if (k < P2_FENCE) sched_fence(L);
                    }
                    char* yd = make_ptr(yo, mhi);
                    char* yd1 = make_ptr(yo ^ 4096, mhi);
                    st_relaxed_u32(yd1 + 0x80000, pack_bf16(y2[0] * inv[0], y2[1] * inv[1]));
                    st_relaxed_u32(yd + 0x82000, pack_bf16(y2[2] * inv[0], y2[3] * inv[1]));
                    st_relaxed_u32(yd, pack_bf16(y0[0] * inv[0], y0[1] * inv[1]));
                    st_relaxed_u32(yd1 + 0x2000, pack_bf16(y0[2] * inv[0], y0[3] * inv[1]));
                    st_relaxed_u32(yd + 0x40000, pack_bf16(y1[0] * inv[0], y1[1] * inv[1]));
                    st_relaxed_u32(yd1 + 0x42000, pack_bf16(y1[2] * inv[0], y1[3] * inv[1]));
                }
                bar_arrive(BAR_SENTC, 384);
                TL(13);
                bar_sync(BAR_SENT, 256);
                } else {
                    bar_sync(BAR_V, 160);
                }
            } else {
                if (it == WO_IT) {
                    PHASE(2);
                    const uint32_t fa = sb + FRAG();
                    mbar_wait_w(sb + MB_W3, 0);
                    KT_MARK(8);
#pragma unroll
                    for (int r = 0; r < 8 + WO_RF1; r++) ldsm4t(wo[r], fa + stg_wo(r));
                }
                bar_sync(BAR_PRO, 288);
            }
            float o[8];
            uint32_t w[4];
            {
                PHASE(1);
                float d[16];
                const uint64_t da = make_desc(SB0 + SM_WV, 16, 1024);
                auto batch = [&](auto k0c, auto k1c) {
                    static_for<decltype(k0c)::value, decltype(k1c)::value>([&](auto kc) {
                        constexpr int i = decltype(kc)::value, k = kstep(ORDV, i), off = (k >> 2) * 256 + (k & 3) * 2;
                        if constexpr (k >= 24) wgmma_ss32u<off, i != 0>(d, da + (k - 24) * 128, xtlo);
                        else wgmma_rs32u<off, i != 0>(d, wv[k], xtlo);
                    });
                };
                const uint32_t vf = VFRAG(), va0 = vf + VBASE(), va1 = (vf ^ 32) + VBASE(), vma = L + (sb + SM_QKV + 4096 + g * 512), sa = (L >> 2) + (sb + SM_S + 768);
                const uint32_t rt = L + (rsb + SM_RT + 8192 + g * 512);
                uint32_t va[2][2][4], vm[4], pw[6];
                wg_fence();
                batch(std::integral_constant<int, 0>(), std::integral_constant<int, TA0>());
                wg_commit();
                batch(std::integral_constant<int, TA0>(), std::integral_constant<int, 32>());
                wg_commit();
                wg_wait<1>();
                if (RT0_B == 3 && (unsigned)s < NSEG - LEAD) bar_sync(BAR_VP, 256);
                softmax40(pw, sa, [&]() {});
                ldsm4t(va[0][0], va0); ldsm4t(va[0][1], va0 + 2048);
                ldsm4t(va[1][0], va1); ldsm4t(va[1][1], va1 + 2048);
                ldsm4(vm, vma);
                if (RT0_B == 1 && (unsigned)s < NSEG - LEAD) bar_sync(BAR_VP, 256);
                wg_wait<0>();
                if (RT0_B == 2 && (unsigned)s < NSEG - LEAD) bar_sync(BAR_VP, 256);
                TL(27);
                float inv[2];
                pv32<true>(w, inv, va, vm, pw, [&]() {
                    uint32_t q[4];
#pragma unroll
                    for (int i = 0; i < 4; i++) q[i] = pack_bf16(kh ? d[2 * i] : d[8 + 2 * i], kh ? d[2 * i + 1] : d[9 + 2 * i]);
                    if (RT0_B == 4 && (unsigned)s < NSEG - LEAD) bar_sync(BAR_VP, 256);
                    if (s + LEAD < NSEG) st_async4(rt, __uint_as_float(q[0]), __uint_as_float(q[1]), __uint_as_float(q[2]), __uint_as_float(q[3]), rsb + MB_RT1);
#pragma unroll
                    for (int i = 0; i < 8; i++) o[i] = kh ? d[8 + i] : d[i];
                });
                TL(26);
            }
            if (s + LEAD < NSEG) {
                PHASE(3);
                const uint32_t rt = L + (sb + SM_RT + 8192 + g * 512), so = FRAG() + (sb + SM_STG + 4096);
                mbar_wait_w(sb + MB_RT1, it & 1);
                TL(28);
                const uint4 v = lds128(rt);
                stsm4t(so, pack_bf16(o[0] + bf_lo(v.x), o[1] + bf_hi(v.x)), pack_bf16(o[2] + bf_lo(v.y), o[3] + bf_hi(v.y)),
                       pack_bf16(o[4] + bf_lo(v.z), o[5] + bf_hi(v.z)), pack_bf16(o[6] + bf_lo(v.w), o[7] + bf_hi(v.w)));
                if (!OTMA) { __syncwarp(); mbar_arrive_if0(L, sb + MB_STG); }
                TL(15);
            }
            if (OTMA) {
                PHASE(7);
                __syncwarp();
                stsm4t((((L << 2) & 0x1C0) | (((L >> 3) ^ (L >> 1)) & 0x30)) + (sb + SM_OT + g * 512), w[0], w[1], w[2], w[3]);
                __syncwarp();
                mbar_arrive_if0(L, sb + MB_STG);
            }
        }
        if ((OTMA || TAIL) && (TM & 2) && COLD()) bar_arrive(BAR_ZP, 160);
        if (TAIL && (TM & 2) && COLD()) last_tile(1);
    }
    KT_END(TAIL ? 3 : 2);
    asm volatile("barrier.cluster.arrive.relaxed; barrier.cluster.wait;" ::: "memory");
}
constexpr int B_UCH = 73 * 64;
constexpr int B_SCH = 33 * 64;
constexpr int B_KLEN = 2128;
constexpr int B_KCH = 2 * B_KLEN * 2 + 64;
constexpr int B_KBOX = 136 * 32;
constexpr int B_SM_U = 0;
constexpr int B_SM_S = 8 * B_UCH;
constexpr int B_SM_K = B_SM_S + 8 * B_SCH;
constexpr int B_SM_KT = B_SM_K + 8 * B_KCH;
constexpr int B_SM_VT = B_SM_KT + 8 * B_KBOX;
constexpr int B_SM_QT = B_SM_VT + 32768;
constexpr int B_SM_BAR = B_SM_QT + 32768;
constexpr int B_SMEM = B_SM_BAR + 128 + 512;
static_assert(B_SM_KT % 256 == 0 && B_SM_S % 512 == 0 && B_SMEM <= 232448, "tiles");
constexpr int PROBE_N = 4;
#define PROBE_R 2
constexpr int B_C = 2056;

__device__ __forceinline__ uint32_t atomic_round_trip(char* p) {
    uint32_t t0, t1, v;
    asm volatile("{.reg .pred p;\n"
                 "mov.u32 %0, %%clock;\n"
                 "atom.relaxed.gpu.global.add.u32 %2, [%3], 1;\n"
                 "setp.ne.u32 p, %2, 0x7FFFFFFF;\n"
                 "mov.u32 %1, 0;\n"
                 "@p mov.u32 %1, %%clock;}" : "=&r"(t0), "=&r"(t1), "=&r"(v) : "l"(p) : "memory");
    return t1 - t0;
}
__device__ __forceinline__ uint32_t round_trips(char* a, char* b, uint32_t stride, int lane) {
    for (int i = lane >> 3; i < 2 * PROBE_N; i += 4) stg128(((i & 1) ? b : a) + (i >> 1) * stride + (lane & 7) * 16, make_uint4(0, 0, 0, 0));
    __syncwarp();
    uint32_t ta = 0xFFFF, tb = 0xFFFF;
    if (lane == 0) {
        __threadfence();
#pragma unroll 1
        for (int i = 0; i < PROBE_N; i++) { ta = min(ta, atomic_round_trip(a + i * stride)); tb = min(tb, atomic_round_trip(b + i * stride)); }
    }
    __syncwarp();
    return ta | (tb << 16);
}
__device__ __forceinline__ void measure_distance(char* mbox, int lane) {
    const uint32_t b = blockIdx.x;
    unsigned smid;
    asm volatile("mov.u32 %0, %%smid;" : "=r"(smid));
    char* w1 = mbox + WIN + (b & 31) * 128;
    uint32_t r = 0xFFFFFFFF;
#pragma unroll 1
    for (int i = 0; i < PROBE_R; i++) r = __vminu2(r, round_trips(w1 + page_off(50 + 5 * i + (b >> 5), 0), w1 + page_off(50 + 5 * i + (b >> 5), 1), 16384, lane));
    if (lane == 0) g_cls[smid] = r;
    if (b == 128) {
        char *p = mbox + page_off(0, 0), *q = mbox + page_off(0, 1);
        uint32_t r0 = 0xFFFFFFFF;
#pragma unroll 1
        for (int i = 0; i < PROBE_R; i++) r0 = __vminu2(r0, round_trips(p, q, 128, lane));
        if (lane == 0) { g_reg[1] = ((r0 & 0xFFFF) > (r0 >> 16)) != ((r & 0xFFFF) > (r >> 16)); if (!EARLY_ROLE) g_reg[0] = 0; g_reg[2] = 0; }
        const uint4 sent = make_uint4(SENT, SENT, SENT, SENT);
        stg128(p + lane * 16, sent); stg128(q + lane * 16, sent);
    }
    if (b == 129) for (int i = lane; i < 128; i += 32) g_xflag[i] = 0;
}

#define SP(i)
#define SP2(i)
#define OUT_STG 0
#define PF_STOP 1
#define SENT_AT 3
#define Q_LATE 1
#define PF_DEPTH 4
#define PF_STRIDE 256
struct ChainInputs { const char* w[4]; const char *x, *mem0; };
#define EF_MASK 15
#define EF(i) (((EF_MASK >> (i)) & 1) ? policy_evict_first() : policy_evict_normal())
__device__ __forceinline__ void l2_prefetch(const char* p, uint32_t bytes) {
    asm volatile("cp.async.bulk.prefetch.L2.global [%0], %1;" ::"l"(p), "r"(bytes) : "memory");
}
#define WG_CONV(N, LIST, A0, A1, A2, A3, LO, OF, ...) \
    if constexpr (NN == N) asm volatile("{.reg .b32 l; .reg .b64 e; add.u32 l, %" #LO ", %" #OF "; mov.b64 e, {l, 0x80000020};\n" \
        "wgmma.mma_async.sync.aligned.m64n" #N "k16.f32.bf16.bf16 {" LIST "}, {%" #A0 ",%" #A1 ",%" #A2 ",%" #A3 "}, e, 1, 1, 1, 0;}" \
        : __VA_ARGS__ : "r"(a[0]), "r"(a[1]), "r"(a[2]), "r"(a[3]), "r"(lo), "n"(OFF));
#define WL4 "%0,%1,%2,%3"
#define WL8 WL4 ",%4,%5,%6,%7"
#define WL12 WL8 ",%8,%9,%10,%11"
#define WL16 WL12 ",%12,%13,%14,%15"
#define WL20 WL16 ",%16,%17,%18,%19"
#define WL24 WL20 ",%20,%21,%22,%23"
#define WL28 WL24 ",%24,%25,%26,%27"
#define WL32 WL28 ",%28,%29,%30,%31"
template <int NN, int OFF> __device__ __forceinline__ void wgmma_conv(float (&d)[32], const uint32_t (&a)[4], uint32_t lo) {
    WG_CONV(8, WL4, 4, 5, 6, 7, 8, 9, R4(0))
    WG_CONV(16, WL8, 8, 9, 10, 11, 12, 13, R4(0), R4(4))
    WG_CONV(24, WL12, 12, 13, 14, 15, 16, 17, R4(0), R4(4), R4(8))
    WG_CONV(32, WL16, 16, 17, 18, 19, 20, 21, R16(0))
    WG_CONV(40, WL20, 20, 21, 22, 23, 24, 25, R16(0), R4(16))
    WG_CONV(48, WL24, 24, 25, 26, 27, 28, 29, R16(0), R4(16), R4(20))
    WG_CONV(56, WL28, 28, 29, 30, 31, 32, 33, R16(0), R4(16), R4(20), R4(24))
    WG_CONV(64, WL32, 32, 33, 34, 35, 36, 37, R16(0), R16(16))
}
__device__ __forceinline__ void copy_to_peer(uint32_t dst, uint32_t src, uint32_t bytes, uint32_t bar) {
    asm volatile("cp.async.bulk.shared::cluster.shared::cta.mbarrier::complete_tx::bytes [%0], [%1], %2, [%3];" ::"r"(dst), "r"(src), "r"(bytes), "r"(bar) : "memory");
}
__device__ __forceinline__ uint32_t lds_volatile(uint32_t a) {
    uint32_t v;
    asm volatile("ld.volatile.shared.u32 %0, [%1];" : "=r"(v) : "r"(a) : "memory");
    return v;
}
__device__ __forceinline__ uint32_t swz64(uint32_t a) { return a ^ ((a >> 3) & 0x30); }
__device__ __forceinline__ void fence_async() { asm volatile("fence.proxy.async.shared::cta;" ::: "memory"); }

__global__ void __cluster_dims__(2, 1, 1) __launch_bounds__(576, 1)
ssm_kernel(const __grid_constant__ CUtensorMap mapK, const __grid_constant__ CUtensorMap mapV, const __grid_constant__ CUtensorMap mapQ,
           const __grid_constant__ CUtensorMap mapO, const bf16* __restrict__ shiftk, const bf16* __restrict__ ssmk, const bf16* __restrict__ Dv,
           char* __restrict__ mbox, const __grid_constant__ ChainInputs ci, bf16* __restrict__ outp) {
    extern __shared__ __align__(128) uint8_t smem_raw[];
    const uint32_t sb = (smem_u32(smem_raw) + 511) & ~511u;
    const int rank = blockIdx.x & 1, ch0 = blockIdx.x * 8, c16 = ch0 & ~15, t0 = rank * 1024;
    const int t = threadIdx.x, warp = t >> 5, lane = t & 31;
    const uint32_t bar = sb + B_SM_BAR, barQ = bar + 64, barU = bar + 72, barY = bar + 80, flag = bar + 88;
    SP(0);
    if (lane == 0 && warp < 16 && blockIdx.x < 128) {
        const int i = warp >> 1;
        if (warp & 1) {
            if (i < 3) { mbar_init(barQ + i * 8, 1); mbar_expect_tx(barQ + i * 8, i ? 16384 : 32768); }
            if (i == 3) sts32(flag, 0);
        } else {
            mbar_init(bar + i * 8, 1);
            asm volatile("fence.mbarrier_init.release.cluster;" ::: "memory");
            mbar_expect_tx(bar + i * 8, B_KBOX + 4096);
            tma_load_2d(sb + B_SM_KT + i * B_KBOX, &mapK, c16, t0 + i * 128 - 8, bar + i * 8, EF(0));
            tma_load_2d(sb + B_SM_VT + i * 4096, &mapV, c16, t0 + i * 128, bar + i * 8, EF(0));
        }
        asm volatile("fence.mbarrier_init.release.cluster;" ::: "memory");
    }
    __syncwarp();
    if (warp == 14) SP2(14);
    KT_START(1);
    if (warp == 17) {
        launch_dependents();
        asm volatile("barrier.cluster.arrive.relaxed.aligned;" ::: "memory");
        measure_distance(mbox, lane);
        asm volatile("barrier.cluster.wait.aligned;" ::: "memory");
        KT_MARK(14);
        return;
    }
    if (blockIdx.x >= 128) return;
    if (warp == 16) {
        asm volatile("barrier.cluster.arrive.relaxed.aligned; barrier.cluster.wait.aligned;" ::: "memory");
        SP2(8);
        if (Q_LATE) for (int i = 0; i < 8; i++) { mbar_wait_w(bar + i * 8, 0); SP2(i); }
        if (lane < 8) tma_load_2d(sb + B_SM_QT + lane * 4096, &mapQ, c16, t0 + lane * 128, barQ, EF(3));
        if (!Q_LATE) for (int i = 0; i < 8; i++) mbar_wait_w(bar + i * 8, 0);
        if (lane == 0) {
            l2_prefetch(ci.x + blockIdx.x * 2048, 2048);
            if (blockIdx.x < 8) l2_prefetch(ci.mem0 + blockIdx.x * 2048, 2048);
        }
        uint32_t v[PF_DEPTH], acc = 0;
#pragma unroll
        for (int u = 0; u < PF_DEPTH; u++) v[u] = 0;
        constexpr int PER = 32 * PF_STRIDE, NW = 65536 / PER;
#define PF_N (4 * NW)
        int i = 0;
#pragma unroll 1
        for (; i < PF_N && lds_volatile(flag) == 0; i += PF_DEPTH) {
#pragma unroll
            for (int u = 0; u < PF_DEPTH; u++) {
                const char* a = ci.w[(i + u) / NW] + blockIdx.x * 65536 + ((i + u) % NW) * PER + lane * PF_STRIDE;
                acc |= v[u];
                asm volatile("ld.global.cg.L2::256B.u32 %0, [%1];" : "=r"(v[u]) : "l"(a) : "memory");
            }
        }
#pragma unroll
        for (int u = 0; u < PF_DEPTH; u++) acc |= v[u];
        if (acc == 0x7FFF7FFFu && v[0] == 0x7FFEu) g_err = 1;
        SP2(12);
        KT_MARK(15);
        return;
    }
    asm volatile("barrier.cluster.arrive.relaxed.aligned;" ::: "memory");
    const int far = warp & 1, unit = rank ^ far;
    uint32_t w[4];
    uint32_t d2;
    asm volatile("ld.global.nc.u32 %0, [%1];" : "=r"(d2) : "l"(Dv + ch0 + (warp >> 2) * 2));
    {
        const int ch = warp & 7, half = warp >> 3;
        const uint32_t kb = sb + B_SM_K + ch * B_KCH;
        const uint4* src = reinterpret_cast<const uint4*>(ssmk + (size_t)(ch0 + ch) * S_LEN);
        uint4 kr[4];
#pragma unroll
        for (int i = 0; i < 4; i++) kr[i] = ldg128(src + half * 128 + i * 32 + lane, EF(1));
        const uint32_t edge = half ? 0u : __ldg(reinterpret_cast<const uint32_t*>(src + 128));
        const uint2 sw = __ldg(reinterpret_cast<const uint2*>(shiftk + (size_t)(c16 + unit * 8 + (lane >> 2)) * 4));
        w[0] = __byte_perm(sw.x, 0, 0x1010); w[1] = __byte_perm(sw.x, 0, 0x3232); w[2] = __byte_perm(sw.y, 0, 0x1010); w[3] = __byte_perm(sw.y, 0, 0x3232);
        if (half) sts128(sb + B_SM_U + ch * B_UCH + 4096 + lane * 16, make_uint4(0, 0, 0, 0));
#pragma unroll
        for (int i = 0; i < 4; i++) {
            const uint4 lo = kr[i];
            const uint32_t nx = __shfl_down_sync(~0u, lo.x, 1), n0 = (i < 3) ? __shfl_sync(~0u, kr[i < 3 ? i + 1 : 3].x, 0) : edge;
            const uint32_t hix = (lane < 31) ? nx : n0;
            const int c = 256 - (half * 128 + 32 * i + lane);
            sts128(kb + c * 16, make_uint4(__byte_perm(hix, lo.w, 0x7610), __byte_perm(lo.w, lo.z, 0x7610), __byte_perm(lo.z, lo.y, 0x7610), __byte_perm(lo.y, lo.x, 0x7610)));
            sts128(kb + B_KLEN * 2 + 64 + c * 16, make_uint4(__byte_perm(lo.w, lo.w, 0x1032), __byte_perm(lo.z, lo.z, 0x1032), __byte_perm(lo.y, lo.y, 0x1032), __byte_perm(lo.x, lo.x, 0x1032)));
        }
        const uint32_t k0w = __shfl_sync(~0u, kr[0].x, 0);
        if (half == 0 && lane < 8) {
            sts128(kb + (257 + lane) * 16, make_uint4(lane == 0 ? (k0w & 0xFFFFu) : 0u, 0u, 0u, 0u));
            sts128(kb + B_KLEN * 2 + 64 + (257 + lane) * 16, make_uint4(0u, 0u, 0u, 0u));
        }
    }
    auto sentinels = [&]() {
        const uint4 sent = make_uint4(SENT, SENT, SENT, SENT);
        char* p0 = mbox + blockIdx.x * 16384 + t * 16;
        if (blockIdx.x != 0 || (t & 255) >= 32) stg128(p0, sent);
        stg128(p0 + 8192, sent);
        char* p1 = mbox + WIN + blockIdx.x * 12800 + t * 16;
        stg128(p1, sent);
        if (t < 288) stg128(p1 + 8192, sent);
    };
    if (SENT_AT == 1) sentinels();
    asm volatile("barrier.cluster.wait.acquire.aligned;" ::: "memory");
    SP(1);
    {
        const int box = warp >> 1, row0 = 63 - 32 * rank - 4 * box;
        const uint32_t kt = sb + B_SM_KT + box * B_KBOX + 256 + lane * 32, s0 = (unit ^ ((lane >> 2) & 1)) * 16;
        const uint32_t a0 = kt + s0, a2 = kt - 64 + (unit ^ (((lane + 6) >> 2) & 1)) * 16, a4 = kt - 128 + (s0 ^ 16), av = sb + B_SM_VT + box * 4096 + lane * 32 + s0;
        const uint32_t ul = (lane & 7) * B_UCH + row0 * 64 + (lane >> 3) * 16;
        const uint32_t ud = sb + (far ? B_SM_S + (lane & 7) * (B_SCH - B_UCH) - (1 - rank) * 2048 : B_SM_U);
        mbar_wait_w(bar + box * 8, 0);
        SP(2);
#pragma unroll
        for (int i = 0; i < 4; i++) {
            uint32_t k0[4], k2[4], k4[4], vv[4], o[4];
            ldsm4t(k0, a0 + i * 1024); ldsm4t(k2, a2 + i * 1024); ldsm4t(k4, a4 + i * 1024); ldsm4t(vv, av + i * 1024);
#pragma unroll
            for (int j = 0; j < 4; j++) {
                uint32_t a = bf16_mul(__byte_perm(k4[j], k2[j], 0x5432), w[3]);
                a = bf16_add(a, bf16_mul(k2[j], w[2]));
                a = bf16_add(a, bf16_mul(__byte_perm(k2[j], k0[j], 0x5432), w[1]));
                a = bf16_add(a, bf16_mul(k0[j], w[0]));
                o[j] = bf16_mul(a, vv[j]);
            }
            stsm4(ud + swz64(ul - i * 64), o[0], o[1], o[2], o[3]);
        }
        fence_async();
        __syncwarp();
        if (far && lane < 8) {
            const uint32_t o = lane * B_UCH + (row0 - 3) * 64;
            copy_to_peer(peer_addr(sb + B_SM_U + o, rank ^ 1), ud + o, 256, peer_addr(barU, rank ^ 1));
        }
    }
    bar_sync(1, 512);
    mbar_wait_w(barU, 0);
    if (SENT_AT == 2) sentinels();
    SP(3);
    const int wg = warp >> 2, wq = warp & 3, hi = wq >> 1, g = lane >> 2, tq = lane & 3;
    const uint32_t zero = lds32(sb + B_SM_U + 4096);
#pragma unroll 1
    for (int cc = 0; cc < 2; cc++) {
        const int ch = 2 * wg + cc;
        const uint32_t kb = sb + B_SM_K + ch * B_KCH, ub = sb + B_SM_U + ch * B_UCH;
        const uint32_t dw = __byte_perm(d2, 0, cc ? 0x3232 : 0x1010);
        const int e0 = B_C - g + 2 * tq;
        const uint32_t f0 = ((e0 & 1) ? (kb + B_KLEN * 2 + 64 + (e0 - 1) * 2) : (kb + e0 * 2)) - 32 * wq;
        const uint32_t lo = uniform((ub >> 4) | 0x10000);
        float d[32];
#pragma unroll
        for (int i = 0; i < 32; i++) d[i] = 0.f;
        uint32_t A[2][2][4];
        static_for<0, 32>([&](auto jc) {
            constexpr int j = decltype(jc)::value, N = 64 - 8 * (j / 4);
            if (j >= 2) wg_wait<1>();
            uint32_t(&a)[4] = A[j & 1][0];
            uint32_t(&b)[4] = A[j & 1][1];
            a[0] = lds32(f0 - 128 * j); a[1] = lds32(f0 - 128 * j - 16); a[2] = lds32(f0 - 128 * j + 16);
            b[0] = lds32(f0 - 128 * j + 32); b[2] = lds32(f0 - 128 * j + 48);
            a[3] = a[0] ^ zero; b[1] = a[2] ^ zero; b[3] = b[0] ^ zero;
            wg_fence();
            wgmma_conv<N, 8 * j>(d, a, lo);
            wgmma_conv<N, 8 * j + 2>(d, b, lo);
            wg_commit();
        });
        wg_wait<0>();
        if (cc) SP(4);
        if (PF_STOP == 1 && cc && t == 0) sts32(flag, 1);
        bar_sync(2 + wg, 128);
        if (!hi && tq == 3) { float x = d[13]; d[13] = d[29]; d[29] = x; x = d[15]; d[15] = d[31]; d[31] = x; }
        if (hi && tq == 0) { d[0] = 0.f; d[2] = 0.f; }
        {
            const uint32_t xs = kb + (wq ^ 2) * 2048 + lane * 4;
            const uint32_t xn = hi ? xs + (tq ? 124 : 140) : xs + (tq < 3 ? 4 : -12), wrap = hi ? (tq ? 0 : -1) : (tq < 3 ? 0 : 1);
#pragma unroll
            for (int nb = 0; nb < 4; nb++) {
                const uint32_t xw = xn + ((nb + wrap) & 3) * 512;
#pragma unroll
                for (int i = 0; i < 2; i++) {
                    const float e0v = hi ? d[4 * nb + 2 * i] : d[16 + 4 * nb + 2 * i], e1v = hi ? d[4 * nb + 2 * i + 1] : d[16 + 4 * nb + 2 * i + 1];
                    sts32(hi ? xw + i * 256 : xs + nb * 512 + i * 256 + 128, __float_as_uint(e0v));
                    sts32(hi ? xs + nb * 512 + i * 256 : xw + i * 256, __float_as_uint(e1v));
                }
            }
        }
        bar_sync(2 + wg, 128);
#pragma unroll
        for (int p = 0; p < 2; p++) {
            int row = 16 * p + (lane >> 4) * 8 + (lane & 7);
            row = hi ? row + 31 : row == 31 ? 63 : row;
            const uint32_t a = sb + B_SM_U + swz64(ch * B_UCH + row * 64 + ((wq & 1) * 2 + ((lane >> 3) & 1)) * 16);
            uint32_t u[4];
            ldsm4t(u, a);
#pragma unroll
            for (int b = 0; b < 4; b++) {
                const int r = 8 * p + 2 * b;
                const float y0 = (hi ? d[16 + r] : d[r]) + __uint_as_float(lds32(kb + wq * 2048 + r * 128 + lane * 4));
                const float y1 = (hi ? d[17 + r] : d[r + 1]) + __uint_as_float(lds32(kb + wq * 2048 + r * 128 + 128 + lane * 4));
                u[b] = bf16_add(pack_bf16(y0, y1), bf16_mul(u[b], dw));
            }
            stsm4t(a, u[0], u[1], u[2], u[3]);
        }
        fence_async();
        bar_sync(2 + wg, 128);
        if (SENT_AT == 3 && cc == 0) sentinels();
        if (wq == 0 && lane == 0) copy_to_peer(peer_addr(sb + B_SM_S + ch * B_SCH, rank ^ 1), ub + rank * 2048, 2048, peer_addr(barY, rank ^ 1));
    }
    if (PF_STOP == 2 && t == 0) sts32(flag, 1);
    SP(5);
    mbar_wait_w(barQ, 0);
    bar_sync(1, 512);
    mbar_wait_w(barY, 0);
    asm volatile("barrier.cluster.arrive.relaxed.aligned;" ::: "memory");
    SP(6);
#pragma unroll
    for (int i = 0; i < 4; i++) {
        const int fr = i & 1, row = 63 - 32 * rank - 2 * warp - (i >> 1);
        const uint32_t qa = sb + B_SM_QT + warp * 2048 + (i >> 1) * 1024 + lane * 32 + ((rank ^ fr ^ (lane >> 2)) & 1) * 16;
        uint32_t y[4], q[4];
        ldsm4t(y, sb + (fr ? B_SM_S + (lane & 7) * (B_SCH - B_UCH) - (1 - rank) * 2048 : B_SM_U) + swz64((lane & 7) * B_UCH + row * 64 + (lane >> 3) * 16));
        ldsm4(q, qa);
        stsm4(qa, bf16_mul(q[0], y[0]), bf16_mul(q[1], y[1]), bf16_mul(q[2], y[2]), bf16_mul(q[3], y[3]));
    }
    fence_async();
    __syncwarp();
    if (lane == 0) {
        asm volatile("cp.async.bulk.tensor.2d.global.shared::cta.bulk_group.L2::cache_hint [%0, {%2, %3}], [%1], %4;"
                     ::"l"(&mapO), "r"(sb + B_SM_QT + warp * 2048), "r"(DM + c16), "r"(t0 + warp * 64), "l"(EF(4)) : "memory");
        asm volatile("cp.async.bulk.commit_group;" ::: "memory");
    }
    if (SENT_AT == 0) sentinels();
    if (warp == 0) SP2(10);
    if (lane == 0) asm volatile("cp.async.bulk.wait_group.read 0;" ::: "memory");
    __syncwarp();
    if (warp == 0) SP2(11);
    asm volatile("barrier.cluster.wait.aligned;" ::: "memory");
    SP(7);
    KT_END(1);
}

typedef CUresult (*EncodeFn)(CUtensorMap*, CUtensorMapDataType, cuuint32_t, void*, const cuuint64_t*, const cuuint64_t*, const cuuint32_t*,
                             const cuuint32_t*, CUtensorMapInterleave, CUtensorMapSwizzle, CUtensorMapL2promotion, CUtensorMapFloatOOBfill);

static void make_map(EncodeFn fn, CUtensorMap* m, const void* ptr, uint64_t inner, uint64_t outer, uint32_t box_in, uint32_t box_out,
                     CUtensorMapL2promotion promo = CU_TENSOR_MAP_L2_PROMOTION_L2_256B) {
    cuuint64_t dims[2] = {inner, outer};
    cuuint64_t strides[1] = {inner * 2};
    cuuint32_t box[2] = {box_in, box_out};
    cuuint32_t es[2] = {1, 1};
    fn(m, CU_TENSOR_MAP_DATA_TYPE_BFLOAT16, 2, const_cast<void*>(ptr), dims, strides, box, es, CU_TENSOR_MAP_INTERLEAVE_NONE,
       CU_TENSOR_MAP_SWIZZLE_128B, promo, CU_TENSOR_MAP_FLOAT_OOB_FILL_NONE);
}

#define G2_ST 7
#define PROMO_W CU_TENSOR_MAP_L2_PROMOTION_L2_256B
#define PROMO_O CU_TENSOR_MAP_L2_PROMOTION_L2_256B
#define SSM_PROMO CU_TENSOR_MAP_L2_PROMOTION_NONE
extern "C" void kernel_launch(void* const* d_in, const int* in_sizes, int n_in, void* d_out, int out_size) {
    const bf16* x = (const bf16*)d_in[0];
    const bf16* mem0 = (const bf16*)d_in[1];
    const bf16* Wq = (const bf16*)d_in[2];
    const bf16* Wk = (const bf16*)d_in[3];
    const bf16* Wv = (const bf16*)d_in[4];
    const bf16* Wo = (const bf16*)d_in[5];
    const bf16* Bq = (const bf16*)d_in[7];
    const bf16* Bk = (const bf16*)d_in[8];
    const bf16* Bv = (const bf16*)d_in[9];
    const bf16* Bsh = (const bf16*)d_in[10];
    const bf16* Bssm = (const bf16*)d_in[11];
    const bf16* BD = (const bf16*)d_in[12];
    bf16* out = (bf16*)d_out;

    static bool init = false;
    static EncodeFn enc = nullptr;
    static void *p_tok, *p_ox, *p_mbox;
    static int nclusters = 64;
    if (!init) {
        cudaDriverEntryPointQueryResult qr;
        cudaGetDriverEntryPoint("cuTensorMapEncodeTiled", (void**)&enc, cudaEnableDefault, &qr);
        cudaGetSymbolAddress(&p_tok, g_tok);
        cudaGetSymbolAddress(&p_ox, g_ox);
        cudaGetSymbolAddress(&p_mbox, g_mbox);
        cudaFuncSetAttribute(proj_kernel<128, 7>, cudaFuncAttributeMaxDynamicSharedMemorySize, PROJ_SMEM);
        cudaFuncSetAttribute(chain_kernel<false>, cudaFuncAttributeMaxDynamicSharedMemorySize, CHAIN_SMEM);
        cudaFuncSetAttribute(chain_kernel<true>, cudaFuncAttributeMaxDynamicSharedMemorySize, CHAIN_SMEM);
        cudaFuncSetAttribute(ssm_kernel, cudaFuncAttributeMaxDynamicSharedMemorySize, B_SMEM);
        cudaLaunchConfig_t cfg = {};
        cfg.gridDim = dim3(132); cfg.blockDim = dim3(384); cfg.dynamicSmemBytes = CHAIN_SMEM;
        cudaLaunchAttribute at[1];
        at[0].id = cudaLaunchAttributeClusterDimension; at[0].val.clusterDim.x = 2; at[0].val.clusterDim.y = 1; at[0].val.clusterDim.z = 1;
        cfg.attrs = at; cfg.numAttrs = 1;
        int n = 0;
        if (cudaOccupancyMaxActiveClusters(&n, chain_kernel<true>, &cfg) == cudaSuccess && n > 64) nclusters = n < 66 ? n : 66;
        (void)cudaGetLastError();
        init = true;
    }
    char* mbox = (char*)(((uintptr_t)p_mbox + 2 * WIN - 1) & ~(uintptr_t)(2 * WIN - 1));
    CUtensorMap mX, mT32, mT16, mTQ, mKV, mWq, mWk, mWv, mWoC, mWo, mOx, mOut, mO8;
    {
        cuuint64_t dims[3] = {64, S_LEN, DM / 64};
        cuuint64_t strides[2] = {DM * 2, 128};
        cuuint32_t box[3] = {64, 32, 4};
        cuuint32_t es[3] = {1, 1, 1};
        enc(&mX, CU_TENSOR_MAP_DATA_TYPE_BFLOAT16, 3, const_cast<bf16*>(x), dims, strides, box, es, CU_TENSOR_MAP_INTERLEAVE_NONE,
            CU_TENSOR_MAP_SWIZZLE_128B, CU_TENSOR_MAP_L2_PROMOTION_L2_256B, CU_TENSOR_MAP_FLOAT_OOB_FILL_NONE);
    }
    make_map(enc, &mT32, p_tok, DH, 4 * NH * 3 * SEG, 64, 32, CU_TENSOR_MAP_L2_PROMOTION_L2_128B);
    make_map(enc, &mT16, p_tok, DH, 4 * NH * 3 * SEG, 64, 16, CU_TENSOR_MAP_L2_PROMOTION_L2_128B);
    {
        cuuint64_t dims[2] = {512, 4 * NH * 12};
        cuuint64_t strides[1] = {2048};
        cuuint32_t box[2] = {256, 4};
        cuuint32_t es[2] = {1, 1};
        enc(&mTQ, CU_TENSOR_MAP_DATA_TYPE_UINT32, 2, p_tok, dims, strides, box, es, CU_TENSOR_MAP_INTERLEAVE_NONE,
            CU_TENSOR_MAP_SWIZZLE_NONE, CU_TENSOR_MAP_L2_PROMOTION_L2_128B, CU_TENSOR_MAP_FLOAT_OOB_FILL_NONE);
    }
    {
        cuuint64_t dims[3] = {64, 4 * NH * 3 * SEG, 2};
        cuuint64_t strides[2] = {DH * 2, 128};
        cuuint32_t box[3] = {64, 32, 2};
        cuuint32_t es[3] = {1, 1, 1};
        enc(&mKV, CU_TENSOR_MAP_DATA_TYPE_BFLOAT16, 3, p_tok, dims, strides, box, es, CU_TENSOR_MAP_INTERLEAVE_NONE,
            CU_TENSOR_MAP_SWIZZLE_128B, CU_TENSOR_MAP_L2_PROMOTION_L2_128B, CU_TENSOR_MAP_FLOAT_OOB_FILL_NONE);
    }
    {
        cuuint64_t dims[3] = {32, S_LEN, HD / 32};
        cuuint64_t strides[2] = {HD * 2, 64};
        cuuint32_t box[3] = {32, 8, 4};
        cuuint32_t es[3] = {1, 1, 1};
        enc(&mO8, CU_TENSOR_MAP_DATA_TYPE_BFLOAT16, 3, p_ox, dims, strides, box, es, CU_TENSOR_MAP_INTERLEAVE_NONE,
            CU_TENSOR_MAP_SWIZZLE_64B, CU_TENSOR_MAP_L2_PROMOTION_L2_128B, CU_TENSOR_MAP_FLOAT_OOB_FILL_NONE);
    }
    make_map(enc, &mWq, Wq, HD, DM, 64, 16, CU_TENSOR_MAP_L2_PROMOTION_L2_128B);
    make_map(enc, &mWk, Wk, HD, DM, 64, 16, CU_TENSOR_MAP_L2_PROMOTION_L2_128B);
    make_map(enc, &mWv, Wv, HD, DM, 64, 16, CU_TENSOR_MAP_L2_PROMOTION_L2_128B);
    make_map(enc, &mWoC, Wo, DM, HD, 64, 16, CU_TENSOR_MAP_L2_PROMOTION_L2_128B);
    const bool early = nclusters >= 66;
    make_map(enc, &mWo, Wo, DM, HD, 64, 64, PROMO_W);
    make_map(enc, &mOx, p_ox, HD, S_LEN, 64, early ? 64 : 128, PROMO_O);
    make_map(enc, &mOut, out, OUT_LD, S_LEN, 64, early ? 64 : 128);

    CUtensorMap mB[4];
    for (int i = 0; i < 4; i++) {
        cuuint64_t dims[2] = {(cuuint64_t)(i < 3 ? DM : OUT_LD), S_LEN};
        cuuint64_t strides[1] = {dims[0] * 2};
        cuuint32_t box[2] = {16, i == 0 ? 136u : i < 3 ? 128u : 64u};
        cuuint32_t es[2] = {1, 1};
        enc(&mB[i], CU_TENSOR_MAP_DATA_TYPE_BFLOAT16, 2, const_cast<bf16*>(i == 0 ? Bk : i == 1 ? Bv : i == 2 ? Bq : out), dims, strides, box, es,
            CU_TENSOR_MAP_INTERLEAVE_NONE, CU_TENSOR_MAP_SWIZZLE_32B, SSM_PROMO, CU_TENSOR_MAP_FLOAT_OOB_FILL_NONE);
    }
    cudaStream_t st = cudaStreamPerThread;
    const ChainInputs ci = {{(const char*)Wv, (const char*)Wk, (const char*)Wq, (const char*)Wo}, (const char*)x, (const char*)mem0};
    ssm_kernel<<<132, 576, B_SMEM, st>>>(mB[0], mB[1], mB[2], mB[3], Bsh, Bssm, BD, mbox, ci, out);
    cudaLaunchAttribute pdl[1];
    pdl[0].id = cudaLaunchAttributeProgrammaticStreamSerialization; pdl[0].val.programmaticStreamSerializationAllowed = 1;
    cudaLaunchConfig_t lc = {};
    lc.stream = st; lc.attrs = pdl;
    lc.gridDim = dim3(2 * nclusters); lc.blockDim = dim3(384); lc.dynamicSmemBytes = CHAIN_SMEM; lc.numAttrs = PDL & 1;
    cudaLaunchKernelEx(&lc, early ? chain_kernel<true> : chain_kernel<false>, mbox, mem0, mX, mT32, mT16, mTQ, mKV, mWq, mWk, mWv, mWoC, mWo, mOx, mOut, mO8);
    if (early) return;
    lc.gridDim = dim3(2 * nclusters); lc.blockDim = dim3(PROJ_THREADS); lc.dynamicSmemBytes = PROJ_SMEM; lc.numAttrs = (PDL >> 1) & 1;
    cudaLaunchKernelEx(&lc, proj_kernel<128, 7>, mWo, mOx, mOut);
}
```

```cpp
#include <cuda_runtime.h>
#include <cuda_bf16.h>
#include <cuda.h>
#include <stdint.h>
#include <type_traits>

typedef __nv_bfloat16 bf16;

constexpr int S_LEN = 2048, DM = 1024, NH = 32, DH = 128, NSEG = 64, SEG = 32;
constexpr int HD = NH * DH;
constexpr int OUT_LD = 2048;
constexpr unsigned SENT = 0xFFFFFFFFu;

__device__ bf16 g_tok[4 * NH * 3 * SEG * DH];
__device__ bf16 g_ox[(size_t)S_LEN * HD];
__device__ uint4 g_mbox[4 * 131072];
__device__ unsigned g_xflag[128];
__device__ unsigned g_reg[4];
__device__ __align__(16) unsigned g_cls[256];
__device__ unsigned g_err;
constexpr uint32_t WIN = 2u << 20;
__host__ __device__ constexpr uint32_t page_off(uint32_t idx, uint32_t c) {
    return ((idx & 1) << 13) | ((idx >> 1) << 16) | (((c ^ idx ^ (idx >> 1) ^ (idx >> 2) ^ (idx >> 4)) & 1) << 12);
}
#define STAT(i, c) (void)(c)
#define EARLY_ROLE 1
#define PDL 3

__device__ __forceinline__ void launch_dependents() { asm volatile("griddepcontrol.launch_dependents;" ::: "memory"); }
__device__ __forceinline__ void wait_prerequisites() { asm volatile("griddepcontrol.wait;" ::: "memory"); }
__device__ __forceinline__ void prefetch_map(const CUtensorMap* m) { asm volatile("prefetch.tensormap [%0];" ::"l"(m) : "memory"); }
#define KT_MARK(k)
#define KT_START(k)
#define KT_END(k)

__device__ __forceinline__ uint32_t smem_u32(const void* p) { return (uint32_t)__cvta_generic_to_shared(p); }
__device__ __forceinline__ void ldsm4(uint32_t& r0, uint32_t& r1, uint32_t& r2, uint32_t& r3, uint32_t a) {
    asm volatile("ldmatrix.sync.aligned.m8n8.x4.shared.b16 {%0,%1,%2,%3}, [%4];" : "=r"(r0), "=r"(r1), "=r"(r2), "=r"(r3) : "r"(a) : "memory");
}
__device__ __forceinline__ void ldsm4t(uint32_t& r0, uint32_t& r1, uint32_t& r2, uint32_t& r3, uint32_t a) {
    asm volatile("ldmatrix.sync.aligned.m8n8.x4.trans.shared.b16 {%0,%1,%2,%3}, [%4];" : "=r"(r0), "=r"(r1), "=r"(r2), "=r"(r3) : "r"(a) : "memory");
}
__device__ __forceinline__ void ldsm2(uint32_t& r0, uint32_t& r1, uint32_t a) {
    asm volatile("ldmatrix.sync.aligned.m8n8.x2.shared.b16 {%0,%1}, [%2];" : "=r"(r0), "=r"(r1) : "r"(a) : "memory");
}
__device__ __forceinline__ void stg128(void* p, uint4 v) {
    asm volatile("st.global.v4.u32 [%0], {%1,%2,%3,%4};" ::"l"(p), "r"(v.x), "r"(v.y), "r"(v.z), "r"(v.w) : "memory");
}
__device__ __forceinline__ void stsm4(uint32_t a, uint32_t r0, uint32_t r1, uint32_t r2, uint32_t r3) {
    asm volatile("stmatrix.sync.aligned.m8n8.x4.shared.b16 [%0], {%1,%2,%3,%4};" ::"r"(a), "r"(r0), "r"(r1), "r"(r2), "r"(r3) : "memory");
}
__device__ __forceinline__ void mma16816(float (&d)[4], uint32_t a0, uint32_t a1, uint32_t a2, uint32_t a3, uint32_t b0, uint32_t b1) {
    asm("mma.sync.aligned.m16n8k16.row.col.f32.bf16.bf16.f32 {%0,%1,%2,%3},{%4,%5,%6,%7},{%8,%9},{%0,%1,%2,%3};"
                 : "+f"(d[0]), "+f"(d[1]), "+f"(d[2]), "+f"(d[3])
                 : "r"(a0), "r"(a1), "r"(a2), "r"(a3), "r"(b0), "r"(b1));
}
__device__ __forceinline__ void mma1688(float (&d)[4], uint32_t a0, uint32_t a1, uint32_t b0) {
    asm("mma.sync.aligned.m16n8k8.row.col.f32.bf16.bf16.f32 {%0,%1,%2,%3},{%4,%5},{%6},{%0,%1,%2,%3};"
        : "+f"(d[0]), "+f"(d[1]), "+f"(d[2]), "+f"(d[3]) : "r"(a0), "r"(a1), "r"(b0));
}
__device__ __forceinline__ uint32_t movmat(uint32_t a) {
    uint32_t d;
    asm volatile("movmatrix.sync.aligned.m8n8.trans.b16 %0, %1;" : "=r"(d) : "r"(a));
    return d;
}
__device__ __forceinline__ uint32_t pack_bf16(float lo, float hi) {
    uint32_t r;
    asm("cvt.rn.bf16x2.f32 %0, %1, %2;" : "=r"(r) : "f"(hi), "f"(lo));
    return r;
}
__device__ __forceinline__ uint32_t bf16_mul(uint32_t a, uint32_t b) {
    uint32_t d;
    asm("mul.rn.bf16x2 %0, %1, %2;" : "=r"(d) : "r"(a), "r"(b));
    return d;
}
__device__ __forceinline__ uint32_t bf16_add(uint32_t a, uint32_t b) {
    uint32_t d;
    asm("add.rn.bf16x2 %0, %1, %2;" : "=r"(d) : "r"(a), "r"(b));
    return d;
}

__device__ __forceinline__ float bf16_round(float x) { return __bfloat162float(__float2bfloat16_rn(x)); }
__device__ __forceinline__ float bf_lo(uint32_t w) { return __uint_as_float(w << 16); }
__device__ __forceinline__ float bf_hi(uint32_t w) { return __uint_as_float(w & 0xFFFF0000u); }
__device__ __forceinline__ void bar_sync(int id, int n) { asm volatile("bar.sync %0, %1;" ::"r"(id), "r"(n) : "memory"); }
__device__ __forceinline__ void bar_sync_keep(int id, int n, uint32_t a, uint32_t b) {
    asm volatile("bar.sync %0, %1; // %2 %3" ::"r"(id), "r"(n), "r"(a), "r"(b) : "memory");
}
__device__ __forceinline__ bool bar_red_or(int id, int n, bool p) {
    uint32_t r;
    asm volatile("{.reg .pred p, q; setp.ne.u32 p, %3, 0; bar.red.or.pred q, %1, %2, p; selp.u32 %0, 1, 0, q;}" : "=r"(r) : "r"(id), "r"(n), "r"((uint32_t)p) : "memory");
    return r != 0;
}
__device__ __forceinline__ void bar_arrive(int id, int n) { asm volatile("bar.arrive %0, %1;" ::"r"(id), "r"(n) : "memory"); }
__device__ __forceinline__ void cp_async16(uint32_t dst, const void* src) {
    asm volatile("cp.async.cg.shared.global [%0], [%1], 16;" ::"r"(dst), "l"(src) : "memory");
}
__device__ __forceinline__ void cp_commit() { asm volatile("cp.async.commit_group;" ::: "memory"); }
template <int N> __device__ __forceinline__ void cp_wait() { asm volatile("cp.async.wait_group %0;" ::"n"(N) : "memory"); }
__device__ __forceinline__ uint4 ld_relaxed_v4(const void* p) {
    uint4 v;
    asm volatile("ld.relaxed.gpu.global.v4.u32 {%0,%1,%2,%3}, [%4];" : "=r"(v.x), "=r"(v.y), "=r"(v.z), "=r"(v.w) : "l"(p) : "memory");
    return v;
}
__device__ __forceinline__ void st_relaxed_u32(void* p, uint32_t v) { asm volatile("st.relaxed.gpu.global.u32 [%0], %1;" ::"l"(p), "r"(v) : "memory"); }
__device__ __forceinline__ void st_relaxed_v2(void* p, uint32_t a, uint32_t b) {
    asm volatile("st.relaxed.gpu.global.v2.u32 [%0], {%1,%2};" ::"l"(p), "r"(a), "r"(b) : "memory");
}
__device__ __forceinline__ void sts128(uint32_t a, uint4 v) {
    asm volatile("st.shared.v4.u32 [%0], {%1,%2,%3,%4};" ::"r"(a), "r"(v.x), "r"(v.y), "r"(v.z), "r"(v.w) : "memory");
}
__device__ __forceinline__ uint4 lds128(uint32_t a) {
    uint4 v;
    asm volatile("ld.shared.v4.u32 {%0,%1,%2,%3}, [%4];" : "=r"(v.x), "=r"(v.y), "=r"(v.z), "=r"(v.w) : "r"(a) : "memory");
    return v;
}
__device__ __forceinline__ void sts32(uint32_t a, uint32_t v) { asm volatile("st.shared.u32 [%0], %1;" ::"r"(a), "r"(v) : "memory"); }
__device__ __forceinline__ uint32_t lds32(uint32_t a) {
    uint32_t v;
    asm volatile("ld.shared.u32 %0, [%1];" : "=r"(v) : "r"(a) : "memory");
    return v;
}
__device__ __forceinline__ void mbar_init(uint32_t a, uint32_t c) { asm volatile("mbarrier.init.shared::cta.b64 [%0], %1;" ::"r"(a), "r"(c) : "memory"); }
__device__ __forceinline__ void mbar_expect_tx(uint32_t a, uint32_t bytes) {
    asm volatile("mbarrier.arrive.expect_tx.shared::cta.b64 _, [%0], %1;" ::"r"(a), "r"(bytes) : "memory");
}
__device__ __forceinline__ void mbar_arrive(uint32_t a) { asm volatile("mbarrier.arrive.shared::cta.b64 _, [%0];" ::"r"(a) : "memory"); }
__device__ __forceinline__ void mbar_wait(uint32_t a, uint32_t parity) {
    asm volatile("{.reg .pred p; .reg .u32 c;\n"
                 "mov.u32 c, 0;\n"
                 "MBW_LOOP:\n"
                 "add.u32 c, c, 1;\n"
                 "setp.gt.u32 p, c, 0x10000;\n"
                 "@!p mbarrier.try_wait.parity.shared::cta.b64 p, [%0], %1;\n"
                 "@!p bra.uni MBW_LOOP;}" ::"r"(a), "r"(parity) : "memory");
}
__device__ __forceinline__ void mbar_wait_w(uint32_t a, uint32_t parity) {
    asm volatile("{.reg .pred p; .reg .u32 c;\n"
                 "mov.u32 c, 0;\n"
                 "MBW_LOOP:\n"
                 "add.u32 c, c, 1;\n"
                 "setp.gt.u32 p, c, 0x10000;\n"
                 "@!p mbarrier.try_wait.parity.shared::cta.b64 p, [%0], %1;\n"
                 "vote.sync.all.pred p, p, 0xFFFFFFFF;\n"
                 "@!p bra.uni MBW_LOOP;}" ::"r"(a), "r"(parity) : "memory");
}
__device__ __forceinline__ void mbar_expect_tx_if0(uint32_t sel, uint32_t a, uint32_t bytes) {
    asm volatile("{.reg .pred p; setp.eq.u32 p, %2, 0; @p mbarrier.arrive.expect_tx.shared::cta.b64 _, [%0], %1;}" ::"r"(a), "r"(bytes), "r"(sel) : "memory");
}
__device__ __forceinline__ void mbar_arrive_if0(uint32_t sel, uint32_t a) {
    asm volatile("{.reg .pred p; setp.eq.u32 p, %1, 0; @p mbarrier.arrive.shared::cta.b64 _, [%0];}" ::"r"(a), "r"(sel) : "memory");
}
__device__ __forceinline__ void bulk_load(uint32_t dst, const void* src, uint32_t bytes, uint32_t bar) {
    asm volatile("cp.async.bulk.shared::cluster.global.mbarrier::complete_tx::bytes [%0], [%1], %2, [%3];" ::"r"(dst), "l"(src), "r"(bytes), "r"(bar) : "memory");
}
__device__ __forceinline__ void tma_load_2d(uint32_t dst, const CUtensorMap* map, int c0, int c1, uint32_t bar) {
    asm volatile("cp.async.bulk.tensor.2d.shared::cluster.global.mbarrier::complete_tx::bytes [%0], [%1, {%3, %4}], [%2];"
                 ::"r"(dst), "l"(map), "r"(bar), "r"(c0), "r"(c1) : "memory");
}
__device__ __forceinline__ void tma_load_2d_both(uint32_t dst, const CUtensorMap* map, int c0, int c1, uint32_t bar) {
    asm volatile("cp.async.bulk.tensor.2d.shared::cluster.global.mbarrier::complete_tx::bytes.multicast::cluster [%0], [%1, {%3, %4}], [%2], %5;"
                 ::"r"(dst), "l"(map), "r"(bar), "r"(c0), "r"(c1), "h"((uint16_t)3) : "memory");
}
__device__ __forceinline__ uint64_t policy_evict_first() {
    uint64_t p;
    asm("createpolicy.fractional.L2::evict_first.b64 %0, 1.0;" : "=l"(p));
    return p;
}
__device__ __forceinline__ uint64_t policy_evict_normal() {
    uint64_t p;
    asm("createpolicy.fractional.L2::evict_normal.b64 %0, 1.0;" : "=l"(p));
    return p;
}
__device__ __forceinline__ void tma_load_2d(uint32_t dst, const CUtensorMap* map, int c0, int c1, uint32_t bar, uint64_t pol) {
    asm volatile("cp.async.bulk.tensor.2d.shared::cluster.global.mbarrier::complete_tx::bytes.L2::cache_hint [%0], [%1, {%3, %4}], [%2], %5;"
                 ::"r"(dst), "l"(map), "r"(bar), "r"(c0), "r"(c1), "l"(pol) : "memory");
}
__device__ __forceinline__ uint4 ldg128(const void* p, uint64_t pol) {
    uint4 v;
    asm("ld.global.nc.L2::cache_hint.v4.u32 {%0,%1,%2,%3}, [%4], %5;" : "=r"(v.x), "=r"(v.y), "=r"(v.z), "=r"(v.w) : "l"(p), "l"(pol));
    return v;
}
__device__ __forceinline__ void stg128(void* p, uint4 v, uint64_t pol) {
    asm volatile("st.global.L2::cache_hint.v4.u32 [%0], {%1,%2,%3,%4}, %5;" ::"l"(p), "r"(v.x), "r"(v.y), "r"(v.z), "r"(v.w), "l"(pol) : "memory");
}
__device__ __forceinline__ void tma_store_2d(const CUtensorMap* map, uint32_t src, int c0, int c1) {
    asm volatile("cp.async.bulk.tensor.2d.global.shared::cta.bulk_group [%0, {%2, %3}], [%1];" ::"l"(map), "r"(src), "r"(c0), "r"(c1) : "memory");
}
__device__ __forceinline__ void tma_store_3d(const CUtensorMap* map, uint32_t src, int c0, int c1, int c2) {
    asm volatile("cp.async.bulk.tensor.3d.global.shared::cta.bulk_group [%0, {%2, %3, %4}], [%1];" ::"l"(map), "r"(src), "r"(c0), "r"(c1), "r"(c2) : "memory");
}
__device__ __forceinline__ char* make_ptr(uint32_t lo, uint32_t hi) {
    uint64_t p;
    asm("mov.b64 %0, {%1, %2};" : "=l"(p) : "r"(lo), "r"(hi));
    return reinterpret_cast<char*>(p);
}
__device__ __forceinline__ uint64_t make_desc(uint32_t saddr, uint32_t lbo, uint32_t sbo) {
    return (uint64_t)((saddr & 0x3FFFF) >> 4) | ((uint64_t)((lbo >> 4) & 0x3FFF) << 16) | ((uint64_t)((sbo >> 4) & 0x3FFF) << 32) | ((uint64_t)1 << 62);
}
__device__ __forceinline__ void wg_fence() { asm volatile("wgmma.fence.sync.aligned;" ::: "memory"); }
__device__ __forceinline__ void wg_commit() { asm volatile("wgmma.commit_group.sync.aligned;" ::: "memory"); }
template <int N> __device__ __forceinline__ void wg_wait() { asm volatile("wgmma.wait_group.sync.aligned %0;" ::"n"(N) : "memory"); }

#define R4(b) "+f"(d[b + 0]), "+f"(d[b + 1]), "+f"(d[b + 2]), "+f"(d[b + 3])
#define R16(b) R4(b), R4(b + 4), R4(b + 8), R4(b + 12)
template <int N> __device__ __forceinline__ void wgmma_proj(float (&d)[N / 2], uint64_t da, uint64_t db) {
    if constexpr (N == 96)
        asm volatile("wgmma.mma_async.sync.aligned.m64n96k16.f32.bf16.bf16 {"
            "%0,%1,%2,%3,%4,%5,%6,%7,%8,%9,%10,%11,%12,%13,%14,%15,%16,%17,%18,%19,%20,%21,%22,%23,%24,%25,%26,%27,%28,%29,%30,%31,%32,%33,%34,%35,%36,%37,%38,%39,"
            "%40,%41,%42,%43,%44,%45,%46,%47"
            "}, %48, %49, 1, 1, 1, 1, 0;" : R16(0), R16(16), R16(32) : "l"(da), "l"(db));
    if constexpr (N == 128)
        asm volatile("wgmma.mma_async.sync.aligned.m64n128k16.f32.bf16.bf16 {"
            "%0,%1,%2,%3,%4,%5,%6,%7,%8,%9,%10,%11,%12,%13,%14,%15,%16,%17,%18,%19,%20,%21,%22,%23,%24,%25,%26,%27,%28,%29,%30,%31,%32,%33,%34,%35,%36,%37,%38,%39,"
            "%40,%41,%42,%43,%44,%45,%46,%47,%48,%49,%50,%51,%52,%53,%54,%55,%56,%57,%58,%59,%60,%61,%62,%63"
            "}, %64, %65, 1, 1, 1, 1, 0;" : R16(0), R16(16), R16(32), R16(48) : "l"(da), "l"(db));
    if constexpr (N == 192)
        asm volatile("wgmma.mma_async.sync.aligned.m64n192k16.f32.bf16.bf16 {"
            "%0,%1,%2,%3,%4,%5,%6,%7,%8,%9,%10,%11,%12,%13,%14,%15,%16,%17,%18,%19,%20,%21,%22,%23,%24,%25,%26,%27,%28,%29,%30,%31,%32,%33,%34,%35,%36,%37,%38,%39,"
            "%40,%41,%42,%43,%44,%45,%46,%47,%48,%49,%50,%51,%52,%53,%54,%55,%56,%57,%58,%59,%60,%61,%62,%63,%64,%65,%66,%67,%68,%69,%70,%71,%72,%73,%74,%75,%76,%7"
            "7,%78,%79,%80,%81,%82,%83,%84,%85,%86,%87,%88,%89,%90,%91,%92,%93,%94,%95"
            "}, %96, %97, 1, 1, 1, 1, 0;" : R16(0), R16(16), R16(32), R16(48), R16(64), R16(80) : "l"(da), "l"(db));
    if constexpr (N == 256)
        asm volatile("wgmma.mma_async.sync.aligned.m64n256k16.f32.bf16.bf16 {"
            "%0,%1,%2,%3,%4,%5,%6,%7,%8,%9,%10,%11,%12,%13,%14,%15,%16,%17,%18,%19,%20,%21,%22,%23,%24,%25,%26,%27,%28,%29,%30,%31,%32,%33,%34,%35,%36,%37,%38,%39,"
            "%40,%41,%42,%43,%44,%45,%46,%47,%48,%49,%50,%51,%52,%53,%54,%55,%56,%57,%58,%59,%60,%61,%62,%63,%64,%65,%66,%67,%68,%69,%70,%71,%72,%73,%74,%75,%76,%7"
            "7,%78,%79,%80,%81,%82,%83,%84,%85,%86,%87,%88,%89,%90,%91,%92,%93,%94,%95,%96,%97,%98,%99,%100,%101,%102,%103,%104,%105,%106,%107,%108,%109,%110,%111,"
            "%112,%113,%114,%115,%116,%117,%118,%119,%120,%121,%122,%123,%124,%125,%126,%127"
            "}, %128, %129, 1, 1, 1, 1, 0;" : R16(0), R16(16), R16(32), R16(48), R16(64), R16(80), R16(96), R16(112) : "l"(da), "l"(db));
}

__device__ __forceinline__ void wgmma_rs32(float (&d)[16], const uint32_t (&a)[4], uint64_t db, bool acc) {
    asm volatile(
        "{.reg .pred p; setp.ne.b32 p, %21, 0;\n"
        "wgmma.mma_async.sync.aligned.m64n32k16.f32.bf16.bf16 {%0,%1,%2,%3,%4,%5,%6,%7,%8,%9,%10,%11,%12,%13,%14,%15}, {%16,%17,%18,%19}, %20, p, 1, 1, 0;}"
        : R16(0) : "r"(a[0]), "r"(a[1]), "r"(a[2]), "r"(a[3]), "l"(db), "n"(1) );
}
__device__ __forceinline__ void wgmma_rs32_first(float (&d)[16], const uint32_t (&a)[4], uint64_t db) {
    asm volatile(
        "{.reg .pred p; setp.ne.b32 p, %21, 0;\n"
        "wgmma.mma_async.sync.aligned.m64n32k16.f32.bf16.bf16 {%0,%1,%2,%3,%4,%5,%6,%7,%8,%9,%10,%11,%12,%13,%14,%15}, {%16,%17,%18,%19}, %20, p, 1, 1, 0;}"
        : R16(0) : "r"(a[0]), "r"(a[1]), "r"(a[2]), "r"(a[3]), "l"(db), "n"(0) );
}
__device__ __forceinline__ void wgmma_ss32(float (&d)[16], uint64_t da, uint64_t db) {
    asm volatile(
        "wgmma.mma_async.sync.aligned.m64n32k16.f32.bf16.bf16 {%0,%1,%2,%3,%4,%5,%6,%7,%8,%9,%10,%11,%12,%13,%14,%15}, %16, %17, 1, 1, 1, 1, 0;"
        : R16(0) : "l"(da), "l"(db));
}
template <int OFF, int ACC> __device__ __forceinline__ void wgmma_rs32u(float (&d)[16], const uint32_t (&a)[4], uint32_t lo) {
    asm volatile(
        "{.reg .pred p; .reg .b32 l; .reg .b64 e; setp.ne.b32 p, %22, 0; add.u32 l, %20, %21; mov.b64 e, {l, 0x40000040};\n"
        "wgmma.mma_async.sync.aligned.m64n32k16.f32.bf16.bf16 {%0,%1,%2,%3,%4,%5,%6,%7,%8,%9,%10,%11,%12,%13,%14,%15}, {%16,%17,%18,%19}, e, p, 1, 1, 0;}"
        : R16(0) : "r"(a[0]), "r"(a[1]), "r"(a[2]), "r"(a[3]), "r"(lo), "n"(OFF), "n"(ACC));
}
template <int OFF, int ACC> __device__ __forceinline__ void wgmma_ss32u(float (&d)[16], uint64_t da, uint32_t lo) {
    asm volatile(
        "{.reg .pred p; .reg .b32 l; .reg .b64 e; setp.ne.b32 p, %19, 0; add.u32 l, %17, %18; mov.b64 e, {l, 0x40000040};\n"
        "wgmma.mma_async.sync.aligned.m64n32k16.f32.bf16.bf16 {%0,%1,%2,%3,%4,%5,%6,%7,%8,%9,%10,%11,%12,%13,%14,%15}, %16, e, p, 1, 1, 1, 0;}"
        : R16(0) : "l"(da), "r"(lo), "n"(OFF), "n"(ACC));
}
template <int K0, int K1, class F> __device__ __forceinline__ void static_for(F f) {
    if constexpr (K0 < K1) { f(std::integral_constant<int, K0>()); static_for<K0 + 1, K1>(f); }
}
__device__ __forceinline__ void st_async4(uint32_t a, float x, float y, float z, float w, uint32_t bar) {
    asm volatile("st.async.weak.shared::cluster.mbarrier::complete_tx::bytes.v4.f32 [%0], {%1,%2,%3,%4}, [%5];" ::"r"(a), "f"(x), "f"(y), "f"(z), "f"(w), "r"(bar) : "memory");
}
__device__ __forceinline__ void st_async2(uint32_t a, float x, float y, uint32_t bar) {
    asm volatile("st.async.weak.shared::cluster.mbarrier::complete_tx::bytes.v2.f32 [%0], {%1,%2}, [%3];" ::"r"(a), "f"(x), "f"(y), "r"(bar) : "memory");
}
__device__ __forceinline__ void st_async1(uint32_t a, uint32_t x, uint32_t bar) {
    asm volatile("st.async.weak.shared::cluster.mbarrier::complete_tx::bytes.b32 [%0], %1, [%2];" ::"r"(a), "r"(x), "r"(bar) : "memory");
}
__device__ __forceinline__ uint32_t peer_addr(uint32_t a, uint32_t rank) {
    uint32_t r;
    asm("mapa.shared::cluster.u32 %0, %1, %2;" : "=r"(r) : "r"(a), "r"(rank));
    return r;
}
__device__ __forceinline__ void stsm4t(uint32_t a, uint32_t r0, uint32_t r1, uint32_t r2, uint32_t r3) {
    asm volatile("stmatrix.sync.aligned.m8n8.x4.trans.shared.b16 [%0], {%1,%2,%3,%4};" ::"r"(a), "r"(r0), "r"(r1), "r"(r2), "r"(r3) : "memory");
}
__device__ __forceinline__ void ldsm4t(uint32_t (&r)[4], uint32_t a) { ldsm4t(r[0], r[1], r[2], r[3], a); }
__device__ __forceinline__ void ldsm4(uint32_t (&r)[4], uint32_t a) { ldsm4(r[0], r[1], r[2], r[3], a); }
__device__ __forceinline__ void mma16816(float (&d)[4], const uint32_t (&a)[4], uint32_t b0, uint32_t b1) { mma16816(d, a[0], a[1], a[2], a[3], b0, b1); }
__device__ __forceinline__ void sched_fence(uint32_t v) {
    asm volatile("{.reg .pred p; setp.ne.u32 p, %0, 0xFFFFFFFF; vote.sync.all.pred p, p, 0xFFFFFFFF; @p bra.uni SF_OK; exit; SF_OK:}" ::"r"(v) : "memory");
}
__device__ __forceinline__ void mma16816v(float (&d)[4], const uint32_t (&a)[4], uint32_t b0, uint32_t b1) {
    asm volatile("mma.sync.aligned.m16n8k16.row.col.f32.bf16.bf16.f32 {%0,%1,%2,%3},{%4,%5,%6,%7},{%8,%9},{%0,%1,%2,%3};"
                 : "+f"(d[0]), "+f"(d[1]), "+f"(d[2]), "+f"(d[3]) : "r"(a[0]), "r"(a[1]), "r"(a[2]), "r"(a[3]), "r"(b0), "r"(b1));
}
__device__ __forceinline__ uint32_t uniform(uint32_t v) { return __reduce_max_sync(~0u, v); }

#define WPRE 0
#define G2_X 0
#define G2_K 4
#define FIN_SO 0
#define PROJ_FAST 1
#define KROT 0
#define WFIRST 0
template <int NT, int STAGES> struct ProjCfg {
    static constexpr int STAGE_BYTES = 16384 + NT * 128;
    static constexpr int EPI = NT == 256 ? STAGES * STAGE_BYTES : 0;
    static constexpr int BARS = 229376 + (NT == 256 ? 192 : 0);
    static_assert(STAGES * STAGE_BYTES <= 229376 && EPI + NT * 256 <= 229376 && STAGES <= 12, "smem");
};
constexpr int PROJ_ROLE = 229376 + 384, PROJ_SMEM = PROJ_ROLE + 16;
__device__ __forceinline__ unsigned claim_pair(unsigned* reg) {
    unsigned smid, ncl = gridDim.x >> 1;
    asm volatile("mov.u32 %0, %%smid;" : "=r"(smid));
    uint2 m;
    for (int guard = 0; guard < 1024; guard++) {
        asm volatile("ld.relaxed.gpu.global.v2.u32 {%0, %1}, [%2];" : "=r"(m.x), "=r"(m.y) : "l"(g_cls + (smid & ~1u)) : "memory");
        if (m.x && m.y) break;
    }
    const unsigned r = __vminu2(m.x, m.y), c = (r & 0xFFFF) > (r >> 16);
    unsigned n = atomicAdd(reg, c ? 0x10000u : 1u);
    const unsigned i = c ? n >> 16 : n & 0xFFFF, order = ((n >> 16) + (n & 0xFFFF)) << 8;
    if (i < 32) return c * 32 + i + order;
    for (int guard = 0; guard < (1 << 20); guard++) {
        asm volatile("ld.relaxed.gpu.global.u32 %0, [%1];" : "=r"(n) : "l"(reg) : "memory");
        if ((n >> 16) + (n & 0xFFFF) >= ncl) break;
    }
    const unsigned other = c ? n & 0xFFFF : n >> 16, k = other + i - 32;
    return (k < 32 ? (c ^ 1) * 32 + k : other > 32 ? 64 + c : 32 + k) + order;
}
template <int NT, int STAGES> __device__ __forceinline__ void proj_init(uint32_t sb) {
    for (int i = 0; i < STAGES; i++) { mbar_init(sb + ProjCfg<NT, STAGES>::BARS + 8 * i, 1); mbar_init(sb + ProjCfg<NT, STAGES>::BARS + 8 * (STAGES + i), 16); }
    asm volatile("fence.mbarrier_init.release.cluster;" ::: "memory");
}
template <int NT, int STAGES, bool SHARE_O, class T, class R>
__device__ __forceinline__ void proj_tiles(uint32_t sb, int warp, uint32_t rank, int ntiles, const CUtensorMap* mapW, const CUtensorMap* mapO,
                                           const CUtensorMap* mapOut, T tile, R ready, int rot = 0) {
    using Cfg = ProjCfg<NT, STAGES>;
    const uint32_t bars = sb + Cfg::BARS;
    const int lane = threadIdx.x & 31;
    if (warp == 8) {
        int st = 0; uint32_t ph = 1;
        for (int i = 0; i < ntiles; i++) {
            int col, tok;
            tile(i, col, tok);
            constexpr bool PRE = WPRE && !SHARE_O;
            if (PRE && lane == 0)
                for (int kb = 0; kb < STAGES; kb++) {
                    mbar_expect_tx(bars + 8 * kb, Cfg::STAGE_BYTES);
                    tma_load_2d_both(sb + kb * Cfg::STAGE_BYTES + rank * 8192, mapW, col + rank * 64, kb * 64, bars + 8 * kb);
                }
            ready(i);
            if (lane == 0) {
                if (PRE) {
                    for (int kb = 0; kb < STAGES; kb++) tma_load_2d(sb + kb * Cfg::STAGE_BYTES + 16384, mapO, kb * 64, tok, bars + 8 * kb);
                    ph = 0;
                }
                for (int kb = PRE ? STAGES : 0; kb < HD / 64; kb++) {
                    mbar_wait(bars + 8 * (STAGES + st), ph);
                    const uint32_t full = bars + 8 * st, sa = sb + st * Cfg::STAGE_BYTES;
                    mbar_expect_tx(full, SHARE_O ? Cfg::STAGE_BYTES : G2_X == 1 ? 16384 : G2_X == 2 ? NT * 128 : Cfg::STAGE_BYTES);
                    if (SHARE_O) {
                        tma_load_2d(sa, mapW, col, kb * 64, full);
                        tma_load_2d(sa + 8192, mapW, col + 64, kb * 64, full);
                        tma_load_2d_both(sa + 16384 + rank * (NT * 64), mapO, kb * 64, tok + rank * (NT / 2), full);
                    } else {
                        const int k0 = ((kb + rot) & 63) * 64;
                        if (WFIRST) tma_load_2d_both(sa + rank * 8192, mapW, col + rank * 64, k0, full);
                        if (G2_X != 1) tma_load_2d(sa + 16384, mapO, k0, G2_X == 3 ? tok & 511 : tok, full);
                        if (G2_X == 4) { tma_load_2d(sa, mapW, col, k0, full); tma_load_2d(sa + 8192, mapW, col + 64, k0, full); }
                        else if (!WFIRST && G2_X != 2) tma_load_2d_both(sa + rank * 8192, mapW, col + rank * 64, k0, full);
                    }
                    if (++st == STAGES) { st = 0; ph ^= 1; }
                }
            }
            __syncwarp();
        }
    } else if (warp < 8) {
        const int wg = warp >> 2;
        uint32_t peer_empty;
        asm volatile("mapa.shared::cluster.u32 %0, %1, %2;" : "=r"(peer_empty) : "r"(bars + 8 * STAGES), "r"(rank ^ 1));
        auto release = [&](int stg) {
            if (lane == 0) {
                mbar_arrive(bars + 8 * (STAGES + stg));
                asm volatile("mbarrier.arrive.shared::cluster.b64 _, [%0];" ::"r"(peer_empty + 8 * stg) : "memory");
            }
        };
        const uint32_t ew = sb + Cfg::EPI + wg * (NT * 128);
        int st = 0; uint32_t ph = 0;
        for (int i = 0; i < ntiles; i++) {
            int col, tok;
            tile(i, col, tok);
            float d[NT / 2];
#pragma unroll
            for (int r = 0; r < NT / 2; r++) d[r] = 0.f;
            int prev = -1;
            for (int kb = 0; kb < HD / 64; kb++) {
                mbar_wait(bars + 8 * st, ph);
                const uint32_t sa = sb + st * Cfg::STAGE_BYTES;
                const uint64_t da = make_desc(sa + wg * 8192, 16, 1024), db = make_desc(sa + 16384, 16, 1024);
                wg_fence();
#pragma unroll
                for (int k = 0; k < (NT == 256 ? 4 : G2_K); k++) wgmma_proj<NT>(d, da + k * 128, db + k * 2);
                wg_commit();
                if (prev >= 0) { wg_wait<1>(); release(prev); }
                prev = st;
                if (++st == STAGES) { st = 0; ph ^= 1; }
            }
            wg_wait<0>();
            release(prev);
            if ((warp & 3) == 0 && lane == 0) asm volatile("cp.async.bulk.wait_group.read 0;" ::: "memory");
            if (Cfg::EPI) bar_sync(1 + wg, 128); else bar_sync(3, 256);
            const uint32_t ea = ew + ((lane >> 4) * 8 + (lane & 7)) * 128 + ((((warp & 3) * 2 + ((lane >> 3) & 1)) ^ (lane & 7)) * 16);
#pragma unroll
            for (int r = 0; r < NT / 16; r++)
                stsm4t(ea + r * 2048, pack_bf16(d[8 * r], d[8 * r + 1]), pack_bf16(d[8 * r + 2], d[8 * r + 3]), pack_bf16(d[8 * r + 4], d[8 * r + 5]), pack_bf16(d[8 * r + 6], d[8 * r + 7]));
            asm volatile("fence.proxy.async.shared::cta;" ::: "memory");
            bar_sync(1 + wg, 128);
            if ((warp & 3) == 0 && lane == 0) {
                tma_store_2d(mapOut, ew, col + wg * 64, tok);
                asm volatile("cp.async.bulk.commit_group;" ::: "memory");
            }
        }
        if ((warp & 3) == 0 && lane == 0) asm volatile("cp.async.bulk.wait_group 0;" ::: "memory");
    }
    __syncwarp();
}
constexpr int PROJ_THREADS = 288;

template <int NT, int STAGES>
__global__ void __cluster_dims__(2, 1, 1) __launch_bounds__(PROJ_THREADS, 1)
proj_kernel(const __grid_constant__ CUtensorMap mapW, const __grid_constant__ CUtensorMap mapO, const __grid_constant__ CUtensorMap mapOut) {
    KT_START(3);
    extern __shared__ __align__(1024) uint8_t smem_proj[];
    const uint32_t sb = smem_u32(smem_proj), role = sb + PROJ_ROLE;
    if (sb & 1023) __trap();
    const uint32_t rank = blockIdx.x & 1;
    const int warp = threadIdx.x >> 5;
    if (threadIdx.x == 0) {
        mbar_init(role + 8, 1);
        mbar_expect_tx(role + 8, 4);
        proj_init<NT, STAGES>(sb);
    }
    if (threadIdx.x == 32) { prefetch_map(&mapO); prefetch_map(&mapW); prefetch_map(&mapOut); }
    __syncwarp();
    asm volatile("barrier.cluster.arrive.relaxed.aligned;" ::: "memory");
    unsigned claimed = 0;
    if (threadIdx.x == 256 && rank == 0) claimed = claim_pair(g_reg + 2);
    __syncwarp();
    asm volatile("barrier.cluster.wait.acquire.aligned;" ::: "memory");
    if (threadIdx.x == 256 && rank == 0) {
        st_async1(peer_addr(role, 1), claimed, peer_addr(role + 8, 1));
        st_async1(peer_addr(role, 0), claimed, peer_addr(role + 8, 0));
        if ((claimed >> 8) + 1 == gridDim.x >> 1) {
            g_reg[0] = 0;
            for (int i = 0; i < 64; i++) reinterpret_cast<uint4*>(g_cls)[i] = make_uint4(0, 0, 0, 0);
        }
    }
    __syncwarp();
    mbar_wait_w(role + 8, 0);
    const int p = lds32(role) & 255, order = lds32(role) >> 8;
    if (p >= 64) return;
    proj_tiles<NT, STAGES, false>(sb, warp, rank, 1, &mapW, &mapO, &mapOut,
                                  [&](int, int& col, int& tok) { col = (p & 7) * 128; tok = S_LEN - 16 * NT + ((p >> 3) * 2 + rank) * NT; },
                                  [&](int) { wait_prerequisites();
                                  }, KROT == 0 ? 0 : KROT == 1 ? (p & 7) * 8 : KROT == 2 ? (p >> 3) * 8 : KROT == 3 ? ((p & 7) + (p >> 3)) * 8 : (p >> 5) * 32);
    KT_END(3);
    asm volatile("barrier.cluster.arrive.relaxed; barrier.cluster.wait;" ::: "memory");
}

#define WO_RF1 6
constexpr int SM_KV = 0, KV_BYTES = 18432;
constexpr int SM_XT = 2 * KV_BYTES;
constexpr int SM_STG = SM_XT + 65536;
constexpr int SM_Z = SM_STG + 6144;
constexpr int SM_RT = SM_Z + 8192;
constexpr int SM_OT = SM_RT + 8192;
constexpr int SM_QKV = SM_RT + 10240;
constexpr int SM_R1 = SM_QKV + 6144;
constexpr int SM_Y = SM_R1;
constexpr int SM_R2 = SM_R1 + 4096;
constexpr int SM_R3 = SM_R2 + 1024;
constexpr int SM_O = SM_R3 + 2048;
constexpr int SM_S = SM_O + 2048;
constexpr int SM_INV = SM_S + 1536;
constexpr int SM_TO = SM_R3;
constexpr int SM_WORK_END = SM_S + 2048;
constexpr int STG_QK = 0, STG_V = 98304;
#define LEAD 2
#define FL_AT (LEAD == 3 ? 0 : 4)
#define KC_AT (LEAD == 3 ? 0 : 4)
#define KC_PRE 1
#define RTF 1
#define XT11 0
#define XT_AT 1
#define RTW 0
#define KVMC 1
#define WO_IT (LEAD - 1)
__host__ __device__ constexpr int stg_wo(int r) { return r < 9 ? KV_BYTES + r * 2048 : r < 13 ? SM_QKV + (r - 9) * 2048 : SM_S; }
static_assert(WO_RF1 == 6 && SM_QKV % 1024 == 0 && SM_S % 1024 == 0 && SM_QKV + 8192 <= SM_TO, "staging of Wo");
__host__ __device__ constexpr int stg_qk(int t, int r) { return t == 0 ? SM_XT + r * 2048 : r < SM_XT / 2048 ? r * 2048 : (r + 24) * 2048; }
constexpr int SM_WO1 = SM_WORK_END - WO_RF1 * 2048;
constexpr int STG_WO = SM_WO1 - 16384;
constexpr int SM_WQK = (SM_WO1 + 16384 > STG_V + 49152) ? SM_WO1 + 16384 : STG_V + 49152;
constexpr int SM_WV = SM_WQK + 32768;
constexpr int SM_WO2 = SM_WV + 16384;
constexpr int SM_BARS = SM_WO2 + 32768;
enum { MB_W0 = SM_BARS, MB_W1 = SM_BARS + 8, MB_W2 = SM_BARS + 16, MB_W3 = SM_BARS + 24, MB_XT = SM_BARS + 32  , MB_KV = SM_BARS + 48  ,
       MB_R3 = SM_BARS + 64, MB_R1 = SM_BARS + 72, MB_R2 = SM_BARS + 80, MB_RT0 = SM_BARS + 88, MB_RT1 = SM_BARS + 96, MB_FREE = SM_BARS + 104,
       MB_P = SM_BARS + 112, MB_V = SM_BARS + 120, MB_STG = SM_BARS + 128, MB_ROLE = SM_BARS + 136, MB_W4 = SM_BARS + 144, MB_W5 = SM_BARS + 152, SM_ROLE = SM_BARS + 160  ,
       MB_FULL = SM_BARS + 176  , MB_EMPTY = SM_BARS + 208  , MB_SUM = SM_BARS + 240 };
constexpr int CHAIN_SMEM = MB_SUM + 8;
static_assert(SM_WORK_END % 1024 == 0 && STG_WO >= STG_V, "work area");
static_assert(SM_Y % 128 == 0, "exchange Y");
static_assert(CHAIN_SMEM <= 232448 && WO_RF1 >= 6, "smem");

#define DLY_X 250
#define DLY_V 0
#define DLY_Y 320
#define DLY_Z 280
#define TS_AT 5
#define EARLY_T 6
#define PH2 0
#define VF1 1
#define COLDV 0
#define COLD() true
#define RT0_B 1
#define PJ_FREE 1
#define PROD10 1
#define QF 0
#define AF 0
#define PRO_LATE 1
#define OTMA 1
#define TM 7
#define ORD0 2
#define ORD1 2
#define ORDV 2
__host__ __device__ constexpr int kstep(int ord, int i) { return ord == 0 ? i : ord == 1 ? (i + 24) % 32 : ord == 2 ? (i % 4 == 3 ? 24 + i / 4 : i / 4 * 3 + i % 4) : ord == 3 ? (i < 16 ? (i % 2 ? 24 + i / 2 : i / 2) : i - 8) : (i < 8 ? i : i < 16 ? i + 16 : i - 8); }

#define GV 1
#define NSV (GV ? 320 : 352)
#define Q3_AT 9
#define NA 7
#define NP2 5
#define P2_FENCE 0
#define SPLIT 5
#define TA0 16
#define Y_CHAIN 1
#define EF_W 1
#define XFLIP 0
#define YFLIP 0
#define ZFLIP 1
#define OFENCE 2
#define REG_A 240
#define REG_B 216
#define REG_C (3 * 168 - REG_A - REG_B)

enum { BAR_Y, BAR_MEM, BAR_PUB, BAR_QK, BAR_S, BAR_O, BAR_SENT, BAR_COMM, BAR_PUBV, BAR_PV, BAR_PDONE, BAR_VP, BAR_ZP, BAR_PRO, BAR_O2, BAR_SV,
       BAR_V = BAR_PV, BAR_SENTC = BAR_PDONE, BAR_Q3 = BAR_PRO, BAR_INV = BAR_PRO, BAR_XT0 = BAR_Y };

__device__ __forceinline__ uint32_t umax4(const uint4& v) { return max(max(v.x, v.y), max(v.z, v.w)); }
__device__ __forceinline__ unsigned gtime() { unsigned t; asm volatile("mov.u32 %0, %%globaltimer_lo;" : "=r"(t)::"memory"); return t; }
__device__ __forceinline__ unsigned clock32() { unsigned t; asm volatile("mov.u32 %0, %%clock;" : "=r"(t)::"memory"); return t; }
__device__ __forceinline__ void spin_cycles(int d) {
    if (d > 0) { const unsigned c0 = clock32(); while (clock32() - c0 < (unsigned)d) {} }
}
__device__ __forceinline__ float ex2_approx(float x) { float y; asm("ex2.approx.ftz.f32 %0, %1;" : "=f"(y) : "f"(x)); return y; }
__device__ __forceinline__ float rcp_approx(float x) { float y; asm("rcp.approx.ftz.f32 %0, %1;" : "=f"(y) : "f"(x)); return y; }
__device__ __forceinline__ void st_sent(const void* p) { asm volatile("st.relaxed.gpu.global.v4.u32 [%0], {%1,%1,%1,%1};" ::"l"(p), "r"(SENT) : "memory"); }
#define POLL_LD(p, a, b, c, d, addr) "@" p " ld.relaxed.gpu.global.v4.u32 {" a "," b "," c "," d "}, [" addr "];\n"
#define POLL_CK(p, a, b, c, d) "max.u32 m, " a "," b "; max.u32 n, " c "," d "; max.u32 m, m, n; setp.eq.u32 " p ", m, 0xFFFFFFFF;\n"
#define POLL_IO(v) "+r"(v.x), "+r"(v.y), "+r"(v.z), "+r"(v.w)
__device__ __forceinline__ void poll_init(uint4& v) { v = make_uint4(SENT, SENT, SENT, SENT); asm volatile("" : POLL_IO(v)); }
__device__ __forceinline__ int poll2(uint4 (&v)[2], const char* a) {
    int c = 0;
    asm volatile("{.reg .pred p0, p1, p; .reg .u32 m, n;\n"
                 "setp.eq.u32 p0, %8, 0; setp.eq.u32 p1, %8, 0;\n"
                 "POLL_LOOP:\n"
                 POLL_LD("p0", "%0", "%1", "%2", "%3", "%9") POLL_LD("p1", "%4", "%5", "%6", "%7", "%9+512")
                 "add.u32 %8, %8, 1;\n"
                 POLL_CK("p0", "%0", "%1", "%2", "%3") POLL_CK("p1", "%4", "%5", "%6", "%7")
                 "or.pred p, p0, p1; setp.lt.and.u32 p, %8, 0x10000, p; vote.sync.any.pred p, p, 0xFFFFFFFF;\n"
                 "@p bra.uni POLL_LOOP;}" : POLL_IO(v[0]), POLL_IO(v[1]), "+r"(c) : "l"(a) : "memory");
    return c;
}
template <int ST> __device__ __forceinline__ int poll4(uint4 (&v)[4], const char* a) {
    int c = 0;
    asm volatile("{.reg .pred p0, p1, p2, p3, p; .reg .u32 m, n;\n"
                 "setp.eq.u32 p0, %16, 0; setp.eq.u32 p1, %16, 0; setp.eq.u32 p2, %16, 0; setp.eq.u32 p3, %16, 0;\n"
                 "POLL_LOOP:\n"
                 POLL_LD("p0", "%0", "%1", "%2", "%3", "%17") POLL_LD("p1", "%4", "%5", "%6", "%7", "%17+%18")
                 POLL_LD("p2", "%8", "%9", "%10", "%11", "%17+%19") POLL_LD("p3", "%12", "%13", "%14", "%15", "%17+%20")
                 "add.u32 %16, %16, 1;\n"
                 POLL_CK("p0", "%0", "%1", "%2", "%3") POLL_CK("p1", "%4", "%5", "%6", "%7") POLL_CK("p2", "%8", "%9", "%10", "%11") POLL_CK("p3", "%12", "%13", "%14", "%15")
                 "or.pred p, p0, p1; or.pred p, p, p2; or.pred p, p, p3; setp.lt.and.u32 p, %16, 0x10000, p; vote.sync.any.pred p, p, 0xFFFFFFFF;\n"
                 "@p bra.uni POLL_LOOP;}" : POLL_IO(v[0]), POLL_IO(v[1]), POLL_IO(v[2]), POLL_IO(v[3]), "+r"(c) : "l"(a), "n"(ST), "n"(2 * ST), "n"(3 * ST) : "memory");
    return c;
}
__device__ __forceinline__ uint32_t add_bf16x2(uint32_t a, uint32_t b) { uint32_t r; asm("add.rn.bf16x2 %0, %1, %2;" : "=r"(r) : "r"(a), "r"(b)); return r; }
__device__ __forceinline__ uint32_t max_bf16x2(uint32_t a, uint32_t b) { uint32_t r; asm("max.bf16x2 %0, %1, %2;" : "=r"(r) : "r"(a), "r"(b)); return r; }
template <class F> __device__ __forceinline__ void softmax40(uint32_t (&pw)[6], uint32_t sa, F mid) {
    const float LOG2E = 1.4426950408889634f;
    uint32_t w[5];
    float e[10];
#pragma unroll
    for (int i = 0; i < 5; i++) w[i] = lds32(sa + i * 128);
    uint32_t m = max_bf16x2(max_bf16x2(max_bf16x2(w[0], w[1]), max_bf16x2(w[2], w[3])), w[4]);
    m = max_bf16x2(m, __shfl_xor_sync(~0u, m, 1));
    m = max_bf16x2(m, __shfl_xor_sync(~0u, m, 2));
    const float mb2 = fmaxf(bf_lo(m), bf_hi(m)) * LOG2E;
#pragma unroll
    for (int i = 0; i < 5; i++) {
        e[2 * i] = ex2_approx(fmaf(bf_lo(w[i]), LOG2E, -mb2));
        e[2 * i + 1] = ex2_approx(fmaf(bf_hi(w[i]), LOG2E, -mb2));
    }
    mid();
#pragma unroll
    for (int i = 0; i < 5; i++) pw[i] = pack_bf16(e[2 * i], e[2 * i + 1]);
    const float sum = (((e[0] + e[1]) + (e[2] + e[3])) + ((e[4] + e[5]) + (e[6] + e[7]))) + (e[8] + e[9]);
    const float hi = bf_hi(__float_as_uint(sum));
    pw[5] = pack_bf16(sum - hi, hi);
}
template <bool NORM, class F> __device__ __forceinline__ void pv32(uint32_t (&w)[4], float (&inv)[2], const uint32_t (&va)[2][2][4], const uint32_t (&vm)[4], const uint32_t (&pw)[6], F mid) {
    float o[2][3][4], t[4] = {0.f, 0.f, 0.f, 0.f};
#pragma unroll
    for (int i = 0; i < 3; i++)
#pragma unroll
        for (int m = 0; m < 2; m++) {
            o[m][i][0] = o[m][i][1] = o[m][i][2] = o[m][i][3] = 0.f;
            if (i < 2) mma16816(o[m][i], va[m][i & 1], pw[2 * i], pw[2 * i + 1]);
            else mma1688(o[m][i], vm[2 * m], vm[2 * m + 1], pw[4]);
        }
    mma1688(t, 0x3F803F80u, 0x3F803F80u, pw[5]);
    mid();
    if (NORM) { inv[0] = rcp_approx(t[0]); inv[1] = rcp_approx(t[1]); }
#pragma unroll
    for (int i = 0; i < 4; i++) {
        const float a = (o[i >> 1][0][2 * (i & 1)] + o[i >> 1][1][2 * (i & 1)]) + o[i >> 1][2][2 * (i & 1)];
        const float b = (o[i >> 1][0][2 * (i & 1) + 1] + o[i >> 1][1][2 * (i & 1) + 1]) + o[i >> 1][2][2 * (i & 1) + 1];
        w[i] = NORM ? pack_bf16(a * inv[0], b * inv[1]) : pack_bf16(a, b);
    }
    if (!NORM) { inv[0] = t[0]; inv[1] = t[1]; }
}
__device__ __forceinline__ uint32_t scale_scores(float a, float b) {
    const float scale = 0.08838834764831845f;
    const uint32_t w = pack_bf16(a, b);
    return pack_bf16(bf_lo(w) * scale, bf_hi(w) * scale);
}

#define TL(i) do {} while (0)
#define TLB(i) do {} while (0)
#define TLC(i) do {} while (0)

#define OPQ_LANE 1
#define SKEW 3
#define SUM_PRE 1
#define HOLD 2
#define SKEW_AT 1
static_assert(SKEW <= 3, "the ring has four stages");
#define CLAIM_T 64
#define PAD_A 0
#define PAD_B 0
#define PAD_C 0
template <int N> __device__ __forceinline__ void code_pad() {
#pragma unroll
    for (int i = 0; i < N; i++) asm volatile("pmevent 0;");
}

constexpr int TILE_N = 192, EARLY_TOK = 3 * TILE_N, LAST_N = S_LEN - EARLY_TOK - 7 * TILE_N, FLAG_END = NSEG + 3;
constexpr int PJ_STAGE = 16384 + TILE_N * 128, PJ_LOW = 0, PJ_MID = SM_XT + 2 * PJ_STAGE;
__device__ __forceinline__ uint32_t pj_stage(uint32_t i) { return SM_XT + (i & 1) * PJ_STAGE + (i >> 1 & 1) * (SM_WORK_END - SM_XT); }
static_assert(PJ_MID <= SM_QKV && PJ_MID + TILE_N * 128 <= SM_WORK_END && SM_WORK_END + 2 * PJ_STAGE <= SM_BARS && PJ_MID <= SM_OT && SM_OT % 512 == 0 && TILE_N * 128 <= SM_XT && LAST_N == 128, "projection");
template <class R, class F>
__device__ __forceinline__ void pj_fetch(uint32_t sb, uint32_t lane, uint32_t it, int nkb, int n, const CUtensorMap* mapW, const CUtensorMap* mapO, int col0, int col1, int k0, int tok, bool soon, R ready, F room) {
    auto weights = [&](int kb) {
        const uint32_t i = it + kb, sa = sb + pj_stage(i), full = sb + MB_FULL + (i & 3) * 8;
        mbar_wait(sb + MB_EMPTY + (i & 3) * 8, (~i >> 2) & 1);
        mbar_expect_tx(full, 16384 + n * 128);
        tma_load_2d(sa, mapW, col0, k0 + kb * 64, full);
        tma_load_2d(sa + 8192, mapW, col1, k0 + kb * 64, full);
    };
    auto rows = [&](int kb) {
        const uint32_t i = it + kb, sa = sb + pj_stage(i) + 16384, full = sb + MB_FULL + (i & 3) * 8;
        for (int t = 0; t < n; t += 64) tma_load_2d(sa + t * 128, mapO, k0 + kb * 64, tok + t, full);
    };
    if (soon) ready();
#pragma unroll 1
    for (int kb = 0; kb < 4; kb++) {
        if (kb == PJ_FREE) room();
        if (lane == 0) { weights(kb); if (soon) rows(kb); }
        __syncwarp();
    }
    if (!soon) ready();
    if (lane == 0) {
#pragma unroll 1
        for (int kb = 0; kb < 4; kb++) if (!soon) rows(kb);
#pragma unroll 1
        for (int kb = 4; kb < nkb; kb++) { weights(kb); rows(kb); }
    }
    __syncwarp();
}
template <int N, int SK = 0, class F>
__device__ __forceinline__ void pj_sum(float (&d)[N / 2], uint32_t sb, uint32_t lane, uint32_t wg, uint32_t it, int nkb, F last) {
    if (SK && HOLD && wg == 1) bar_arrive(BAR_O2, 256);
#pragma unroll
    for (int r = 0; r < N / 2; r++) d[r] = 0.f;
#pragma unroll 1
    for (int kb = 0; kb < nkb; kb++) {
        const uint32_t i = it + kb, sa = sb + pj_stage(i);
        if (SK && wg == 1 && kb == nkb - SK) bar_sync(BAR_O2, 256);
        if (SK && HOLD && wg == 0 && kb == HOLD) bar_sync(BAR_O2, 256);
        mbar_wait_w(sb + MB_FULL + (i & 3) * 8, (i >> 2) & 1);
        const uint64_t da = make_desc(sa + wg * 8192, 16, 1024), db = make_desc(sa + 16384, 16, 1024);
        wg_fence();
#pragma unroll
        for (int k = 0; k < 4; k++) wgmma_proj<N>(d, da + k * 128, db + k * 2);
        wg_commit();
        if (SK && SKEW_AT == 0 && wg == 0 && kb == nkb - 1) bar_arrive(BAR_O2, 256);
        if (kb > 0) { wg_wait<1>(); mbar_arrive_if0(lane, sb + MB_EMPTY + ((i - 1) & 3) * 8); }
    }
    if (SK && SKEW_AT == 1 && wg == 0) bar_arrive(BAR_O2, 256);
    last();
    wg_wait<0>();
    if (SK && SKEW_AT == 2 && wg == 0) bar_arrive(BAR_O2, 256);
    mbar_arrive_if0(lane, sb + MB_EMPTY + ((it + nkb - 1) & 3) * 8);
}
template <int N>
__device__ __forceinline__ void pj_store(const float (&d)[N / 2], uint32_t box, uint32_t t, int bar, const CUtensorMap* mapOut, int col, int tok) {
    const uint32_t ea = box + (((t >> 4) & 1) * 8 + (t & 7)) * 128 + ((((t >> 5) * 2 + ((t >> 3) & 1)) ^ (t & 7)) * 16);
#pragma unroll
    for (int r = 0; r < N / 16; r++)
        stsm4t(ea + r * 2048, pack_bf16(d[8 * r], d[8 * r + 1]), pack_bf16(d[8 * r + 2], d[8 * r + 3]), pack_bf16(d[8 * r + 4], d[8 * r + 5]), pack_bf16(d[8 * r + 6], d[8 * r + 7]));
    asm volatile("fence.proxy.async.shared::cta;" ::: "memory");
    bar_sync(bar, 128);
    if (t == 0) {
        for (int r = 0; r < N; r += 64) tma_store_2d(mapOut, box + r * 128, col, tok + r);
        asm volatile("cp.async.bulk.commit_group;" ::: "memory");
    }
}
template <int N>
__device__ __forceinline__ void pj_last(uint32_t sb, uint32_t wg, uint32_t t, int bar, const CUtensorMap* mapOut, int col, int tok) {
    float d[N / 2];
    mbar_expect_tx_if0(t | (wg ^ 1), sb + MB_SUM, N * 128);
    uint4 u[N / 16];
    pj_sum<N, SKEW>(d, sb, t & 31, wg, 0, 32, [&]() {
        if (SUM_PRE && wg == 1) {
            mbar_wait_w(sb + MB_SUM, 0);
#pragma unroll
            for (int r = 0; r < N / 16; r++) u[r] = lds128(sb + PJ_LOW + t * 16 + r * 2048);
        }
        if (SUM_PRE && wg == 0) mbar_wait_w(sb + MB_FREE, LEAD & 1);
    });
    if (wg == 0) {
        const uint32_t rsb = sb ^ (1u << 24), dst = rsb + PJ_LOW + t * 16;
        if (!SUM_PRE) mbar_wait_w(sb + MB_FREE, LEAD & 1);
#pragma unroll
        for (int r = 0; r < N / 16; r++)
            st_async4(dst + r * 2048, __uint_as_float(pack_bf16(d[8 * r], d[8 * r + 1])), __uint_as_float(pack_bf16(d[8 * r + 2], d[8 * r + 3])),
                      __uint_as_float(pack_bf16(d[8 * r + 4], d[8 * r + 5])), __uint_as_float(pack_bf16(d[8 * r + 6], d[8 * r + 7])), rsb + MB_SUM);
    } else {
        if (!SUM_PRE) mbar_wait_w(sb + MB_SUM, 0);
#pragma unroll
        for (int r = 0; r < N / 16; r++) {
            const uint4 v = SUM_PRE ? u[r] : lds128(sb + PJ_LOW + t * 16 + r * 2048);
            d[8 * r] += bf_lo(v.x); d[8 * r + 1] += bf_hi(v.x); d[8 * r + 2] += bf_lo(v.y); d[8 * r + 3] += bf_hi(v.y);
            d[8 * r + 4] += bf_lo(v.z); d[8 * r + 5] += bf_hi(v.z); d[8 * r + 6] += bf_lo(v.w); d[8 * r + 7] += bf_hi(v.w);
        }
        pj_store<N>(d, sb + PJ_MID, t, bar, mapOut, col, tok);
        if (t == 0) asm volatile("cp.async.bulk.wait_group.read 0;" ::: "memory");
        __syncwarp();
    }
}
#define NOINL 0
__device__ __forceinline__
void pj_tile(uint32_t wg, const CUtensorMap* mapOut) {
    uint32_t t, rank;
    asm volatile("mov.u32 %0, %%tid.x; and.b32 %0, %0, 127; mov.u32 %1, %%ctaid.x; and.b32 %1, %1, 1;" : "=r"(t), "=r"(rank));
    const uint32_t base = 1024 | (rank << 24), pr = lds32(base + SM_ROLE);
    const int col = (pr & 7) * 128 + 64 * rank, tok = EARLY_TOK + (pr >> 3) * TILE_N;
    if (pr >> 3 == 7) pj_last<LAST_N>(base, wg, t, BAR_O, mapOut, col, tok); else pj_last<TILE_N>(base, wg, t, BAR_O, mapOut, col, tok);
}
__device__ __forceinline__ void pj_early(uint32_t sb, uint32_t e, uint32_t rank, const CUtensorMap* mapW, const CUtensorMap* mapO, const CUtensorMap* mapOut) {
    const uint32_t warp = threadIdx.x >> 5, lane = threadIdx.x & 31;
    if (warp == 8) {
        wait_prerequisites();
#pragma unroll 1
        for (int i = 0; i < EARLY_T; i++) {
            const int col = ((i & 1) * 4 + e * 2 + rank) * 128;
            pj_fetch(sb, lane, i * 64, 64, TILE_N, mapW, mapO, col, col + 64, 0, (i >> 1) * TILE_N, false, [&]() {
                if (i & 1) return;
                const unsigned need = TILE_N / SEG * (i / 2 + 1) + LEAD;
                for (int guard = 0; guard < (1 << 16); guard++) {
                    const uint4 f = ld_relaxed_v4(g_xflag + lane * 4);
                    if (__all_sync(~0u, min(min(f.x, f.y), min(f.z, f.w)) >= need)) break;
                    __nanosleep(500);
                }
                asm volatile("fence.acq_rel.gpu; fence.proxy.async.global;" ::: "memory");
                if (i == 0 && rank == 0 && lane == 0 && atomicAdd(g_reg + 2, 1) == 1) {
                    g_reg[0] = 0;
                    for (int k = 0; k < 64; k++) reinterpret_cast<uint4*>(g_cls)[k] = make_uint4(0, 0, 0, 0);
                }
                __syncwarp();
            }, []() {});
        }
    } else if (warp < 8) {
        const uint32_t wg = warp >> 2, t = threadIdx.x & 127;
#pragma unroll 1
        for (int i = 0; i < EARLY_T; i++) {
            float d[TILE_N / 2];
            pj_sum<TILE_N>(d, sb, lane, wg, i * 64, 64, []() {});
            if (t == 0) asm volatile("cp.async.bulk.wait_group.read 0;" ::: "memory");
            bar_sync(1 + wg, 128);
            pj_store<TILE_N>(d, sb + (wg ? PJ_MID : PJ_LOW), t, 1 + wg, mapOut, ((i & 1) * 4 + e * 2 + rank) * 128 + wg * 64, (i >> 1) * TILE_N);
        }
        if (t == 0) asm volatile("cp.async.bulk.wait_group 0;" ::: "memory");
    }
    __syncwarp();
}
template <bool TAIL>
__global__ void __cluster_dims__(2, 1, 1) __launch_bounds__(384, 1)
chain_kernel(char* __restrict__ mbox, const bf16* __restrict__ mem0,
             const __grid_constant__ CUtensorMap mapX, const __grid_constant__ CUtensorMap mapT32, const __grid_constant__ CUtensorMap mapT16,
             const __grid_constant__ CUtensorMap mapTQ, const __grid_constant__ CUtensorMap mapKV,
             const __grid_constant__ CUtensorMap mapWq, const __grid_constant__ CUtensorMap mapWk, const __grid_constant__ CUtensorMap mapWv,
             const __grid_constant__ CUtensorMap mapWo, const __grid_constant__ CUtensorMap mapPW, const __grid_constant__ CUtensorMap mapPO,
             const __grid_constant__ CUtensorMap mapOut, const __grid_constant__ CUtensorMap mapO8) {
    KT_START(2);
    extern __shared__ __align__(1024) uint8_t smem_chain[];
    constexpr uint32_t SB0 = 1024;
    if (smem_u32(smem_chain) != (SB0 | ((blockIdx.x & 1) << 24))) __trap();
    const int kh = blockIdx.x & 1;
    if (threadIdx.x == 0) {
        const uint32_t sb = smem_u32(smem_chain);
        for (int i = 0; i < 14; i++) mbar_init(sb + SM_BARS + 8 * i, 1);
        mbar_init(sb + MB_P, 4); mbar_init(sb + MB_V, 4); mbar_init(sb + MB_STG, 8); mbar_init(sb + MB_ROLE, 1); mbar_init(sb + MB_W4, 1); mbar_init(sb + MB_W5, 1);
        mbar_expect_tx(sb + MB_ROLE, 4);
        asm volatile("fence.mbarrier_init.release.cluster;" ::: "memory");
    }
    if (TAIL && threadIdx.x == 96) {
        const uint32_t sb = smem_u32(smem_chain);
        for (int i = 0; i < 4; i++) { mbar_init(sb + MB_FULL + 8 * i, 1); mbar_init(sb + MB_EMPTY + 8 * i, 8); }
        mbar_init(sb + MB_SUM, 1);
        asm volatile("fence.mbarrier_init.release.cluster;" ::: "memory");
    }
    if (threadIdx.x == 32) { prefetch_map(&mapWv); prefetch_map(&mapWq); prefetch_map(&mapWk); prefetch_map(&mapWo); prefetch_map(&mapX); }
    __syncwarp();
    asm volatile("barrier.cluster.arrive.relaxed.aligned;" ::: "memory");
    unsigned claimed = 0;
    if (threadIdx.x == CLAIM_T && kh == 0) claimed = claim_pair(g_reg) & 255;
    __syncwarp();
    asm volatile("barrier.cluster.wait.acquire.aligned;" ::: "memory");
    if (threadIdx.x == CLAIM_T && kh == 0) {
        st_async1((SB0 | (1u << 24)) + SM_ROLE, claimed, (SB0 | (1u << 24)) + MB_ROLE);
        st_async1(SB0 + SM_ROLE, claimed, SB0 + MB_ROLE);
    }
    __syncwarp();
    mbar_wait_w(smem_u32(smem_chain) + MB_ROLE, 0);
    const int pair = uniform(lds32(smem_u32(smem_chain) + SM_ROLE));
#define YFLIP_() (uniform(lds32(sb + SM_ROLE + 4)) ^ YFLIP)
    if (pair >= 64) {
        if (TAIL) pj_early(smem_u32(smem_chain), pair - 64, kh, &mapPW, &mapPO, &mapOut);
        if (TAIL) KT_END(3);
        return;
    }
    if (threadIdx.x == 0) KT_MARK(5);
    const int h = pair >> 1, nh = pair & 1, j = 2 * nh + kh, role = 2 * pair + kh;
#define WG_ORDER 0x210
    const int warp = uniform(((WG_ORDER >> (4 * (threadIdx.x >> 7))) & 3) * 4 + ((threadIdx.x >> 5) & 3));
    const uint32_t g = warp & 3, sb = SB0 | (kh << 24), rsb = sb ^ (1u << 24), cls = pair >> 5, kflip = ZFLIP ^ kh;
    const uint32_t mlo = (uint32_t)(uintptr_t)mbox, mhi = (uint32_t)((uintptr_t)mbox >> 32);
    auto lane16 = [&]() {
        uint32_t t;
        asm volatile("{.reg .u32 l, x; mov.u32 l, %%laneid; xor.b32 x, l, 1; shl.b32 x, x, 4; shfl.sync.bfly.b32 %0, x, 1, 0x1f, 0xffffffff;}" : "=r"(t));
        return t;
    };
#define PHASE(k) uint32_t L; asm volatile("{.reg .u32 t; shr.u32 t, %1, %3; add.u32 %0, %2, t;}" : "=r"(L) : "r"(it), "r"(l16), "n"(8 + (k)))
#define ROWPAT() ((((L << 3) & 0x380) | ((L << 2) & 0x400)) | ((L ^ (L >> 3)) & 0x10) | (L & 0x60))
#define FRAG() (ROWPAT() ^ (g << 5))
#define QFRAG() ((((L >> 1) & 0x80) | (L & 0x70)) + ((L & 0x80) ? SM_KV + 16384 + kvo : SM_QKV))
#define VFRAG() (ROWPAT() ^ ((g & 1) << 6))
#define VBASE() (sb + SM_KV + 8192 + (g >> 1) * 4096 + kvo)
#define XTLO() ((uint32_t)make_desc(SB0 + SM_XT, 16, 1024) + (ui & 1) * 2048)
    auto last_tile = [&](uint32_t wg) {
        KT_END(2);
        pj_tile(wg, &mapOut);
    };
    if (warp >= 8) {
        asm volatile("setmaxnreg.dec.sync.aligned.u32 %0;" ::"n"(REG_C));
        code_pad<PAD_C>();
        const uint32_t l16 = lane16(), lane = l16 >> 4;
        auto load_xt = [&](int seg, int half) {
            const uint32_t bar = sb + MB_XT + (seg & 1) * 8;
            if (half == 0) mbar_expect_tx(bar, 32768);
            asm volatile("cp.async.bulk.tensor.3d.shared::cluster.global.mbarrier::complete_tx::bytes [%0], [%1, {%3, %4, %5}], [%2];"
                         ::"r"(sb + SM_XT + (seg & 1) * 32768 + half * 16384), "l"(&mapX), "r"(bar), "r"(0), "r"(seg * SEG), "r"(8 * kh + 4 * (half ^ kflip)) : "memory");
        };
        if (warp == 8) {
            const CUtensorMap* ws = kh ? &mapWq : &mapWk;
            const CUtensorMap* wn = kh ? &mapWk : &mapWq;
            const uint64_t pol = EF_W ? policy_evict_first() : policy_evict_normal();
            const int col = h * DH + 64 * nh, row = 512 * kh;
            if (lane == 0) { mbar_expect_tx(sb + MB_W0, 49152); mbar_expect_tx(sb + MB_W1, 49152); mbar_expect_tx(sb + MB_W4, 49152); mbar_expect_tx(sb + MB_W2, 49152); mbar_expect_tx(sb + MB_W3, 65536); }
            __syncwarp();
            if (lane < 24) {
                const int k = lane ^ (16 * kflip);
                tma_load_2d(sb + STG_V + lane * 2048, &mapWv, col, row + 16 * k, sb + MB_W0, pol);
                tma_load_2d(sb + stg_qk(0, lane), ws, col, row + 16 * k, sb + MB_W1, pol);
                tma_load_2d(sb + stg_qk(1, lane), wn, col, row + 16 * k, sb + MB_W4, pol);
            }
            if (lane < 8) {
                const int k = (24 + lane) ^ (16 * kflip);
                tma_load_2d(sb + SM_WQK + lane * 4096, ws, col, row + 16 * k, sb + MB_W2, pol);
                tma_load_2d(sb + SM_WQK + lane * 4096 + 2048, wn, col, row + 16 * k, sb + MB_W2, pol);
                tma_load_2d(sb + SM_WV + lane * 2048, &mapWv, col, row + 16 * k, sb + MB_W2, pol);
            }
            __syncwarp();
        }
        if (warp == 9) {
            bar_sync(BAR_XT0, 160);
            if (lane == 0) { load_xt(0, 0); load_xt(0, 1); }
            __syncwarp();
        }
        if (warp == 10 && lane == 0) {
            wait_prerequisites();
            launch_dependents();
            sts32(sb + SM_ROLE + 4, g_reg[1]);
        }
        __syncwarp();
        bar_sync(BAR_PDONE, 384);
        KT_MARK(9);
        if ((warp & 1) == 0) for (int c = (warp - 8) * 16 + lane; c < 512; c += 64) {
            uint32_t w[4];
#pragma unroll
            for (int r = 0; r < 4; r++) {
                const uint32_t lo = reinterpret_cast<const uint16_t*>(mem0)[(2 * r) * DM + 512 * kh + c], hi = reinterpret_cast<const uint16_t*>(mem0)[(2 * r + 1) * DM + 512 * kh + c];
                w[r] = lo | (hi << 16);
            }
            sts128(sb + SM_Z + (c ^ (256 * kflip)) * 16, make_uint4(w[0], w[1], w[2], w[3]));
        }
        if (warp == 11) {
            const uint32_t dst = lane < 14 ? stg_wo(lane) : lane < 16 ? SM_WO1 + (lane - 8) * 2048 : SM_WO2 + (lane - 16) * 2048;
            tma_load_2d(sb + dst, &mapWo, 256 * j + 64 * (lane >> 3), h * DH + 16 * (lane & 7), sb + MB_W3, EF_W ? policy_evict_first() : policy_evict_normal());
        }
        auto tok_start = [&](int s) {
            if (lane == 0) {
                if (TS_AT == 0) TL(21);
                if (s > -LEAD && (OTMA || s + LEAD - 1 < NSEG)) {
                    mbar_wait(sb + MB_STG, (s + LEAD - 1) & 1);
                    if (TS_AT == 1) TL(21);
                    if (TS_AT == 2) TL(21);
                    asm volatile("fence.proxy.async.shared::cta;" ::: "memory");
                    if (TS_AT == 3) TL(21);
                    const int r = ((s + LEAD - 1) & 3) * NH + h;
                    if (s + LEAD - 1 < NSEG) {
                        tma_store_2d(kh ? &mapT32 : &mapTQ, sb + SM_STG, kh ? 64 * nh : 256 * nh, kh ? r * 96 + 32 : r * 12);
                        tma_store_2d(&mapT16, sb + SM_STG + 4096, 64 * nh, r * 96 + 64 + 16 * kh);
                    }
                    if (OTMA && s > 0) tma_store_3d(&mapO8, sb + SM_OT, 0, (s - 1) * SEG + 8 * j, 4 * h);
                    asm volatile("cp.async.bulk.commit_group;" ::: "memory");
                    if (TS_AT == 4) TL(21);
                }
                if (s + LEAD + 1 < NSEG) load_xt(s + LEAD + 1, 0);
                if (s < 0) asm volatile("cp.async.bulk.wait_group.read 0;" ::: "memory");
                if (s < 0) {
                    asm volatile("mbarrier.arrive.shared::cluster.b64 _, [%0];" ::"r"(rsb + MB_FREE) : "memory");
                    mbar_wait(sb + MB_FREE, (s + LEAD) & 1);
                }
            }
            __syncwarp();
        };
        auto tok_mid = [&](int s, bool flag) {
            if (lane == 0) {
                if (s + LEAD + 1 < NSEG) load_xt(s + LEAD + 1, 1);
                if (flag && s > -LEAD && s + LEAD - 1 < NSEG) {
                    asm volatile("cp.async.bulk.wait_group 0;" ::: "memory");
                    st_relaxed_u32(g_xflag + role, s + LEAD);
                }
            }
            __syncwarp();
        };
        auto tok_flag = [&](int s) {
            asm volatile("cp.async.bulk.wait_group 0;" ::: "memory");
            asm volatile("{.reg .pred p; setp.lt.u32 p, %2, %3; @p st.relaxed.gpu.global.u32 [%0], %1;}" ::"l"(g_xflag + role), "r"(s + LEAD), "r"(s + (l16 << 8)), "n"(NSEG + 1 - LEAD) : "memory");
        };
        auto kv_check = [&](int s) {
            if (s + 1 < NSEG) {
                if (lane < 4) {
                    unsigned f; int guard = 0;
                    do {
                        asm volatile("ld.acquire.gpu.global.u32 %0, [%1];" : "=r"(f) : "l"(g_xflag + h * 4 + lane) : "memory");
                        if (++guard > (1 << 20)) __trap();
                    } while (f <= (unsigned)(s + 1));
                }
                __syncwarp();
                asm volatile("fence.proxy.async.global;" ::: "memory");
            }
        };
        auto kv_load = [&](int s) {
            if (lane == 0 && s + 1 < NSEG) {
                const uint32_t bar = sb + MB_KV + ((s + 1) & 1) * 8, dst = sb + SM_KV + ((s + 1) & 1) * KV_BYTES;
                const int row = (((s + 1) & 3) * NH + h) * 96;
                mbar_expect_tx(bar, KV_BYTES);
                if (KVMC) asm volatile("cp.async.bulk.tensor.3d.shared::cluster.global.mbarrier::complete_tx::bytes.multicast::cluster [%0], [%1, {%3, %4, %3}], [%2], %5;"
                             ::"r"(dst + kh * 8192), "l"(&mapKV), "r"(bar), "r"(0), "r"(row + 32 + 32 * kh), "h"((uint16_t)3) : "memory");
                else for (int i = 0; i < 2; i++) asm volatile("cp.async.bulk.tensor.3d.shared::cluster.global.mbarrier::complete_tx::bytes [%0], [%1, {%3, %4, %3}], [%2];"
                             ::"r"(dst + i * 8192), "l"(&mapKV), "r"(bar), "r"(0), "r"(row + 32 + 32 * i) : "memory");
                bulk_load(dst + 16384, g_tok + row * DH + j * 1024, 2048, bar);
            }
            __syncwarp();
        };
        if (warp == 9) {
#pragma unroll 1
            for (int s = -LEAD; s < 0; s++) { tok_start(s); KT_MARK(13 + s); bar_arrive(BAR_PRO, 288); tok_mid(s, true); }
        }
        if (warp == 11) { kv_check(-1); kv_load(-1); }
        bar_arrive(BAR_MEM, 384);
        const uint32_t idx = (pair & 31) + 32 * (kh ^ 1);
        const uint32_t ybox = mlo + page_off(idx, cls ^ YFLIP_()), xoth = mlo + WIN + page_off((pair & 31) ^ 1, cls ^ XFLIP);
        const uint32_t zline = mlo + WIN + page_off(32 + (idx >> 5), cls ^ ZFLIP) + (idx & 31) * 128, zbox = mlo + WIN + (page_off(32 + kh, 0) & ~4096u);
        const uint32_t xtype = g == GV ? 2 : g == 2 ? 0 : 1;
        const int send = TAIL && PROD10 && g == 2 ? NSEG - 1 : NSEG;
        const uint32_t ydst = (lane >> 3) * 128 + ((lane & 7) ^ (lane >> 3)) * 16, ysrc = lane * 128 + ((2 * g) ^ (lane & 7)) * 16;
#pragma unroll 1
        for (int s = 0; s < send; s++) {
            const uint32_t slot = (s & 3) << 14;
            if (g == 3) {
                if (KC_AT == 0) kv_check(s);
                unsigned f = 0;
                const unsigned* fp = g_xflag + h * 4 + (lane & 3);
                auto kv_seen = [&]() {
                    for (int guard = 0; guard < (1 << 20) && s + 1 < NSEG && __any_sync(~0u, f <= (unsigned)(s + 1)); guard++) {
                        asm volatile("ld.relaxed.gpu.global.u32 %0, [%1];" : "=r"(f) : "l"(fp) : "memory");
                    }
                    asm volatile("fence.proxy.async.global;" ::: "memory");
                };
                if (TS_AT == 9) TL(21);
                const uint32_t L = l16, kvo = (s & 1) * KV_BYTES, qa = QFRAG(), sa = sb + SM_S + 512 + (L >> 2);
                float sc[4] = {0.f, 0.f, 0.f, 0.f}, sd[4] = {0.f, 0.f, 0.f, 0.f};
                uint32_t a[4][4], kb[2][4];
                mbar_wait_w(sb + MB_KV + (s & 1) * 8, (s >> 1) & 1);
                mbar_wait_w(sb + MB_P, s & 1);
#pragma unroll
                for (int c = 0; c < 2; c++) {
                    const uint32_t qc = qa + (sb + (nh ^ c) * 1024), kc = L + (sb + SM_QKV + 2048 + (nh ^ c) * 1024);
                    if (TS_AT == 7 && c) TL(21);
                    if (KC_AT == 4 && c) asm volatile("ld.relaxed.gpu.global.u32 %0, [%1];" : "=r"(f) : "l"(fp) : "memory");
                    if (c) bar_sync(BAR_QK, 224);
                    if (KC_AT == 1 && c) asm volatile("ld.relaxed.gpu.global.u32 %0, [%1];" : "=r"(f) : "l"(fp) : "memory");
                    ldsm4t(kb[0], kc); ldsm4t(a[0], qc); ldsm4t(a[1], qc + 256);
                    ldsm4t(kb[1], kc + 512); ldsm4t(a[2], qc + 512); ldsm4t(a[3], qc + 768);
                    mma16816v(sc, a[0], kb[0][0], kb[0][1]);
                    mma16816v(sd, a[1], kb[0][2], kb[0][3]);
                    mma16816v(sc, a[2], kb[1][0], kb[1][1]);
                    mma16816v(sd, a[3], kb[1][2], kb[1][3]);
                }
                sts32(sa, scale_scores(sc[0] + sd[0], sc[1] + sd[1]));
                sts32(sa + 768, scale_scores(sc[2] + sd[2], sc[3] + sd[3]));
                bar_arrive(BAR_S, 160);
                if (KC_AT == 2) asm volatile("ld.relaxed.gpu.global.u32 %0, [%1];" : "=r"(f) : "l"(fp) : "memory");
                TL(25);
                if (KC_AT && KC_PRE) kv_seen();
                if (KC_PRE == 3) kv_load(s);
                bar_sync(BAR_SV, NSV);
                if (KC_AT == 0 || KC_PRE == 2) kv_load(s);
                if (!RTW && lane == 0 && s + LEAD < NSEG) {
                    if (!RTF) asm volatile("fence.proxy.async.shared::cta;" ::: "memory");
                    asm volatile("cp.async.bulk.shared::cluster.shared::cta.mbarrier::complete_tx::bytes [%0], [%1], %2, [%3];" ::"r"(rsb + SM_RT), "r"(sb + SM_Z), "n"(8192), "r"(rsb + MB_RT0) : "memory");
                    if (TS_AT == 10) { mbar_wait(sb + MB_RT0, (s + LEAD) & 1); TL(21); }
                }
                __syncwarp();
                if (KC_AT && KC_PRE == 0) kv_seen();
                if (XT11 == 1) tok_mid(s, false);
                if (KC_AT && KC_PRE < 2) kv_load(s);
                if (XT11 == 2) tok_mid(s, false);
            } else {
                if (g == 1) { tok_start(s); if (XT_AT == 2) tok_mid(s, false); if (FL_AT == 4) tok_flag(s); if (XT_AT == 3) tok_mid(s, false); if (TS_AT == 5) TL(21); if (s == 0) KT_MARK(13); }
                const char* p = make_ptr(l16 + (xoth + xtype * 1024 + slot), mhi);
                uint4 v[2];
                const uint32_t dst = l16 + (sb + SM_QKV + xtype * 2048 + (nh ^ 1) * 1024);
                asm volatile("" ::"l"(p));
                poll_init(v[0]); poll_init(v[1]);
                if (g == GV) {
                    bar_sync(BAR_PUBV, 160);
                    if (FL_AT == 1) tok_flag(s);
                    mbar_wait_w(sb + MB_V, s & 1);
                    if (FL_AT == 2) tok_flag(s);
                    spin_cycles(DLY_V);
                } else {
                    bar_sync(BAR_PUB, 192);
                    spin_cycles(DLY_X);
                }
                const int r = poll2(v, p);
                sts128(dst, v[0]); sts128(dst + 512, v[1]);
                STAT(1, r > 1 && warp == 10);
                if (g != GV) bar_arrive(BAR_QK, 224);
                if (TS_AT == 6 && g == 0) TL(21);
                if (FL_AT == 3 && g == 1) tok_flag(s);
                if (OTMA && FL_AT == 0 && g == 1) asm volatile("cp.async.bulk.wait_group.read 0;" ::: "memory");
                if (g == GV) { bar_arrive(BAR_V, 160); if (GV == 0) bar_arrive(BAR_SV, NSV); TL(17); }
                if (g == 1) {
                    TL(31);
                    if (!OTMA) asm volatile("cp.async.bulk.wait_group.read 0;" ::: "memory");
                    if (XT_AT == 1) tok_mid(s, false);
                    if (XT_AT == 0 && !XT11) bar_sync(BAR_SV, NSV);
                    else bar_arrive(BAR_SV, NSV);
                    if (!XT11 && XT_AT == 0) tok_mid(s, FL_AT == 0);
                    TL(22);
                }
                if (g == 2 && s >= 1) {
                    TL(16);
                    const uint32_t prev = (slot - 0x4000) & 0xC000;
                    const char* y = make_ptr(l16 + (ybox + prev), mhi);
                    const char* x = make_ptr(l16 + (xoth + prev + kh * 1536), mhi);
#pragma unroll
                    for (int i = 0; i < 8; i++) st_sent(y + i * 512);
#pragma unroll
                    for (int i = 0; i < 3; i++) st_sent(x + i * 512);
                    st_relaxed_u32(make_ptr(lane * 4 + (zline + (slot ^ 0x8000)), mhi), SENT);
                    TL(23);
                }
            }
            if (s + 1 == NSEG) break;
            {
                const char* p = make_ptr(l16 + (ybox + g * 1024 + slot), mhi);
                char* zdst = make_ptr(lane * 4 + (zline + g * 32 + slot), mhi);
                const uint32_t dst = ydst + (sb + SM_Y + g * 1024), dst1 = (ydst ^ 64) + (sb + SM_Y + g * 1024 + 512), src = ysrc + (sb + SM_Y), src1 = (ysrc ^ 16) + (sb + SM_Y);
                asm volatile("" ::"l"(p), "l"(zdst));
                uint4 v[2];
                poll_init(v[0]); poll_init(v[1]);
                bar_sync(BAR_SENTC, 384);
                spin_cycles(DLY_Y);
                const int r = poll2(v, p);
                STAT(2, r > 1 && warp == 8);
                sts128(dst, v[0]); sts128(dst1, v[1]);
                bar_sync(BAR_Y, 256);
                TL(18);
                uint32_t b[2][4];
                ldsm4t(b[0], src); ldsm4t(b[1], src1);
                const uint32_t one = 0x3F803F80u;
                float d0[4] = {0.f, 0.f, 0.f, 0.f}, d1[4] = {0.f, 0.f, 0.f, 0.f};
                mma16816(d0, one, one, one, one, b[0][0], b[0][1]);
                mma16816(d1, one, one, one, one, b[1][0], b[1][1]);
                mma16816(d0, one, one, one, one, b[0][2], b[0][3]);
                mma16816(d1, one, one, one, one, b[1][2], b[1][3]);
                const uint32_t w = (lane & 4) ? pack_bf16(d1[0], d1[1]) : pack_bf16(d0[0], d0[1]);
                asm volatile("{.reg .pred p; setp.lt.u32 p, %2, 128; @p st.relaxed.gpu.global.u32 [%0], %1;}" ::"l"(zdst), "r"(w), "r"(l16) : "memory");
                if (s + LEAD < NSEG) bar_arrive(BAR_ZP, 256);
                TL(19);
            }
            {
                const char* p = make_ptr(l16 + (zbox + g * 512 + slot), mhi);
                const uint32_t dst = l16 + (sb + SM_Z + g * 512);
                asm volatile("" ::"l"(p));
                uint4 v[4];
                poll_init(v[0]); poll_init(v[1]); poll_init(v[2]); poll_init(v[3]);
                bar_sync(BAR_COMM, 128);
                spin_cycles(DLY_Z);
                const int r = poll4<2048>(v, p);
                STAT(0, r > 1 && warp == 8);
#pragma unroll
                for (int i = 0; i < 4; i++) sts128(dst + i * 2048, v[i]);
                bar_arrive(BAR_MEM, 384);
                TL(20);
            }
        }
        if ((OTMA || TAIL) && (TM & 4) && COLD()) {
            uint32_t t, rank;
            asm volatile("mov.u32 %0, %%tid.x; mov.u32 %1, %%ctaid.x; and.b32 %1, %1, 1;" : "=r"(t), "=r"(rank));
            const uint32_t base = SB0 | (rank << 24), ln = t & 31, pr = lds32(base + SM_ROLE), col = (pr & 7) * 128, tg = pr >> 3;
            if (t >> 5 == (PROD10 ? 10 : 8)) {
                if (TAIL) {
                if (PROD10) {
                    bar_arrive(BAR_PUB, 192); bar_arrive(BAR_QK, 224);
                    if (ln == 0) { prefetch_map(&mapPW); prefetch_map(&mapPO); prefetch_map(&mapOut); }
                    __syncwarp();
                }
                pj_fetch(base, ln, 0, 32, tg == 7 ? LAST_N : TILE_N, &mapPW, &mapPO, col + 64 * (rank ^ 1), col + 64 * rank, HD / 2 * rank, EARLY_TOK + tg * TILE_N, PROD10 && tg < 7, [&]() {
                    const unsigned need = tg == 7 ? FLAG_END : (S_LEN - LAST_N) / SEG + LEAD;
                    for (int guard = 0; guard < (1 << 20); guard++) {
                        uint32_t f0, f1;
                        asm volatile("{.reg .b64 t; ld.acquire.gpu.global.b64 t, [%2]; mov.b64 {%0, %1}, t;}" : "=r"(f0), "=r"(f1) : "l"(g_xflag + 64 * rank + 2 * ln) : "memory");
                        if (__all_sync(~0u, min(f0, f1) >= need)) break;
                    }
                    asm volatile("fence.proxy.async.global;" ::: "memory");
                }, [&]() {
                    mbar_wait_w(base + MB_P, (NSEG - 1) & 1);
                    mbar_wait_w(base + MB_V, (NSEG - 1) & 1);
                });
                }
            } else if (t >> 5 == 9) {
                bar_sync(BAR_ZP, 160);
                if (ln == 0) {
                    if (OTMA) {
                        asm volatile("fence.proxy.async.shared::cta;" ::: "memory");
                        tma_store_3d(&mapO8, base + SM_OT, 0, S_LEN - SEG + 16 * (pr & 1) + 8 * rank, 2 * (pr & ~1u));
                        asm volatile("cp.async.bulk.commit_group;" ::: "memory");
                    }
                    if (OTMA) asm volatile("cp.async.bulk.wait_group 0;" ::: "memory");
                    if (TAIL) asm volatile("mbarrier.arrive.shared::cluster.b64 _, [%0];" ::"r"((base ^ (1u << 24)) + MB_FREE) : "memory");
                    if (!OTMA) asm volatile("fence.acq_rel.gpu;" ::: "memory");
                    if (TAIL) st_relaxed_u32(g_xflag + 2 * pr + rank, FLAG_END);
                }
                __syncwarp();
            }
        }
    } else if (warp < 4) {
        asm volatile("setmaxnreg.inc.sync.aligned.u32 %0;" ::"n"(REG_A));
        code_pad<PAD_A>();
        const uint32_t l16 = lane16();
        uint32_t wa[2][24][4];
        {
            const uint32_t L = l16, fa = sb + FRAG();
            mbar_wait_w(sb + MB_W1, 0);
            KT_MARK(7);
#pragma unroll
            for (int t = 0; t < 2; t++) {
#pragma unroll
                for (int r = 0; r < 24; r++) ldsm4t(wa[t][r], fa + stg_qk(t, r));
                if (t == 0) { bar_arrive(BAR_XT0, 160); mbar_wait_w(sb + MB_W4, 0); }
            }
            mbar_wait_w(sb + MB_W2, 0);
            bar_sync(BAR_PDONE, 384);
        }
        auto batch1 = [&](float (&d)[16], uint32_t lo, auto tc, auto k0c, auto k1c) {
            constexpr int t = decltype(tc)::value;
            const uint64_t da = make_desc(SB0 + SM_WQK, 16, 1024);
            wg_fence();
            static_for<decltype(k0c)::value, decltype(k1c)::value>([&](auto kc) {
                constexpr int i = decltype(kc)::value, k = kstep(t ? ORD1 : ORD0, i), off = (k >> 2) * 256 + (k & 3) * 2;
                if constexpr (k >= 24) wgmma_ss32u<off, i != 0 || t != 0>(d, da + ((k - 24) * 2 + t) * 128, lo);
                else wgmma_rs32u<off, i != 0 || t != 0>(d, wa[t][k], lo);
            });
            wg_commit();
        };
        const uint32_t xbox = mlo + WIN + page_off(pair & 31, cls ^ XFLIP);
        const uint32_t ybox = mlo + page_off(24 + 2 * g + 32 * nh, kh ^ YFLIP_()) + h * 128;
#pragma unroll 1
        for (uint32_t it = 0; it < NSEG + LEAD; it++) {
            const int s = (int)it - LEAD;
            const uint32_t ui = uniform(it), slot = ((ui + 4 - LEAD) & 3) << 14, kvo = ((LEAD & 1 ? ~ui : ui) & 1) * KV_BYTES, xtlo = XTLO();
            {
                PHASE(5);
                const uint32_t first = L | (g << 9);
                if (s >= 0) mbar_expect_tx_if0(first, sb + MB_R1, 2048);
                if (s + LEAD < NSEG) {
                    mbar_expect_tx_if0(first, sb + MB_RT0, 8192);
                    mbar_wait_w(sb + MB_XT + (ui & 1) * 8, (it >> 1) & 1);
                }
            }
            if (s >= 0) {
                PHASE(0);
                const uint32_t mb = L + (sb + SM_Z), ra = L + (sb + g * 512), r1 = L + (rsb + SM_R1 + g * 512), r1b = rsb + MB_R1;
                sched_fence(r1);
                bar_sync(BAR_MEM, 384);
                TLB(0);
                float acc[2][2][4];
#pragma unroll
                for (int t = 0; t < 4; t++) { acc[t >> 1][t & 1][0] = acc[t >> 1][t & 1][1] = acc[t >> 1][t & 1][2] = acc[t >> 1][t & 1][3] = 0.f; }
                uint32_t b[4][4];
                uint4 u0, u1;
#pragma unroll
                for (int p = 0; p < 4; p++) ldsm4t(b[p], mb + p * 512);
#pragma unroll
                for (int p = 0; p < 12; p++) {
#pragma unroll
                    for (int u = 0; u < 2; u++) {
                        mma16816v(acc[0][u], wa[0][2 * p + u], b[p & 3][2 * u], b[p & 3][2 * u + 1]);
                        mma16816v(acc[1][u], wa[1][2 * p + u], b[p & 3][2 * u], b[p & 3][2 * u + 1]);
                    }
                    if (p + 4 < 12) ldsm4t(b[p & 3], mb + (p + 4) * 512);
                    if (AF >> p & 1) sched_fence(L);
                    if (p == Q3_AT) {
                        bar_sync(BAR_Q3, 256);
                        u0 = lds128(ra + SM_R3); u1 = lds128(ra + SM_O);
                    }
                }
                st_async4(r1, (acc[0][0][0] + __uint_as_float(u0.x)) + acc[0][1][0], (acc[0][0][1] + __uint_as_float(u0.y)) + acc[0][1][1],
                          (acc[0][0][2] + __uint_as_float(u0.z)) + acc[0][1][2], (acc[0][0][3] + __uint_as_float(u0.w)) + acc[0][1][3], r1b);
                TL(1);
                const float o0 = (acc[1][0][0] + __uint_as_float(u1.x)) + acc[1][1][0], o1 = (acc[1][0][1] + __uint_as_float(u1.y)) + acc[1][1][1];
                const float o2 = (acc[1][0][2] + __uint_as_float(u1.z)) + acc[1][1][2], o3 = (acc[1][0][3] + __uint_as_float(u1.w)) + acc[1][1][3];
                const uint32_t l4 = L >> 2, qo = SM_QKV + kh * 2048 + nh * 1024 + g * 256, qr = l4 + (rsb + qo), ql = l4 + (sb + qo), pb = rsb + MB_P;
                char* xd = make_ptr(l4 + (xbox + kh * 1024 + g * 256 + slot), mhi);
                asm volatile("" ::"l"(xd), "r"(qr), "r"(pb), "r"(qr + 128), "f"(o0), "f"(o1), "f"(o2), "f"(o3));
                mbar_wait_w(sb + MB_R1, s & 1);
                const uint4 v = lds128(ra + SM_R1);
                const uint32_t w0 = pack_bf16(o0 + __uint_as_float(v.x), o1 + __uint_as_float(v.y)), w1 = pack_bf16(o2 + __uint_as_float(v.z), o3 + __uint_as_float(v.w));
                st_relaxed_u32(xd, w0);
                st_relaxed_u32(xd + 128, w1);
                bar_arrive(BAR_PUB, 192);
                st_async1(qr, w0, pb);
                st_async1(qr + 128, w1, pb);
                sts32(ql, w0);
                sts32(ql + 128, w1);
                __syncwarp();
                mbar_expect_tx_if0(L, sb + MB_P, 256);
                TL(2);
                if (s + LEAD < NSEG) bar_sync(BAR_VP, 256);
            } else if (!PRO_LATE) {
                bar_sync(BAR_PRO, 288);
            }
            if (s + LEAD < NSEG) {
                float d[16];
                batch1(d, xtlo, std::integral_constant<int, 0>(), std::integral_constant<int, 0>(), std::integral_constant<int, 32>());
                PHASE(1);
                const uint32_t rt = L + (rsb + SM_RT + g * 2048);
                wg_wait<0>();
                TL(7);
                if (s >= 0) {
                    const uint32_t pk = L + (sb + SM_Z + g * 2048);
#pragma unroll
                    for (int i = 0; i < 4; i++) sts128(pk + i * 512, make_uint4(__float_as_uint(d[4 * i]), __float_as_uint(d[4 * i + 1]), __float_as_uint(d[4 * i + 2]), __float_as_uint(d[4 * i + 3])));
                    if (RTF) asm volatile("fence.proxy.async.shared::cta;" ::: "memory");
                    if (RTW) {
                        __syncwarp();
                        asm volatile("{.reg .pred p; setp.eq.u32 p, %3, 0; @p cp.async.bulk.shared::cluster.shared::cta.mbarrier::complete_tx::bytes [%0], [%1], 2048, [%2];}"
                                     ::"r"(rsb + SM_RT + g * 2048), "r"(sb + SM_Z + g * 2048), "r"(rsb + MB_RT0), "r"(L) : "memory");
                    }
                } else {
                    if (PRO_LATE) bar_sync(BAR_PRO, 288);
#pragma unroll
                    for (int i = 0; i < 4; i++) st_async4(rt + i * 512, d[4 * i], d[4 * i + 1], d[4 * i + 2], d[4 * i + 3], rsb + MB_RT0);
                }
            }
            if (s + 1 == NSEG) { bar_arrive(BAR_SV, NSV); break; }
            if (s >= 0) {
                PHASE(2);
                const uint32_t fo = FRAG() + (sb + SM_WO2 + 16384), lo = L + (sb + SM_O), yo = (L >> 2) + (ybox + slot);
                uint32_t a1[8][4];
                bar_sync(BAR_SV, NSV);
                if (TS_AT == 13) TLB(21);
#pragma unroll
                for (int k = 0; k < 8; k++) ldsm4t(a1[k], fo + k * 2048);
                sched_fence(yo);
                bar_sync(BAR_O2, 256);
                TLB(14);
                float y0[4] = {0.f, 0.f, 0.f, 0.f}, y1[4] = {0.f, 0.f, 0.f, 0.f};
                uint32_t b[2][4];
                ldsm4t(b[0], lo); ldsm4t(b[1], lo + 512);
                sched_fence(L);
#pragma unroll
                for (int p = 0; p < 4; p++) {
                    mma16816v(y0, a1[2 * p], b[p & 1][0], b[p & 1][1]);
                    mma16816v(y1, a1[2 * p + 1], b[p & 1][2], b[p & 1][3]);
                    if (p < 2) ldsm4t(b[p & 1], lo + (p + 2) * 512);
                }
                bar_sync(BAR_INV, 256);
                float i0, i1;
                asm volatile("ld.shared.v2.f32 {%0, %1}, [%2];" : "=f"(i0), "=f"(i1) : "r"(((L >> 1) & 0x18) + (sb + SM_INV + g * 32)) : "memory");
                st_relaxed_u32(make_ptr(yo, mhi), pack_bf16((y0[0] + y1[0]) * i0, (y0[1] + y1[1]) * i1));
                st_relaxed_u32(make_ptr(yo ^ 4096, mhi) + 0x2000, pack_bf16((y0[2] + y1[2]) * i0, (y0[3] + y1[3]) * i1));
                bar_arrive(BAR_SENTC, 384);
                TL(6);
            }
            if (s + LEAD < NSEG) {
                PHASE(4);
                float d[16];
                const uint32_t rt = L + (sb + SM_RT + g * 2048);
                if (s >= 0) bar_sync(BAR_SENT, 256);
                if (TS_AT == 12) TLB(21);
                mbar_wait_w(sb + MB_RT0, it & 1);
                if (TS_AT == 11) TL(21);
                if (s >= 0) bar_arrive(BAR_Y, 256);
                if (RT0_B && s >= 0) bar_arrive(BAR_VP, 256);
#pragma unroll
                for (int i = 0; i < 4; i++) {
                    const uint4 v = lds128(rt + i * 512);
                    d[4 * i] = __uint_as_float(v.x); d[4 * i + 1] = __uint_as_float(v.y); d[4 * i + 2] = __uint_as_float(v.z); d[4 * i + 3] = __uint_as_float(v.w);
                }
                if (SPLIT > 0) batch1(d, xtlo, std::integral_constant<int, 1>(), std::integral_constant<int, 0>(), std::integral_constant<int, SPLIT>());
                if (s >= 0) bar_sync(BAR_ZP, 256);
                TLB(30);
                batch1(d, xtlo, std::integral_constant<int, 1>(), std::integral_constant<int, SPLIT>(), std::integral_constant<int, 32>());
                const uint32_t so = (kh ? FRAG() : ((L & 0x100) << 2) + (L & 0xF0) + g * 256) + (sb + SM_STG);
                wg_wait<0>();
                TL(8);
                uint32_t w[8];
#pragma unroll
                for (int i = 0; i < 8; i++) w[i] = pack_bf16(d[2 * i], d[2 * i + 1]);
                if (kh) {
                    stsm4t(so, w[0], w[1], w[2], w[3]);
                    stsm4t(so + 2048, w[4], w[5], w[6], w[7]);
                } else {
                    stsm4(so, w[0], w[1], w[2], w[3]);
                    stsm4(so + 2048, w[4], w[5], w[6], w[7]);
                }
                __syncwarp();
                mbar_arrive_if0(L, sb + MB_STG);
                TL(9);
            } else {
                bar_arrive(BAR_SENT, 256);
                bar_arrive(BAR_Y, 256);
                if (OTMA) mbar_arrive_if0(l16, sb + MB_STG);
            }
        }
        if (TAIL && (TM & 1) && COLD()) last_tile(0);
    } else {
        asm volatile("setmaxnreg.inc.sync.aligned.u32 %0;" ::"n"(REG_B));
        code_pad<PAD_B>();
        const uint32_t l16 = lane16();
        uint32_t wv[24][4], wo[8 + WO_RF1][4];
        {
            const uint32_t L = l16, fa = sb + FRAG();
            mbar_wait_w(sb + MB_W0, 0);
            KT_MARK(6);
#pragma unroll
            for (int r = 0; r < 24; r++) ldsm4t(wv[r], fa + STG_V + r * 2048);
#pragma unroll
            for (int r = 0; r < 8 + WO_RF1; r++) asm volatile("" : "=r"(wo[r][0]), "=r"(wo[r][1]), "=r"(wo[r][2]), "=r"(wo[r][3]));
            mbar_wait_w(sb + MB_W2, 0);
            bar_sync(BAR_PDONE, 384);
        }
        const uint32_t xbox = mlo + WIN + page_off(pair & 31, cls ^ XFLIP);
        const uint32_t ybox = mlo + page_off(2 * g + 32 * nh, kh ^ YFLIP_()) + h * 128;
#pragma unroll 1
        for (uint32_t it = 0; it < NSEG + LEAD; it++) {
            const int s = (int)it - LEAD;
            const uint32_t ui = uniform(it), slot = ((ui + 4 - LEAD) & 3) << 14, kvo = ((LEAD & 1 ? ~ui : ui) & 1) * KV_BYTES, xtlo = XTLO();
            {
                PHASE(5);
                const uint32_t first = L | (g << 9);
                if (s >= 0) mbar_expect_tx_if0(first, sb + MB_R2, 1024);
                if (s + LEAD < NSEG) {
                    mbar_expect_tx_if0(first, sb + MB_RT1, 2048);
                    mbar_wait_w(sb + MB_XT + (ui & 1) * 8, (it >> 1) & 1);
                }
            }
            if (s >= 0) {
                PHASE(0);
                uint32_t fr = FRAG();
                asm("" : "+r"(fr));
                const uint32_t fo = fr + sb, l4 = L >> 2;
                {
                    const uint32_t mb = L + (sb + SM_Z), aw = fo + SM_WQK, ra = L + (sb + g * 512), r2 = (L >> 1) + (rsb + SM_R2 + g * 256), r2b = rsb + MB_R2;
                    uint32_t a[NA][4], b[4][4];
#pragma unroll
                    for (int i = 0; i < NA; i++) ldsm4t(a[i], aw + i * 2048);
                    sched_fence(L);
                    TL(24);
                    bar_sync(BAR_MEM, 384);
#pragma unroll
                    for (int p = 0; p < 4; p++) ldsm4t(b[p], mb + (12 + p) * 512);
                    sched_fence(L);
                    float c[2][4] = {{0.f, 0.f, 0.f, 0.f}, {0.f, 0.f, 0.f, 0.f}};
#pragma unroll
                    for (int i = 0; i < 16; i++) {
                        mma16816v(c[i & 1], a[i % NA], b[i >> 2][i & 2], b[i >> 2][(i & 2) + 1]);
                        ldsm4t(a[i % NA], aw + (i + NA) * 2048);
                        if (QF >> i & 1) sched_fence(L);
                    }
                    sts128(ra + SM_R3, make_uint4(__float_as_uint(c[0][0]), __float_as_uint(c[0][1]), __float_as_uint(c[0][2]), __float_as_uint(c[0][3])));
                    sts128(ra + SM_O, make_uint4(__float_as_uint(c[1][0]), __float_as_uint(c[1][1]), __float_as_uint(c[1][2]), __float_as_uint(c[1][3])));
                    bar_arrive(BAR_Q3, 256);
                    if (QF >> 16 & 1) sched_fence(L);
                    TL(29);
                    float acc[4][4];
#pragma unroll
                    for (int t = 0; t < 4; t++) { acc[t][0] = acc[t][1] = acc[t][2] = acc[t][3] = 0.f; }
#pragma unroll
                    for (int i = 16; i < 24; i++) {
                        mma16816v(acc[i & 1], a[i % NA], b[(i - 16) >> 1][2 * (i & 1)], b[(i - 16) >> 1][2 * (i & 1) + 1]);
                        if (i + NA < 24) ldsm4t(a[i % NA], aw + (i + NA) * 2048);
                        else ldsm4t(a[i % NA], mb + (i + NA - 24) * 512);
                    }
#pragma unroll
                    for (int p = 0; p < 12; p++) {
                        mma16816v(acc[(2 * p) & 3], wv[2 * p], a[(24 + p) % NA][0], a[(24 + p) % NA][1]);
                        mma16816v(acc[(2 * p + 1) & 3], wv[2 * p + 1], a[(24 + p) % NA][2], a[(24 + p) % NA][3]);
                        if (p + NA < 12) ldsm4t(a[(24 + p) % NA], mb + (p + NA) * 512);
                    }
                    if (s + LEAD < NSEG) bar_arrive(BAR_VP, 256);
                    float o[4];
#pragma unroll
                    for (int i = 0; i < 4; i++) o[i] = (acc[0][i] + acc[1][i]) + (acc[2][i] + acc[3][i]);
                    st_async2(r2, kh ? o[0] : o[2], kh ? o[1] : o[3], r2b);
                    TL(10);
                    const float o0 = kh ? o[2] : o[0], o1 = kh ? o[3] : o[1];
                    const uint32_t qo = SM_QKV + 4096 + nh * 1024 + (2 * g + kh) * 128, qr = l4 + (rsb + qo), ql = l4 + (sb + qo), vb = rsb + MB_V, rl = (L >> 1) + (sb + SM_R2 + g * 256);
                    char* xd = make_ptr(l4 + (xbox + 2048 + (2 * g + kh) * 128 + slot), mhi);
                    asm volatile("" ::"l"(xd), "r"(qr), "r"(vb), "f"(o0), "f"(o1));
                    mbar_wait_w(sb + MB_R2, s & 1);
                    uint32_t vx, vy;
                    asm volatile("ld.shared.v2.u32 {%0,%1}, [%2];" : "=r"(vx), "=r"(vy) : "r"(rl) : "memory");
                    const uint32_t w0 = pack_bf16(o0 + __uint_as_float(vx), o1 + __uint_as_float(vy));
                    st_relaxed_u32(xd, w0);
                    bar_arrive(BAR_PUBV, 160);
                    st_async1(qr, w0, vb);
                    sts32(ql, w0);
                    __syncwarp();
                    mbar_expect_tx_if0(L, sb + MB_V, 128);
                    TL(11);
                }
                const uint32_t vma = L + (sb + SM_QKV + 4096 + g * 512), yo = l4 + (ybox + slot);
                uint32_t va[2][2][4];
                {
                    const uint32_t qa = QFRAG(), vf = fr ^ ((g << 5) ^ ((g & 1) << 6)), va0 = vf + VBASE(), va1 = (vf ^ 32) + VBASE();
                    const uint32_t kf = ((L << 3) & 0x380) | ((L ^ (L >> 3)) & 0x30) | (L & 0x40), kb0 = sb + SM_KV + kvo + g * 1024;
                    const int d = (int)(L >> 6) - (int)((L >> 3) & 6) + 8 * (j - (int)g);
                    const uint32_t keep = (d < 0 ? 0u : 0xFFFFu) | (d < 1 ? 0u : 0xFFFF0000u), sa = l4 + (sb + SM_S + g * 128);
                    const uint32_t q0 = qa + (sb + nh * 1024), q1 = qa + (sb + (nh ^ 1) * 1024);
                    float sc[4] = {0.f, 0.f, 0.f, 0.f}, sd[4] = {0.f, 0.f, 0.f, 0.f};
                    uint32_t a[4][4], kb[2][4];
                    mbar_wait_w(sb + MB_KV + ((LEAD & 1 ? ~ui : ui) & 1) * 8, (s >> 1) & 1);
                    ldsm4(kb[0], kf + (kb0 + nh * 4096)); ldsm4(kb[1], (kf ^ 64) + (kb0 + nh * 4096));
                    mbar_wait_w(sb + MB_P, s & 1);
                    TL(12);
#pragma unroll
                    for (int k = 0; k < 4; k++) ldsm4t(a[k], q0 + k * 256);
#pragma unroll
                    for (int k = 0; k < 4; k++) mma16816v((k & 1) ? sd : sc, a[k], kb[k >> 1][2 * (k & 1)], kb[k >> 1][2 * (k & 1) + 1]);
                    ldsm4(kb[0], kf + (kb0 + (nh ^ 1) * 4096)); ldsm4(kb[1], (kf ^ 64) + (kb0 + (nh ^ 1) * 4096));
                    sched_fence(vf | yo);
                    if (TS_AT == 8) TL(21);
                    bar_sync(BAR_QK, 224);
                    TLB(3);
#pragma unroll
                    for (int k = 0; k < 4; k++) ldsm4t(a[k], q1 + k * 256);
                    sched_fence(L);
#pragma unroll
                    for (int k = 0; k < 4; k++) mma16816v((k & 1) ? sd : sc, a[k], kb[k >> 1][2 * (k & 1)], kb[k >> 1][2 * (k & 1) + 1]);
                    ldsm4t(va[0][0], va0); ldsm4t(va[0][1], va0 + 2048);
                    sts32(sa, scale_scores(sc[0] + sd[0], sc[1] + sd[1]));
                    sts32(sa + 768, (scale_scores(sc[2] + sd[2], sc[3] + sd[3]) & keep) | (0xFF80FF80u & ~keep));
                    bar_arrive(BAR_SV, NSV);
                    ldsm4t(va[1][0], va1); ldsm4t(va[1][1], va1 + 2048);
                }
                bar_sync(BAR_S, 160);
                TLB(4);
                uint32_t pw[6], vm[4];
                if (s + 1 < NSEG) {
                softmax40(pw, l4 + (sb + SM_S), [&]() {
                    bar_sync(BAR_V, 160);
                    ldsm4(vm, vma);
                });
                uint32_t a1[NP2][4];
                float inv[2];
                {
                    uint32_t w[4];
                    pv32<false>(w, inv, va, vm, pw, [&]() {
                        sched_fence(L);
#pragma unroll
                        for (int k = 0; k < NP2; k++) ldsm4t(a1[k], fo + SM_WO2 + k * 2048);
                    });
#pragma unroll
                    for (int i = 0; i < 4; i++) sts32(l4 + (sb + SM_O + g * 512) + i * 128, w[i]);
                }
                const uint32_t lo = L + (sb + SM_O);
                bar_arrive(BAR_O2, 256);
                bar_sync(BAR_O, 128);
                TLB(5);
                {
                    float y0[4] = {0.f, 0.f, 0.f, 0.f}, y1[4] = {0.f, 0.f, 0.f, 0.f}, y2[4] = {0.f, 0.f, 0.f, 0.f};
                    uint32_t b[4][4];
#pragma unroll
                    for (int p = 0; p < 4; p++) ldsm4t(b[p], lo + p * 512);
                    inv[0] = rcp_approx(inv[0]); inv[1] = rcp_approx(inv[1]);
                    asm volatile("st.shared.v2.f32 [%0], {%1, %2};" ::"r"(((L >> 1) & 0x18) + (sb + SM_INV + g * 32)), "f"(inv[0]), "f"(inv[1]) : "memory");
                    bar_arrive(BAR_INV, 256);
                    sched_fence(L);
#pragma unroll
                    for (int k = 0; k < 8; k++) {
                        const int p = k >> 1, u = k & 1;
                        mma16816v(y2, a1[k % NP2], b[p][2 * u], b[p][2 * u + 1]);
                        if (k + NP2 < 8) ldsm4t(a1[k % NP2], fo + SM_WO2 + (k + NP2) * 2048);
                        else if (k + NP2 < 16 - WO_RF1) ldsm4t(a1[k % NP2], fo + SM_WO1 + (k + NP2 - 8 + WO_RF1) * 2048);
                        mma16816v(y0, wo[k], b[p][2 * u], b[p][2 * u + 1]);
                        if (k < WO_RF1) mma16816v(y1, wo[8 + (k < WO_RF1 ? k : 0)], b[p][2 * u], b[p][2 * u + 1]);
                        else mma16816v(y1, a1[(k + 8 - WO_RF1) % NP2], b[p][2 * u], b[p][2 * u + 1]);
                        if (k < P2_FENCE) sched_fence(L);
                    }
                    char* yd = make_ptr(yo, mhi);
                    char* yd1 = make_ptr(yo ^ 4096, mhi);
                    st_relaxed_u32(yd1 + 0x80000, pack_bf16(y2[0] * inv[0], y2[1] * inv[1]));
                    st_relaxed_u32(yd + 0x82000, pack_bf16(y2[2] * inv[0], y2[3] * inv[1]));
                    st_relaxed_u32(yd, pack_bf16(y0[0] * inv[0], y0[1] * inv[1]));
                    st_relaxed_u32(yd1 + 0x2000, pack_bf16(y0[2] * inv[0], y0[3] * inv[1]));
                    st_relaxed_u32(yd + 0x40000, pack_bf16(y1[0] * inv[0], y1[1] * inv[1]));
                    st_relaxed_u32(yd1 + 0x42000, pack_bf16(y1[2] * inv[0], y1[3] * inv[1]));
                }
                bar_arrive(BAR_SENTC, 384);
                TL(13);
                bar_sync(BAR_SENT, 256);
                } else {
                    bar_sync(BAR_V, 160);
                }
            } else {
                if (it == WO_IT) {
                    PHASE(2);
                    const uint32_t fa = sb + FRAG();
                    mbar_wait_w(sb + MB_W3, 0);
                    KT_MARK(8);
#pragma unroll
                    for (int r = 0; r < 8 + WO_RF1; r++) ldsm4t(wo[r], fa + stg_wo(r));
                }
                bar_sync(BAR_PRO, 288);
            }
            float o[8];
            uint32_t w[4];
            {
                PHASE(1);
                float d[16];
                const uint64_t da = make_desc(SB0 + SM_WV, 16, 1024);
                auto batch = [&](auto k0c, auto k1c) {
                    static_for<decltype(k0c)::value, decltype(k1c)::value>([&](auto kc) {
                        constexpr int i = decltype(kc)::value, k = kstep(ORDV, i), off = (k >> 2) * 256 + (k & 3) * 2;
                        if constexpr (k >= 24) wgmma_ss32u<off, i != 0>(d, da + (k - 24) * 128, xtlo);
                        else wgmma_rs32u<off, i != 0>(d, wv[k], xtlo);
                    });
                };
                const uint32_t vf = VFRAG(), va0 = vf + VBASE(), va1 = (vf ^ 32) + VBASE(), vma = L + (sb + SM_QKV + 4096 + g * 512), sa = (L >> 2) + (sb + SM_S + 768);
                const uint32_t rt = L + (rsb + SM_RT + 8192 + g * 512);
                uint32_t va[2][2][4], vm[4], pw[6];
                wg_fence();
                batch(std::integral_constant<int, 0>(), std::integral_constant<int, TA0>());
                wg_commit();
                batch(std::integral_constant<int, TA0>(), std::integral_constant<int, 32>());
                wg_commit();
                wg_wait<1>();
                if (RT0_B == 3 && (unsigned)s < NSEG - LEAD) bar_sync(BAR_VP, 256);
                softmax40(pw, sa, [&]() {});
                ldsm4t(va[0][0], va0); ldsm4t(va[0][1], va0 + 2048);
                ldsm4t(va[1][0], va1); ldsm4t(va[1][1], va1 + 2048);
                ldsm4(vm, vma);
                if (RT0_B == 1 && (unsigned)s < NSEG - LEAD) bar_sync(BAR_VP, 256);
                wg_wait<0>();
                if (RT0_B == 2 && (unsigned)s < NSEG - LEAD) bar_sync(BAR_VP, 256);
                TL(27);
                float inv[2];
                pv32<true>(w, inv, va, vm, pw, [&]() {
                    uint32_t q[4];
#pragma unroll
                    for (int i = 0; i < 4; i++) q[i] = pack_bf16(kh ? d[2 * i] : d[8 + 2 * i], kh ? d[2 * i + 1] : d[9 + 2 * i]);
                    if (RT0_B == 4 && (unsigned)s < NSEG - LEAD) bar_sync(BAR_VP, 256);
                    if (s + LEAD < NSEG) st_async4(rt, __uint_as_float(q[0]), __uint_as_float(q[1]), __uint_as_float(q[2]), __uint_as_float(q[3]), rsb + MB_RT1);
#pragma unroll
                    for (int i = 0; i < 8; i++) o[i] = kh ? d[8 + i] : d[i];
                });
                TL(26);
            }
            if (s + LEAD < NSEG) {
                PHASE(3);
                const uint32_t rt = L + (sb + SM_RT + 8192 + g * 512), so = FRAG() + (sb + SM_STG + 4096);
                mbar_wait_w(sb + MB_RT1, it & 1);
                TL(28);
                const uint4 v = lds128(rt);
                stsm4t(so, pack_bf16(o[0] + bf_lo(v.x), o[1] + bf_hi(v.x)), pack_bf16(o[2] + bf_lo(v.y), o[3] + bf_hi(v.y)),
                       pack_bf16(o[4] + bf_lo(v.z), o[5] + bf_hi(v.z)), pack_bf16(o[6] + bf_lo(v.w), o[7] + bf_hi(v.w)));
                if (!OTMA) { __syncwarp(); mbar_arrive_if0(L, sb + MB_STG); }
                TL(15);
            }
            if (OTMA) {
                PHASE(7);
                __syncwarp();
                stsm4t((((L << 2) & 0x1C0) | (((L >> 3) ^ (L >> 1)) & 0x30)) + (sb + SM_OT + g * 512), w[0], w[1], w[2], w[3]);
                __syncwarp();
                mbar_arrive_if0(L, sb + MB_STG);
            }
        }
        if ((OTMA || TAIL) && (TM & 2) && COLD()) bar_arrive(BAR_ZP, 160);
        if (TAIL && (TM & 2) && COLD()) last_tile(1);
    }
    KT_END(TAIL ? 3 : 2);
    asm volatile("barrier.cluster.arrive.relaxed; barrier.cluster.wait;" ::: "memory");
}
constexpr int B_UCH = 73 * 64;
constexpr int B_SCH = 33 * 64;
constexpr int B_KLEN = 2128;
constexpr int B_KCH = 2 * B_KLEN * 2 + 64;
constexpr int B_KBOX = 136 * 32;
constexpr int B_SM_U = 0;
constexpr int B_SM_S = 8 * B_UCH;
constexpr int B_SM_K = B_SM_S + 8 * B_SCH;
constexpr int B_SM_KT = B_SM_K + 8 * B_KCH;
constexpr int B_SM_VT = B_SM_KT + 8 * B_KBOX;
constexpr int B_SM_QT = B_SM_VT + 32768;
constexpr int B_SM_BAR = B_SM_QT + 32768;
constexpr int B_SMEM = B_SM_BAR + 128 + 512;
static_assert(B_SM_KT % 256 == 0 && B_SM_S % 512 == 0 && B_SMEM <= 232448, "tiles");
constexpr int PROBE_N = 4;
#define PROBE_R 2
constexpr int B_C = 2056;

__device__ __forceinline__ uint32_t atomic_round_trip(char* p) {
    uint32_t t0, t1, v;
    asm volatile("{.reg .pred p;\n"
                 "mov.u32 %0, %%clock;\n"
                 "atom.relaxed.gpu.global.add.u32 %2, [%3], 1;\n"
                 "setp.ne.u32 p, %2, 0x7FFFFFFF;\n"
                 "mov.u32 %1, 0;\n"
                 "@p mov.u32 %1, %%clock;}" : "=&r"(t0), "=&r"(t1), "=&r"(v) : "l"(p) : "memory");
    return t1 - t0;
}
__device__ __forceinline__ uint32_t round_trips(char* a, char* b, uint32_t stride, int lane) {
    for (int i = lane >> 3; i < 2 * PROBE_N; i += 4) stg128(((i & 1) ? b : a) + (i >> 1) * stride + (lane & 7) * 16, make_uint4(0, 0, 0, 0));
    __syncwarp();
    uint32_t ta = 0xFFFF, tb = 0xFFFF;
    if (lane == 0) {
        __threadfence();
#pragma unroll 1
        for (int i = 0; i < PROBE_N; i++) { ta = min(ta, atomic_round_trip(a + i * stride)); tb = min(tb, atomic_round_trip(b + i * stride)); }
    }
    __syncwarp();
    return ta | (tb << 16);
}
__device__ __forceinline__ void measure_distance(char* mbox, int lane) {
    const uint32_t b = blockIdx.x;
    unsigned smid;
    asm volatile("mov.u32 %0, %%smid;" : "=r"(smid));
    char* w1 = mbox + WIN + (b & 31) * 128;
    uint32_t r = 0xFFFFFFFF;
#pragma unroll 1
    for (int i = 0; i < PROBE_R; i++) r = __vminu2(r, round_trips(w1 + page_off(50 + 5 * i + (b >> 5), 0), w1 + page_off(50 + 5 * i + (b >> 5), 1), 16384, lane));
    if (lane == 0) g_cls[smid] = r;
    if (b == 128) {
        char *p = mbox + page_off(0, 0), *q = mbox + page_off(0, 1);
        uint32_t r0 = 0xFFFFFFFF;
#pragma unroll 1
        for (int i = 0; i < PROBE_R; i++) r0 = __vminu2(r0, round_trips(p, q, 128, lane));
        if (lane == 0) { g_reg[1] = ((r0 & 0xFFFF) > (r0 >> 16)) != ((r & 0xFFFF) > (r >> 16)); if (!EARLY_ROLE) g_reg[0] = 0; g_reg[2] = 0; }
        const uint4 sent = make_uint4(SENT, SENT, SENT, SENT);
        stg128(p + lane * 16, sent); stg128(q + lane * 16, sent);
    }
    if (b == 129) for (int i = lane; i < 128; i += 32) g_xflag[i] = 0;
}

#define SP(i)
#define SP2(i)
#define OUT_STG 0
#define PF_STOP 1
#define SENT_AT 3
#define Q_LATE 1
#define PF_DEPTH 4
#define PF_STRIDE 256
struct ChainInputs { const char* w[4]; const char *x, *mem0; };
#define EF_MASK 15
#define EF(i) (((EF_MASK >> (i)) & 1) ? policy_evict_first() : policy_evict_normal())
__device__ __forceinline__ void l2_prefetch(const char* p, uint32_t bytes) {
    asm volatile("cp.async.bulk.prefetch.L2.global [%0], %1;" ::"l"(p), "r"(bytes) : "memory");
}
#define WG_CONV(N, LIST, A0, A1, A2, A3, LO, OF, ...) \
    if constexpr (NN == N) asm volatile("{.reg .b32 l; .reg .b64 e; add.u32 l, %" #LO ", %" #OF "; mov.b64 e, {l, 0x80000020};\n" \
        "wgmma.mma_async.sync.aligned.m64n" #N "k16.f32.bf16.bf16 {" LIST "}, {%" #A0 ",%" #A1 ",%" #A2 ",%" #A3 "}, e, 1, 1, 1, 0;}" \
        : __VA_ARGS__ : "r"(a[0]), "r"(a[1]), "r"(a[2]), "r"(a[3]), "r"(lo), "n"(OFF));
#define WL4 "%0,%1,%2,%3"
#define WL8 WL4 ",%4,%5,%6,%7"
#define WL12 WL8 ",%8,%9,%10,%11"
#define WL16 WL12 ",%12,%13,%14,%15"
#define WL20 WL16 ",%16,%17,%18,%19"
#define WL24 WL20 ",%20,%21,%22,%23"
#define WL28 WL24 ",%24,%25,%26,%27"
#define WL32 WL28 ",%28,%29,%30,%31"
template <int NN, int OFF> __device__ __forceinline__ void wgmma_conv(float (&d)[32], const uint32_t (&a)[4], uint32_t lo) {
    WG_CONV(8, WL4, 4, 5, 6, 7, 8, 9, R4(0))
    WG_CONV(16, WL8, 8, 9, 10, 11, 12, 13, R4(0), R4(4))
    WG_CONV(24, WL12, 12, 13, 14, 15, 16, 17, R4(0), R4(4), R4(8))
    WG_CONV(32, WL16, 16, 17, 18, 19, 20, 21, R16(0))
    WG_CONV(40, WL20, 20, 21, 22, 23, 24, 25, R16(0), R4(16))
    WG_CONV(48, WL24, 24, 25, 26, 27, 28, 29, R16(0), R4(16), R4(20))
    WG_CONV(56, WL28, 28, 29, 30, 31, 32, 33, R16(0), R4(16), R4(20), R4(24))
    WG_CONV(64, WL32, 32, 33, 34, 35, 36, 37, R16(0), R16(16))
}
__device__ __forceinline__ void copy_to_peer(uint32_t dst, uint32_t src, uint32_t bytes, uint32_t bar) {
    asm volatile("cp.async.bulk.shared::cluster.shared::cta.mbarrier::complete_tx::bytes [%0], [%1], %2, [%3];" ::"r"(dst), "r"(src), "r"(bytes), "r"(bar) : "memory");
}
__device__ __forceinline__ uint32_t lds_volatile(uint32_t a) {
    uint32_t v;
    asm volatile("ld.volatile.shared.u32 %0, [%1];" : "=r"(v) : "r"(a) : "memory");
    return v;
}
__device__ __forceinline__ uint32_t swz64(uint32_t a) { return a ^ ((a >> 3) & 0x30); }
__device__ __forceinline__ void fence_async() { asm volatile("fence.proxy.async.shared::cta;" ::: "memory"); }

__global__ void __cluster_dims__(2, 1, 1) __launch_bounds__(576, 1)
ssm_kernel(const __grid_constant__ CUtensorMap mapK, const __grid_constant__ CUtensorMap mapV, const __grid_constant__ CUtensorMap mapQ,
           const __grid_constant__ CUtensorMap mapO, const bf16* __restrict__ shiftk, const bf16* __restrict__ ssmk, const bf16* __restrict__ Dv,
           char* __restrict__ mbox, const __grid_constant__ ChainInputs ci, bf16* __restrict__ outp) {
    extern __shared__ __align__(128) uint8_t smem_raw[];
    const uint32_t sb = (smem_u32(smem_raw) + 511) & ~511u;
    const int rank = blockIdx.x & 1, ch0 = blockIdx.x * 8, c16 = ch0 & ~15, t0 = rank * 1024;
    const int t = threadIdx.x, warp = t >> 5, lane = t & 31;
    const uint32_t bar = sb + B_SM_BAR, barQ = bar + 64, barU = bar + 72, barY = bar + 80, flag = bar + 88;
    SP(0);
    if (lane == 0 && warp < 16 && blockIdx.x < 128) {
        const int i = warp >> 1;
        if (warp & 1) {
            if (i < 3) { mbar_init(barQ + i * 8, 1); mbar_expect_tx(barQ + i * 8, i ? 16384 : 32768); }
            if (i == 3) sts32(flag, 0);
        } else {
            mbar_init(bar + i * 8, 1);
            asm volatile("fence.mbarrier_init.release.cluster;" ::: "memory");
            mbar_expect_tx(bar + i * 8, B_KBOX + 4096);
            tma_load_2d(sb + B_SM_KT + i * B_KBOX, &mapK, c16, t0 + i * 128 - 8, bar + i * 8, EF(0));
            tma_load_2d(sb + B_SM_VT + i * 4096, &mapV, c16, t0 + i * 128, bar + i * 8, EF(0));
        }
        asm volatile("fence.mbarrier_init.release.cluster;" ::: "memory");
    }
    __syncwarp();
    if (warp == 14) SP2(14);
    KT_START(1);
    if (warp == 17) {
        launch_dependents();
        asm volatile("barrier.cluster.arrive.relaxed.aligned;" ::: "memory");
        measure_distance(mbox, lane);
        asm volatile("barrier.cluster.wait.aligned;" ::: "memory");
        KT_MARK(14);
        return;
    }
    if (blockIdx.x >= 128) return;
    if (warp == 16) {
        asm volatile("barrier.cluster.arrive.relaxed.aligned; barrier.cluster.wait.aligned;" ::: "memory");
        SP2(8);
        if (Q_LATE) for (int i = 0; i < 8; i++) { mbar_wait_w(bar + i * 8, 0); SP2(i); }
        if (lane < 8) tma_load_2d(sb + B_SM_QT + lane * 4096, &mapQ, c16, t0 + lane * 128, barQ, EF(3));
        if (!Q_LATE) for (int i = 0; i < 8; i++) mbar_wait_w(bar + i * 8, 0);
        if (lane == 0) {
            l2_prefetch(ci.x + blockIdx.x * 2048, 2048);
            if (blockIdx.x < 8) l2_prefetch(ci.mem0 + blockIdx.x * 2048, 2048);
        }
        uint32_t v[PF_DEPTH], acc = 0;
#pragma unroll
        for (int u = 0; u < PF_DEPTH; u++) v[u] = 0;
        constexpr int PER = 32 * PF_STRIDE, NW = 65536 / PER;
#define PF_N (4 * NW)
        int i = 0;
#pragma unroll 1
        for (; i < PF_N && lds_volatile(flag) == 0; i += PF_DEPTH) {
#pragma unroll
            for (int u = 0; u < PF_DEPTH; u++) {
                const char* a = ci.w[(i + u) / NW] + blockIdx.x * 65536 + ((i + u) % NW) * PER + lane * PF_STRIDE;
                acc |= v[u];
                asm volatile("ld.global.cg.L2::256B.u32 %0, [%1];" : "=r"(v[u]) : "l"(a) : "memory");
            }
        }
#pragma unroll
        for (int u = 0; u < PF_DEPTH; u++) acc |= v[u];
        if (acc == 0x7FFF7FFFu && v[0] == 0x7FFEu) g_err = 1;
        SP2(12);
        KT_MARK(15);
        return;
    }
    asm volatile("barrier.cluster.arrive.relaxed.aligned;" ::: "memory");
    const int far = warp & 1, unit = rank ^ far;
    uint32_t w[4];
    uint32_t d2;
    asm volatile("ld.global.nc.u32 %0, [%1];" : "=r"(d2) : "l"(Dv + ch0 + (warp >> 2) * 2));
    {
        const int ch = warp & 7, half = warp >> 3;
        const uint32_t kb = sb + B_SM_K + ch * B_KCH;
        const uint4* src = reinterpret_cast<const uint4*>(ssmk + (size_t)(ch0 + ch) * S_LEN);
        uint4 kr[4];
#pragma unroll
        for (int i = 0; i < 4; i++) kr[i] = ldg128(src + half * 128 + i * 32 + lane, EF(1));
        const uint32_t edge = half ? 0u : __ldg(reinterpret_cast<const uint32_t*>(src + 128));
        const uint2 sw = __ldg(reinterpret_cast<const uint2*>(shiftk + (size_t)(c16 + unit * 8 + (lane >> 2)) * 4));
        w[0] = __byte_perm(sw.x, 0, 0x1010); w[1] = __byte_perm(sw.x, 0, 0x3232); w[2] = __byte_perm(sw.y, 0, 0x1010); w[3] = __byte_perm(sw.y, 0, 0x3232);
        if (half) sts128(sb + B_SM_U + ch * B_UCH + 4096 + lane * 16, make_uint4(0, 0, 0, 0));
#pragma unroll
        for (int i = 0; i < 4; i++) {
            const uint4 lo = kr[i];
            const uint32_t nx = __shfl_down_sync(~0u, lo.x, 1), n0 = (i < 3) ? __shfl_sync(~0u, kr[i < 3 ? i + 1 : 3].x, 0) : edge;
            const uint32_t hix = (lane < 31) ? nx : n0;
            const int c = 256 - (half * 128 + 32 * i + lane);
            sts128(kb + c * 16, make_uint4(__byte_perm(hix, lo.w, 0x7610), __byte_perm(lo.w, lo.z, 0x7610), __byte_perm(lo.z, lo.y, 0x7610), __byte_perm(lo.y, lo.x, 0x7610)));
            sts128(kb + B_KLEN * 2 + 64 + c * 16, make_uint4(__byte_perm(lo.w, lo.w, 0x1032), __byte_perm(lo.z, lo.z, 0x1032), __byte_perm(lo.y, lo.y, 0x1032), __byte_perm(lo.x, lo.x, 0x1032)));
        }
        const uint32_t k0w = __shfl_sync(~0u, kr[0].x, 0);
        if (half == 0 && lane < 8) {
            sts128(kb + (257 + lane) * 16, make_uint4(lane == 0 ? (k0w & 0xFFFFu) : 0u, 0u, 0u, 0u));
            sts128(kb + B_KLEN * 2 + 64 + (257 + lane) * 16, make_uint4(0u, 0u, 0u, 0u));
        }
    }
    auto sentinels = [&]() {
        const uint4 sent = make_uint4(SENT, SENT, SENT, SENT);
        char* p0 = mbox + blockIdx.x * 16384 + t * 16;
        if (blockIdx.x != 0 || (t & 255) >= 32) stg128(p0, sent);
        stg128(p0 + 8192, sent);
        char* p1 = mbox + WIN + blockIdx.x * 12800 + t * 16;
        stg128(p1, sent);
        if (t < 288) stg128(p1 + 8192, sent);
    };
    if (SENT_AT == 1) sentinels();
    asm volatile("barrier.cluster.wait.acquire.aligned;" ::: "memory");
    SP(1);
    {
        const int box = warp >> 1, row0 = 63 - 32 * rank - 4 * box;
        const uint32_t kt = sb + B_SM_KT + box * B_KBOX + 256 + lane * 32, s0 = (unit ^ ((lane >> 2) & 1)) * 16;
        const uint32_t a0 = kt + s0, a2 = kt - 64 + (unit ^ (((lane + 6) >> 2) & 1)) * 16, a4 = kt - 128 + (s0 ^ 16), av = sb + B_SM_VT + box * 4096 + lane * 32 + s0;
        const uint32_t ul = (lane & 7) * B_UCH + row0 * 64 + (lane >> 3) * 16;
        const uint32_t ud = sb + (far ? B_SM_S + (lane & 7) * (B_SCH - B_UCH) - (1 - rank) * 2048 : B_SM_U);
        mbar_wait_w(bar + box * 8, 0);
        SP(2);
#pragma unroll
        for (int i = 0; i < 4; i++) {
            uint32_t k0[4], k2[4], k4[4], vv[4], o[4];
            ldsm4t(k0, a0 + i * 1024); ldsm4t(k2, a2 + i * 1024); ldsm4t(k4, a4 + i * 1024); ldsm4t(vv, av + i * 1024);
#pragma unroll
            for (int j = 0; j < 4; j++) {
                uint32_t a = bf16_mul(__byte_perm(k4[j], k2[j], 0x5432), w[3]);
                a = bf16_add(a, bf16_mul(k2[j], w[2]));
                a = bf16_add(a, bf16_mul(__byte_perm(k2[j], k0[j], 0x5432), w[1]));
                a = bf16_add(a, bf16_mul(k0[j], w[0]));
                o[j] = bf16_mul(a, vv[j]);
            }
            stsm4(ud + swz64(ul - i * 64), o[0], o[1], o[2], o[3]);
        }
        fence_async();
        __syncwarp();
        if (far && lane < 8) {
            const uint32_t o = lane * B_UCH + (row0 - 3) * 64;
            copy_to_peer(peer_addr(sb + B_SM_U + o, rank ^ 1), ud + o, 256, peer_addr(barU, rank ^ 1));
        }
    }
    bar_sync(1, 512);
    mbar_wait_w(barU, 0);
    if (SENT_AT == 2) sentinels();
    SP(3);
    const int wg = warp >> 2, wq = warp & 3, hi = wq >> 1, g = lane >> 2, tq = lane & 3;
    const uint32_t zero = lds32(sb + B_SM_U + 4096);
#pragma unroll 1
    for (int cc = 0; cc < 2; cc++) {
        const int ch = 2 * wg + cc;
        const uint32_t kb = sb + B_SM_K + ch * B_KCH, ub = sb + B_SM_U + ch * B_UCH;
        const uint32_t dw = __byte_perm(d2, 0, cc ? 0x3232 : 0x1010);
        const int e0 = B_C - g + 2 * tq;
        const uint32_t f0 = ((e0 & 1) ? (kb + B_KLEN * 2 + 64 + (e0 - 1) * 2) : (kb + e0 * 2)) - 32 * wq;
        const uint32_t lo = uniform((ub >> 4) | 0x10000);
        float d[32];
#pragma unroll
        for (int i = 0; i < 32; i++) d[i] = 0.f;
        uint32_t A[2][2][4];
        static_for<0, 32>([&](auto jc) {
            constexpr int j = decltype(jc)::value, N = 64 - 8 * (j / 4);
            if (j >= 2) wg_wait<1>();
            uint32_t(&a)[4] = A[j & 1][0];
            uint32_t(&b)[4] = A[j & 1][1];
            a[0] = lds32(f0 - 128 * j); a[1] = lds32(f0 - 128 * j - 16); a[2] = lds32(f0 - 128 * j + 16);
            b[0] = lds32(f0 - 128 * j + 32); b[2] = lds32(f0 - 128 * j + 48);
            a[3] = a[0] ^ zero; b[1] = a[2] ^ zero; b[3] = b[0] ^ zero;
            wg_fence();
            wgmma_conv<N, 8 * j>(d, a, lo);
            wgmma_conv<N, 8 * j + 2>(d, b, lo);
            wg_commit();
        });
        wg_wait<0>();
        if (cc) SP(4);
        if (PF_STOP == 1 && cc && t == 0) sts32(flag, 1);
        bar_sync(2 + wg, 128);
        if (!hi && tq == 3) { float x = d[13]; d[13] = d[29]; d[29] = x; x = d[15]; d[15] = d[31]; d[31] = x; }
        if (hi && tq == 0) { d[0] = 0.f; d[2] = 0.f; }
        {
            const uint32_t xs = kb + (wq ^ 2) * 2048 + lane * 4;
            const uint32_t xn = hi ? xs + (tq ? 124 : 140) : xs + (tq < 3 ? 4 : -12), wrap = hi ? (tq ? 0 : -1) : (tq < 3 ? 0 : 1);
#pragma unroll
            for (int nb = 0; nb < 4; nb++) {
                const uint32_t xw = xn + ((nb + wrap) & 3) * 512;
#pragma unroll
                for (int i = 0; i < 2; i++) {
                    const float e0v = hi ? d[4 * nb + 2 * i] : d[16 + 4 * nb + 2 * i], e1v = hi ? d[4 * nb + 2 * i + 1] : d[16 + 4 * nb + 2 * i + 1];
                    sts32(hi ? xw + i * 256 : xs + nb * 512 + i * 256 + 128, __float_as_uint(e0v));
                    sts32(hi ? xs + nb * 512 + i * 256 : xw + i * 256, __float_as_uint(e1v));
                }
            }
        }
        bar_sync(2 + wg, 128);
#pragma unroll
        for (int p = 0; p < 2; p++) {
            int row = 16 * p + (lane >> 4) * 8 + (lane & 7);
            row = hi ? row + 31 : row == 31 ? 63 : row;
            const uint32_t a = sb + B_SM_U + swz64(ch * B_UCH + row * 64 + ((wq & 1) * 2 + ((lane >> 3) & 1)) * 16);
            uint32_t u[4];
            ldsm4t(u, a);
#pragma unroll
            for (int b = 0; b < 4; b++) {
                const int r = 8 * p + 2 * b;
                const float y0 = (hi ? d[16 + r] : d[r]) + __uint_as_float(lds32(kb + wq * 2048 + r * 128 + lane * 4));
                const float y1 = (hi ? d[17 + r] : d[r + 1]) + __uint_as_float(lds32(kb + wq * 2048 + r * 128 + 128 + lane * 4));
                u[b] = bf16_add(pack_bf16(y0, y1), bf16_mul(u[b], dw));
            }
            stsm4t(a, u[0], u[1], u[2], u[3]);
        }
        fence_async();
        bar_sync(2 + wg, 128);
        if (SENT_AT == 3 && cc == 0) sentinels();
        if (wq == 0 && lane == 0) copy_to_peer(peer_addr(sb + B_SM_S + ch * B_SCH, rank ^ 1), ub + rank * 2048, 2048, peer_addr(barY, rank ^ 1));
    }
    if (PF_STOP == 2 && t == 0) sts32(flag, 1);
    SP(5);
    mbar_wait_w(barQ, 0);
    bar_sync(1, 512);
    mbar_wait_w(barY, 0);
    asm volatile("barrier.cluster.arrive.relaxed.aligned;" ::: "memory");
    SP(6);
#pragma unroll
    for (int i = 0; i < 4; i++) {
        const int fr = i & 1, row = 63 - 32 * rank - 2 * warp - (i >> 1);
        const uint32_t qa = sb + B_SM_QT + warp * 2048 + (i >> 1) * 1024 + lane * 32 + ((rank ^ fr ^ (lane >> 2)) & 1) * 16;
        uint32_t y[4], q[4];
        ldsm4t(y, sb + (fr ? B_SM_S + (lane & 7) * (B_SCH - B_UCH) - (1 - rank) * 2048 : B_SM_U) + swz64((lane & 7) * B_UCH + row * 64 + (lane >> 3) * 16));
        ldsm4(q, qa);
        stsm4(qa, bf16_mul(q[0], y[0]), bf16_mul(q[1], y[1]), bf16_mul(q[2], y[2]), bf16_mul(q[3], y[3]));
    }
    fence_async();
    __syncwarp();
    if (lane == 0) {
        asm volatile("cp.async.bulk.tensor.2d.global.shared::cta.bulk_group.L2::cache_hint [%0, {%2, %3}], [%1], %4;"
                     ::"l"(&mapO), "r"(sb + B_SM_QT + warp * 2048), "r"(DM + c16), "r"(t0 + warp * 64), "l"(EF(4)) : "memory");
        asm volatile("cp.async.bulk.commit_group;" ::: "memory");
    }
    if (SENT_AT == 0) sentinels();
    if (warp == 0) SP2(10);
    if (lane == 0) asm volatile("cp.async.bulk.wait_group.read 0;" ::: "memory");
    __syncwarp();
    if (warp == 0) SP2(11);
    asm volatile("barrier.cluster.wait.aligned;" ::: "memory");
    SP(7);
    KT_END(1);
}

typedef CUresult (*EncodeFn)(CUtensorMap*, CUtensorMapDataType, cuuint32_t, void*, const cuuint64_t*, const cuuint64_t*, const cuuint32_t*,
                             const cuuint32_t*, CUtensorMapInterleave, CUtensorMapSwizzle, CUtensorMapL2promotion, CUtensorMapFloatOOBfill);

static void make_map(EncodeFn fn, CUtensorMap* m, const void* ptr, uint64_t inner, uint64_t outer, uint32_t box_in, uint32_t box_out,
                     CUtensorMapL2promotion promo = CU_TENSOR_MAP_L2_PROMOTION_L2_256B) {
    cuuint64_t dims[2] = {inner, outer};
    cuuint64_t strides[1] = {inner * 2};
    cuuint32_t box[2] = {box_in, box_out};
    cuuint32_t es[2] = {1, 1};
    fn(m, CU_TENSOR_MAP_DATA_TYPE_BFLOAT16, 2, const_cast<void*>(ptr), dims, strides, box, es, CU_TENSOR_MAP_INTERLEAVE_NONE,
       CU_TENSOR_MAP_SWIZZLE_128B, promo, CU_TENSOR_MAP_FLOAT_OOB_FILL_NONE);
}

#define G2_ST 7
#define PROMO_W CU_TENSOR_MAP_L2_PROMOTION_L2_256B
#define PROMO_O CU_TENSOR_MAP_L2_PROMOTION_L2_256B
#define SSM_PROMO CU_TENSOR_MAP_L2_PROMOTION_NONE
extern "C" void kernel_launch(void* const* d_in, const int* in_sizes, int n_in, void* d_out, int out_size) {
    const bf16* x = (const bf16*)d_in[0];
    const bf16* mem0 = (const bf16*)d_in[1];
    const bf16* Wq = (const bf16*)d_in[2];
    const bf16* Wk = (const bf16*)d_in[3];
    const bf16* Wv = (const bf16*)d_in[4];
    const bf16* Wo = (const bf16*)d_in[5];
    const bf16* Bq = (const bf16*)d_in[7];
    const bf16* Bk = (const bf16*)d_in[8];
    const bf16* Bv = (const bf16*)d_in[9];
    const bf16* Bsh = (const bf16*)d_in[10];
    const bf16* Bssm = (const bf16*)d_in[11];
    const bf16* BD = (const bf16*)d_in[12];
    bf16* out = (bf16*)d_out;

    static bool init = false;
    static EncodeFn enc = nullptr;
    static void *p_tok, *p_ox, *p_mbox;
    static int nclusters = 64;
    if (!init) {
        cudaDriverEntryPointQueryResult qr;
        cudaGetDriverEntryPoint("cuTensorMapEncodeTiled", (void**)&enc, cudaEnableDefault, &qr);
        cudaGetSymbolAddress(&p_tok, g_tok);
        cudaGetSymbolAddress(&p_ox, g_ox);
        cudaGetSymbolAddress(&p_mbox, g_mbox);
        cudaFuncSetAttribute(proj_kernel<128, 7>, cudaFuncAttributeMaxDynamicSharedMemorySize, PROJ_SMEM);
        cudaFuncSetAttribute(chain_kernel<false>, cudaFuncAttributeMaxDynamicSharedMemorySize, CHAIN_SMEM);
        cudaFuncSetAttribute(chain_kernel<true>, cudaFuncAttributeMaxDynamicSharedMemorySize, CHAIN_SMEM);
        cudaFuncSetAttribute(ssm_kernel, cudaFuncAttributeMaxDynamicSharedMemorySize, B_SMEM);
        cudaLaunchConfig_t cfg = {};
        cfg.gridDim = dim3(132); cfg.blockDim = dim3(384); cfg.dynamicSmemBytes = CHAIN_SMEM;
        cudaLaunchAttribute at[1];
        at[0].id = cudaLaunchAttributeClusterDimension; at[0].val.clusterDim.x = 2; at[0].val.clusterDim.y = 1; at[0].val.clusterDim.z = 1;
        cfg.attrs = at; cfg.numAttrs = 1;
        int n = 0;
        if (cudaOccupancyMaxActiveClusters(&n, chain_kernel<true>, &cfg) == cudaSuccess && n > 64) nclusters = n < 66 ? n : 66;
        (void)cudaGetLastError();
        init = true;
    }
    char* mbox = (char*)(((uintptr_t)p_mbox + 2 * WIN - 1) & ~(uintptr_t)(2 * WIN - 1));
    CUtensorMap mX, mT32, mT16, mTQ, mKV, mWq, mWk, mWv, mWoC, mWo, mOx, mOut, mO8;
    {
        cuuint64_t dims[3] = {64, S_LEN, DM / 64};
        cuuint64_t strides[2] = {DM * 2, 128};
        cuuint32_t box[3] = {64, 32, 4};
        cuuint32_t es[3] = {1, 1, 1};
        enc(&mX, CU_TENSOR_MAP_DATA_TYPE_BFLOAT16, 3, const_cast<bf16*>(x), dims, strides, box, es, CU_TENSOR_MAP_INTERLEAVE_NONE,
            CU_TENSOR_MAP_SWIZZLE_128B, CU_TENSOR_MAP_L2_PROMOTION_L2_256B, CU_TENSOR_MAP_FLOAT_OOB_FILL_NONE);
    }
    make_map(enc, &mT32, p_tok, DH, 4 * NH * 3 * SEG, 64, 32, CU_TENSOR_MAP_L2_PROMOTION_L2_128B);
    make_map(enc, &mT16, p_tok, DH, 4 * NH * 3 * SEG, 64, 16, CU_TENSOR_MAP_L2_PROMOTION_L2_128B);
    {
        cuuint64_t dims[2] = {512, 4 * NH * 12};
        cuuint64_t strides[1] = {2048};
        cuuint32_t box[2] = {256, 4};
        cuuint32_t es[2] = {1, 1};
        enc(&mTQ, CU_TENSOR_MAP_DATA_TYPE_UINT32, 2, p_tok, dims, strides, box, es, CU_TENSOR_MAP_INTERLEAVE_NONE,
            CU_TENSOR_MAP_SWIZZLE_NONE, CU_TENSOR_MAP_L2_PROMOTION_L2_128B, CU_TENSOR_MAP_FLOAT_OOB_FILL_NONE);
    }
    {
        cuuint64_t dims[3] = {64, 4 * NH * 3 * SEG, 2};
        cuuint64_t strides[2] = {DH * 2, 128};
        cuuint32_t box[3] = {64, 32, 2};
        cuuint32_t es[3] = {1, 1, 1};
        enc(&mKV, CU_TENSOR_MAP_DATA_TYPE_BFLOAT16, 3, p_tok, dims, strides, box, es, CU_TENSOR_MAP_INTERLEAVE_NONE,
            CU_TENSOR_MAP_SWIZZLE_128B, CU_TENSOR_MAP_L2_PROMOTION_L2_128B, CU_TENSOR_MAP_FLOAT_OOB_FILL_NONE);
    }
    {
        cuuint64_t dims[3] = {32, S_LEN, HD / 32};
        cuuint64_t strides[2] = {HD * 2, 64};
        cuuint32_t box[3] = {32, 8, 4};
        cuuint32_t es[3] = {1, 1, 1};
        enc(&mO8, CU_TENSOR_MAP_DATA_TYPE_BFLOAT16, 3, p_ox, dims, strides, box, es, CU_TENSOR_MAP_INTERLEAVE_NONE,
            CU_TENSOR_MAP_SWIZZLE_64B, CU_TENSOR_MAP_L2_PROMOTION_L2_128B, CU_TENSOR_MAP_FLOAT_OOB_FILL_NONE);
    }
    make_map(enc, &mWq, Wq, HD, DM, 64, 16, CU_TENSOR_MAP_L2_PROMOTION_L2_128B);
    make_map(enc, &mWk, Wk, HD, DM, 64, 16, CU_TENSOR_MAP_L2_PROMOTION_L2_128B);
    make_map(enc, &mWv, Wv, HD, DM, 64, 16, CU_TENSOR_MAP_L2_PROMOTION_L2_128B);
    make_map(enc, &mWoC, Wo, DM, HD, 64, 16, CU_TENSOR_MAP_L2_PROMOTION_L2_128B);
    const bool early = nclusters >= 66;
    make_map(enc, &mWo, Wo, DM, HD, 64, 64, PROMO_W);
    make_map(enc, &mOx, p_ox, HD, S_LEN, 64, early ? 64 : 128, PROMO_O);
    make_map(enc, &mOut, out, OUT_LD, S_LEN, 64, early ? 64 : 128);

    CUtensorMap mB[4];
    for (int i = 0; i < 4; i++) {
        cuuint64_t dims[2] = {(cuuint64_t)(i < 3 ? DM : OUT_LD), S_LEN};
        cuuint64_t strides[1] = {dims[0] * 2};
        cuuint32_t box[2] = {16, i == 0 ? 136u : i < 3 ? 128u : 64u};
        cuuint32_t es[2] = {1, 1};
        enc(&mB[i], CU_TENSOR_MAP_DATA_TYPE_BFLOAT16, 2, const_cast<bf16*>(i == 0 ? Bk : i == 1 ? Bv : i == 2 ? Bq : out), dims, strides, box, es,
            CU_TENSOR_MAP_INTERLEAVE_NONE, CU_TENSOR_MAP_SWIZZLE_32B, SSM_PROMO, CU_TENSOR_MAP_FLOAT_OOB_FILL_NONE);
    }
    cudaStream_t st = cudaStreamPerThread;
    const ChainInputs ci = {{(const char*)Wv, (const char*)Wk, (const char*)Wq, (const char*)Wo}, (const char*)x, (const char*)mem0};
    ssm_kernel<<<132, 576, B_SMEM, st>>>(mB[0], mB[1], mB[2], mB[3], Bsh, Bssm, BD, mbox, ci, out);
    cudaLaunchAttribute pdl[1];
    pdl[0].id = cudaLaunchAttributeProgrammaticStreamSerialization; pdl[0].val.programmaticStreamSerializationAllowed = 1;
    cudaLaunchConfig_t lc = {};
    lc.stream = st; lc.attrs = pdl;
    lc.gridDim = dim3(2 * nclusters); lc.blockDim = dim3(384); lc.dynamicSmemBytes = CHAIN_SMEM; lc.numAttrs = PDL & 1;
    cudaLaunchKernelEx(&lc, early ? chain_kernel<true> : chain_kernel<false>, mbox, mem0, mX, mT32, mT16, mTQ, mKV, mWq, mWk, mWv, mWoC, mWo, mOx, mOut, mO8);
    if (early) return;
    lc.gridDim = dim3(2 * nclusters); lc.blockDim = dim3(PROJ_THREADS); lc.dynamicSmemBytes = PROJ_SMEM; lc.numAttrs = (PDL >> 1) & 1;
    cudaLaunchKernelEx(&lc, proj_kernel<128, 7>, mWo, mOx, mOut);
}
```
